```python
import torch

def _softmax(x, axis=-1):
    return torch.softmax(x, dim=axis)

def _gelu(x):
    return torch.nn.functional.gelu(x, approximate='tanh')

def _silu(x):
    return torch.nn.functional.silu(x)

def _sigmoid(x):
    return torch.sigmoid(x)

def _layernorm(x, axis=-1, eps=1e-05):
    m = x.mean(dim=axis, keepdim=True)
    v = x.var(dim=axis, keepdim=True, unbiased=False)
    return (x - m) / torch.sqrt(v + eps)

def _scatter_add(tgt, idx, src, axis=0):
    return tgt.clone().index_add_(axis, idx, src)

def _segment_sum(src, seg, n):
    out = torch.zeros((n,) + src.shape[1:], dtype=src.dtype)
    return out.index_add_(0, seg, src)

def _pad(x, pw):
    flat = tuple((v for pair in reversed(pw) for v in pair))
    return torch.nn.functional.pad(x, flat)
kernel_name = 'interleave_layers__memory_aug_recurrent_mem_tr__softmax_full_mha__prompt'

def setup_inputs():

    _w = lambda a: (lambda t: t.to(torch.bfloat16) if t.is_floating_point() else t)(torch.as_tensor(a))

    def _A_setup():
        B, S, Dm = (1, 2048, 640)
        H, Dh = (32, 192)
        M, seg = (8, 32)
        seg = min(seg, S)
        S = S // seg * seg
        return {'x': _w((lambda *s: torch.randn(*s, dtype=torch.bfloat16) * 0.05)(B, S, Dm)), 'mem0': _w((lambda *s: torch.randn(*s, dtype=torch.bfloat16) * 0.8)(B, M, Dm)), 'Wq': _w((lambda *s: torch.randn(*s, dtype=torch.bfloat16) * 0.8)(Dm, H, Dh) * Dm ** (-0.5)), 'Wk': _w((lambda *s: torch.randn(*s, dtype=torch.bfloat16) * 0.8)(Dm, H, Dh) * Dm ** (-0.5)), 'Wv': _w((lambda *s: torch.randn(*s, dtype=torch.bfloat16) * 0.8)(Dm, H, Dh) * Dm ** (-0.5)), 'Wo': _w((lambda *s: torch.randn(*s, dtype=torch.bfloat16) * 0.8)(H, Dh, Dm) * (H * Dh) ** (-0.5)), 'seg_len': seg}
    _A_in = _A_setup()

    def _B_setup():
        B, S, D = (1, 2048, 640)
        return {'x': _w((lambda *s: torch.randn(*s, dtype=torch.bfloat16) * 0.05)(B, S, D)), 'wqkv': _w((lambda *s: torch.randn(*s, dtype=torch.bfloat16) * 0.05)(D, 3 * D)), 'wo': _w((lambda *s: torch.randn(*s, dtype=torch.bfloat16) * 0.05)(D, D))}
    _B_in = _B_setup()
    return {'A_x': _A_in['x'], 'A_mem0': _A_in['mem0'], 'A_Wq': _A_in['Wq'], 'A_Wk': _A_in['Wk'], 'A_Wv': _A_in['Wv'], 'A_Wo': _A_in['Wo'], 'A_seg_len': _A_in['seg_len'], 'B_x': _B_in['x'], 'B_wqkv': _B_in['wqkv'], 'B_wo': _B_in['wo']}

def reference(A_x, A_mem0, A_Wq, A_Wk, A_Wv, A_Wo, A_seg_len, B_x, B_wqkv, B_wo):

    def _A_ref(x, mem0, Wq, Wk, Wv, Wo, seg_len):
        B, S, Dm = x.shape
        H, Dh = (Wq.shape[1], Wq.shape[2])
        M = mem0.shape[1]
        scale = Dh ** (-0.5)
        n_seg = S // seg_len
        L = M + seg_len
        idx = torch.arange(L)
        mask = (idx[:, None] < M) | (idx[:, None] >= idx[None, :])
        mem = mem0
        outs = []
        for s in range(n_seg):
            xs = x[:, s * seg_len:(s + 1) * seg_len, :].clone()
            h = torch.concatenate([mem, xs], axis=1)
            q = torch.einsum('btd,dhe->bhte', h, Wq)
            k = torch.einsum('btd,dhe->bhte', h, Wk)
            v = torch.einsum('btd,dhe->bhte', h, Wv)
            scores = torch.einsum('bhqe,bhke->bhqk', q, k) * scale
            scores = torch.where(mask[None, None], scores, -1000000000.0)
            p = _softmax(scores, axis=-1)
            o = torch.einsum('bhqk,bhke->bhqe', p, v)
            o = torch.einsum('bhte,hed->btd', o, Wo)
            mem = o[:, :M, :].clone()
            outs.append(o[:, M:, :])
        return torch.concatenate(outs, axis=1)

    def _B_ref(x, wqkv, wo):
        B, S, D = x.shape
        H = 32
        Dh = D // H
        qkv = (lambda x, *d: x.permute(*d))((x @ wqkv).reshape(B, S, 3, H, Dh), 2, 0, 3, 1, 4)
        q, k, v = (qkv[0], qkv[1], qkv[2])
        scale = Dh ** (-0.5)
        scores = torch.einsum('bhqd,bhkd->bhqk', q, k) * scale
        p = _softmax(scores, axis=-1)
        o = torch.einsum('bhqk,bhkd->bhqd', p, v)
        return (lambda x, *d: x.permute(*d))(o, 0, 2, 1, 3).reshape(B, S, D) @ wo
    x = A_x
    x = x + _A_ref(_layernorm(x, axis=-1), A_mem0, A_Wq, A_Wk, A_Wv, A_Wo, A_seg_len)
    x = x + _B_ref(_layernorm(x, axis=-1), B_wqkv, B_wo)
    x = x + _A_ref(_layernorm(x, axis=-1), A_mem0, A_Wq, A_Wk, A_Wv, A_Wo, A_seg_len)
    x = x + _B_ref(_layernorm(x, axis=-1), B_wqkv, B_wo)
    return x
```

```cpp
#include <cuda_runtime.h>
#include <cuda_bf16.h>
#include <cuda.h>
#include <stdint.h>
#include <stdlib.h>

namespace {

constexpr int SEQ = 2048, DM = 640, HD = 6144, NSEG = 64;
constexpr int SPIN_LIMIT = 1 << 20;

__device__ __align__(128) float4 g_x[SEQ * DM / 4];
__device__ __align__(16) uint32_t g_xf[SEQ * DM / 2];
__device__ __align__(128) uint32_t g_xs[SEQ * DM / 2];
__device__ __align__(16) uint32_t g_of[SEQ * DM / 2];
__device__ __nv_bfloat16 g_q[SEQ * HD], g_o[SEQ * HD];
constexpr int KV_K = 0, KV_V = 16384, KV_KM = 32768, KV_VM = 36864, KV_BYTES = 40960;
__device__ __align__(128) uint8_t g_kv[16 * 96 * KV_BYTES];
#define OP_B4 0
#define OP_B8 11
#define OP_B16 13
#define QA_END 12
__host__ __device__ constexpr int op_split(int b) { return b < OP_B4 ? 2 : b < OP_B8 ? 4 : b < OP_B16 ? 8 : 16; }
__host__ __device__ constexpr int fin_items(int b) { return b < OP_B8 ? 4 : op_split(b); }
#define BQ_HALF 10
__host__ __device__ constexpr int bq_items(int b) { return b < BQ_HALF ? 6 : 12; }
__device__ __align__(128) uint2 g_part[16 * 16 * 16 * 40 * 32];
__device__ __align__(128) uint32_t g_xn[SEQ * DM / 2];
constexpr int SY_Q = 128, SY_T = 160, SY_UP = 192, SY_N = 193;
__device__ __align__(16) uint32_t g_sync[SY_N];
constexpr int NSLOT = 92;
__device__ uint32_t g_pool[(NSLOT + 2) * 2048];
__device__ int g_smpart[256], g_orient[NSLOT];
__device__ uint32_t g_ctapart[96];
__device__ uint32_t g_bqkv[3 * 32 * 256 * 96];

#define XT(i)
#define MISS(k, n)
#define PRO(i)
#define TRACE(w)
#define ITEM(code, w)
#define STAT(k)
#define TMV(i, v)
#define TM(i)
#define TMD(i, dep)

__device__ __forceinline__ uint32_t gtime() { uint32_t c; asm volatile("mov.u32 %0, %%globaltimer_lo;" : "=r"(c) :: "memory"); return c; }
__device__ __forceinline__ uint32_t clk32() { uint32_t c; asm volatile("mov.u32 %0, %%clock;" : "=r"(c) :: "memory"); return c; }
__device__ __forceinline__ uint32_t s2u(const void* p) { return (uint32_t)__cvta_generic_to_shared(p); }
__device__ __forceinline__ uint32_t pack2(float a, float b) {
  uint32_t r; asm("cvt.rn.bf16x2.f32 %0, %1, %2;" : "=r"(r) : "f"(b), "f"(a)); return r; }
__device__ __forceinline__ float bf_lo(uint32_t w) { return __uint_as_float(w << 16); }
__device__ __forceinline__ float bf_hi(uint32_t w) { return __uint_as_float(w & 0xffff0000u); }
__device__ __forceinline__ float ex2(float x) { float y; asm("ex2.approx.ftz.f32 %0, %1;" : "=f"(y) : "f"(x)); return y; }

__device__ __forceinline__ void mbar_init(uint32_t bar, uint32_t n) {
  asm volatile("mbarrier.init.shared::cta.b64 [%0], %1;" :: "r"(bar), "r"(n) : "memory"); }
__device__ __forceinline__ void mbar_expect(uint32_t bar, uint32_t bytes) {
  asm volatile("mbarrier.arrive.expect_tx.shared::cta.b64 _, [%0], %1;" :: "r"(bar), "r"(bytes) : "memory"); }
__device__ __forceinline__ void mbar_arrive(uint32_t bar) {
  asm volatile("mbarrier.arrive.shared::cta.b64 _, [%0];" :: "r"(bar) : "memory"); }
__device__ __forceinline__ void mbar_arrive_remote(uint32_t bar) {
  asm volatile("mbarrier.arrive.shared::cluster.b64 _, [%0];" :: "r"(bar) : "memory"); }
__device__ __forceinline__ void mbar_wait_slow(uint32_t bar, uint32_t ph) {
  asm volatile("{.reg .pred p; .reg .u32 n; mov.u32 n, 0;\n"
               "W: mbarrier.try_wait.parity.shared::cta.b64 p, [%0], %1; @p bra D;\n"
               "add.u32 n, n, 1; setp.gt.u32 p, n, %2; @p trap; bra W;\n"
               "D: }" :: "r"(bar), "r"(ph), "n"(SPIN_LIMIT) : "memory");
}
__device__ __forceinline__ void mbar_wait(uint32_t bar, uint32_t ph) {
  uint32_t ok;
  asm volatile("{.reg .pred p; mbarrier.try_wait.parity.shared::cta.b64 p, [%1], %2; selp.u32 %0, 1, 0, p;}" : "=r"(ok) : "r"(bar), "r"(ph) : "memory");
  if (__builtin_expect(!ok, 0)) mbar_wait_slow(bar, ph);
}
__device__ __forceinline__ bool elect() {
  uint32_t p; asm volatile("{.reg .pred q; elect.sync _|q, 0xffffffff; selp.u32 %0, 1, 0, q;}" : "=r"(p)); return p; }
__device__ __forceinline__ void mbar_wait_cluster(uint32_t bar, uint32_t ph) {
  asm volatile("{.reg .pred p; .reg .u32 n; mov.u32 n, 0;\n"
               "W: mbarrier.try_wait.parity.acquire.cluster.shared::cta.b64 p, [%0], %1; @p bra D;\n"
               "add.u32 n, n, 1; setp.gt.u32 p, n, %2; @p trap; bra W;\n"
               "D: }" :: "r"(bar), "r"(ph), "n"(SPIN_LIMIT) : "memory");
}
__device__ __forceinline__ void spin_guard(int& n) {
  asm volatile("{.reg .pred p; add.s32 %0, %0, 1; setp.gt.s32 p, %0, %1; @p trap;}" : "+r"(n) : "n"(SPIN_LIMIT));
}
__device__ __forceinline__ void pdl_wait() { asm volatile("griddepcontrol.wait;" ::: "memory"); TRACE(1); }
__device__ __forceinline__ void pdl_launch() { asm volatile("griddepcontrol.launch_dependents;" ::: "memory"); }
__device__ __forceinline__ uint32_t ld_acquire(const uint32_t* p) { uint32_t v; asm volatile("ld.acquire.gpu.global.u32 %0, [%1];" : "=r"(v) : "l"(p) : "memory"); return v; }
__device__ __forceinline__ void red_release(uint32_t* p, uint32_t v) { asm volatile("red.release.gpu.global.add.u32 [%0], %1;" :: "l"(p), "r"(v) : "memory"); }
__device__ __forceinline__ void fence_async_global() { asm volatile("fence.proxy.async.global;" ::: "memory"); }
__device__ __forceinline__ void fence_async() { asm volatile("fence.proxy.async.shared::cta;" ::: "memory"); }
__device__ __forceinline__ void bar_sync(int id, int n) { asm volatile("bar.sync %0, %1;" :: "r"(id), "r"(n) : "memory"); }
__device__ __forceinline__ void bar_arrive(int id, int n) { asm volatile("bar.arrive %0, %1;" :: "r"(id), "r"(n) : "memory"); }
__device__ __forceinline__ void tma_load(uint32_t dst, const CUtensorMap* m, int c0, int c1, uint32_t bar) {
  asm volatile("cp.async.bulk.tensor.2d.shared::cluster.global.mbarrier::complete_tx::bytes [%0], [%1, {%3, %4}], [%2];"
               :: "r"(dst), "l"(m), "r"(bar), "r"(c0), "r"(c1) : "memory"); }
__device__ __forceinline__ void tma_store(const CUtensorMap* m, uint32_t src, int c0, int c1) {
  asm volatile("cp.async.bulk.tensor.2d.global.shared::cta.bulk_group [%0, {%2, %3}], [%1];"
               :: "l"(m), "r"(src), "r"(c0), "r"(c1) : "memory"); }
__device__ __forceinline__ void tma_store_stream(const CUtensorMap* m, uint32_t src, int c0, int c1) {
  asm volatile("{.reg .b64 pol; createpolicy.fractional.L2::evict_first.b64 pol, 1.0;\n"
               "cp.async.bulk.tensor.2d.global.shared::cta.bulk_group.L2::cache_hint [%0, {%2, %3}], [%1], pol;}"
               :: "l"(m), "r"(src), "r"(c0), "r"(c1) : "memory"); }
__device__ __forceinline__ void bulk_load(uint32_t dst, const void* src, uint32_t bytes, uint32_t bar) {
  asm volatile("cp.async.bulk.shared::cluster.global.mbarrier::complete_tx::bytes [%0], [%1], %2, [%3];"
               :: "r"(dst), "l"(src), "r"(bytes), "r"(bar) : "memory"); }
__device__ __forceinline__ void bulk_push(uint32_t dst, uint32_t src, uint32_t bytes, uint32_t bar) {
  asm volatile("cp.async.bulk.shared::cluster.shared::cta.mbarrier::complete_tx::bytes [%0], [%1], %2, [%3];"
               :: "r"(dst), "r"(src), "r"(bytes), "r"(bar) : "memory"); }
__device__ __forceinline__ void bulk_store(void* dst, uint32_t src, uint32_t bytes) {
  asm volatile("cp.async.bulk.global.shared::cta.bulk_group [%0], [%1], %2;" :: "l"(dst), "r"(src), "r"(bytes) : "memory"); }
__device__ __forceinline__ void bulk_commit() { asm volatile("cp.async.bulk.commit_group;" ::: "memory"); }
template <int N> __device__ __forceinline__ void bulk_wait_read() { asm volatile("cp.async.bulk.wait_group.read %0;" :: "n"(N) : "memory"); }
template <int N> __device__ __forceinline__ void bulk_wait() { asm volatile("cp.async.bulk.wait_group %0;" :: "n"(N) : "memory"); }

__device__ __forceinline__ uint64_t mkdesc(uint32_t addr, uint32_t lbo, uint32_t sbo, uint32_t sw) {
  return (uint64_t)((addr & 0x3FFFF) >> 4) | ((uint64_t)(lbo >> 4) << 16) | ((uint64_t)(sbo >> 4) << 32) | ((uint64_t)sw << 62); }
__device__ __forceinline__ void wg_fence() { asm volatile("wgmma.fence.sync.aligned;" ::: "memory"); }
__device__ __forceinline__ void wg_commit() { asm volatile("wgmma.commit_group.sync.aligned;" ::: "memory"); }
template <int N> __device__ __forceinline__ void wg_wait() { asm volatile("wgmma.wait_group.sync.aligned %0;" :: "n"(N) : "memory"); }
template <int N> __device__ __forceinline__ void reg_fence(float* d) {
#pragma unroll
  for (int i = 0; i < N; i++) asm volatile("" : "+f"(d[i]) :: "memory");
}

__device__ __forceinline__ void mma16(float* d, uint32_t a0, uint32_t a1, uint32_t a2, uint32_t a3, uint32_t b0, uint32_t b1) {
  asm volatile("mma.sync.aligned.m16n8k16.row.col.f32.bf16.bf16.f32 {%0,%1,%2,%3},{%4,%5,%6,%7},{%8,%9},{%0,%1,%2,%3};"
               : "+f"(d[0]), "+f"(d[1]), "+f"(d[2]), "+f"(d[3]) : "r"(a0), "r"(a1), "r"(a2), "r"(a3), "r"(b0), "r"(b1)); }
__device__ __forceinline__ void mma8(float* d, uint32_t a0, uint32_t a1, uint32_t b0) {
  asm volatile("mma.sync.aligned.m16n8k8.row.col.f32.bf16.bf16.f32 {%0,%1,%2,%3},{%4,%5},{%6},{%0,%1,%2,%3};"
               : "+f"(d[0]), "+f"(d[1]), "+f"(d[2]), "+f"(d[3]) : "r"(a0), "r"(a1), "r"(b0)); }
__device__ __forceinline__ void ldsm4(uint32_t* r, uint32_t a) {
  asm volatile("ldmatrix.sync.aligned.m8n8.x4.shared.b16 {%0,%1,%2,%3},[%4];" : "=r"(r[0]), "=r"(r[1]), "=r"(r[2]), "=r"(r[3]) : "r"(a) : "memory"); }
__device__ __forceinline__ uint4 ldsm4v(uint32_t a) { uint32_t r[4]; ldsm4(r, a); return make_uint4(r[0], r[1], r[2], r[3]); }
__device__ __forceinline__ void ldsm4t(uint32_t* r, uint32_t a) {
  asm volatile("ldmatrix.sync.aligned.m8n8.x4.trans.shared.b16 {%0,%1,%2,%3},[%4];" : "=r"(r[0]), "=r"(r[1]), "=r"(r[2]), "=r"(r[3]) : "r"(a) : "memory"); }
__device__ __forceinline__ void ldsm2t(uint32_t* r, uint32_t a) {
  asm volatile("ldmatrix.sync.aligned.m8n8.x2.trans.shared.b16 {%0,%1},[%2];" : "=r"(r[0]), "=r"(r[1]) : "r"(a) : "memory"); }
__device__ __forceinline__ void stsm4(uint32_t a, uint32_t r0, uint32_t r1, uint32_t r2, uint32_t r3) {
  asm volatile("stmatrix.sync.aligned.m8n8.x4.shared.b16 [%0], {%1,%2,%3,%4};" :: "r"(a), "r"(r0), "r"(r1), "r"(r2), "r"(r3) : "memory"); }
__device__ __forceinline__ void stsm4t(uint32_t a, uint32_t r0, uint32_t r1, uint32_t r2, uint32_t r3) {
  asm volatile("stmatrix.sync.aligned.m8n8.x4.trans.shared.b16 [%0], {%1,%2,%3,%4};" :: "r"(a), "r"(r0), "r"(r1), "r"(r2), "r"(r3) : "memory"); }
__device__ __forceinline__ void stsm2(uint32_t a, uint32_t r0, uint32_t r1) {
  asm volatile("stmatrix.sync.aligned.m8n8.x2.shared.b16 [%0], {%1,%2};" :: "r"(a), "r"(r0), "r"(r1) : "memory"); }
__device__ __forceinline__ void stsm2t(uint32_t a, uint32_t r0, uint32_t r1) {
  asm volatile("stmatrix.sync.aligned.m8n8.x2.trans.shared.b16 [%0], {%1,%2};" :: "r"(a), "r"(r0), "r"(r1) : "memory"); }
__device__ __forceinline__ void sts32(uint32_t a, uint32_t v) { asm volatile("st.shared.b32 [%0], %1;" :: "r"(a), "r"(v) : "memory"); }
__device__ __forceinline__ void sts64f(uint32_t a, float x, float y) { asm volatile("st.shared.v2.f32 [%0], {%1,%2};" :: "r"(a), "f"(x), "f"(y) : "memory"); }
__device__ __forceinline__ void sts128(uint32_t a, uint4 v) {
  asm volatile("st.shared.v4.b32 [%0], {%1,%2,%3,%4};" :: "r"(a), "r"(v.x), "r"(v.y), "r"(v.z), "r"(v.w) : "memory"); }
__device__ __forceinline__ void sts128f(uint32_t a, float x, float y, float z, float w) {
  asm volatile("st.shared.v4.f32 [%0], {%1,%2,%3,%4};" :: "r"(a), "f"(x), "f"(y), "f"(z), "f"(w) : "memory"); }
__device__ __forceinline__ float lds32f(uint32_t a) { float v; asm volatile("ld.shared.f32 %0, [%1];" : "=f"(v) : "r"(a) : "memory"); return v; }
__device__ __forceinline__ float2 lds64f(uint32_t a) { float2 v; asm volatile("ld.shared.v2.f32 {%0,%1}, [%2];" : "=f"(v.x), "=f"(v.y) : "r"(a) : "memory"); return v; }
__device__ __forceinline__ float4 lds128f(uint32_t a) {
  float4 v; asm volatile("ld.shared.v4.f32 {%0,%1,%2,%3}, [%4];" : "=f"(v.x), "=f"(v.y), "=f"(v.z), "=f"(v.w) : "r"(a) : "memory"); return v; }
__device__ __forceinline__ uint4 lds128(uint32_t a) {
  uint4 v; asm volatile("ld.shared.v4.b32 {%0,%1,%2,%3}, [%4];" : "=r"(v.x), "=r"(v.y), "=r"(v.z), "=r"(v.w) : "r"(a) : "memory"); return v; }
__device__ __forceinline__ uint4 ldg_strong128(const void* p) {
  uint4 v; asm volatile("ld.relaxed.gpu.global.v4.u32 {%0,%1,%2,%3}, [%4];" : "=r"(v.x), "=r"(v.y), "=r"(v.z), "=r"(v.w) : "l"(p) : "memory"); return v; }
__device__ __forceinline__ uint2 ldg_strong64(const void* p) {
  uint2 v; asm volatile("ld.relaxed.gpu.global.v2.u32 {%0,%1}, [%2];" : "=r"(v.x), "=r"(v.y) : "l"(p) : "memory"); return v; }
__device__ __forceinline__ void stg_strong32(void* p, uint32_t v) { asm volatile("st.relaxed.gpu.global.u32 [%0], %1;" :: "l"(p), "r"(v) : "memory"); }
__device__ __forceinline__ void stg_strong128(void* p, uint4 v) {
  asm volatile("st.relaxed.gpu.global.v4.u32 [%0], {%1,%2,%3,%4};" :: "l"(p), "r"(v.x), "r"(v.y), "r"(v.z), "r"(v.w) : "memory"); }
__device__ __forceinline__ uint32_t mapa(uint32_t a, uint32_t r) {
  uint32_t o; asm("mapa.shared::cluster.u32 %0, %1, %2;" : "=r"(o) : "r"(a), "r"(r)); return o; }
__device__ __forceinline__ void st_async2f(uint32_t a, float x, float y, uint32_t bar) {
  asm volatile("st.async.shared::cluster.mbarrier::complete_tx::bytes.v2.f32 [%0], {%1,%2}, [%3];" :: "r"(a), "f"(x), "f"(y), "r"(bar) : "memory"); }
__device__ __forceinline__ void st_async32(uint32_t a, uint32_t x, uint32_t bar) {
  asm volatile("st.async.shared::cluster.mbarrier::complete_tx::bytes.b32 [%0], %1, [%2];" :: "r"(a), "r"(x), "r"(bar) : "memory"); }
__device__ __forceinline__ uint32_t lds32(uint32_t a) { uint32_t v; asm volatile("ld.shared.b32 %0, [%1];" : "=r"(v) : "r"(a) : "memory"); return v; }
__device__ __forceinline__ void st_async64(uint32_t a, uint32_t x, uint32_t y, uint32_t bar) {
  asm volatile("st.async.shared::cluster.mbarrier::complete_tx::bytes.v2.b32 [%0], {%1,%2}, [%3];" :: "r"(a), "r"(x), "r"(y), "r"(bar) : "memory"); }
__device__ __forceinline__ void st_async128(uint32_t a, uint4 v, uint32_t bar) {
  asm volatile("st.async.shared::cluster.mbarrier::complete_tx::bytes.v4.b32 [%0], {%1,%2,%3,%4}, [%5];" :: "r"(a), "r"(v.x), "r"(v.y), "r"(v.z), "r"(v.w), "r"(bar) : "memory"); }
__device__ __forceinline__ uint2 lds64(uint32_t a) { uint2 v; asm volatile("ld.shared.v2.b32 {%0,%1}, [%2];" : "=r"(v.x), "=r"(v.y) : "r"(a) : "memory"); return v; }
__device__ __forceinline__ void sts64(uint32_t a, uint32_t x, uint32_t y) { asm volatile("st.shared.v2.b32 [%0], {%1,%2};" :: "r"(a), "r"(x), "r"(y) : "memory"); }
__device__ __forceinline__ uint32_t ldg_strong32(const void* p) { uint32_t v; asm volatile("ld.relaxed.gpu.global.u32 %0, [%1];" : "=r"(v) : "l"(p) : "memory"); return v; }
__device__ __forceinline__ uint32_t transpose8(uint32_t x) { uint32_t r; asm volatile("movmatrix.sync.aligned.m8n8.trans.b16 %0, %1;" : "=r"(r) : "r"(x)); return r; }
__device__ __forceinline__ uint32_t hadd2(uint32_t a, uint32_t b) { uint32_t r; asm("add.rn.bf16x2 %0, %1, %2;" : "=r"(r) : "r"(a), "r"(b)); return r; }
__device__ __forceinline__ uint32_t min4(uint4 v) { return min(__vimin3_u32(v.x, v.y, v.z), v.w); }

__device__ __forceinline__ void wg_rs64_01(float* d, uint32_t a0, uint32_t a1, uint32_t a2, uint32_t a3, uint64_t db, int sd) {
  asm volatile("{.reg .pred p; setp.ne.b32 p, %37, 0;\n"
    "wgmma.mma_async.sync.aligned.m64n64k16.f32.bf16.bf16 {%0,%1,%2,%3,%4,%5,%6,%7,%8,%9,%10,%11,%12,%13,%14,%15,%16,%17,%18,%19,%20,%21,%22,%23,%24,%25,%26,%27,%28,%29,%30,%31}, {%32,%33,%34,%35}, %36, p, 1, 1, 1;}"
    : "+f"(d[0]),"+f"(d[1]),"+f"(d[2]),"+f"(d[3]),"+f"(d[4]),"+f"(d[5]),"+f"(d[6]),"+f"(d[7]),"+f"(d[8]),"+f"(d[9]),"+f"(d[10]),"+f"(d[11]),"+f"(d[12]),"+f"(d[13]),"+f"(d[14]),"+f"(d[15]),"+f"(d[16]),"+f"(d[17]),"+f"(d[18]),"+f"(d[19]),"+f"(d[20]),"+f"(d[21]),"+f"(d[22]),"+f"(d[23]),"+f"(d[24]),"+f"(d[25]),"+f"(d[26]),"+f"(d[27]),"+f"(d[28]),"+f"(d[29]),"+f"(d[30]),"+f"(d[31])
    : "r"(a0), "r"(a1), "r"(a2), "r"(a3), "l"(db), "r"(sd));
}
__device__ __forceinline__ void wg_ss192_01(float* d, uint64_t da, uint64_t db, int sd) {
  asm volatile("{.reg .pred p; setp.ne.b32 p, %98, 0;\n"
    "wgmma.mma_async.sync.aligned.m64n192k16.f32.bf16.bf16 {%0,%1,%2,%3,%4,%5,%6,%7,%8,%9,%10,%11,%12,%13,%14,%15,%16,%17,%18,%19,%20,%21,%22,%23,%24,%25,%26,%27,%28,%29,%30,%31,%32,%33,%34,%35,%36,%37,%38,%39,%40,%41,%42,%43,%44,%45,%46,%47,%48,%49,%50,%51,%52,%53,%54,%55,%56,%57,%58,%59,%60,%61,%62,%63,%64,%65,%66,%67,%68,%69,%70,%71,%72,%73,%74,%75,%76,%77,%78,%79,%80,%81,%82,%83,%84,%85,%86,%87,%88,%89,%90,%91,%92,%93,%94,%95}, %96, %97, p, 1, 1, 0, 1;}"
    : "+f"(d[0]),"+f"(d[1]),"+f"(d[2]),"+f"(d[3]),"+f"(d[4]),"+f"(d[5]),"+f"(d[6]),"+f"(d[7]),"+f"(d[8]),"+f"(d[9]),"+f"(d[10]),"+f"(d[11]),"+f"(d[12]),"+f"(d[13]),"+f"(d[14]),"+f"(d[15]),"+f"(d[16]),"+f"(d[17]),"+f"(d[18]),"+f"(d[19]),"+f"(d[20]),"+f"(d[21]),"+f"(d[22]),"+f"(d[23]),"+f"(d[24]),"+f"(d[25]),"+f"(d[26]),"+f"(d[27]),"+f"(d[28]),"+f"(d[29]),"+f"(d[30]),"+f"(d[31]),"+f"(d[32]),"+f"(d[33]),"+f"(d[34]),"+f"(d[35]),"+f"(d[36]),"+f"(d[37]),"+f"(d[38]),"+f"(d[39]),"+f"(d[40]),"+f"(d[41]),"+f"(d[42]),"+f"(d[43]),"+f"(d[44]),"+f"(d[45]),"+f"(d[46]),"+f"(d[47]),"+f"(d[48]),"+f"(d[49]),"+f"(d[50]),"+f"(d[51]),"+f"(d[52]),"+f"(d[53]),"+f"(d[54]),"+f"(d[55]),"+f"(d[56]),"+f"(d[57]),"+f"(d[58]),"+f"(d[59]),"+f"(d[60]),"+f"(d[61]),"+f"(d[62]),"+f"(d[63]),"+f"(d[64]),"+f"(d[65]),"+f"(d[66]),"+f"(d[67]),"+f"(d[68]),"+f"(d[69]),"+f"(d[70]),"+f"(d[71]),"+f"(d[72]),"+f"(d[73]),"+f"(d[74]),"+f"(d[75]),"+f"(d[76]),"+f"(d[77]),"+f"(d[78]),"+f"(d[79]),"+f"(d[80]),"+f"(d[81]),"+f"(d[82]),"+f"(d[83]),"+f"(d[84]),"+f"(d[85]),"+f"(d[86]),"+f"(d[87]),"+f"(d[88]),"+f"(d[89]),"+f"(d[90]),"+f"(d[91]),"+f"(d[92]),"+f"(d[93]),"+f"(d[94]),"+f"(d[95])
    : "l"(da), "l"(db), "r"(sd));
}
__device__ __forceinline__ void wg_ss128_01(float* d, uint64_t da, uint64_t db, int sd) {
  asm volatile("{.reg .pred p; setp.ne.b32 p, %66, 0;\n"
    "wgmma.mma_async.sync.aligned.m64n128k16.f32.bf16.bf16 {%0,%1,%2,%3,%4,%5,%6,%7,%8,%9,%10,%11,%12,%13,%14,%15,%16,%17,%18,%19,%20,%21,%22,%23,%24,%25,%26,%27,%28,%29,%30,%31,%32,%33,%34,%35,%36,%37,%38,%39,%40,%41,%42,%43,%44,%45,%46,%47,%48,%49,%50,%51,%52,%53,%54,%55,%56,%57,%58,%59,%60,%61,%62,%63}, %64, %65, p, 1, 1, 0, 1;}"
    : "+f"(d[0]),"+f"(d[1]),"+f"(d[2]),"+f"(d[3]),"+f"(d[4]),"+f"(d[5]),"+f"(d[6]),"+f"(d[7]),"+f"(d[8]),"+f"(d[9]),"+f"(d[10]),"+f"(d[11]),"+f"(d[12]),"+f"(d[13]),"+f"(d[14]),"+f"(d[15]),"+f"(d[16]),"+f"(d[17]),"+f"(d[18]),"+f"(d[19]),"+f"(d[20]),"+f"(d[21]),"+f"(d[22]),"+f"(d[23]),"+f"(d[24]),"+f"(d[25]),"+f"(d[26]),"+f"(d[27]),"+f"(d[28]),"+f"(d[29]),"+f"(d[30]),"+f"(d[31]),"+f"(d[32]),"+f"(d[33]),"+f"(d[34]),"+f"(d[35]),"+f"(d[36]),"+f"(d[37]),"+f"(d[38]),"+f"(d[39]),"+f"(d[40]),"+f"(d[41]),"+f"(d[42]),"+f"(d[43]),"+f"(d[44]),"+f"(d[45]),"+f"(d[46]),"+f"(d[47]),"+f"(d[48]),"+f"(d[49]),"+f"(d[50]),"+f"(d[51]),"+f"(d[52]),"+f"(d[53]),"+f"(d[54]),"+f"(d[55]),"+f"(d[56]),"+f"(d[57]),"+f"(d[58]),"+f"(d[59]),"+f"(d[60]),"+f"(d[61]),"+f"(d[62]),"+f"(d[63])
    : "l"(da), "l"(db), "r"(sd));
}
__device__ __forceinline__ void wg_ss160_01(float* d, uint64_t da, uint64_t db, int sd) {
  asm volatile("{.reg .pred p; setp.ne.b32 p, %82, 0;\n"
    "wgmma.mma_async.sync.aligned.m64n160k16.f32.bf16.bf16 {%0,%1,%2,%3,%4,%5,%6,%7,%8,%9,%10,%11,%12,%13,%14,%15,%16,%17,%18,%19,%20,%21,%22,%23,%24,%25,%26,%27,%28,%29,%30,%31,%32,%33,%34,%35,%36,%37,%38,%39,%40,%41,%42,%43,%44,%45,%46,%47,%48,%49,%50,%51,%52,%53,%54,%55,%56,%57,%58,%59,%60,%61,%62,%63,%64,%65,%66,%67,%68,%69,%70,%71,%72,%73,%74,%75,%76,%77,%78,%79}, %80, %81, p, 1, 1, 0, 1;}"
    : "+f"(d[0]),"+f"(d[1]),"+f"(d[2]),"+f"(d[3]),"+f"(d[4]),"+f"(d[5]),"+f"(d[6]),"+f"(d[7]),"+f"(d[8]),"+f"(d[9]),"+f"(d[10]),"+f"(d[11]),"+f"(d[12]),"+f"(d[13]),"+f"(d[14]),"+f"(d[15]),"+f"(d[16]),"+f"(d[17]),"+f"(d[18]),"+f"(d[19]),"+f"(d[20]),"+f"(d[21]),"+f"(d[22]),"+f"(d[23]),"+f"(d[24]),"+f"(d[25]),"+f"(d[26]),"+f"(d[27]),"+f"(d[28]),"+f"(d[29]),"+f"(d[30]),"+f"(d[31]),"+f"(d[32]),"+f"(d[33]),"+f"(d[34]),"+f"(d[35]),"+f"(d[36]),"+f"(d[37]),"+f"(d[38]),"+f"(d[39]),"+f"(d[40]),"+f"(d[41]),"+f"(d[42]),"+f"(d[43]),"+f"(d[44]),"+f"(d[45]),"+f"(d[46]),"+f"(d[47]),"+f"(d[48]),"+f"(d[49]),"+f"(d[50]),"+f"(d[51]),"+f"(d[52]),"+f"(d[53]),"+f"(d[54]),"+f"(d[55]),"+f"(d[56]),"+f"(d[57]),"+f"(d[58]),"+f"(d[59]),"+f"(d[60]),"+f"(d[61]),"+f"(d[62]),"+f"(d[63]),"+f"(d[64]),"+f"(d[65]),"+f"(d[66]),"+f"(d[67]),"+f"(d[68]),"+f"(d[69]),"+f"(d[70]),"+f"(d[71]),"+f"(d[72]),"+f"(d[73]),"+f"(d[74]),"+f"(d[75]),"+f"(d[76]),"+f"(d[77]),"+f"(d[78]),"+f"(d[79])
    : "l"(da), "l"(db), "r"(sd));
}
__device__ __forceinline__ void wg_rs32_00(float* d, uint32_t a0, uint32_t a1, uint32_t a2, uint32_t a3, uint64_t db, int sd) {
  asm volatile("{.reg .pred p; setp.ne.b32 p, %21, 0;\n"
    "wgmma.mma_async.sync.aligned.m64n32k16.f32.bf16.bf16 {%0,%1,%2,%3,%4,%5,%6,%7,%8,%9,%10,%11,%12,%13,%14,%15}, {%16,%17,%18,%19}, %20, p, 1, 1, 0;}"
    : "+f"(d[0]),"+f"(d[1]),"+f"(d[2]),"+f"(d[3]),"+f"(d[4]),"+f"(d[5]),"+f"(d[6]),"+f"(d[7]),"+f"(d[8]),"+f"(d[9]),"+f"(d[10]),"+f"(d[11]),"+f"(d[12]),"+f"(d[13]),"+f"(d[14]),"+f"(d[15])
    : "r"(a0), "r"(a1), "r"(a2), "r"(a3), "l"(db), "r"(sd));
}
__device__ __forceinline__ void wg_rs64_00(float* d, uint32_t a0, uint32_t a1, uint32_t a2, uint32_t a3, uint64_t db, int sd) {
  asm volatile("{.reg .pred p; setp.ne.b32 p, %37, 0;\n"
    "wgmma.mma_async.sync.aligned.m64n64k16.f32.bf16.bf16 {%0,%1,%2,%3,%4,%5,%6,%7,%8,%9,%10,%11,%12,%13,%14,%15,%16,%17,%18,%19,%20,%21,%22,%23,%24,%25,%26,%27,%28,%29,%30,%31}, {%32,%33,%34,%35}, %36, p, 1, 1, 0;}"
    : "+f"(d[0]),"+f"(d[1]),"+f"(d[2]),"+f"(d[3]),"+f"(d[4]),"+f"(d[5]),"+f"(d[6]),"+f"(d[7]),"+f"(d[8]),"+f"(d[9]),"+f"(d[10]),"+f"(d[11]),"+f"(d[12]),"+f"(d[13]),"+f"(d[14]),"+f"(d[15]),"+f"(d[16]),"+f"(d[17]),"+f"(d[18]),"+f"(d[19]),"+f"(d[20]),"+f"(d[21]),"+f"(d[22]),"+f"(d[23]),"+f"(d[24]),"+f"(d[25]),"+f"(d[26]),"+f"(d[27]),"+f"(d[28]),"+f"(d[29]),"+f"(d[30]),"+f"(d[31])
    : "r"(a0), "r"(a1), "r"(a2), "r"(a3), "l"(db), "r"(sd));
}
__device__ __forceinline__ void wg_rs128_00(float* d, uint32_t a0, uint32_t a1, uint32_t a2, uint32_t a3, uint64_t db, int sd) {
  asm volatile("{.reg .pred p; setp.ne.b32 p, %69, 0;\n"
    "wgmma.mma_async.sync.aligned.m64n128k16.f32.bf16.bf16 {%0,%1,%2,%3,%4,%5,%6,%7,%8,%9,%10,%11,%12,%13,%14,%15,%16,%17,%18,%19,%20,%21,%22,%23,%24,%25,%26,%27,%28,%29,%30,%31,%32,%33,%34,%35,%36,%37,%38,%39,%40,%41,%42,%43,%44,%45,%46,%47,%48,%49,%50,%51,%52,%53,%54,%55,%56,%57,%58,%59,%60,%61,%62,%63}, {%64,%65,%66,%67}, %68, p, 1, 1, 0;}"
    : "+f"(d[0]),"+f"(d[1]),"+f"(d[2]),"+f"(d[3]),"+f"(d[4]),"+f"(d[5]),"+f"(d[6]),"+f"(d[7]),"+f"(d[8]),"+f"(d[9]),"+f"(d[10]),"+f"(d[11]),"+f"(d[12]),"+f"(d[13]),"+f"(d[14]),"+f"(d[15]),"+f"(d[16]),"+f"(d[17]),"+f"(d[18]),"+f"(d[19]),"+f"(d[20]),"+f"(d[21]),"+f"(d[22]),"+f"(d[23]),"+f"(d[24]),"+f"(d[25]),"+f"(d[26]),"+f"(d[27]),"+f"(d[28]),"+f"(d[29]),"+f"(d[30]),"+f"(d[31]),"+f"(d[32]),"+f"(d[33]),"+f"(d[34]),"+f"(d[35]),"+f"(d[36]),"+f"(d[37]),"+f"(d[38]),"+f"(d[39]),"+f"(d[40]),"+f"(d[41]),"+f"(d[42]),"+f"(d[43]),"+f"(d[44]),"+f"(d[45]),"+f"(d[46]),"+f"(d[47]),"+f"(d[48]),"+f"(d[49]),"+f"(d[50]),"+f"(d[51]),"+f"(d[52]),"+f"(d[53]),"+f"(d[54]),"+f"(d[55]),"+f"(d[56]),"+f"(d[57]),"+f"(d[58]),"+f"(d[59]),"+f"(d[60]),"+f"(d[61]),"+f"(d[62]),"+f"(d[63])
    : "r"(a0), "r"(a1), "r"(a2), "r"(a3), "l"(db), "r"(sd));
}
__device__ __forceinline__ void wg_rs24_01(float* d, uint32_t a0, uint32_t a1, uint32_t a2, uint32_t a3, uint64_t db, int sd) {
  asm volatile("{.reg .pred p; setp.ne.b32 p, %17, 0;\n"
    "wgmma.mma_async.sync.aligned.m64n24k16.f32.bf16.bf16 {%0,%1,%2,%3,%4,%5,%6,%7,%8,%9,%10,%11}, {%12,%13,%14,%15}, %16, p, 1, 1, 1;}"
    : "+f"(d[0]),"+f"(d[1]),"+f"(d[2]),"+f"(d[3]),"+f"(d[4]),"+f"(d[5]),"+f"(d[6]),"+f"(d[7]),"+f"(d[8]),"+f"(d[9]),"+f"(d[10]),"+f"(d[11])
    : "r"(a0), "r"(a1), "r"(a2), "r"(a3), "l"(db), "r"(sd));
}

#define AB_POLY 0x77
__device__ __forceinline__ constexpr bool poly_group(int group) { return (AB_POLY >> (group & 7)) & 1; }

template <int V> struct Int { static constexpr int value = V; };

__device__ __forceinline__ int frag_word(int row, int col) {
  return (((row >> 4) * 40 + (col >> 4)) * 32 + (row & 7) * 4 + ((col & 7) >> 1)) * 4 + ((row >> 3) & 1) + ((col >> 3) & 1) * 2;
}

#define PLACE 4
__device__ __forceinline__ bool helper_sm() {
  uint32_t m; asm("mov.u32 %0, %%smid;" : "=r"(m));
  return m < 2 || m >= 120 || (m >= 92 && m < 102) || (m >= 106 && m < 117) || m == 118;
}
__device__ __forceinline__ void hold_sm() {
  if (threadIdx.x == 0 && helper_sm()) {
    const uint32_t t0 = gtime();
    while (ldg_strong32(g_sync + SY_UP) < 96 && gtime() - t0 < 6000) {}
  }
}

template <int NG>
__device__ __forceinline__ void ln_rows(float4 (&v)[NG][5], uint32_t scratch) {
  const int warp = threadIdx.x >> 5, g = (threadIdx.x & 31) >> 2;
  float stat[NG];
#pragma unroll
  for (int pass = 0; pass < 2; pass++) {
#pragma unroll
    for (int r = 0; r < NG; r++) {
      float s = 0.f;
#pragma unroll
      for (int i = 0; i < 5; i++) {
        float4& t = v[r][i];
        if (pass == 0) s += (t.x + t.y) + (t.z + t.w);
        else { t.x -= stat[r]; t.y -= stat[r]; t.z -= stat[r]; t.w -= stat[r]; s += (t.x * t.x + t.y * t.y) + (t.z * t.z + t.w * t.w); }
      }
      s += __shfl_xor_sync(~0u, s, 1);
      s += __shfl_xor_sync(~0u, s, 2);
      stat[r] = s;
    }
    bar_sync(1, 256);
    if ((threadIdx.x & 3) == 0) {
#pragma unroll
      for (int r = 0; r < NG; r++) sts32(scratch + ((r * 8 + g) * 8 + warp) * 4, __float_as_uint(stat[r]));
    }
    bar_sync(1, 256);
#pragma unroll
    for (int r = 0; r < NG; r++) {
      const float4 a = lds128f(scratch + (r * 8 + g) * 32), b = lds128f(scratch + (r * 8 + g) * 32 + 16);
      stat[r] = (((a.x + a.y) + (a.z + a.w)) + ((b.x + b.y) + (b.z + b.w))) * (1.f / DM);
    }
  }
#pragma unroll
  for (int r = 0; r < NG; r++) {
    const float rs = rsqrtf(stat[r] + 1e-5f);
#pragma unroll
    for (int i = 0; i < 5; i++) { v[r][i].x *= rs; v[r][i].y *= rs; v[r][i].z *= rs; v[r][i].w *= rs; }
  }
}

#define HOLD 1
template <bool FIRST>
__global__ void __launch_bounds__(256) ln_kernel(const __nv_bfloat16* __restrict__ xin) {
  __shared__ __align__(16) float scratch[128];
  const int warp = threadIdx.x >> 5, lane = threadIdx.x & 31;
  TRACE(0);
  if (!FIRST) pdl_wait();
  pdl_launch();
  if (blockIdx.x >= 128) { if (HOLD) hold_sm(); return; }
  float4 v[2][5];
  float4* x = g_x + (blockIdx.x * 80 + warp * 5) * 32 + lane;
#pragma unroll
  for (int r = 0; r < 2; r++)
#pragma unroll
    for (int i = 0; i < 5; i++) {
      if (FIRST) {
        const uint32_t* src = reinterpret_cast<const uint32_t*>(xin) + (blockIdx.x * 16 + r * 8 + (lane >> 2)) * (DM / 2) + warp * 40 + i * 8 + (lane & 3);
        const uint32_t a = src[0], b = src[4];
        v[r][i] = make_float4(bf_lo(a), bf_hi(a), bf_lo(b), bf_hi(b));
        x[(r * 40 + i) * 32] = v[r][i];
      } else {
        v[r][i] = x[(r * 40 + i) * 32];
      }
    }
  ln_rows<2>(v, s2u(scratch));
  {
    uint32_t* xs = g_xs + ((blockIdx.x >> 1) * 80 + warp * 10) * 128 + (blockIdx.x & 1) * 64 + lane;
#pragma unroll
    for (int i = 0; i < 5; i++)
#pragma unroll
      for (int r = 0; r < 2; r++) { xs[i * 256 + r * 32] = pack2(v[r][i].x, v[r][i].y); xs[i * 256 + 128 + r * 32] = pack2(v[r][i].z, v[r][i].w); }
  }
  if (blockIdx.x >= QA_END * 8) {
    uint4* dst = reinterpret_cast<uint4*>(g_xf) + (blockIdx.x * 40 + warp * 5) * 32 + lane;
#pragma unroll
    for (int i = 0; i < 5; i++)
      dst[i * 32] = make_uint4(pack2(v[0][i].x, v[0][i].y), pack2(v[1][i].x, v[1][i].y), pack2(v[0][i].z, v[0][i].w), pack2(v[1][i].z, v[1][i].w));
  } else {
#pragma unroll
    for (int i = 0; i < 5; i++) {
      const int u = warp * 5 + i;
      uint32_t* xn = g_xn + (((blockIdx.x >> 3) * 10 + (u >> 2)) * 16 + (blockIdx.x & 1) * 8 + (blockIdx.x & 6)) * 256 + (u & 3) * 64 + lane;
#pragma unroll
      for (int r = 0; r < 2; r++) { xn[r * 256] = pack2(v[r][i].x, v[r][i].y); xn[r * 256 + 32] = pack2(v[r][i].z, v[r][i].w); }
    }
  }
  TRACE(2);
  if (HOLD) hold_sm();
}

struct XsParams {
  CUtensorMap w[3];
  CUtensorMap o[3];
  const uint32_t* a;
  __nv_bfloat16* out;
  int ntiles, tiles_per_mat, rb0, nowait, stream_out;
  int npf, pft, ahead;
  const uint8_t* pf[4];
};
constexpr int XS_STAGES = 12, XS_STAGE_BYTES = 16384;
constexpr int XS_SMEM = 1024 + XS_STAGES * XS_STAGE_BYTES + 4 * 8192 + 256;
enum { EPI_QKV = 0, EPI_BQKV = 1, EPI_RES = 2, EPI_OUT = 3 };

template <int EPI, bool MC>
__global__ void __launch_bounds__(384, 1) xs_gemm(const __grid_constant__ XsParams p) {
  extern __shared__ uint8_t smem_raw[];
  const uint32_t sb = (s2u(smem_raw) + 1023) & ~1023u;
  const uint32_t stg = sb + XS_STAGES * XS_STAGE_BYTES, bars = stg + 4 * 8192;
  const int warp = __shfl_sync(~0u, threadIdx.x >> 5, 0), lane = threadIdx.x & 31;
  const int tot = (16 - p.rb0) * p.ntiles;
  const int rank = blockIdx.x & 1, bid = MC ? (blockIdx.x & ~15) + rank * 8 + ((blockIdx.x >> 1) & 7) : blockIdx.x;
  const int u0 = p.rb0 * p.ntiles + bid * tot / gridDim.x, u1 = p.rb0 * p.ntiles + (bid + 1) * tot / gridDim.x;
  auto release = [&](int stage) {
    const uint32_t bar = bars + 8 * (XS_STAGES + stage);
    if (lane == 0) mbar_arrive(bar);
    if (MC && lane == 1) asm volatile("mbarrier.arrive.shared::cluster.b64 _, [%0];" :: "r"(mapa(bar, rank ^ 1)) : "memory");
  };
  TRACE(0);
  pdl_launch();
  if (threadIdx.x == 0) {
    for (int i = 0; i < XS_STAGES; i++) { mbar_init(bars + 8 * i, 1); mbar_init(bars + 8 * (XS_STAGES + i), MC ? 16 : 8); }
    fence_async();
    if (MC) asm volatile("fence.mbarrier_init.release.cluster;" ::: "memory");
  }
  __syncthreads();
  if (MC) asm volatile("barrier.cluster.arrive.relaxed.aligned; barrier.cluster.wait.aligned;" ::: "memory");
  if (warp >= 8) {
    asm volatile("setmaxnreg.dec.sync.aligned.u32 40;");
    if (warp == 8 && lane == 0) {
      int st = 0; uint32_t ph = 1;
      auto l2_ahead = [&](int u) {
        if (u >= u1 || (!MC && u != u0)) return;
        const int t = u % p.ntiles, m = t / p.tiles_per_mat, col = (t - m * p.tiles_per_mat) * 64;
        for (int kb = MC ? u / p.ntiles : 0; kb < (MC ? 10 : 5); kb += MC ? 16 : 1)
          asm volatile("cp.async.bulk.prefetch.tensor.2d.L2.global [%0, {%1, %2}];" :: "l"(&p.w[m]), "r"(col), "r"(kb * (MC ? 64 : 128)) : "memory");
      };
      for (int i = 0; i < p.ahead; i++) l2_ahead(u0 + i);
      for (int u = u0; u < u1; u++) {
        const int t = u % p.ntiles, m = t / p.tiles_per_mat, col = (t - m * p.tiles_per_mat) * 64;
        l2_ahead(u + p.ahead);
        if (u == u0 || t == 0) {
          if (u == u0 && !p.nowait) pdl_wait();
          for (int i = 0; i < 10; i++) {
            mbar_wait(bars + 8 * (XS_STAGES + st), ph);
            mbar_expect(bars + 8 * st, XS_STAGE_BYTES);
            for (int w = 0; w < 8; w++)
              bulk_load(sb + st * XS_STAGE_BYTES + w * 2048, p.a + ((u / p.ntiles * 8 + w) * 40 + 4 * i) * 128, 2048, bars + 8 * st);
            if (++st == XS_STAGES) { st = 0; ph ^= 1; }
          }
        }
        if (u1 - u <= p.pft && blockIdx.x < 128) {
          const int bytes = 61440 / p.pft;
          const size_t off = (size_t)blockIdx.x * 61440 + (u1 - u - 1) * bytes;
          for (int i = 0; i < p.npf; i++) asm volatile("cp.async.bulk.prefetch.L2.global [%0], %1;" :: "l"(p.pf[i] + off), "r"(bytes) : "memory");
        }
        for (int kb = 0; kb < 5; kb++) {
          mbar_wait(bars + 8 * (XS_STAGES + st), ph);
          mbar_expect(bars + 8 * st, XS_STAGE_BYTES);
          if (MC) {
            asm volatile("cp.async.bulk.tensor.2d.shared::cluster.global.mbarrier::complete_tx::bytes.multicast::cluster [%0], [%1, {%3, %4}], [%2], %5;"
                         :: "r"(sb + st * XS_STAGE_BYTES + rank * 8192), "l"(&p.w[m]), "r"(bars + 8 * st), "r"(col), "r"(kb * 128 + rank * 64), "h"((uint16_t)3) : "memory");
          } else {
            tma_load(sb + st * XS_STAGE_BYTES, &p.w[m], col, kb * 128, bars + 8 * st);
          }
          if (++st == XS_STAGES) { st = 0; ph ^= 1; }
        }
      }
    }
    __syncwarp();
    if (MC) asm volatile("barrier.cluster.arrive.relaxed.aligned;" ::: "memory");
  } else {
    asm volatile("setmaxnreg.inc.sync.aligned.u32 232;");
    const int wg = warp >> 2, g = lane >> 2, c = lane & 3;
    if (!p.nowait) pdl_wait();
    XT(0);
    int st = 0; uint32_t ph = 0;
    for (int u = u0; u < u1;) {
    const int rb = u / p.ntiles, t0 = u - rb * p.ntiles, t1 = min(p.ntiles, t0 + u1 - u);
    uint32_t a[160];
#pragma unroll
    for (int i = 0; i < 10; i++) {
      mbar_wait(bars + 8 * st, ph);
#pragma unroll
      for (int k = 4 * i; k < 4 * i + 4; k++) {
        const uint4 v = lds128(sb + st * XS_STAGE_BYTES + warp * 2048 + (k & 3) * 512 + lane * 16);
        a[4 * k] = v.x; a[4 * k + 1] = v.y; a[4 * k + 2] = v.z; a[4 * k + 3] = v.w;
      }
      __syncwarp();
      release(st);
      if (++st == XS_STAGES) { st = 0; ph ^= 1; }
    }
    XT(1);
    const int row0 = rb * 128 + wg * 64;
    for (int t = t0; t < t1; t++, u++) {
      float d[32];
      int prev = 0;
      if (wg == 1 || u != u0) bar_sync(4 + wg, 256);
#pragma unroll
      for (int kb = 0; kb < 5; kb++) {
        mbar_wait(bars + 8 * st, ph);
        const uint64_t db = mkdesc(sb + st * XS_STAGE_BYTES, 0, 1024, 1);
        if (kb == 0) wg_fence();
#pragma unroll
        for (int kk = 0; kk < 8; kk++) {
          const int k = kb * 8 + kk;
          wg_rs64_01(d, a[4 * k], a[4 * k + 1], a[4 * k + 2], a[4 * k + 3], db + kk * 128, k != 0);
        }
        wg_commit();
        if (kb == 4 && (wg == 0 || u + 1 != u1)) bar_arrive(5 - wg, 256);
        if (kb > 0) { wg_wait<1>(); release(prev); }
        prev = st;
        if (++st == XS_STAGES) { st = 0; ph ^= 1; }
      }
      wg_wait<0>();
      reg_fence<32>(d);
      release(prev);
      XT(2 + u - u0);
      if (EPI == EPI_QKV) {
        const int m = t / p.tiles_per_mat, col = (t - m * p.tiles_per_mat) * 64;
        const uint32_t buf = stg + (wg * 2 + (u & 1)) * 8192;
        const int r = (warp & 3) * 16 + (lane & 7) + ((lane >> 3) & 1) * 8;
#pragma unroll
        for (int j = 0; j < 8; j += 2)
          stsm4(buf + r * 128 + (((j + (lane >> 4)) ^ (r & 7)) << 4), pack2(d[4 * j], d[4 * j + 1]), pack2(d[4 * j + 2], d[4 * j + 3]),
                pack2(d[4 * j + 4], d[4 * j + 5]), pack2(d[4 * j + 6], d[4 * j + 7]));
        fence_async();
        if ((threadIdx.x & 127) == 0) bulk_wait_read<0>();
        bar_sync(2 + wg, 128);
        if ((threadIdx.x & 127) == 0) {
          if (p.stream_out == 2) {} else if (p.stream_out) tma_store_stream(&p.o[m], buf, col, row0); else tma_store(&p.o[m], buf, col, row0);
          bulk_commit();
        }
      } else {
        float4* x = g_x + ((rb * 16 + warp * 2) * 40 + t * 4) * 32 + lane;
        uint32_t* out = reinterpret_cast<uint32_t*>(p.out) + (rb * 128 + warp * 16 + g) * (DM / 2) + t * 32 + c;
#pragma unroll
        for (int j = 0; j < 4; j++) {
#pragma unroll
          for (int r = 0; r < 2; r++) {
            float4 y = x[(r * 40 + j) * 32];
            y.x += d[8 * j + 2 * r]; y.y += d[8 * j + 2 * r + 1]; y.z += d[8 * j + 4 + 2 * r]; y.w += d[8 * j + 5 + 2 * r];
            if (EPI == EPI_RES) x[(r * 40 + j) * 32] = y;
            else { out[r * 8 * (DM / 2) + 8 * j] = pack2(y.x, y.y); out[r * 8 * (DM / 2) + 8 * j + 4] = pack2(y.z, y.w); }
          }
        }
      }
    }
    }
    if (EPI == EPI_QKV && (threadIdx.x & 127) == 0) {
      bulk_wait<0>();
      if (p.nowait) { fence_async_global(); red_release(g_sync + SY_Q, 1); }
    }
    __syncwarp();
    if (MC) asm volatile("barrier.cluster.arrive.relaxed.aligned; barrier.cluster.wait.aligned;" ::: "memory");
    TRACE(2);
  }
}

__device__ __forceinline__ uint8_t* pool_at(uint32_t off) {
  return reinterpret_cast<uint8_t*>((reinterpret_cast<uintptr_t>(g_pool) + 8191) & ~(uintptr_t)8191) + off; }
__device__ __forceinline__ uint32_t page_latency(uint32_t* w) {
  uint32_t best = ~0u;
  stg_strong32(w, 0u);
  for (int r = 0; r < 4; r++) {
    uint32_t t0, t1, v;
    asm volatile("mov.u32 %0, %%clock;" : "=r"(t0) :: "memory");
    asm volatile("atom.relaxed.gpu.global.exch.b32 %0, [%1], 0;" : "=r"(v) : "l"(w) : "memory");
    asm volatile("{.reg .u32 t; add.u32 t, %1, 1; mov.u32 %0, %%clock; sub.u32 %0, %0, %1;}" : "=r"(t1) : "r"(__shfl_sync(1u, v, 0)) : "memory");
    best = min(best, t1 - t0);
  }
  return best;
}
__global__ void __launch_bounds__(128) probe_kernel() {
  __shared__ int near0[4];
  TRACE(0);
  pdl_launch();
  const int w = threadIdx.x >> 5, slot = w == 0 ? NSLOT : blockIdx.x + 132 * (w - 1);
  if ((threadIdx.x & 31) == 0 && (w == 0 || slot < NSLOT)) {
    uint32_t* q = reinterpret_cast<uint32_t*>(pool_at(slot * 8192)) + (w == 0 ? (blockIdx.x & 31) * 32 + (blockIdx.x >> 5) : 0);
    near0[w] = page_latency(q) < page_latency(q + 1024);
  }
  __syncthreads();
  TRACE(2);
  if ((threadIdx.x & 31) == 0) {
    const int part = near0[0] ? 0 : 1;
    if (w == 0) { uint32_t smid; asm("mov.u32 %0, %%smid;" : "=r"(smid)); g_smpart[smid & 255] = part; }
    else if (slot < NSLOT) g_orient[slot] = near0[w] ? part : 1 - part;
  }
}

struct ChainParams {
  CUtensorMap wq, wk, wv, wo;
  const __nv_bfloat16* mem0;
  int d1, d2, dn, dx, mode, zero;
};
constexpr int CH_WQ = 0, CH_WO = 81920, CH_X = CH_WO + 86016, CH_M = CH_X, CH_Q = CH_X + 34816, CH_KM = CH_Q + 2048, CH_VP = CH_KM + 2048,
              CH_K = CH_X + 40960, CH_O = CH_K, CH_L = CH_K + 3072, CH_V = CH_K + 4096, CH_VX = CH_V + 12288, CH_R2 = CH_VX,
              CH_SX = CH_VX + 3072, CH_SO = CH_SX + 2048, CH_ID = CH_SO + 1024, CH_TAB = CH_ID + 256, CH_BAR = CH_TAB + 384;
constexpr int CH_SMEM = CH_BAR + 144;
constexpr int MB_WO = CH_BAR, MB_WQ = CH_BAR + 8, MB_X = CH_BAR + 16, MB_V = CH_BAR + 24, MB_T = CH_BAR + 32, MB_F = CH_BAR + 40, MB_G = CH_BAR + 48, MB_W = CH_BAR + 56;
enum { NB_PROJ = 1, NB_O = 2, NB_W1 = 3, NB_PRE = 4, NB_ST = 5, NB_MEM = 6, NB_XFREE = 7, NB_H1 = 8, NB_PUB = 9, NB_W2 = 10, NB_PROJ2 = 11, NB_PRE2 = 12, NB_H2 = 13, NB_W1V = 14 };
#define CH_NQ 9
#define CH_XMODE 2
#define CH_PUSH 1
#define CH_CHAIN 0
#define CH_GATE 1
#define CH_PA 6
#define CH_PB 10
#define CH_PC 12
#define CH_PL 3
#define CH_DBL 0x2108
#define CH_PD 2
#define CH_ZD 1
#define SCHED() asm volatile("griddepcontrol.launch_dependents;" ::: "memory")
__device__ __forceinline__ uint32_t opaque(uint32_t x) { return __shfl_sync(~0u, x, threadIdx.x & 31); }
__device__ __forceinline__ uint32_t nz(uint32_t x) { uint32_t r; asm("max.u32 %0, %1, 1;" : "=r"(r) : "r"(x)); return r; }
__device__ __forceinline__ uint32_t set_tag(uint32_t w, uint32_t tag) { uint32_t r; asm("lop3.b32 %0, %1, %2, 1, 0xD8;" : "=r"(r) : "r"(w), "r"(tag)); return r; }
__device__ __forceinline__ uint32_t pack_tag(float lo, float hi, uint32_t tag) { return set_tag(__byte_perm(__float_as_uint(lo) + tag, pack2(hi, hi), 0x7632), tag); }
__device__ __forceinline__ uint32_t differ(uint32_t a, uint32_t b, uint32_t t) { uint32_t r; asm("lop3.b32 %0, %1, %2, %3, 0x7E;" : "=r"(r) : "r"(a), "r"(b), "r"(t)); return r; }
__device__ __forceinline__ uint32_t clk64() { uint64_t c; asm volatile("mov.u64 %0, %%clock64;" : "=l"(c) :: "memory"); return (uint32_t)c; }
__device__ __forceinline__ void until(uint32_t t) { while ((int)(clk64() - t) < 0) {} }
__device__ __forceinline__ float rcp(float x) { float y; asm("rcp.approx.ftz.f32 %0, %1;" : "=f"(y) : "f"(x)); return y; }

__device__ __forceinline__ void push_values(uint32_t sb, int s, int j) {
  const int r1 = j == 2 ? 0 : j + 1, r2 = j == 0 ? 2 : j - 1;
  const uint32_t src = sb + CH_V + j * 4096;
  if (s < NSEG - 1) {
    fence_async();
    bulk_push(mapa(src, r1), src, 4096, mapa(sb + MB_V, r1));
    bulk_push(mapa(src, r2), src, 4096, mapa(sb + MB_V, r2));
  }
}

template <int WG>
__device__ __forceinline__ void chain_compute(const ChainParams& p, const uint32_t sb) {
  const int tid = threadIdx.x & 127, t4 = __shfl_sync(~0u, tid >> 5, 0), lane = tid & 31;
  const int cta = blockIdx.x, h = cta / 3, j = cta - 3 * h;
  uint32_t ak[80], av[80], tw[4 * CH_NQ];
  const uint32_t wq = opaque(sb + CH_WQ + (WG * 320 + (lane & 7) + (lane >> 4) * 8) * 128 + (((2 * t4 + ((lane >> 3) & 1)) ^ (lane & 7)) << 4));
#pragma unroll
  for (int k = 0; k < 20; k++) {
    if (k == 0 || (WG * 20 + k) % 8 == 0) mbar_wait(sb + MB_W + 8 * ((WG * 20 + k) / 8), 0);
    ldsm4t(&ak[4 * k], wq + k * 2048);
  }
  bar_arrive(NB_PROJ2, 384);
#pragma unroll
  for (int k = 0; k < 20; k++) {
    if (k == 0 || (WG * 20 + k) % 8 == 0) mbar_wait(sb + MB_W + 40 + 8 * ((WG * 20 + k) / 8), 0);
    ldsm4t(&av[4 * k], wq + CH_WO + k * 2048);
  }
  bar_arrive(NB_PRE2, 384);
  const int r1 = j == 2 ? 0 : j + 1, r2 = j == 0 ? 2 : j - 1;
  const uint32_t l16 = opaque(sb + lane * 16), l8 = opaque(sb + lane * 8), l4 = opaque(sb + lane * 4);
  const uint32_t t16 = l16 + t4 * 512, t8 = l8 + t4 * 256;
  auto refill = [&]() {
#pragma unroll
    for (int k = 0; k < CH_NQ; k++) ldsm4t(&tw[4 * k], wq + k * 2048);
  };
  auto batch = [&](float* d, const uint32_t (&a)[80], int acc, bool fill) {
    const uint64_t d0 = mkdesc(1024 + CH_X + WG * 20480, 512, 128, 0);
    wg_fence();
#pragma unroll
    for (int k = 0; k < 20; k++) {
      if (fill && !(k & 1) && k / 2 < CH_NQ) {
        uint32_t w = wq;
        if (k > 0 && CH_CHAIN) asm volatile("lop3.b32 %0, %1, %2, %3, 0xF8;" : "=r"(w) : "r"(wq), "r"(tw[2 * k - 1]), "r"(p.zero));
        __syncwarp();
        ldsm4t(&tw[2 * k], w + k * 1024);
        __syncwarp();
      }
      wg_rs32_00(d, a[4 * k], a[4 * k + 1], a[4 * k + 2], a[4 * k + 3], d0 + k * 64, acc | k);
    }
    wg_commit();
    wg_wait<0>();
    reg_fence<16>(d);
  };
  auto tokens = [&](int s, auto first) {
    float d[16];
    mbar_wait(sb + MB_T, s & 1);
    batch(d, WG == 0 ? ak : av, 0, WG == 0 && !first.value);
    s--; TM(10); s++;
    if (WG == 1 && !first.value) mbar_wait(sb + MB_F, (s - 1) & 1);
    const uint32_t kt = t16 + CH_K, vt = t16 + CH_V + j * 4096;
#pragma unroll
    for (int i = 0; i < 2; i++)
      sts128((WG == 0 ? kt : vt) + i * 2048, make_uint4(pack2(d[8 * i], d[8 * i + 1]), pack2(d[8 * i + 2], d[8 * i + 3]), pack2(d[8 * i + 4], d[8 * i + 5]), pack2(d[8 * i + 6], d[8 * i + 7])));
    if (first.value || CH_GATE != 1) bar_sync(NB_H1, 256); else bar_sync(NB_PUB, 384);
    const uint32_t own = WG == 0 ? vt : kt;
#pragma unroll
    for (int i = 0; i < 2; i++) {
      const uint4 t = lds128(own + i * 2048);
      d[8 * i] = bf_lo(t.x); d[8 * i + 1] = bf_hi(t.x); d[8 * i + 2] = bf_lo(t.y); d[8 * i + 3] = bf_hi(t.y);
      d[8 * i + 4] = bf_lo(t.z); d[8 * i + 5] = bf_hi(t.z); d[8 * i + 6] = bf_lo(t.w); d[8 * i + 7] = bf_hi(t.w);
    }
    reg_fence<16>(d);
    if (!first.value && CH_GATE == 2) bar_sync(NB_PUB, 384);
    batch(d, WG == 0 ? av : ak, 1, WG == 1 && !first.value);
    s--; TM(11); s++;
    if (WG == 0) bar_arrive(NB_XFREE, 256);
#pragma unroll
    for (int i = 0; i < 2; i++) {
      const uint32_t w0 = pack2(d[8 * i], d[8 * i + 1]), w1 = pack2(d[8 * i + 2], d[8 * i + 3]), w2 = pack2(d[8 * i + 4], d[8 * i + 5]), w3 = pack2(d[8 * i + 6], d[8 * i + 7]);
      if (WG == 1) stsm4t(own + i * 2048, w0, w1, w2, w3); else stsm4(own + i * 2048, w0, w1, w2, w3);
    }
    if (CH_PUSH == 0 && WG == 0) {
      if (t4 == 0) {
        bar_sync(NB_H2, 128);
        if (elect()) push_values(sb, s, j);
        __syncwarp();
      } else {
        bar_arrive(NB_H2, 128);
      }
    }
    if (first.value) { mbar_wait(sb + MB_WQ, 0); refill(); mbar_wait(sb + MB_WO, 0); }
  };
  asm volatile("barrier.cluster.wait.aligned;" ::: "memory");
  tokens(0, Int<1>());
  uint32_t wo = opaque(sb + CH_WO + (WG == 0 ? (t4 >> 1) * 36864 : 73728 + t4 * 1024) + ((lane & 7) + (lane >> 4) * 8) * 64 +
                             (((((lane >> 3) & 1) + (WG == 0 ? (t4 & 1) * 2 : 0)) ^ ((lane >> 1) & 3)) << 4));
  const uint32_t kmul = __shfl_sync(~0u, tid & 32 ? -3 : 1, 0), ko0 = __shfl_sync(~0u, (tid >> 6) * 3072 + (tid & 32) * 24, 0),
                 ko1 = __shfl_sync(~0u, (tid >> 6) * 1024 + 1024 + (tid & 32) * 24, 0);
  uint32_t tag = opaque(1);
  const uint32_t o768 = __shfl_sync(~0u, (tid >> 5) * 768, 0);
  bar_sync(NB_ST, 384);
  uint8_t* pdst[WG == 0 ? 6 : 1];
#pragma unroll
  for (int i = 0; i < (WG == 0 ? 6 : 1); i++) {
    const int line = WG == 0 ? 24 * j + 12 * (t4 >> 1) + 2 * (t4 & 1) + 4 * (i >> 1) + (i & 1) : j == 0 ? 72 + t4 : 74 + 2 * j + (t4 & 1);
    pdst[i] = pool_at(__shfl_sync(~0u, lds32(sb + CH_TAB + line * 4), 0) + h * 128);
  }
  auto project = [&](int s, float (&dv)[4], uint4 (&kf)[2]) {
    float dq[4] = {}, dk[4] = {};
    uint32_t b[40], w[80];
#pragma unroll
    for (int i = 0; i < 4 * CH_NQ; i++) w[i] = tw[i];
    bar_sync(NB_MEM, 384);
    ldsm4t(&b[0], l16 + CH_M + WG * 5120);
    ldsm4t(&b[4], l16 + CH_M + WG * 5120 + 512);
    TMD(0, b[0]);
    int nw = CH_NQ, nb = 2;
#pragma unroll
    for (int k = 0; k < 20; k++) {
      SCHED();
      mma16(dq, w[4 * k], w[4 * k + 1], w[4 * k + 2], w[4 * k + 3], b[2 * k], b[2 * k + 1]);
      mma16(dk, ak[4 * k], ak[4 * k + 1], ak[4 * k + 2], ak[4 * k + 3], b[2 * k], b[2 * k + 1]);
      mma16(dv, av[4 * k], av[4 * k + 1], av[4 * k + 2], av[4 * k + 3], b[2 * k], b[2 * k + 1]);
#pragma unroll
      for (int i = 0; i < (CH_DBL >> k & 1) + 1; i++) {
        if (nb < 10 && 2 * nb <= nw) { ldsm4t(&b[4 * nb], l16 + CH_M + WG * 5120 + nb * 512); nb++; }
        else if (nw < 20) { ldsm4t(&w[4 * nw], wq + nw * 2048); nw++; }
        else if (WG == 1 && nw < 22) { kf[nw - 20] = ldsm4v(l16 + ((l16 ^ tag) & 256) * kmul + (nw == 20 ? ko0 : ko1) + CH_K); nw++; }
      }
    }
    const float k2 = 0.07216878364870322f * 1.44269504089f;
    sts32(l4 + t4 * 512 + CH_Q + WG * 128, pack2(dq[0] * k2, dq[1] * k2));
    sts32(l4 + t4 * 512 + CH_Q + WG * 128 + 256, pack2(dq[2] * k2, dq[3] * k2));
    stsm2t(t16 + CH_KM + WG * 256, pack2(dk[0], dk[1]), pack2(dk[2], dk[3]));
    if (WG == 1) sts128f(t16 + CH_VP, dv[0], dv[1], dv[2], dv[3]);
    TM(1);
  };
#pragma unroll 1
  for (int s = 0; s < NSEG - 1; s++) {
    float dv[4] = {};
    uint4 kf[2];
    project(s, dv, kf);
    bar_sync(NB_PROJ, 256);
    if (WG == 0) {
      const float4 pv = lds128f(t16 + CH_VP);
      const uint32_t v0 = pack2(dv[0] + pv.x, dv[1] + pv.y), v1 = pack2(dv[2] + pv.z, dv[3] + pv.w);
      const uint32_t xo = t8 + CH_VX + j * 1024;
      st_async64(mapa(xo, r1), v0, v1, mapa(sb + MB_X, r1));
      st_async64(mapa(xo, r2), v0, v1, mapa(sb + MB_X, r2));
      sts64(xo, v0, v1);
      __syncwarp();
      if (elect()) mbar_arrive(sb + MB_X);
      bar_arrive(NB_PROJ2, 256);
      TM(3);
      uint32_t w[144];
      auto tile_of = [](int n) { return n < 27 ? n % 3 : (0x26484 >> 2 * (n - 27)) & 3; };
      auto step_of = [](int n) { return n < 27 ? n / 3 : 9 + ((0x29610 >> 2 * (n - 27)) & 3); };
      auto wload = [&](int n) { ldsm4t(&w[4 * n], wo + tile_of(n) * 12288 + (step_of(n) % 3) * 4096 + (step_of(n) / 3) * 1024); };
#pragma unroll
      for (int n = 0; n < CH_PA; n++) wload(n);
      bar_sync(NB_PRE, 256);
#pragma unroll
      for (int n = CH_PA; n < CH_PB; n++) wload(n);
      bar_arrive(NB_PRE2, 256);
      if (CH_PC > CH_PB) {
        mbar_wait(sb + MB_X, s & 1);
        for (int i = 0; i < CH_PD; i++) wo = __shfl_xor_sync(~0u, wo, p.zero);
#pragma unroll
        for (int n = CH_PB; n < CH_PC; n++) wload(n);
      }
      TM(4);
      bar_sync(NB_O, 256);
      {
        float x[3][4] = {};
        uint32_t ob[24];
        float4 l;
        ldsm4t(&ob[0], l16 + CH_O);
        ldsm4t(&ob[4], l16 + CH_O + 512);
        TMD(7, ob[0]);
        int nw = CH_PC, no = 2;
        float i0, i1;
        uint8_t* dst[6];
        uint32_t lo[6], hi[6];
        auto pre = [&](int i) { lo[i] = __float_as_uint(x[i >> 1][2 * (i & 1)] * i0) + tag; hi[i] = pack2(0.f, x[i >> 1][2 * (i & 1) + 1] * i1); };
        auto emit = [&](int i) { stg_strong32(dst[i], set_tag(__byte_perm(lo[i], hi[i], 0x7632), tag)); };
#pragma unroll
        for (int n = 0; n < 36; n++) {
          SCHED();
          mma16(x[tile_of(n)], w[4 * n], w[4 * n + 1], w[4 * n + 2], w[4 * n + 3], ob[step_of(n) * 2], ob[step_of(n) * 2 + 1]);
          if (n >= CH_PL) {
            if (no < 6 && no * 2 <= step_of(min(nw, 35))) { ldsm4t(&ob[4 * no], l16 + CH_O + no * 512); no++; }
            else if (nw < 36) { wload(nw); nw++; }
          }
          if (n == 18) l = lds128f(sb + CH_L + ((l16 ^ tag) & 0x30));
          if (n == 26) { i0 = rcp(l.x + l.y); i1 = rcp(l.z + l.w); asm volatile("" : "+f"(i0), "+f"(i1)); }
          if (n >= 28 && n < 34) { dst[n - 28] = pdst[n - 28] + ((l4 ^ tag) & 0x7c); asm volatile("" : "+l"(dst[n - 28])); }
          if (n == 32) { for (int i = 0; i < 2; i++) { pre(i); asm volatile("" : "+r"(lo[i]), "+r"(hi[i])); } }
          if (n == 33) { emit(0); emit(1); }
        }
        for (int i = 2; i < 6; i++) pre(i);
        for (int i = 2; i < 6; i++) emit(i);
      }
      TM(8);
    } else {
      {
        float d0[4] = {}, d1[4] = {}, dm[4] = {};
        uint32_t q[16], km[4];
#pragma unroll
        for (int e = 0; e < 4; e++) {
          ldsm4t(&q[4 * e], l16 + (e ^ t4) * 512 + CH_Q);
          if (e == 1) ldsm4(km, t16 + CH_KM);
        }
        SCHED();
        mma16(d0, q[0], q[1], q[2], q[3], kf[0].x, kf[0].y);
        mma16(d1, q[4], q[5], q[6], q[7], kf[0].z, kf[0].w);
        mma16(dm, q[0], q[1], q[2], q[3], hadd2(km[0], km[2]), hadd2(km[1], km[3]));
        mma16(d0, q[8], q[9], q[10], q[11], kf[1].x, kf[1].y);
        mma16(d1, q[12], q[13], q[14], q[15], kf[1].z, kf[1].w);
        const uint32_t w0 = pack2((d0[0] + d0[2]) + (d1[0] + d1[2]), (d0[1] + d0[3]) + (d1[1] + d1[3])), w1 = pack2(dm[0] + dm[2], dm[1] + dm[3]);
        const uint32_t xo = l4 + t4 * 128, x1 = mapa(xo, r1), x2 = mapa(xo, r2);
        st_async32(x1 + CH_SX + 512, w1, mapa(sb + MB_X, r1));
        st_async32(x2 + CH_SX + 1536, w1, mapa(sb + MB_X, r2));
        st_async32(x1 + CH_SX, w0, mapa(sb + MB_X, r1));
        st_async32(x2 + CH_SX + 1024, w0, mapa(sb + MB_X, r2));
        sts32(xo + CH_SO, w0);
        sts32(xo + CH_SO + 512, w1);
      }
      TM(3);
      float sc[3][4] = {};
      uint32_t wd[12];
      float big;
      auto attend = [&](auto first) {
        uint4 vb[6];
        uint2 vm[3];
        float e[10];
        uint32_t ow[6];
        if (first.value) {
          const uint2 id = lds64(l8 + CH_ID);
          bar_sync(NB_W1V, 160);
          uint32_t r[8];
          ldsm4(r, l16 + CH_SO); ldsm4(r + 4, l16 + CH_SO + 512);
#pragma unroll
          for (int u = 0; u < 6; u++) vb[u] = ldsm4v(t16 + CH_V + u * 2048);
          bar_arrive(NB_PRE, 256);
          uint32_t sxa = l16 + ((l16 ^ tag) & 256) * 3;
          asm volatile("" : "+r"(sxa));
          sxa += CH_SX;
          SCHED();
          mma8(sc[0], r[0], r[1], id.x);
          mma8(sc[1], r[2], r[3], id.x);
          mma16(sc[2], r[4], r[5], r[6], r[7], id.x, id.y);
          TM(7);
          mbar_wait(sb + MB_X, s & 1);
          TM(4);
          uint32_t t[16];
          ldsm4(t, sxa); ldsm4(t + 4, sxa + 256); ldsm4(t + 8, sxa + 512);
          SCHED();
          mma16(sc[0], t[0], t[1], t[2], t[3], id.x, id.y);
          ldsm4(t + 12, sxa + 768);
          SCHED();
          mma16(sc[1], t[4], t[5], t[6], t[7], id.x, id.y);
#pragma unroll
          for (int u = 0; u < 2; u++) vm[u] = lds64(t8 + CH_VX + u * 1024);
          SCHED();
          e[0] = ex2(sc[0][0]);
          mma16(sc[2], t[8], t[9], t[10], t[11], id.x, id.y);
          vm[2] = lds64(t8 + CH_VX + 2048);
          SCHED();
          e[1] = ex2(sc[0][1]);
          ldsm4t(&wd[0], wo);
          SCHED();
          e[2] = ex2(sc[0][2]);
          SCHED();
          e[3] = ex2(sc[0][3]);
          mma16(sc[2], t[12], t[13], t[14], t[15], id.x, id.y);
          SCHED();
          e[4] = ex2(sc[1][0]);
          ldsm4t(&wd[4], wo + 4096);
          SCHED();
          e[5] = ex2(sc[1][1]);
        } else {
#pragma unroll
          for (int u = 0; u < 6; u++) vb[u] = ldsm4v(t16 + CH_V + u * 2048);
#pragma unroll
          for (int u = 0; u < 3; u++) vm[u] = lds64(t8 + CH_VX + u * 1024);
        }
        float o[3][4] = {};
        if (!first.value) {
#pragma unroll
          for (int i = 0; i < 6; i++) e[i] = ex2(sc[i >> 2][i & 3]);
        }
        const uint32_t p1 = pack2(e[0], e[1]), p2 = pack2(e[2], e[3]);
        float l = (e[0] + e[1]) + (e[2] + e[3]);
        asm volatile("" : "+f"(l));
        SCHED();
        e[6] = ex2(sc[1][2]);
        mma16(o[0], vb[0].x, vb[0].y, vb[0].z, vb[0].w, p1, p2);
        if (first.value) { sc[2][0] += sc[2][2]; sc[2][1] += sc[2][3]; }
        SCHED();
        e[7] = ex2(sc[1][3]);
        mma16(o[1], vb[2].x, vb[2].y, vb[2].z, vb[2].w, p1, p2);
        SCHED();
        e[8] = ex2(sc[2][0]);
        mma16(o[2], vb[4].x, vb[4].y, vb[4].z, vb[4].w, p1, p2);
        big = fmaxf(fmaxf(fmaxf(fabsf(sc[0][0]), fabsf(sc[0][1])), fmaxf(fabsf(sc[0][2]), fabsf(sc[0][3]))), fmaxf(fabsf(sc[2][0]), fabsf(sc[2][1])));
        SCHED();
        e[9] = ex2(sc[2][1]);
        const uint32_t p3 = pack2(e[4], e[5]), p4 = pack2(e[6], e[7]);
        l += (e[4] + e[5]) + (e[6] + e[7]);
#pragma unroll
        for (int u = 0; u < 3; u++) mma16(o[u], vb[2 * u + 1].x, vb[2 * u + 1].y, vb[2 * u + 1].z, vb[2 * u + 1].w, p3, p4);
        big = fmaxf(big, fmaxf(fmaxf(fabsf(sc[1][0]), fabsf(sc[1][1])), fmaxf(fabsf(sc[1][2]), fabsf(sc[1][3]))));
        SCHED();
        const uint32_t p0 = pack2(e[8], e[9]);
        l += e[8] + e[9];
        l += __shfl_xor_sync(~0u, l, 1);
        if (first.value) ldsm4t(&wd[8], wo + 8192);
#pragma unroll
        for (int u = 0; u < 3; u++) mma8(o[u], vm[u].x, vm[u].y, p0);
        SCHED();
#pragma unroll
        for (int u = 0; u < 3; u++) { ow[2 * u] = pack2(o[u][0], o[u][1]); ow[2 * u + 1] = pack2(o[u][2], o[u][3]); }
        stsm4(l16 + o768 + CH_O, ow[0], ow[1], ow[2], ow[3]);
        stsm2(l16 + o768 + CH_O + 512, ow[4], ow[5]);
        if (t4 == 0) sts32(sb + CH_L + (((l4 ^ tag) >> 1) & 0x3c), __float_as_uint(l));
      };
      attend(Int<1>());
      const uint32_t redo = __any_sync(~0u, big > 30.f);
      TM(6);
      asm volatile("{.reg .pred p; setp.eq.u32 p, %0, 0; @p bar.arrive 2, 256;}" :: "r"(redo) : "memory");
      if (redo) {
        float mx = fmaxf(sc[2][0], sc[2][1]);
#pragma unroll
        for (int i = 0; i < 4; i++) mx = fmaxf(mx, fmaxf(sc[0][i], sc[1][i]));
        mx = fmaxf(mx, __shfl_xor_sync(~0u, mx, 1));
        mx = fmaxf(mx, __shfl_xor_sync(~0u, mx, 2));
#pragma unroll
        for (int i = 0; i < 4; i++) { sc[0][i] -= mx; sc[1][i] -= mx; }
        sc[2][0] -= mx; sc[2][1] -= mx;
        attend(Int<0>());
        bar_arrive(NB_O, 256);
      }
      {
        float z[4] = {};
        const uint32_t scr = l8 + CH_V + r1 * 4096;
        uint32_t ow[6];
        __syncwarp();
        uint32_t oa = l16;
        for (int i = 0; i < CH_ZD; i++) oa = __shfl_xor_sync(~0u, oa, p.zero);
        ldsm4t(ow, oa + o768 + CH_O);
        ldsm2t(ow + 4, oa + o768 + CH_O + 512);
#pragma unroll
        for (int u = 0; u < 3; u++) mma16(z, wd[4 * u], wd[4 * u + 1], wd[4 * u + 2], wd[4 * u + 3], ow[2 * u], ow[2 * u + 1]);
        if (j == 0) {
          float y[4] = {};
          uint32_t we[12];
#pragma unroll
          for (int u = 0; u < 3; u++) ldsm4t(&we[4 * u], (wo ^ 32) + u * 4096);
#pragma unroll
          for (int u = 0; u < 3; u++) mma16(y, we[4 * u], we[4 * u + 1], we[4 * u + 2], we[4 * u + 3], ow[2 * u], ow[2 * u + 1]);
          sts64f(scr + t4 * 512 + 2048, y[0], y[1]); sts64f(scr + t4 * 512 + 2304, y[2], y[3]);
        }
        sts64f(scr + t4 * 512, z[0], z[1]); sts64f(scr + t4 * 512 + 256, z[2], z[3]);
        bar_sync(NB_W1, 128);
        if (j == 0 || t4 < 2) {
          float2 q[4];
          const float4 l = lds128f(sb + CH_L + ((l16 ^ tag) & 0x30));
#pragma unroll
          for (int i = 0; i < 4; i++) q[i] = lds64f(scr + (t4 >> 1) * 2048 + (t4 & 1) * 256 + i * 512);
          stg_strong32(pdst[0] + ((l4 ^ tag) & 0x7c), pack_tag(((q[0].x + q[1].x) + (q[2].x + q[3].x)) * rcp(l.x + l.y), ((q[0].y + q[1].y) + (q[2].y + q[3].y)) * rcp(l.z + l.w), tag));
        }
      }
      TM(2);
    }
    bar_sync(NB_ST, 384);
    tokens(s + 1, Int<0>());
    TM(9);
    tag ^= 0x10001;
  }
  {
    float dv[4] = {};
    uint4 kf[2];
    project(NSEG - 1, dv, kf);
    bar_sync(NB_PROJ, 256);
    if (WG == 0) {
      const float4 pv = lds128f(t16 + CH_VP);
      sts64(t8 + CH_VX + j * 1024, pack2(dv[0] + pv.x, dv[1] + pv.y), pack2(dv[2] + pv.z, dv[3] + pv.w));
      bar_arrive(NB_PROJ2, 256);
      bar_arrive(NB_PRE2, 256);
    }
  }
}

__device__ __forceinline__ void chain_comm(const ChainParams& p, const uint32_t sb) {
  [[maybe_unused]] constexpr int WG = 2;
  const int tid = threadIdx.x & 127, t4 = __shfl_sync(~0u, tid >> 5, 0), lane = tid & 31;
  const int cta = blockIdx.x, h = cta / 3, j = cta - 3 * h, colbase = cta * 64;
  const uint8_t* const xs = reinterpret_cast<const uint8_t*>(g_xs);
  if (t4 == 0 && elect()) {
    mbar_expect(sb + MB_T, 40960);
    bulk_load(sb + CH_X, xs, 40960, sb + MB_T);
  }
  uint32_t smid; asm("mov.u32 %0, %%smid;" : "=r"(smid));
  if (tid == 96) stg_strong32(g_ctapart + cta, ldg_strong32(g_smpart + (smid & 255)) + 1);
  const int orient = tid < NSLOT ? (int)ldg_strong32(g_orient + tid) : 0;
  bar_sync(NB_PROJ2, 384);
  if (t4 == 0 && elect()) {
    mbar_expect(sb + MB_WQ, 81920);
    for (int i = 0; i < 5; i++) tma_load(sb + CH_WQ + i * 16384, &p.wq, colbase, i * 128, sb + MB_WQ);
  }
  bar_sync(NB_PRE2, 384);
  if (t4 == 0 && elect()) {
    mbar_expect(sb + MB_WO, 86016);
    for (int i = 0; i < 6; i++) tma_load(sb + CH_WO + i * 12288, &p.wo, j * 192 + i * 32, h * 192, sb + MB_WO);
    tma_load(sb + CH_WO + 73728, &p.wo, j == 0 ? 576 : 592 + j * 16, h * 192, sb + MB_WO);
  }
  if (tid < NSLOT) {
    const uint32_t* part_of = g_ctapart + (tid >= 80 ? cta : tid);
    uint32_t reader = 0;
    int n = 0;
    while (reader == 0) { reader = ldg_strong32(part_of); spin_guard(n); }
    sts32(sb + CH_TAB + tid * 4, tid * 8192 + (orient + 1 == reader ? 0 : 4096));
  }
  __syncwarp();
  asm volatile("barrier.cluster.wait.aligned;" ::: "memory");
  const uint32_t l8 = opaque(sb + t4 * 256 + lane * 8);
  {
    const uint32_t* m0 = reinterpret_cast<const uint32_t*>(p.mem0) + (lane >> 2) * (DM / 2) + t4 * 80 + (lane & 3);
    uint32_t g[20];
#pragma unroll
    for (int i = 0; i < 20; i++) g[i] = transpose8(m0[i * 4]);
    const uint32_t id = (lane >> 3) == (lane & 3) ? ((lane & 4) ? 0x3f800000u : 0x00003f80u) : 0u;
    if (t4 == 0) sts64(l8 + CH_ID, id, id);
    bar_sync(NB_XFREE, 256);
#pragma unroll
    for (int i = 0; i < 20; i++) sts32(sb + CH_M + (t4 * 20 + i) * 128 + lane * 4, g[i]);
  }
  bar_sync(NB_ST, 384);
  uint8_t* const pool = pool_at(0);
  const uint8_t* const psrc = pool + opaque(lds32(sb + CH_TAB + min(cta, 79) * 4) + t4 * 1024 + lane * 4);
  const uint32_t mdst = opaque((80 + cta / 20) * 8192 + (t4 & 1) * 4096 + (cta % 20) * 128 + lane * 4);
  int st = 0;
  uint32_t tag = opaque(1);
  bar_sync(NB_MEM, 384);
#pragma unroll 1
  for (int s = 0;; s++) {
    TM(0);
    STAT(0);
    if (t4 == 0) {
      if (elect()) {
        const uint32_t t0 = clk64();
        if (CH_XMODE == 3 && s < NSEG - 1) {
          mbar_expect(sb + MB_T, 40960);
          mbar_arrive_remote(mapa(sb + MB_G, j == 2 ? 0 : j + 1)); mbar_arrive_remote(mapa(sb + MB_G, j == 0 ? 2 : j - 1));
        }
        if (CH_PUSH == 1) push_values(sb, s, j);
        fence_async();
        uint8_t* dst = g_kv + ((s >> 2) * 96 + cta) * KV_BYTES + (s & 3) * 4096;
        bulk_store(dst + KV_K, sb + CH_K, 4096);
        bulk_store(dst + KV_V, sb + CH_V + j * 4096, 4096);
        bulk_commit();
        if (CH_XMODE == 3 && s < NSEG - 1) {
          mbar_wait(sb + MB_G, s & 1);
          until(t0 + p.dx);
          asm volatile("cp.async.bulk.shared::cluster.global.mbarrier::complete_tx::bytes.multicast::cluster [%0], [%1], %2, [%3], %4;"
                       :: "r"(sb + CH_X + 10240 + j * 8192), "l"(xs + (s + 1) * 40960 + 10240 + j * 8192), "r"(8192), "r"(sb + MB_T), "h"((uint16_t)7) : "memory");
        }
        bulk_wait_read<0>();
      }
      __syncwarp();
    }
    if (t4 == 2 && s < NSEG - 1) { mbar_wait(sb + MB_V, s & 1); bar_arrive(NB_W1V, 160); }
    auto xload = [&]() {
      mbar_wait(sb + MB_G, s & 1);
      asm volatile("cp.async.bulk.shared::cluster.global.mbarrier::complete_tx::bytes.multicast::cluster [%0], [%1], %2, [%3], %4;"
                   :: "r"(sb + CH_X + j * 11648), "l"(xs + (s + 1) * 40960 + j * 11648), "r"(j == 2 ? 11520 : 11648), "r"(sb + MB_T), "h"((uint16_t)7) : "memory");
    };
    bar_sync(NB_PROJ2, 256);
    if (t4 == 0 && s < NSEG - 1 && elect()) {
      if (CH_XMODE < 2) { mbar_arrive_remote(mapa(sb + MB_G, j == 2 ? 0 : j + 1)); mbar_arrive_remote(mapa(sb + MB_G, j == 0 ? 2 : j - 1)); }
      mbar_expect(sb + MB_X, 4096);
      if (CH_XMODE < 3) mbar_expect(sb + MB_T, 40960);
      if (CH_XMODE >= 2) bulk_load(sb + CH_X, xs + (s + 1) * 40960, CH_XMODE == 2 ? 34816 : 10240, sb + MB_T);
    }
    __syncwarp();
    STAT(1);
    TM(1);
    {
      const uint2 a = lds64(l8 + t4 * 256 + CH_KM), b = lds64(l8 + t4 * 256 + CH_KM + 256), v = lds64(l8 + CH_VX + j * 1024);
      uint8_t* dst = g_kv + (((s >> 2) * 96 + cta) * KV_BYTES + (s & 3) * 1024 + (l8 & 1023));
      *reinterpret_cast<uint2*>(dst + KV_KM) = make_uint2(hadd2(a.x, b.x), hadd2(a.y, b.y));
      *reinterpret_cast<uint2*>(dst + KV_VM) = v;
    }

    if (CH_XMODE == 1 && t4 == 1 && s < NSEG - 1 && elect()) xload();
    __syncwarp();
    TM(4);
    bar_sync(NB_PRE2, 256);
    if (t4 == 0 && s < NSEG - 1 && elect()) {
      if (CH_XMODE == 0) xload();
      bulk_load(sb + CH_Q, xs + (s + 1) * 40960 + 34816, 6144, sb + MB_T);
    }
    __syncwarp();
    if ((s & 3) == 3) {
      bar_sync(NB_W2, 128);
      if (t4 == 0 && elect()) { bulk_wait<0>(); fence_async_global(); red_release(g_sync + (s >> 2) * 8 + 4, 1); }
      __syncwarp();
    }
    if (s == NSEG - 1) break;
    if (s == NSEG - 3 && cta == 95 && t4 == 2 && elect()) red_release(g_sync + 15 * 8 + 4, 0x10000);
    __syncwarp();
    const uint8_t* ms = pool + (lds32(sb + CH_TAB + (80 + st * 4 + t4) * 4) + (l8 & 255));
    uint8_t* md = pool + (mdst + (t4 < 2 ? st : st == 2 ? 0 : st + 1) * 32768);
    asm volatile("" : "+l"(ms), "+l"(md));
    TM(2);
    bar_sync(NB_ST, 384);
    __syncwarp();
    uint32_t tg = clk32();
    if (t4 == 3 && elect()) {
      if (s < NSEG - 2) mbar_expect(sb + MB_V, 8192);
      mbar_arrive_remote(mapa(sb + MB_F, j == 2 ? 0 : j + 1));
      mbar_arrive_remote(mapa(sb + MB_F, j == 0 ? 2 : j - 1));
    }
    __syncwarp();
    STAT(2);
    if (cta < 80) {
      TM(3);
      until(tg + p.d1);
      float2 q[4];
      for (int n = 0;;) {
        uint32_t u[8];
#pragma unroll
        for (int i = 0; i < 8; i++) u[i] = ldg_strong32(psrc + i * 128);
        spin_guard(n);
        sts64f(l8 + CH_R2, ((bf_lo(u[0]) + bf_lo(u[1])) + (bf_lo(u[2]) + bf_lo(u[3]))) + ((bf_lo(u[4]) + bf_lo(u[5])) + (bf_lo(u[6]) + bf_lo(u[7]))),
               ((bf_hi(u[0]) + bf_hi(u[1])) + (bf_hi(u[2]) + bf_hi(u[3]))) + ((bf_hi(u[4]) + bf_hi(u[5])) + (bf_hi(u[6]) + bf_hi(u[7]))));
        uint32_t bad;
        asm volatile("{.reg .pred p, q; .reg .b32 a; lop3.b32 a, %1, %2, %3, 0xFE; lop3.b32 a, a, %4, 1, 0xA8; setp.ne.u32 p, a, 0;\n"
                     "bar.red.or.pred q, %5, 128, p; selp.u32 %0, 1, 0, q;}"
                     : "=r"(bad) : "r"(differ(u[0], u[1], tag)), "r"(differ(u[2], u[3], tag)), "r"(differ(u[4], u[5], tag)), "r"(differ(u[6], u[7], tag)), "n"((int)NB_W2) : "memory");
#pragma unroll
        for (int k = 0; k < 4; k++) asm volatile("ld.volatile.shared.v2.f32 {%0,%1}, [%2];" : "=f"(q[k].x), "=f"(q[k].y) : "r"(l8 - t4 * 256 + CH_R2 + k * 256) : "memory");
        TMV(12, n - 1);
        if (!bad) break;
      }
      if (CH_GATE) bar_arrive(NB_PUB, 384);
      SCHED();
      TM(9);
      stg_strong32(md, min(nz(pack2((q[0].x + q[1].x) + (q[2].x + q[3].x), (q[0].y + q[1].y) + (q[2].y + q[3].y))), t4 < 2 ? ~0u : 0u));
      tg = clk64() + p.d2;
      TM(8);
    } else {
      tg += p.dn;
      if (CH_GATE) bar_arrive(NB_PUB, 384);
    }
    STAT(3);
    until(tg);
    TM(10);
    for (int n = 0;;) {
      uint2 g[10];
#pragma unroll
      for (int i = 0; i < 10; i++) g[i] = ldg_strong64(ms + i * 256);
      if (n == 0) bar_sync(NB_XFREE, 256);
      spin_guard(n);
      uint32_t m = ~0u;
#pragma unroll
      for (int i = 0; i < 10; i++) { sts64(l8 + CH_M + t4 * 2304 + i * 256, g[i].x, g[i].y); m = __vimin3_u32(m, g[i].x, g[i].y); }
      TMV(13, n - 1);
      if (!__any_sync(~0u, m == 0)) break;
    }
    TM(11);
    if (t4 == 0) bar_sync(NB_MEM, 384); else bar_arrive(NB_MEM, 384);
    if (++st == 3) st = 0;
    tag ^= 0x10001;
  }
  TRACE(2);
}

#define CH_R0 232
#define CH_R1 232
#define CH_R2N 40
__global__ void __launch_bounds__(384, 1) chain_kernel(const __grid_constant__ ChainParams p) {
  extern __shared__ __align__(1024) uint8_t smem_raw[];
  const uint32_t sb = s2u(smem_raw);
  const int wg = __shfl_sync(~0u, threadIdx.x >> 7, 0);
  if (threadIdx.x < 32 && elect()) {
    atomicAdd(g_sync + SY_UP, 1);
    if ((sb & 0xffffff) != 1024) __trap();
    mbar_init(sb + MB_WO, 1); mbar_init(sb + MB_WQ, 1); mbar_init(sb + MB_X, 5); mbar_init(sb + MB_V, 1); mbar_init(sb + MB_T, 1); mbar_init(sb + MB_F, 2); mbar_init(sb + MB_G, 2);
    for (int i = 0; i < 10; i++) mbar_init(sb + MB_W + 8 * i, 1);
    asm volatile("fence.mbarrier_init.release.cluster;" ::: "memory");
    mbar_expect(sb + MB_V, 8192);
    for (int i = 0; i < 10; i++) {
      const int n = i % 5 < 2 ? (i % 5) * 2 : i % 5 == 2 ? 1 : i % 5;
      const uint32_t bar = sb + MB_W + 8 * (n + (i < 5 ? 0 : 5));
      mbar_expect(bar, 16384);
      tma_load(sb + (i < 5 ? CH_WQ : CH_WO) + n * 16384, i < 5 ? &p.wk : &p.wv, blockIdx.x * 64, n * 128, bar);
    }
  }
  __syncthreads();
  asm volatile("barrier.cluster.arrive.relaxed.aligned;" ::: "memory");
  pdl_wait();
  pdl_launch();
  if (wg == 2) {
    asm volatile("setmaxnreg.dec.sync.aligned.u32 %0;" :: "n"(CH_R2N));
    chain_comm(p, sb);
  } else if (wg == 0) {
    asm volatile("setmaxnreg.inc.sync.aligned.u32 %0;" :: "n"(CH_R0));
    chain_compute<0>(p, sb);
  } else {
    asm volatile("setmaxnreg.inc.sync.aligned.u32 %0;" :: "n"(CH_R1));
    chain_compute<1>(p, sb);
  }
}

struct PostParams { CUtensorMap q, o, wq, wo, wb; int nq, pace; };
constexpr int OP_STAGES = 4, OP_STAGE_BYTES = 57344;
constexpr int OP_SMEM = 1024 + OP_STAGES * OP_STAGE_BYTES + 256 + 1024;
enum { IT_ATT = 0, IT_OP = 1, IT_FIN = 2, IT_BQ = 3 };

__device__ __forceinline__ uint32_t item_count(int type, int b) { return type == IT_ATT ? 32 : type == IT_OP ? 2 * op_split(b) : type == IT_FIN ? fin_items(b) : bq_items(b); }
__device__ __forceinline__ int item_stages(int type, int b) { return type == IT_ATT ? 3 : type == IT_OP ? 96 / op_split(b) : type == IT_FIN ? (b < OP_B8 ? 2 + op_split(b) : 5) : 10; }
__device__ __forceinline__ uint32_t item_need(int type, int b) { return type == IT_ATT ? 96 : item_count(type - 1, b); }
__device__ __forceinline__ void wait_count(const uint32_t* c, uint32_t n) {
  int spin = 0;
  while ((ld_acquire(c) & 0xffff) < n) { __nanosleep(32); spin_guard(spin); }
}

template <int HALF, bool QREG>
__device__ __forceinline__ void attn_a_warp(uint32_t sb, uint32_t bars, int& st, uint32_t& ph, uint32_t done, int& nd, const float* q) {
  constexpr int NT = HALF ? 5 : 3;
  const int lane = threadIdx.x & 31, g = lane >> 2, c = lane & 3, seg = (threadIdx.x >> 5) & 3, l7 = lane & 7;
  const uint32_t qrow = (seg * 32 + HALF * 16 + (lane & 15)) * 128;
  float sc[NT][4] = {};
  uint32_t base[3];
#pragma unroll
  for (int u = 0; u < 3; u++) {
    mbar_wait(bars + 8 * st, ph);
    base[u] = sb + st * OP_STAGE_BYTES;
    if (++st == OP_STAGES) { st = 0; ph ^= 1; }
    uint32_t km[8];
#pragma unroll
    for (int q = 0; q < 2; q++) ldsm4(&km[4 * q], base[u] + 49152 + seg * 1024 + q * 512 + lane * 16);
#pragma unroll
    for (int kk = 0; kk < 4; kk++) {
      uint32_t a[4];
      if (QREG) {
#pragma unroll
        for (int i = 0; i < 4; i++) a[i] = pack2(q[32 * u + 8 * kk + 2 * i], q[32 * u + 8 * kk + 2 * i + 1]);
      } else {
        ldsm4(a, base[u] + qrow + (((2 * kk + (lane >> 4)) ^ l7) << 4));
      }
      mma16(sc[0], a[0], a[1], a[2], a[3], km[2 * kk], km[2 * kk + 1]);
#pragma unroll
      for (int t = 0; t <= HALF; t++) {
        const uint4 kb = ldsm4v(base[u] + 16384 + seg * 4096 + t * 2048 + kk * 512 + lane * 16);
        mma16(sc[1 + 2 * t], a[0], a[1], a[2], a[3], kb.x, kb.y);
        mma16(sc[2 + 2 * t], a[0], a[1], a[2], a[3], kb.z, kb.w);
      }
    }
  }
  const float k2 = 0.07216878364870322f * 1.44269504089f, NEG = -INFINITY;
  if (2 * c > g) { sc[NT - 2][0] = NEG; sc[NT - 1][2] = NEG; }
  if (2 * c + 1 > g) { sc[NT - 2][1] = NEG; sc[NT - 1][3] = NEG; }
  sc[NT - 1][0] = sc[NT - 1][1] = NEG;
  uint32_t pp[NT][2]; float inv[2];
#pragma unroll
  for (int hh = 0; hh < 2; hh++) {
    float m = NEG, l = 0.f;
#pragma unroll
    for (int n = 0; n < NT; n++) m = fmaxf(m, fmaxf(sc[n][2 * hh], sc[n][2 * hh + 1]));
    m = fmaxf(m, __shfl_xor_sync(~0u, m, 1)); m = fmaxf(m, __shfl_xor_sync(~0u, m, 2));
#pragma unroll
    for (int n = 0; n < NT; n++) { const float x = ex2((sc[n][2 * hh] - m) * k2), y = ex2((sc[n][2 * hh + 1] - m) * k2); l += x + y; pp[n][hh] = pack2(x, y); }
    l += __shfl_xor_sync(~0u, l, 1); l += __shfl_xor_sync(~0u, l, 2);
    inv[hh] = 1.f / l;
  }
#pragma unroll
  for (int u = 0; u < 3; u++) {
    float o[8][4] = {};
    uint32_t vm[8];
#pragma unroll
    for (int q = 0; q < 4; q++) { const uint2 t = lds64(base[u] + 53248 + seg * 1024 + q * 256 + lane * 8); vm[2 * q] = t.x; vm[2 * q + 1] = t.y; }
#pragma unroll
    for (int n = 0; n < 8; n += 2) {
      mma8(o[n], pp[0][0], pp[0][1], vm[n]);
      mma8(o[n + 1], pp[0][0], pp[0][1], vm[n + 1]);
#pragma unroll
      for (int t = 0; t <= HALF; t++) {
        const uint4 vb = ldsm4v(base[u] + 32768 + seg * 4096 + t * 2048 + n * 256 + (lane & 8) * 32 + (lane & 16) * 8 + l7 * 16);
        mma16(o[n], pp[1 + 2 * t][0], pp[1 + 2 * t][1], pp[2 + 2 * t][0], pp[2 + 2 * t][1], vb.x, vb.y);
        mma16(o[n + 1], pp[1 + 2 * t][0], pp[1 + 2 * t][1], pp[2 + 2 * t][0], pp[2 + 2 * t][1], vb.z, vb.w);
      }
    }
#pragma unroll
    for (int n = 0; n < 8; n += 2)
      stsm4(base[u] + qrow + (((n + (lane >> 4)) ^ l7) << 4), pack2(o[n][0] * inv[0], o[n][1] * inv[0]), pack2(o[n][2] * inv[1], o[n][3] * inv[1]),
            pack2(o[n + 1][0] * inv[0], o[n + 1][1] * inv[0]), pack2(o[n + 1][2] * inv[1], o[n + 1][3] * inv[1]));
    fence_async();
    __syncwarp();
    if (lane == 0) mbar_arrive(done + 8 * (nd & 7));
    nd++;
  }
}

template <int NG>
__device__ __forceinline__ void fin_item(uint32_t sb, uint32_t bars, int& st, uint32_t& ph, uint32_t scratch, int b, int idx) {
  const int warp = threadIdx.x >> 5, lane = threadIdx.x & 31;
  float4* x = g_x + ((b * 16 + idx * NG) * 40 + warp * 5) * 32 + lane;
  float4 v[NG][5];
#pragma unroll
  for (int r0 = 0; r0 < NG; r0 += 2) {
    mbar_wait(bars + 8 * st, ph);
#pragma unroll
    for (int r = r0; r < r0 + 2 && r < NG; r++)
#pragma unroll
      for (int i = 0; i < 5; i++) v[r][i] = lds128f(sb + st * OP_STAGE_BYTES + (((r - r0) * 40 + warp * 5 + i) * 32 + lane) * 16);
    __syncwarp();
    if (lane == 0) mbar_arrive(bars + 8 * (OP_STAGES + st));
    if (++st == OP_STAGES) { st = 0; ph ^= 1; }
  }
  for (int k0 = 0; k0 < op_split(b); k0 += 4 / NG) {
    mbar_wait(bars + 8 * st, ph);
#pragma unroll
    for (int q4 = 0; q4 < 4; q4++)
#pragma unroll
      for (int i = 0; i < 5; i++) {
        const uint2 q = lds64(sb + st * OP_STAGE_BYTES + ((q4 * 40 + warp * 5 + i) * 32 + lane) * 8);
        float4& t = v[q4 % NG][i];
        t.x += bf_lo(q.x); t.y += bf_hi(q.x); t.z += bf_lo(q.y); t.w += bf_hi(q.y);
      }
    __syncwarp();
    if (lane == 0) mbar_arrive(bars + 8 * (OP_STAGES + st));
    if (++st == OP_STAGES) { st = 0; ph ^= 1; }
  }
#pragma unroll
  for (int r = 0; r < NG; r++)
#pragma unroll
    for (int i = 0; i < 5; i++) x[(r * 40 + i) * 32] = v[r][i];
  ln_rows<NG>(v, scratch);
#pragma unroll
  for (int i = 0; i < 5; i++) {
    const int u = warp * 5 + i;
    uint32_t* xn = g_xn + ((b * 10 + (u >> 2)) * 16 + idx * NG) * 256 + (u & 3) * 64 + lane;
#pragma unroll
    for (int r = 0; r < NG; r++) { xn[r * 256] = pack2(v[r][i].x, v[r][i].y); xn[r * 256 + 32] = pack2(v[r][i].z, v[r][i].w); }
  }
}

__global__ void __launch_bounds__(384, 1) post_kernel(const __grid_constant__ PostParams p) {
  extern __shared__ uint8_t smem_raw[];
  const uint32_t sb = (s2u(smem_raw) + 1023) & ~1023u, bars = sb + OP_STAGES * OP_STAGE_BYTES;
  const uint32_t bIF = bars + 64, bIE = bars + 96, done = bars + 128, bGo = bars + 192, slots = bars + 208, scratch = bars + 256;
  const int warp = __shfl_sync(~0u, threadIdx.x >> 5, 0), lane = threadIdx.x & 31;
  TRACE(0);
  pdl_launch();
  if (threadIdx.x == 0) {
    for (int i = 0; i < 4; i++) {
      mbar_init(bars + 8 * i, 1); mbar_init(bars + 8 * (OP_STAGES + i), 8);
      mbar_init(bIF + 8 * i, 1); mbar_init(bIE + 8 * i, 2); mbar_init(done + 8 * i, 8); mbar_init(done + 32 + 8 * i, 8);
    }
    mbar_init(bGo, 1);
    fence_async();
  }
  __syncthreads();
  if (warp >= 8) {
    asm volatile("setmaxnreg.dec.sync.aligned.u32 56;");
    if (warp == 9) {
      const int b = lane & 15;
      for (int n = 0;; n++) {
        if (n > 0) mbar_wait(bGo, (n - 1) & 1);
        mbar_wait(bIE + 8 * (n & 3), ((n >> 2) & 1) ^ 1);
        int code, spin = 0, ticket = 0;
        if (lane == 0) ticket = atomicAdd(g_sync + SY_T, 1);
        for (;;) {
          const uint4 hd = ldg_strong128(g_sync + b * 8), pr = ldg_strong128(g_sync + b * 8 + 4);
          const uint32_t hv[4] = {hd.x, hd.y, hd.z, hd.w}, pv[4] = {pr.x, pr.y, pr.z, pr.w};
          const uint32_t chain_done = __ballot_sync(~0u, (pr.x & 0xffff) >= 96);
          int left[4], avail[4], rdy = 0, claimed = 0, upstream = 0;
#pragma unroll
          for (int t = 0; t < 4; t++) {
            const int cnt = lane < 16 ? item_count(t, b) : 0;
            left[t] = max(cnt - (int)hv[t], 0);
            claimed += cnt - left[t];
            const bool ready = (pv[t] & 0xffff) >= item_need(t, b);
            rdy |= ready << t;
            bool ok = ready || (t == IT_ATT ? pr.x >= 0x10000 : !upstream || (t == IT_OP && (chain_done >> 15 & 1)));
            if (t == IT_BQ && (chain_done >> 12 & 9) == 1) ok = false;
            avail[t] = ok ? left[t] : 0;
            upstream |= __any_sync(~0u, left[t] > 0);
          }
          if (!upstream) { code = -1; break; }
          int rank = max(__shfl_sync(~0u, ticket, 0) - __reduce_add_sync(~0u, claimed), 0), type = -1, mine = 0;
#pragma unroll
          for (int c = 0; c < 7; c++) {
            const int t = c == 0 || c == 4 ? IT_FIN : c == 1 || c == 6 ? IT_ATT : c == 2 ? IT_OP : IT_BQ;
            int a = c == 1 || c == 2 || ((rdy >> t & 1) == (c < 4)) ? avail[t] : 0;
            if (c == 6) a = b < QA_END && !(rdy & 1) && ((chain_done << 1 | 1) >> b & 1) ? left[t] : 0;
            const int tot = __reduce_add_sync(~0u, a);
            if (type < 0) { if (rank < tot) { type = t; mine = a; } else rank -= tot; }
          }
          if (type >= 0) {
#pragma unroll
            for (int o = 1; o < 16; o <<= 1) { const int y = __shfl_up_sync(~0u, mine, o); if (lane >= o) mine += y; }
            const int blk = __ffs(__ballot_sync(~0u, mine > rank)) - 1;
            const int early = !(__shfl_sync(~0u, rdy, blk) >> type & 1);
            uint32_t idx = 0;
            if (lane == 0) { idx = atomicAdd(g_sync + blk * 8 + type, 1); ld_acquire(g_sync + blk * 8 + 4 + type); }
            idx = __shfl_sync(~0u, idx, 0);
            if (idx < item_count(type, blk)) { code = (chain_done >> 15 & 1) << 22 | (chain_done >> 13 & 1) << 21 | early << 20 | type << 16 | blk << 8 | idx; break; }
          } else {
            __nanosleep(50);
          }
          spin_guard(spin);
        }
        if (lane == 0) {
          fence_async_global();
          sts32(slots + 4 * (n & 3), code);
          mbar_arrive(bIF + 8 * (n & 3));
        }
        __syncwarp();
        if (code < 0) break;
      }
    } else if (warp == 8 && lane == 0) {
      int st = 0; uint32_t ph = 1, tn = clk32();
      int pace = 0;
      auto gap = [&](int kb) {
        if (pace) {
          uint32_t t = clk32();
          while ((int)(t - tn) < 0) t = clk32();
          tn = t + kb * pace;
        }
      };
      auto tma_paced = [&](uint32_t dst, const CUtensorMap* m, int c0, int c1, uint32_t bar, int kb) { gap(kb); tma_load(dst, m, c0, c1, bar); };
      auto bulk_paced = [&](uint32_t dst, const void* src, int bytes, uint32_t bar) {
        const int piece = pace ? (bytes % 8192 ? 10240 : 8192) : bytes;
        for (int o = 0; o < bytes; o += piece) { gap(piece >> 10); bulk_load(dst + o, static_cast<const uint8_t*>(src) + o, piece, bar); }
      };
      for (int n = 0;; n++) {
        mbar_wait(bIF + 8 * (n & 3), (n >> 2) & 1);
        const int code = (int)lds32(slots + 4 * (n & 3));
        if (code < 0) break;
        const int type = (code >> 16) & 15, b = (code >> 8) & 255, idx = code & 255;
        mbar_arrive(bIE + 8 * (n & 3));
        pace = code >> 22 ? 0 : p.pace;
        const int nst = item_stages(type, b), ng = 16 / fin_items(b);
        const int kb0 = type == IT_OP ? (idx >> 1) * nst : 0;
        const bool half = type == IT_BQ && bq_items(b) == 12;
        const int col = type == IT_ATT ? idx * 192 : type == IT_OP ? (idx & 1) * 320 : idx * (half ? 160 : 320);
        const int pre = !(code >> 20 & 1) ? 0 : type == IT_ATT ? 2 : type == IT_FIN ? (ng + 1) / 2 : OP_STAGES - 1;
        const bool qa = type == IT_ATT && b < QA_END;
        if (qa) {
          for (int kb = 0; kb < 10; kb++) {
            const uint32_t dst = sb + st * OP_STAGE_BYTES, bar = bars + 8 * st;
            mbar_wait(bars + 8 * (OP_STAGES + st), ph);
            mbar_expect(bar, 40960);
            bulk_paced(dst, g_xn + (b * 10 + kb) * 4096, 16384, bar);
            for (int i = 0; i < 3; i++) tma_paced(dst + 16384 + i * 8192, &p.wq, col + i * 64, kb * 64, bar, 8);
            if (++st == OP_STAGES) { st = 0; ph ^= 1; }
          }
        } else if (type == IT_ATT) {
          wait_count(g_sync + SY_Q, p.nq);
          fence_async_global();
        }
        int sta = st;
        for (int kb = 0; kb < nst; kb++) {
          const uint32_t dst = sb + st * OP_STAGE_BYTES, bar = bars + 8 * st;
          mbar_wait(bars + 8 * (OP_STAGES + st), ph);
          if (type == IT_ATT) {
            mbar_expect(bar, qa ? 40960 : OP_STAGE_BYTES);
            if (!qa) tma_paced(dst, &p.q, col + kb * 64, b * 128, bar, 16);
          } else if (type == IT_FIN) {
            const int bytes = ng == 1 && kb == 0 ? 20480 : 40960;
            mbar_expect(bar, bytes);
            if (kb < (ng + 1) / 2) bulk_paced(dst, g_x + (b * 16 + idx * ng + 2 * kb) * 1280, bytes, bar);
          } else {
            const int nb = half ? 3 : 5;
            mbar_expect(bar, 16384 + nb * 8192);
            for (int i = 0; i < nb; i++) tma_paced(dst + 16384 + i * 8192, type == IT_OP ? &p.wo : &p.wb, col + i * 64, (kb0 + kb) * 64, bar, 8);
          }
          if (++st == OP_STAGES) { st = 0; ph ^= 1; }
          if (kb < pre) continue;
          if (kb == pre) {
            if (pre) { wait_count(g_sync + b * 8 + 4 + type, item_need(type, b)); fence_async_global(); }
            if ((type == IT_ATT || type == IT_FIN) && !(code >> 21)) mbar_arrive(bGo);
          }
          for (int k = kb == pre ? 0 : kb; k <= kb; k++) {
            const uint32_t da = sb + sta * OP_STAGE_BYTES, ba = bars + 8 * sta;
            if (type == IT_ATT) {
              bulk_paced(da + 16384, g_kv + (b * 96 + idx * 3 + k) * KV_BYTES, KV_BYTES, ba);
            } else if (type == IT_OP) {
              tma_paced(da, &p.o, (kb0 + k) * 64, b * 128, ba, 16);
            } else if (type == IT_BQ) {
              bulk_paced(da, g_xn + (b * 10 + k) * 4096, 16384, ba);
            } else if (k >= (ng + 1) / 2) {
              const int k0 = (k - (ng + 1) / 2) * (4 / ng);
              for (int i = 0; i < 4 / ng; i++) bulk_paced(da + i * ng * 10240, g_part + ((b * 16 + k0 + i) * 16 + idx * ng) * 1280, ng * 10240, ba);
            }
            if (++sta == OP_STAGES) sta = 0;
          }
        }
      }
    } else if (warp == 10 && lane == 0) {
      int st = 0, nd = 0;
      for (int n = 0;; n++) {
        mbar_wait(bIF + 8 * (n & 3), (n >> 2) & 1);
        const int code = (int)lds32(slots + 4 * (n & 3));
        if (code < 0) break;
        const int type = (code >> 16) & 15, b = (code >> 8) & 255, idx = code & 255;
        if (type == IT_ATT) {
          if (b < QA_END) st = (st + 10) & (OP_STAGES - 1);
          for (int u = 0; u < 3; u++) {
            mbar_wait(done + 8 * (nd & 7), (nd >> 3) & 1);
            nd++;
            tma_store(&p.o, sb + st * OP_STAGE_BYTES, idx * 192 + u * 64, b * 128);
            bulk_commit();
            bulk_wait_read<0>();
            asm volatile("mbarrier.arrive.shared::cta.b64 _, [%0], 8;" :: "r"(bars + 8 * (OP_STAGES + st)) : "memory");
            st = (st + 1) & (OP_STAGES - 1);
          }
          bulk_wait<0>();
          fence_async_global();
        } else {
          mbar_wait(done + 8 * (nd & 7), (nd >> 3) & 1);
          nd++;
          st = (st + item_stages(type, b)) & (OP_STAGES - 1);
        }
        if (type != IT_BQ) red_release(g_sync + b * 8 + 5 + type, 1);
        mbar_arrive(bIE + 8 * (n & 3));
      }
    }
  } else {
    asm volatile("setmaxnreg.inc.sync.aligned.u32 224;");
    const int wg = warp >> 2, g = lane >> 2, c = lane & 3;
    int st = 0, nd = 0; uint32_t ph = 0;
#pragma unroll 1
    for (int n = 0;; n++) {
      mbar_wait(bIF + 8 * (n & 3), (n >> 2) & 1);
      const int code = __shfl_sync(~0u, (int)lds32(slots + 4 * (n & 3)), 0);
      if (code < 0) { TRACE(2); break; }
      const int type = (code >> 16) & 15, b = (code >> 8) & 255, idx = code & 255;
      ITEM(code & 0xfffff, 0);
      if (type == IT_ATT) {
        if (b < QA_END) {
          float q[96] = {};
          reg_fence<96>(q);
          int prev = 0;
#pragma unroll 1
          for (int kb = 0; kb < 10; kb++) {
            mbar_wait(bars + 8 * st, ph);
            const uint32_t base = sb + st * OP_STAGE_BYTES;
            const uint64_t da = mkdesc(base + wg * 8192, 128, 1024, 0), db = mkdesc(base + 16384, 8192, 1024, 1);
            wg_fence();
#pragma unroll
            for (int kk = 0; kk < 4; kk++) wg_ss192_01(q, da + kk * 16, db + kk * 128, (kb | kk) != 0);
            wg_commit();
            if (kb > 0) { wg_wait<1>(); if (lane == 0) mbar_arrive(bars + 8 * (OP_STAGES + prev)); }
            prev = st;
            if (++st == OP_STAGES) { st = 0; ph ^= 1; }
          }
          wg_wait<0>();
          reg_fence<96>(q);
          if (lane == 0) mbar_arrive(bars + 8 * (OP_STAGES + prev));
          if (wg == 0) attn_a_warp<0, true>(sb, bars, st, ph, done, nd, q); else attn_a_warp<1, true>(sb, bars, st, ph, done, nd, q);
        } else {
          if (wg == 0) attn_a_warp<0, false>(sb, bars, st, ph, done, nd, nullptr); else attn_a_warp<1, false>(sb, bars, st, ph, done, nd, nullptr);
        }
      } else {
        if (type == IT_FIN) {
          if (fin_items(b) == 4) fin_item<4>(sb, bars, st, ph, scratch, b, idx);
          else if (fin_items(b) == 8) fin_item<2>(sb, bars, st, ph, scratch, b, idx);
          else fin_item<1>(sb, bars, st, ph, scratch, b, idx);
        } else {
          float d[160] = {};
          reg_fence<160>(d);
          const int nkb = item_stages(type, b);
          const bool half = type == IT_BQ && bq_items(b) == 12;
          int prev = 0;
          auto mainloop = [&](auto H) {
#pragma unroll 1
            for (int kb = 0; kb < nkb; kb++) {
              mbar_wait(bars + 8 * st, ph);
              const uint32_t base = sb + st * OP_STAGE_BYTES;
              const uint64_t da = mkdesc(base + wg * 8192, 128, 1024, type == IT_OP), db = mkdesc(base + 16384, 8192, 1024, 1);
              const int ka = type == IT_OP ? 2 : 16;
              wg_fence();
#pragma unroll
              for (int kk = 0; kk < 4; kk++) {
                if (H.value) {
                  wg_ss160_01(d, da + kk * ka, db + kk * 128, (kb | kk) != 0);
                } else {
                  wg_ss192_01(d, da + kk * ka, db + kk * 128, (kb | kk) != 0);
                  wg_ss128_01(d + 96, da + kk * ka, db + kk * 128 + 3 * 512, (kb | kk) != 0);
                }
              }
              wg_commit();
              if (kb == nkb - 3 && threadIdx.x == 0 && !(code >> 21)) mbar_arrive(bGo);
              if (kb > 0) { wg_wait<1>(); if (lane == 0) mbar_arrive(bars + 8 * (OP_STAGES + prev)); }
              prev = st;
              if (++st == OP_STAGES) { st = 0; ph ^= 1; }
            }
            wg_wait<0>();
          };
          if (half) mainloop(Int<1>()); else mainloop(Int<0>());
          reg_fence<160>(d);
          if (lane == 0) mbar_arrive(bars + 8 * (OP_STAGES + prev));
          if (type == IT_OP) {
            uint2* dst = g_part + (((b * 16 + (idx >> 1)) * 16 + warp * 2) * 40 + (idx & 1) * 20) * 32 + lane;
#pragma unroll
            for (int u = 0; u < 20; u++) {
              dst[u * 32] = make_uint2(pack2(d[8 * u], d[8 * u + 1]), pack2(d[8 * u + 4], d[8 * u + 5]));
              dst[(40 + u) * 32] = make_uint2(pack2(d[8 * u + 2], d[8 * u + 3]), pack2(d[8 * u + 6], d[8 * u + 7]));
            }
          } else {
            const int row = b * 128 + warp * 16 + g;
            const int h0 = idx * (half ? 8 : 16);
            const float sc = h0 < 32 ? 0.22360679775f * 1.44269504089f : 1.f;
            const bool lo = c < 2;
            uint32_t* da = g_bqkv + (h0 * 256 + (row >> 3)) * 96 + lane;
            uint32_t* db = da + 256 * 96 + (lo ? 2 : -2);
#pragma unroll
            for (int r = 0; r < 2; r++) {
              const uint32_t pad = !(c & 1) && (h0 >= 64 || (h0 >= 32 && (row & 1) && poly_group((row >> 3) + r))) ? 0x00003f80u : 0u;
#pragma unroll
              for (int q = 0; q < 8; q++) {
                if (q >= 4 && half) break;
                uint32_t w[5];
#pragma unroll
                for (int i = 0; i < 5; i++) w[i] = pack2(d[20 * q + 4 * i + 2 * r] * sc, d[20 * q + 4 * i + 2 * r + 1] * sc);
                const int o = q * 2 * 256 * 96 + r * 96;
                da[o] = w[0]; da[o + 32] = w[1]; da[o + 64] = lo ? w[2] : pad;
                db[o] = lo ? w[3] : w[2]; db[o + 32] = lo ? w[4] : w[3]; db[o + 64] = lo ? pad : w[4];
              }
            }
          }
        }
        __syncwarp();
        if (lane == 0) mbar_arrive(done + 8 * (nd & 7));
        nd++;
      }
      if (code >> 21 && threadIdx.x == 128) mbar_arrive(bGo);
      ITEM(code & 0xfffff, 1);
    }
  }
}

constexpr int AB_SMEM = 1024 + 2 * 98304 + 256;
#define AB_N 32
#define AB_WG 4
constexpr int AB_T = AB_WG * 128, AB_PASS = 8 / AB_WG;
__device__ __forceinline__ float ex2_poly(float t) {
  const uint32_t r = __float_as_uint(t) & 0xffff8000u;
  const float f = t - __uint_as_float(r);
  const float p = fmaf(fmaf(fmaf(-5.869912678e-38f, f, -1.700740250e-37f), f, -5.234869734e-37f), f, -7.522601252e-37f);
  uint32_t y;
  asm("mad.lo.u32 %0, %1, 256, %2;" : "=r"(y) : "r"(r), "r"(__float_as_uint(p)));
  return __uint_as_float(y);
}
__device__ __forceinline__ float sq2(uint32_t w) { const float a = bf_lo(w), b = bf_hi(w); return fmaf(a, a, b * b); }

__device__ __forceinline__ void attn_b_store(const float* o, int h, int row0, int lane) {
  const int g = lane >> 2, c = lane & 3;
  const float i0 = 1.f / __shfl_sync(~0u, o[8], (lane & ~3) | 2), i1 = 1.f / __shfl_sync(~0u, o[10], (lane & ~3) | 2);
#pragma unroll
  for (int jj = 0; jj < 3; jj++) {
    if (jj < 2 || c < 2) {
      const int col = h * 20 + 8 * jj + 2 * c;
      g_of[frag_word(row0 + g, col)] = pack2(o[4 * jj] * i0, o[4 * jj + 1] * i0);
      g_of[frag_word(row0 + g + 8, col)] = pack2(o[4 * jj + 2] * i1, o[4 * jj + 3] * i1);
    }
  }
}

__device__ __forceinline__ void attn_b_qk(float* s, uint32_t q0, uint32_t q1, uint32_t q2, uint32_t q3, uint32_t q4, uint32_t q5, uint32_t z0, uint32_t z1,
                                          uint64_t dk, uint64_t dk2) {
  wg_rs32_00(s, q0, q1, q2, q3, dk, 0);
  wg_rs32_00(s, q4, q5, z0, z1, dk2, 1);
}

__global__ void __launch_bounds__(AB_T, 1) attn_b_kernel() {
  extern __shared__ uint8_t smem_raw[];
  const uint32_t sb = (s2u(smem_raw) + 1023) & ~1023u, sK = sb, sV = sb + 98304, bars = sb + 2 * 98304;
  const int warp = __shfl_sync(~0u, threadIdx.x >> 5, 0), lane = threadIdx.x & 31;
  const int h = blockIdx.x >> 2, quarter = blockIdx.x & 3;
  TRACE(0);
  pdl_launch();
  pdl_wait();
  if (blockIdx.x < NSLOT) for (int i = threadIdx.x; i < 512; i += AB_T) reinterpret_cast<uint4*>(pool_at(blockIdx.x * 8192))[i] = make_uint4(0, 0, 0, 0);
  if (blockIdx.x == 30 && threadIdx.x < 96) g_ctapart[threadIdx.x] = 0;
  if (blockIdx.x == 31) for (int i = threadIdx.x; i < SY_N; i += AB_T) g_sync[i] = 0;
  if (threadIdx.x == 0) {
    for (int i = 0; i < 8; i++) mbar_init(bars + 8 * i, 1);
    fence_async();
    const uint8_t* gk = reinterpret_cast<const uint8_t*>(g_bqkv + (32 + h) * 256 * 96);
    const uint8_t* gv = reinterpret_cast<const uint8_t*>(g_bqkv + (64 + h) * 256 * 96);
    for (int i = 0; i < 8; i++) {
      mbar_expect(bars + 8 * i, 24576);
      bulk_load(sK + i * 12288, gk + i * 12288, 12288, bars + 8 * i);
      bulk_load(sV + i * 12288, gv + i * 12288, 12288, bars + 8 * i);
    }
  }
  __syncthreads();
  float qmax = 0.f;
  constexpr int NT = SEQ / AB_N, PER = 256 / AB_N;
#pragma unroll 1
  for (int pass = 0; pass < AB_PASS; pass++) {
    const int row0 = quarter * 512 + ((warp >> 2) * AB_PASS + pass) * 64 + (warp & 3) * 16;
    const uint32_t* gq = g_bqkv + (h * 256 + (row0 >> 3)) * 96 + lane;
    const uint32_t q0 = gq[0], q1 = gq[96], q2 = gq[32], q3 = gq[128];
    uint32_t q4 = gq[64], q5 = gq[160];
    const uint32_t z0 = gq[64 + 3 - (lane & 3)], z1 = gq[160 + 3 - (lane & 3)];
    {
      float n0 = sq2(q0) + sq2(q2) + sq2(q4), n1 = sq2(q1) + sq2(q3) + sq2(q5);
      n0 += __shfl_xor_sync(~0u, n0, 1); n1 += __shfl_xor_sync(~0u, n1, 1);
      n0 += __shfl_xor_sync(~0u, n0, 2); n1 += __shfl_xor_sync(~0u, n1, 2);
      qmax = (n0 > qmax || n0 != n0) ? n0 : qmax;
      qmax = (n1 > qmax || n1 != n1) ? n1 : qmax;
    }
    if ((lane & 3) == 2) { q4 = 0x43BCu; q5 = 0x43BCu; }
    float o[12];
    uint64_t dk = mkdesc(sK, 128, 384, 0), dk2 = mkdesc(sK + 256, 0, 384, 0), dv = mkdesc(sV, 384, 128, 0);
    float sa[AB_N / 2], sb2[AB_N / 2];
    uint32_t pa[AB_N / 4], pb[AB_N / 4];
    if (pass == 0) mbar_wait(bars, 0);
    wg_fence();
    attn_b_qk(sa, q0, q1, q2, q3, q4, q5, z0, z1, dk, dk2);
    wg_commit();
    attn_b_qk(sb2, q0, q1, q2, q3, q4, q5, z0, z1, dk + AB_N * 3, dk2 + AB_N * 3);
    wg_commit();
#pragma unroll 1
    for (int kt = 0; kt < NT; kt += 2) {
      const int nx = kt + 2 < NT ? kt + 2 : 0;
      if (pass == 0 && (nx & (PER - 1)) == 0) mbar_wait(bars + 8 * (nx / PER), 0);
      const uint64_t nk = dk + nx * (AB_N * 3), nk2 = dk2 + nx * (AB_N * 3);
      wg_wait<1>();
      reg_fence<AB_N / 2>(sa);
#pragma unroll
      for (int i = 0; i < AB_N / 4; i++) pa[i] = pack2(ex2(sa[2 * i]), poly_group(i >> 1) ? ex2_poly(sa[2 * i + 1]) : ex2(sa[2 * i + 1]));
      wg_fence();
#pragma unroll
      for (int kk = 0; kk < AB_N / 16; kk++) wg_rs24_01(o, pa[4 * kk], pa[4 * kk + 1], pa[4 * kk + 2], pa[4 * kk + 3], dv + kk * 48, kk | kt);
      attn_b_qk(sa, q0, q1, q2, q3, q4, q5, z0, z1, nk, nk2);
      wg_commit();
      wg_wait<1>();
      reg_fence<AB_N / 2>(sb2);
#pragma unroll
      for (int i = 0; i < AB_N / 4; i++) pb[i] = pack2(ex2(sb2[2 * i]), poly_group((i >> 1) + AB_N / 8) ? ex2_poly(sb2[2 * i + 1]) : ex2(sb2[2 * i + 1]));
      wg_fence();
#pragma unroll
      for (int kk = 0; kk < AB_N / 16; kk++) wg_rs24_01(o, pb[4 * kk], pb[4 * kk + 1], pb[4 * kk + 2], pb[4 * kk + 3], dv + AB_N * 3 + kk * 48, 1);
      attn_b_qk(sb2, q0, q1, q2, q3, q4, q5, z0, z1, nk + AB_N * 3, nk2 + AB_N * 3);
      wg_commit();
      dv += AB_N * 6;
    }
    wg_wait<0>();
    reg_fence<12>(o); reg_fence<AB_N / 2>(sa); reg_fence<AB_N / 2>(sb2);
    attn_b_store(o, h, row0, lane);
  }
  float kmax = 0.f;
#pragma unroll
  for (int i = 0; i < SEQ / AB_T; i++) {
    const int key = threadIdx.x + AB_T * i;
    const uint32_t a = sK + (key >> 3) * 384 + (key & 7) * 16;
    const uint4 x = lds128(a), y = lds128(a + 128);
    const uint2 z = lds64(a + 256);
    const float n = ((sq2(x.x) + sq2(x.y)) + (sq2(x.z) + sq2(x.w))) + ((sq2(y.x) + sq2(y.y)) + (sq2(y.z) + sq2(y.w))) + (sq2(z.x) + sq2(z.y));
    kmax = (n > kmax || n != n) ? n : kmax;
  }
  const uint32_t kbits = __reduce_max_sync(~0u, __float_as_uint(kmax) & 0x7fffffffu);
  if (lane == 0) sts32(bars + 64 + warp * 4, kbits);
  __syncthreads();
  kmax = __uint_as_float(__reduce_max_sync(~0u, lds32(bars + 64 + (lane & (AB_T / 32 - 1)) * 4)));
  TRACE(2);
  if (!__syncthreads_or(!(qmax * kmax <= 10000.f))) return;
#pragma unroll 1
  for (int pass = 0; pass < AB_PASS; pass++) {
    const int row0 = quarter * 512 + ((warp >> 2) * AB_PASS + pass) * 64 + (warp & 3) * 16;
    const uint32_t* gq = g_bqkv + (h * 256 + (row0 >> 3)) * 96 + lane;
    const uint32_t q0 = gq[0], q1 = gq[96], q2 = gq[32], q3 = gq[128], q4 = gq[64], q5 = gq[160];
    float o[12];
#pragma unroll
    for (int i = 0; i < 12; i++) o[i] = 0.f;
    float m0 = -INFINITY, m1 = -INFINITY;
#pragma unroll 1
    for (int kt = 0; kt < 32; kt++) {
      float s[32];
      const uint64_t dk = mkdesc(sK + kt * 3072, 128, 384, 0), dk2 = mkdesc(sK + kt * 3072 + 256, 0, 384, 0);
      wg_fence();
      wg_rs64_00(s, q0, q1, q2, q3, dk, 0);
      wg_rs64_00(s, q4, q5, 0, 0, dk2, 1);
      wg_commit();
      wg_wait<0>();
      reg_fence<32>(s); reg_fence<12>(o);
      float n0 = m0, n1 = m1;
#pragma unroll
      for (int jj = 0; jj < 8; jj++) { n0 = fmaxf(n0, fmaxf(s[4 * jj], s[4 * jj + 1])); n1 = fmaxf(n1, fmaxf(s[4 * jj + 2], s[4 * jj + 3])); }
      n0 = fmaxf(n0, __shfl_xor_sync(~0u, n0, 1)); n0 = fmaxf(n0, __shfl_xor_sync(~0u, n0, 2));
      n1 = fmaxf(n1, __shfl_xor_sync(~0u, n1, 1)); n1 = fmaxf(n1, __shfl_xor_sync(~0u, n1, 2));
      const float r0 = ex2(m0 - n0), r1 = ex2(m1 - n1);
      m0 = n0; m1 = n1;
#pragma unroll
      for (int jj = 0; jj < 3; jj++) { o[4 * jj] *= r0; o[4 * jj + 1] *= r0; o[4 * jj + 2] *= r1; o[4 * jj + 3] *= r1; }
      uint32_t pp[16];
#pragma unroll
      for (int jj = 0; jj < 8; jj++) {
        pp[2 * jj] = pack2(ex2(s[4 * jj] - m0), ex2(s[4 * jj + 1] - m0));
        pp[2 * jj + 1] = pack2(ex2(s[4 * jj + 2] - m1), ex2(s[4 * jj + 3] - m1));
      }
      const uint64_t dv = mkdesc(sV + kt * 3072, 384, 128, 0);
      wg_fence();
#pragma unroll
      for (int kk = 0; kk < 4; kk++) wg_rs24_01(o, pp[4 * kk], pp[4 * kk + 1], pp[4 * kk + 2], pp[4 * kk + 3], dv + kk * 48, 1);
      wg_commit();
    }
    wg_wait<0>();
    reg_fence<12>(o);
    attn_b_store(o, h, row0, lane);
  }
}

typedef CUresult (*EncodeFn)(CUtensorMap*, CUtensorMapDataType, cuuint32_t, void*, const cuuint64_t*, const cuuint64_t*,
                             const cuuint32_t*, const cuuint32_t*, CUtensorMapInterleave, CUtensorMapSwizzle,
                             CUtensorMapL2promotion, CUtensorMapFloatOOBfill);

void make_map(EncodeFn enc, CUtensorMap* m, const void* ptr, int cols, int rows, int box_rows, int box_cols = 64) {
  const cuuint64_t dims[2] = {(cuuint64_t)cols, (cuuint64_t)rows};
  const cuuint64_t strides[1] = {(cuuint64_t)cols * 2};
  const cuuint32_t box[2] = {(cuuint32_t)box_cols, (cuuint32_t)box_rows}, es[2] = {1, 1};
  enc(m, CU_TENSOR_MAP_DATA_TYPE_BFLOAT16, 2, const_cast<void*>(ptr), dims, strides, box, es, CU_TENSOR_MAP_INTERLEAVE_NONE,
      box_cols == 64 ? CU_TENSOR_MAP_SWIZZLE_128B : CU_TENSOR_MAP_SWIZZLE_64B, CU_TENSOR_MAP_L2_PROMOTION_L2_256B, CU_TENSOR_MAP_FLOAT_OOB_FILL_NONE);
}
template <class... KA, class... A>
void launch(void (*kern)(KA...), int grid, int block, int smem, int cluster, bool pdl, A... args) {
  cudaFuncSetAttribute(kern, cudaFuncAttributeMaxDynamicSharedMemorySize, smem);
  cudaLaunchConfig_t cfg = {};
  cfg.gridDim = dim3(grid); cfg.blockDim = dim3(block); cfg.dynamicSmemBytes = smem; cfg.stream = cudaStreamPerThread;
  cudaLaunchAttribute at[2];
  int n = 0;
  if (cluster > 1) { at[n].id = cudaLaunchAttributeClusterDimension; at[n].val.clusterDim.x = cluster; at[n].val.clusterDim.y = 1; at[n].val.clusterDim.z = 1; n++; }
  if (pdl) { at[n].id = cudaLaunchAttributeProgrammaticStreamSerialization; at[n].val.programmaticStreamSerializationAllowed = 1; n++; }
  cfg.attrs = at; cfg.numAttrs = n;
  cudaLaunchKernelEx(&cfg, kern, args...);
}
template <class T> void* sym(T& s) { void* p = nullptr; cudaGetSymbolAddress(&p, s); return p; }

}

#define MODE(b) 0
extern "C" void kernel_launch(void* const* d_in, const int* in_sizes, int n_in, void* d_out, int out_size) {
  const __nv_bfloat16* x = (const __nv_bfloat16*)d_in[0];
  void* fn = nullptr; cudaDriverEntryPointQueryResult qr;
  cudaGetDriverEntryPoint("cuTensorMapEncodeTiled", &fn, cudaEnableDefault, &qr);
  EncodeFn enc = (EncodeFn)fn;

  XsParams pq = {}, pc = {};
  ChainParams ch = {};
  PostParams op = {};
  void* q = sym(g_q);
  make_map(enc, &pq.w[0], d_in[2], HD, DM, 128); make_map(enc, &pq.o[0], q, HD, SEQ, 64);
  pq.a = (const uint32_t*)sym(g_xf);
  pq.ntiles = 96; pq.tiles_per_mat = 96; pq.rb0 = QA_END; pq.nowait = 1;
  make_map(enc, &pc.w[0], d_in[9], DM, DM, 128);
  pc.a = (const uint32_t*)sym(g_of); pc.ntiles = 10; pc.tiles_per_mat = 10; pc.out = (__nv_bfloat16*)d_out;
  ch.wq = pq.w[0];
  make_map(enc, &ch.wk, d_in[3], HD, DM, 128); make_map(enc, &ch.wv, d_in[4], HD, DM, 128);
  make_map(enc, &ch.wo, d_in[5], DM, HD, 192, 32);
  ch.mem0 = (const __nv_bfloat16*)d_in[1];
  ch.d1 = 200; ch.d2 = 350; ch.dn = 1150; ch.dx = 500;
  make_map(enc, &op.o, sym(g_o), HD, SEQ, 128); make_map(enc, &op.wo, d_in[5], DM, HD, 64);
  make_map(enc, &op.q, q, HD, SEQ, 128);
  make_map(enc, &op.wq, d_in[2], HD, DM, 64);
  make_map(enc, &op.wb, d_in[8], 1920, DM, 64);
  op.nq = 72; op.pace = 0;

  launch(probe_kernel, 132, 64, 200 * 1024, 1, false);
  for (int layer = 0; layer < 2; layer++) {
    launch(layer == 0 ? ln_kernel<true> : ln_kernel<false>, 132, 256, 200 * 1024, 1, layer != 0, x);
    launch(chain_kernel, 96, 384, CH_SMEM, 3, true, ch);
    launch(xs_gemm<EPI_QKV, false>, 36, 384, XS_SMEM, 1, !MODE(1), pq);
    launch(post_kernel, 132, 384, OP_SMEM, 1, true, op);
    launch(attn_b_kernel, 128, AB_T, AB_SMEM, 1, true);
    launch(layer == 0 ? xs_gemm<EPI_RES, false> : xs_gemm<EPI_OUT, false>, 80, 384, XS_SMEM, 1, true, pc);
  }
}
```

```cpp
#include <cuda_runtime.h>
#include <cuda_bf16.h>
#include <cuda.h>
#include <stdint.h>
#include <stdlib.h>

namespace {

constexpr int SEQ = 2048, DM = 640, HD = 6144, NSEG = 64;
constexpr int SPIN_LIMIT = 1 << 20;
#define HINT 7

__device__ __align__(128) uint2 g_x[SEQ * DM / 4];
__device__ __align__(128) uint32_t g_xn[SEQ * DM / 2];
__device__ __align__(128) uint32_t g_of[SEQ * DM / 2];
__device__ __align__(128) uint4 g_o[SEQ * HD / 8];
__device__ __align__(128) uint4 g_q[SEQ * HD / 8];
constexpr int KV_K = 0, KV_KM = 16384, KV_V = 20480, KV_VM = 36864, KV_BYTES = 40960;
__device__ __align__(128) uint8_t g_kv[16 * 96 * KV_BYTES];
#define OP_B8 11
#define OP_B16 14
#define OP_N4 16
#define BQ_12 12
#define BQ_24 14
#define FIN_16 12
__host__ __device__ constexpr int op_split(int b) { return b < OP_B8 ? 4 : b < OP_B16 ? 8 : 16; }
__host__ __device__ constexpr int op_tiles(int b) { return b < OP_N4 ? 2 : 4; }
__host__ __device__ constexpr int fin_items(int b) { return b < OP_B8 ? 4 : b < FIN_16 ? 8 : 16; }
__host__ __device__ constexpr int bq_items(int b) { return b < BQ_12 ? 6 : b < BQ_24 ? 12 : 24; }
__host__ __device__ constexpr int ln_items(int layer, int b) { return layer == 0 && b < 2 ? 16 : 4; }
__device__ __align__(128) uint2 g_part[16 * 16 * 16 * 40 * 32];
constexpr int SY_P = 128, SY_T = 192, SY_UP = 224, SY_OB = 225, SY_PRE = 256, SY_PART = 288, SY_N = 384;
__device__ __align__(128) uint32_t g_sync[2 * SY_N];
constexpr int NSLOT = 92;
__device__ uint32_t g_pool[(NSLOT + 2) * 2048];
__device__ uint32_t g_smpart[256], g_orient[NSLOT];
__device__ __align__(128) uint32_t g_bqkv[3 * 32 * 256 * 96];

#define XT(i)
#define MISS(k, n)
#define PRO(i)
#define TRACE(w)
#define ITEM(code, w)
#define STAT(k)
#define TMV(i, v)
#define TM(i)
#define TMD(i, dep)

__device__ __forceinline__ uint32_t gtime() { uint32_t c; asm volatile("mov.u32 %0, %%globaltimer_lo;" : "=r"(c) :: "memory"); return c; }
__device__ __forceinline__ uint32_t clk32() { uint32_t c; asm volatile("mov.u32 %0, %%clock;" : "=r"(c) :: "memory"); return c; }
__device__ __forceinline__ uint32_t s2u(const void* p) { return (uint32_t)__cvta_generic_to_shared(p); }
__device__ __forceinline__ uint32_t pack2(float a, float b) {
  uint32_t r; asm("cvt.rn.bf16x2.f32 %0, %1, %2;" : "=r"(r) : "f"(b), "f"(a)); return r; }
__device__ __forceinline__ float bf_lo(uint32_t w) { return __uint_as_float(w << 16); }
__device__ __forceinline__ float bf_hi(uint32_t w) { return __uint_as_float(w & 0xffff0000u); }
__device__ __forceinline__ float ex2(float x) { float y; asm("ex2.approx.ftz.f32 %0, %1;" : "=f"(y) : "f"(x)); return y; }

__device__ __forceinline__ void mbar_init(uint32_t bar, uint32_t n) {
  asm volatile("mbarrier.init.shared::cta.b64 [%0], %1;" :: "r"(bar), "r"(n) : "memory"); }
__device__ __forceinline__ void mbar_expect(uint32_t bar, uint32_t bytes) {
  asm volatile("mbarrier.arrive.expect_tx.shared::cta.b64 _, [%0], %1;" :: "r"(bar), "r"(bytes) : "memory"); }
__device__ __forceinline__ void mbar_arrive(uint32_t bar) {
  asm volatile("mbarrier.arrive.shared::cta.b64 _, [%0];" :: "r"(bar) : "memory"); }
__device__ __forceinline__ void mbar_arrive_remote(uint32_t bar) {
  asm volatile("mbarrier.arrive.shared::cluster.b64 _, [%0];" :: "r"(bar) : "memory"); }
__device__ __forceinline__ void mbar_wait_slow(uint32_t bar, uint32_t ph) {
  asm volatile("{.reg .pred p; .reg .u32 n; mov.u32 n, 0;\n"
               "W: mbarrier.try_wait.parity.shared::cta.b64 p, [%0], %1; @p bra D;\n"
               "add.u32 n, n, 1; setp.gt.u32 p, n, %2; @p trap; bra W;\n"
               "D: }" :: "r"(bar), "r"(ph), "n"(SPIN_LIMIT) : "memory");
}
__device__ __forceinline__ void mbar_wait(uint32_t bar, uint32_t ph) {
  uint32_t ok;
  asm volatile("{.reg .pred p; mbarrier.try_wait.parity.shared::cta.b64 p, [%1], %2; selp.u32 %0, 1, 0, p;}" : "=r"(ok) : "r"(bar), "r"(ph) : "memory");
  if (__builtin_expect(!ok, 0)) mbar_wait_slow(bar, ph);
}
__device__ __forceinline__ void mbar_wait_uniform(uint32_t bar, uint32_t ph) {
  asm volatile("{.reg .pred p; .reg .u32 n; mov.u32 n, 0;\n"
               "W: mbarrier.try_wait.parity.shared::cta.b64 p, [%0], %1; vote.sync.all.pred p, p, 0xffffffff; @p bra.uni D;\n"
               "add.u32 n, n, 1; setp.gt.u32 p, n, %2; @p trap; bra.uni W;\n"
               "D: }" :: "r"(bar), "r"(ph), "n"(SPIN_LIMIT) : "memory");
}
__device__ __forceinline__ bool elect() {
  uint32_t p; asm volatile("{.reg .pred q; elect.sync _|q, 0xffffffff; selp.u32 %0, 1, 0, q;}" : "=r"(p)); return p; }
__device__ __forceinline__ void mbar_wait_cluster(uint32_t bar, uint32_t ph) {
  asm volatile("{.reg .pred p; .reg .u32 n; mov.u32 n, 0;\n"
               "W: mbarrier.try_wait.parity.acquire.cluster.shared::cta.b64 p, [%0], %1; @p bra D;\n"
               "add.u32 n, n, 1; setp.gt.u32 p, n, %2; @p trap; bra W;\n"
               "D: }" :: "r"(bar), "r"(ph), "n"(SPIN_LIMIT) : "memory");
}
__device__ __forceinline__ void spin_guard(int& n) {
  asm volatile("{.reg .pred p; add.s32 %0, %0, 1; setp.gt.s32 p, %0, %1; @p trap;}" : "+r"(n) : "n"(SPIN_LIMIT));
}
__device__ __forceinline__ void pdl_wait() { asm volatile("griddepcontrol.wait;" ::: "memory"); TRACE(1); }
__device__ __forceinline__ void pdl_launch() { asm volatile("griddepcontrol.launch_dependents;" ::: "memory"); }
__device__ __forceinline__ uint32_t ld_acquire(const uint32_t* p) { uint32_t v; asm volatile("ld.acquire.gpu.global.u32 %0, [%1];" : "=r"(v) : "l"(p) : "memory"); return v; }
__device__ __forceinline__ void red_release(uint32_t* p, uint32_t v) { asm volatile("red.release.gpu.global.add.u32 [%0], %1;" :: "l"(p), "r"(v) : "memory"); }
__device__ __forceinline__ void fence_async_global() { asm volatile("fence.proxy.async.global;" ::: "memory"); }
__device__ __forceinline__ void fence_async() { asm volatile("fence.proxy.async.shared::cta;" ::: "memory"); }
__device__ __forceinline__ void bar_sync(int id, int n) { asm volatile("bar.sync %0, %1;" :: "r"(id), "r"(n) : "memory"); }
__device__ __forceinline__ void bar_arrive(int id, int n) { asm volatile("bar.arrive %0, %1;" :: "r"(id), "r"(n) : "memory"); }
__device__ __forceinline__ void tma_load(uint32_t dst, const CUtensorMap* m, int c0, int c1, uint32_t bar) {
  asm volatile("cp.async.bulk.tensor.2d.shared::cluster.global.mbarrier::complete_tx::bytes [%0], [%1, {%3, %4}], [%2];"
               :: "r"(dst), "l"(m), "r"(bar), "r"(c0), "r"(c1) : "memory"); }
__device__ __forceinline__ void tma_store(const CUtensorMap* m, uint32_t src, int c0, int c1) {
  asm volatile("cp.async.bulk.tensor.2d.global.shared::cta.bulk_group [%0, {%2, %3}], [%1];"
               :: "l"(m), "r"(src), "r"(c0), "r"(c1) : "memory"); }
__device__ __forceinline__ uint64_t evict_first() { uint64_t p; asm("createpolicy.fractional.L2::evict_first.b64 %0, 1.0;" : "=l"(p)); return p; }
__device__ __forceinline__ void bulk_load_last(uint32_t dst, const void* src, uint32_t bytes, uint32_t bar) {
  asm volatile("cp.async.bulk.shared::cluster.global.mbarrier::complete_tx::bytes.L2::cache_hint [%0], [%1], %2, [%3], %4;"
               :: "r"(dst), "l"(src), "r"(bytes), "r"(bar), "l"(evict_first()) : "memory"); }
__device__ __forceinline__ void bulk_store_stream(void* dst, uint32_t src, uint32_t bytes) {
  asm volatile("cp.async.bulk.global.shared::cta.bulk_group.L2::cache_hint [%0], [%1], %2, %3;" :: "l"(dst), "r"(src), "r"(bytes), "l"(evict_first()) : "memory"); }
__device__ __forceinline__ void bulk_load(uint32_t dst, const void* src, uint32_t bytes, uint32_t bar) {
  asm volatile("cp.async.bulk.shared::cluster.global.mbarrier::complete_tx::bytes [%0], [%1], %2, [%3];"
               :: "r"(dst), "l"(src), "r"(bytes), "r"(bar) : "memory"); }
__device__ __forceinline__ void bulk_push(uint32_t dst, uint32_t src, uint32_t bytes, uint32_t bar) {
  asm volatile("cp.async.bulk.shared::cluster.shared::cta.mbarrier::complete_tx::bytes [%0], [%1], %2, [%3];"
               :: "r"(dst), "r"(src), "r"(bytes), "r"(bar) : "memory"); }
__device__ __forceinline__ void bulk_store(void* dst, uint32_t src, uint32_t bytes) {
  asm volatile("cp.async.bulk.global.shared::cta.bulk_group [%0], [%1], %2;" :: "l"(dst), "r"(src), "r"(bytes) : "memory"); }
__device__ __forceinline__ void bulk_commit() { asm volatile("cp.async.bulk.commit_group;" ::: "memory"); }
template <int N> __device__ __forceinline__ void bulk_wait_read() { asm volatile("cp.async.bulk.wait_group.read %0;" :: "n"(N) : "memory"); }
template <int N> __device__ __forceinline__ void bulk_wait() { asm volatile("cp.async.bulk.wait_group %0;" :: "n"(N) : "memory"); }

__device__ __forceinline__ uint64_t mkdesc(uint32_t addr, uint32_t lbo, uint32_t sbo, uint32_t sw) {
  return (uint64_t)((addr & 0x3FFFF) >> 4) | ((uint64_t)(lbo >> 4) << 16) | ((uint64_t)(sbo >> 4) << 32) | ((uint64_t)sw << 62); }
__device__ __forceinline__ void wg_fence() { asm volatile("wgmma.fence.sync.aligned;" ::: "memory"); }
__device__ __forceinline__ void wg_commit() { asm volatile("wgmma.commit_group.sync.aligned;" ::: "memory"); }
template <int N> __device__ __forceinline__ void wg_wait() { asm volatile("wgmma.wait_group.sync.aligned %0;" :: "n"(N) : "memory"); }
template <int N> __device__ __forceinline__ void reg_fence(float* d) {
#pragma unroll
  for (int i = 0; i < N; i++) asm volatile("" : "+f"(d[i]) :: "memory");
}

__device__ __forceinline__ void mma16(float* d, uint32_t a0, uint32_t a1, uint32_t a2, uint32_t a3, uint32_t b0, uint32_t b1) {
  asm volatile("mma.sync.aligned.m16n8k16.row.col.f32.bf16.bf16.f32 {%0,%1,%2,%3},{%4,%5,%6,%7},{%8,%9},{%0,%1,%2,%3};"
               : "+f"(d[0]), "+f"(d[1]), "+f"(d[2]), "+f"(d[3]) : "r"(a0), "r"(a1), "r"(a2), "r"(a3), "r"(b0), "r"(b1)); }
__device__ __forceinline__ void mma8(float* d, uint32_t a0, uint32_t a1, uint32_t b0) {
  asm volatile("mma.sync.aligned.m16n8k8.row.col.f32.bf16.bf16.f32 {%0,%1,%2,%3},{%4,%5},{%6},{%0,%1,%2,%3};"
               : "+f"(d[0]), "+f"(d[1]), "+f"(d[2]), "+f"(d[3]) : "r"(a0), "r"(a1), "r"(b0)); }
__device__ __forceinline__ void ldsm4(uint32_t* r, uint32_t a) {
  asm volatile("ldmatrix.sync.aligned.m8n8.x4.shared.b16 {%0,%1,%2,%3},[%4];" : "=r"(r[0]), "=r"(r[1]), "=r"(r[2]), "=r"(r[3]) : "r"(a) : "memory"); }
__device__ __forceinline__ uint4 ldsm4v(uint32_t a) { uint32_t r[4]; ldsm4(r, a); return make_uint4(r[0], r[1], r[2], r[3]); }
__device__ __forceinline__ void ldsm4t(uint32_t* r, uint32_t a) {
  asm volatile("ldmatrix.sync.aligned.m8n8.x4.trans.shared.b16 {%0,%1,%2,%3},[%4];" : "=r"(r[0]), "=r"(r[1]), "=r"(r[2]), "=r"(r[3]) : "r"(a) : "memory"); }
__device__ __forceinline__ void ldsm2t(uint32_t* r, uint32_t a) {
  asm volatile("ldmatrix.sync.aligned.m8n8.x2.trans.shared.b16 {%0,%1},[%2];" : "=r"(r[0]), "=r"(r[1]) : "r"(a) : "memory"); }
__device__ __forceinline__ void stsm4(uint32_t a, uint32_t r0, uint32_t r1, uint32_t r2, uint32_t r3) {
  asm volatile("stmatrix.sync.aligned.m8n8.x4.shared.b16 [%0], {%1,%2,%3,%4};" :: "r"(a), "r"(r0), "r"(r1), "r"(r2), "r"(r3) : "memory"); }
__device__ __forceinline__ void stsm4t(uint32_t a, uint32_t r0, uint32_t r1, uint32_t r2, uint32_t r3) {
  asm volatile("stmatrix.sync.aligned.m8n8.x4.trans.shared.b16 [%0], {%1,%2,%3,%4};" :: "r"(a), "r"(r0), "r"(r1), "r"(r2), "r"(r3) : "memory"); }
__device__ __forceinline__ void stsm2(uint32_t a, uint32_t r0, uint32_t r1) {
  asm volatile("stmatrix.sync.aligned.m8n8.x2.shared.b16 [%0], {%1,%2};" :: "r"(a), "r"(r0), "r"(r1) : "memory"); }
__device__ __forceinline__ void stsm2t(uint32_t a, uint32_t r0, uint32_t r1) {
  asm volatile("stmatrix.sync.aligned.m8n8.x2.trans.shared.b16 [%0], {%1,%2};" :: "r"(a), "r"(r0), "r"(r1) : "memory"); }
__device__ __forceinline__ void sts32(uint32_t a, uint32_t v) { asm volatile("st.shared.b32 [%0], %1;" :: "r"(a), "r"(v) : "memory"); }
__device__ __forceinline__ void sts64f(uint32_t a, float x, float y) { asm volatile("st.shared.v2.f32 [%0], {%1,%2};" :: "r"(a), "f"(x), "f"(y) : "memory"); }
__device__ __forceinline__ void sts128(uint32_t a, uint4 v) {
  asm volatile("st.shared.v4.b32 [%0], {%1,%2,%3,%4};" :: "r"(a), "r"(v.x), "r"(v.y), "r"(v.z), "r"(v.w) : "memory"); }
__device__ __forceinline__ void sts128f(uint32_t a, float x, float y, float z, float w) {
  asm volatile("st.shared.v4.f32 [%0], {%1,%2,%3,%4};" :: "r"(a), "f"(x), "f"(y), "f"(z), "f"(w) : "memory"); }
__device__ __forceinline__ float lds32f(uint32_t a) { float v; asm volatile("ld.shared.f32 %0, [%1];" : "=f"(v) : "r"(a) : "memory"); return v; }
__device__ __forceinline__ float2 lds64f(uint32_t a) { float2 v; asm volatile("ld.shared.v2.f32 {%0,%1}, [%2];" : "=f"(v.x), "=f"(v.y) : "r"(a) : "memory"); return v; }
__device__ __forceinline__ float4 lds128f(uint32_t a) {
  float4 v; asm volatile("ld.shared.v4.f32 {%0,%1,%2,%3}, [%4];" : "=f"(v.x), "=f"(v.y), "=f"(v.z), "=f"(v.w) : "r"(a) : "memory"); return v; }
__device__ __forceinline__ uint4 lds128(uint32_t a) {
  uint4 v; asm volatile("ld.shared.v4.b32 {%0,%1,%2,%3}, [%4];" : "=r"(v.x), "=r"(v.y), "=r"(v.z), "=r"(v.w) : "r"(a) : "memory"); return v; }
__device__ __forceinline__ uint4 ldg_strong128(const void* p) {
  uint4 v; asm volatile("ld.relaxed.gpu.global.v4.u32 {%0,%1,%2,%3}, [%4];" : "=r"(v.x), "=r"(v.y), "=r"(v.z), "=r"(v.w) : "l"(p) : "memory"); return v; }
__device__ __forceinline__ uint2 ldg_strong64(const void* p) {
  uint2 v; asm volatile("ld.relaxed.gpu.global.v2.u32 {%0,%1}, [%2];" : "=r"(v.x), "=r"(v.y) : "l"(p) : "memory"); return v; }
__device__ __forceinline__ void stg_strong32(void* p, uint32_t v) { asm volatile("st.relaxed.gpu.global.u32 [%0], %1;" :: "l"(p), "r"(v) : "memory"); }
__device__ __forceinline__ void stg_strong128(void* p, uint4 v) {
  asm volatile("st.relaxed.gpu.global.v4.u32 [%0], {%1,%2,%3,%4};" :: "l"(p), "r"(v.x), "r"(v.y), "r"(v.z), "r"(v.w) : "memory"); }
__device__ __forceinline__ uint32_t mapa(uint32_t a, uint32_t r) {
  uint32_t o; asm("mapa.shared::cluster.u32 %0, %1, %2;" : "=r"(o) : "r"(a), "r"(r)); return o; }
__device__ __forceinline__ void st_async2f(uint32_t a, float x, float y, uint32_t bar) {
  asm volatile("st.async.shared::cluster.mbarrier::complete_tx::bytes.v2.f32 [%0], {%1,%2}, [%3];" :: "r"(a), "f"(x), "f"(y), "r"(bar) : "memory"); }
__device__ __forceinline__ void st_async32(uint32_t a, uint32_t x, uint32_t bar) {
  asm volatile("st.async.shared::cluster.mbarrier::complete_tx::bytes.b32 [%0], %1, [%2];" :: "r"(a), "r"(x), "r"(bar) : "memory"); }
__device__ __forceinline__ uint32_t lds32(uint32_t a) { uint32_t v; asm volatile("ld.shared.b32 %0, [%1];" : "=r"(v) : "r"(a) : "memory"); return v; }
__device__ __forceinline__ void st_async64(uint32_t a, uint32_t x, uint32_t y, uint32_t bar) {
  asm volatile("st.async.shared::cluster.mbarrier::complete_tx::bytes.v2.b32 [%0], {%1,%2}, [%3];" :: "r"(a), "r"(x), "r"(y), "r"(bar) : "memory"); }
__device__ __forceinline__ void st_async128(uint32_t a, uint4 v, uint32_t bar) {
  asm volatile("st.async.shared::cluster.mbarrier::complete_tx::bytes.v4.b32 [%0], {%1,%2,%3,%4}, [%5];" :: "r"(a), "r"(v.x), "r"(v.y), "r"(v.z), "r"(v.w), "r"(bar) : "memory"); }
__device__ __forceinline__ uint2 lds64(uint32_t a) { uint2 v; asm volatile("ld.shared.v2.b32 {%0,%1}, [%2];" : "=r"(v.x), "=r"(v.y) : "r"(a) : "memory"); return v; }
__device__ __forceinline__ void sts64(uint32_t a, uint32_t x, uint32_t y) { asm volatile("st.shared.v2.b32 [%0], {%1,%2};" :: "r"(a), "r"(x), "r"(y) : "memory"); }
__device__ __forceinline__ uint32_t ldg_strong32(const void* p) { uint32_t v; asm volatile("ld.relaxed.gpu.global.u32 %0, [%1];" : "=r"(v) : "l"(p) : "memory"); return v; }
__device__ __forceinline__ uint32_t transpose8(uint32_t x) { uint32_t r; asm volatile("movmatrix.sync.aligned.m8n8.trans.b16 %0, %1;" : "=r"(r) : "r"(x)); return r; }
__device__ __forceinline__ uint32_t hadd2(uint32_t a, uint32_t b) { uint32_t r; asm("add.rn.bf16x2 %0, %1, %2;" : "=r"(r) : "r"(a), "r"(b)); return r; }
__device__ __forceinline__ uint32_t min4(uint4 v) { return min(__vimin3_u32(v.x, v.y, v.z), v.w); }

__device__ __forceinline__ void wg_ss192_01(float* d, uint64_t da, uint64_t db, int sd) {
  asm volatile("{.reg .pred p; setp.ne.b32 p, %98, 0;\n"
    "wgmma.mma_async.sync.aligned.m64n192k16.f32.bf16.bf16 {%0,%1,%2,%3,%4,%5,%6,%7,%8,%9,%10,%11,%12,%13,%14,%15,%16,%17,%18,%19,%20,%21,%22,%23,%24,%25,%26,%27,%28,%29,%30,%31,%32,%33,%34,%35,%36,%37,%38,%39,%40,%41,%42,%43,%44,%45,%46,%47,%48,%49,%50,%51,%52,%53,%54,%55,%56,%57,%58,%59,%60,%61,%62,%63,%64,%65,%66,%67,%68,%69,%70,%71,%72,%73,%74,%75,%76,%77,%78,%79,%80,%81,%82,%83,%84,%85,%86,%87,%88,%89,%90,%91,%92,%93,%94,%95}, %96, %97, p, 1, 1, 0, 1;}"
    : "+f"(d[0]),"+f"(d[1]),"+f"(d[2]),"+f"(d[3]),"+f"(d[4]),"+f"(d[5]),"+f"(d[6]),"+f"(d[7]),"+f"(d[8]),"+f"(d[9]),"+f"(d[10]),"+f"(d[11]),"+f"(d[12]),"+f"(d[13]),"+f"(d[14]),"+f"(d[15]),"+f"(d[16]),"+f"(d[17]),"+f"(d[18]),"+f"(d[19]),"+f"(d[20]),"+f"(d[21]),"+f"(d[22]),"+f"(d[23]),"+f"(d[24]),"+f"(d[25]),"+f"(d[26]),"+f"(d[27]),"+f"(d[28]),"+f"(d[29]),"+f"(d[30]),"+f"(d[31]),"+f"(d[32]),"+f"(d[33]),"+f"(d[34]),"+f"(d[35]),"+f"(d[36]),"+f"(d[37]),"+f"(d[38]),"+f"(d[39]),"+f"(d[40]),"+f"(d[41]),"+f"(d[42]),"+f"(d[43]),"+f"(d[44]),"+f"(d[45]),"+f"(d[46]),"+f"(d[47]),"+f"(d[48]),"+f"(d[49]),"+f"(d[50]),"+f"(d[51]),"+f"(d[52]),"+f"(d[53]),"+f"(d[54]),"+f"(d[55]),"+f"(d[56]),"+f"(d[57]),"+f"(d[58]),"+f"(d[59]),"+f"(d[60]),"+f"(d[61]),"+f"(d[62]),"+f"(d[63]),"+f"(d[64]),"+f"(d[65]),"+f"(d[66]),"+f"(d[67]),"+f"(d[68]),"+f"(d[69]),"+f"(d[70]),"+f"(d[71]),"+f"(d[72]),"+f"(d[73]),"+f"(d[74]),"+f"(d[75]),"+f"(d[76]),"+f"(d[77]),"+f"(d[78]),"+f"(d[79]),"+f"(d[80]),"+f"(d[81]),"+f"(d[82]),"+f"(d[83]),"+f"(d[84]),"+f"(d[85]),"+f"(d[86]),"+f"(d[87]),"+f"(d[88]),"+f"(d[89]),"+f"(d[90]),"+f"(d[91]),"+f"(d[92]),"+f"(d[93]),"+f"(d[94]),"+f"(d[95])
    : "l"(da), "l"(db), "r"(sd));
}
__device__ __forceinline__ void wg_ss128_01(float* d, uint64_t da, uint64_t db, int sd) {
  asm volatile("{.reg .pred p; setp.ne.b32 p, %66, 0;\n"
    "wgmma.mma_async.sync.aligned.m64n128k16.f32.bf16.bf16 {%0,%1,%2,%3,%4,%5,%6,%7,%8,%9,%10,%11,%12,%13,%14,%15,%16,%17,%18,%19,%20,%21,%22,%23,%24,%25,%26,%27,%28,%29,%30,%31,%32,%33,%34,%35,%36,%37,%38,%39,%40,%41,%42,%43,%44,%45,%46,%47,%48,%49,%50,%51,%52,%53,%54,%55,%56,%57,%58,%59,%60,%61,%62,%63}, %64, %65, p, 1, 1, 0, 1;}"
    : "+f"(d[0]),"+f"(d[1]),"+f"(d[2]),"+f"(d[3]),"+f"(d[4]),"+f"(d[5]),"+f"(d[6]),"+f"(d[7]),"+f"(d[8]),"+f"(d[9]),"+f"(d[10]),"+f"(d[11]),"+f"(d[12]),"+f"(d[13]),"+f"(d[14]),"+f"(d[15]),"+f"(d[16]),"+f"(d[17]),"+f"(d[18]),"+f"(d[19]),"+f"(d[20]),"+f"(d[21]),"+f"(d[22]),"+f"(d[23]),"+f"(d[24]),"+f"(d[25]),"+f"(d[26]),"+f"(d[27]),"+f"(d[28]),"+f"(d[29]),"+f"(d[30]),"+f"(d[31]),"+f"(d[32]),"+f"(d[33]),"+f"(d[34]),"+f"(d[35]),"+f"(d[36]),"+f"(d[37]),"+f"(d[38]),"+f"(d[39]),"+f"(d[40]),"+f"(d[41]),"+f"(d[42]),"+f"(d[43]),"+f"(d[44]),"+f"(d[45]),"+f"(d[46]),"+f"(d[47]),"+f"(d[48]),"+f"(d[49]),"+f"(d[50]),"+f"(d[51]),"+f"(d[52]),"+f"(d[53]),"+f"(d[54]),"+f"(d[55]),"+f"(d[56]),"+f"(d[57]),"+f"(d[58]),"+f"(d[59]),"+f"(d[60]),"+f"(d[61]),"+f"(d[62]),"+f"(d[63])
    : "l"(da), "l"(db), "r"(sd));
}
__device__ __forceinline__ void wg_ss160_01(float* d, uint64_t da, uint64_t db, int sd) {
  asm volatile("{.reg .pred p; setp.ne.b32 p, %82, 0;\n"
    "wgmma.mma_async.sync.aligned.m64n160k16.f32.bf16.bf16 {%0,%1,%2,%3,%4,%5,%6,%7,%8,%9,%10,%11,%12,%13,%14,%15,%16,%17,%18,%19,%20,%21,%22,%23,%24,%25,%26,%27,%28,%29,%30,%31,%32,%33,%34,%35,%36,%37,%38,%39,%40,%41,%42,%43,%44,%45,%46,%47,%48,%49,%50,%51,%52,%53,%54,%55,%56,%57,%58,%59,%60,%61,%62,%63,%64,%65,%66,%67,%68,%69,%70,%71,%72,%73,%74,%75,%76,%77,%78,%79}, %80, %81, p, 1, 1, 0, 1;}"
    : "+f"(d[0]),"+f"(d[1]),"+f"(d[2]),"+f"(d[3]),"+f"(d[4]),"+f"(d[5]),"+f"(d[6]),"+f"(d[7]),"+f"(d[8]),"+f"(d[9]),"+f"(d[10]),"+f"(d[11]),"+f"(d[12]),"+f"(d[13]),"+f"(d[14]),"+f"(d[15]),"+f"(d[16]),"+f"(d[17]),"+f"(d[18]),"+f"(d[19]),"+f"(d[20]),"+f"(d[21]),"+f"(d[22]),"+f"(d[23]),"+f"(d[24]),"+f"(d[25]),"+f"(d[26]),"+f"(d[27]),"+f"(d[28]),"+f"(d[29]),"+f"(d[30]),"+f"(d[31]),"+f"(d[32]),"+f"(d[33]),"+f"(d[34]),"+f"(d[35]),"+f"(d[36]),"+f"(d[37]),"+f"(d[38]),"+f"(d[39]),"+f"(d[40]),"+f"(d[41]),"+f"(d[42]),"+f"(d[43]),"+f"(d[44]),"+f"(d[45]),"+f"(d[46]),"+f"(d[47]),"+f"(d[48]),"+f"(d[49]),"+f"(d[50]),"+f"(d[51]),"+f"(d[52]),"+f"(d[53]),"+f"(d[54]),"+f"(d[55]),"+f"(d[56]),"+f"(d[57]),"+f"(d[58]),"+f"(d[59]),"+f"(d[60]),"+f"(d[61]),"+f"(d[62]),"+f"(d[63]),"+f"(d[64]),"+f"(d[65]),"+f"(d[66]),"+f"(d[67]),"+f"(d[68]),"+f"(d[69]),"+f"(d[70]),"+f"(d[71]),"+f"(d[72]),"+f"(d[73]),"+f"(d[74]),"+f"(d[75]),"+f"(d[76]),"+f"(d[77]),"+f"(d[78]),"+f"(d[79])
    : "l"(da), "l"(db), "r"(sd));
}
__device__ __forceinline__ void wg_ss80_01(float* d, uint64_t da, uint64_t db, int sd) {
  asm volatile("{.reg .pred p; setp.ne.b32 p, %42, 0;\n"
    "wgmma.mma_async.sync.aligned.m64n80k16.f32.bf16.bf16 {%0,%1,%2,%3,%4,%5,%6,%7,%8,%9,%10,%11,%12,%13,%14,%15,%16,%17,%18,%19,%20,%21,%22,%23,%24,%25,%26,%27,%28,%29,%30,%31,%32,%33,%34,%35,%36,%37,%38,%39}, %40, %41, p, 1, 1, 0, 1;}"
    : "+f"(d[0]),"+f"(d[1]),"+f"(d[2]),"+f"(d[3]),"+f"(d[4]),"+f"(d[5]),"+f"(d[6]),"+f"(d[7]),"+f"(d[8]),"+f"(d[9]),"+f"(d[10]),"+f"(d[11]),"+f"(d[12]),"+f"(d[13]),"+f"(d[14]),"+f"(d[15]),"+f"(d[16]),"+f"(d[17]),"+f"(d[18]),"+f"(d[19]),"+f"(d[20]),"+f"(d[21]),"+f"(d[22]),"+f"(d[23]),"+f"(d[24]),"+f"(d[25]),"+f"(d[26]),"+f"(d[27]),"+f"(d[28]),"+f"(d[29]),"+f"(d[30]),"+f"(d[31]),"+f"(d[32]),"+f"(d[33]),"+f"(d[34]),"+f"(d[35]),"+f"(d[36]),"+f"(d[37]),"+f"(d[38]),"+f"(d[39])
    : "l"(da), "l"(db), "r"(sd));
}
__device__ __forceinline__ void wg_rs32_00(float* d, uint32_t a0, uint32_t a1, uint32_t a2, uint32_t a3, uint64_t db, int sd) {
  asm volatile("{.reg .pred p; setp.ne.b32 p, %21, 0;\n"
    "wgmma.mma_async.sync.aligned.m64n32k16.f32.bf16.bf16 {%0,%1,%2,%3,%4,%5,%6,%7,%8,%9,%10,%11,%12,%13,%14,%15}, {%16,%17,%18,%19}, %20, p, 1, 1, 0;}"
    : "+f"(d[0]),"+f"(d[1]),"+f"(d[2]),"+f"(d[3]),"+f"(d[4]),"+f"(d[5]),"+f"(d[6]),"+f"(d[7]),"+f"(d[8]),"+f"(d[9]),"+f"(d[10]),"+f"(d[11]),"+f"(d[12]),"+f"(d[13]),"+f"(d[14]),"+f"(d[15])
    : "r"(a0), "r"(a1), "r"(a2), "r"(a3), "l"(db), "r"(sd));
}
__device__ __forceinline__ void wg_rs64_00(float* d, uint32_t a0, uint32_t a1, uint32_t a2, uint32_t a3, uint64_t db, int sd) {
  asm volatile("{.reg .pred p; setp.ne.b32 p, %37, 0;\n"
    "wgmma.mma_async.sync.aligned.m64n64k16.f32.bf16.bf16 {%0,%1,%2,%3,%4,%5,%6,%7,%8,%9,%10,%11,%12,%13,%14,%15,%16,%17,%18,%19,%20,%21,%22,%23,%24,%25,%26,%27,%28,%29,%30,%31}, {%32,%33,%34,%35}, %36, p, 1, 1, 0;}"
    : "+f"(d[0]),"+f"(d[1]),"+f"(d[2]),"+f"(d[3]),"+f"(d[4]),"+f"(d[5]),"+f"(d[6]),"+f"(d[7]),"+f"(d[8]),"+f"(d[9]),"+f"(d[10]),"+f"(d[11]),"+f"(d[12]),"+f"(d[13]),"+f"(d[14]),"+f"(d[15]),"+f"(d[16]),"+f"(d[17]),"+f"(d[18]),"+f"(d[19]),"+f"(d[20]),"+f"(d[21]),"+f"(d[22]),"+f"(d[23]),"+f"(d[24]),"+f"(d[25]),"+f"(d[26]),"+f"(d[27]),"+f"(d[28]),"+f"(d[29]),"+f"(d[30]),"+f"(d[31])
    : "r"(a0), "r"(a1), "r"(a2), "r"(a3), "l"(db), "r"(sd));
}
__device__ __forceinline__ void wg_rs24_01(float* d, uint32_t a0, uint32_t a1, uint32_t a2, uint32_t a3, uint64_t db, int sd) {
  asm volatile("{.reg .pred p; setp.ne.b32 p, %17, 0;\n"
    "wgmma.mma_async.sync.aligned.m64n24k16.f32.bf16.bf16 {%0,%1,%2,%3,%4,%5,%6,%7,%8,%9,%10,%11}, {%12,%13,%14,%15}, %16, p, 1, 1, 1;}"
    : "+f"(d[0]),"+f"(d[1]),"+f"(d[2]),"+f"(d[3]),"+f"(d[4]),"+f"(d[5]),"+f"(d[6]),"+f"(d[7]),"+f"(d[8]),"+f"(d[9]),"+f"(d[10]),"+f"(d[11])
    : "r"(a0), "r"(a1), "r"(a2), "r"(a3), "l"(db), "r"(sd));
}

#define AB_POLY 0x77
__device__ __forceinline__ constexpr bool poly_group(int group) { return (AB_POLY >> (group & 7)) & 1; }

template <int V> struct Int { static constexpr int value = V; };

__device__ __forceinline__ int core_word(int row, int col) {
  return ((((row >> 7) * 10 + (col >> 6)) * 16 + ((row >> 3) & 15)) * 8 + ((col >> 3) & 7)) * 32 + (row & 7) * 4 + ((col & 7) >> 1);
}
__device__ __forceinline__ void wait_count(const uint32_t* c, uint32_t n) {
  int spin = 0;
  while ((ld_acquire(c) & 0xffff) < n) { __nanosleep(32); spin_guard(spin); }
}
__device__ __forceinline__ void wait_count_uniform(const uint32_t* c, uint32_t n) {
  for (int spin = 0; !__all_sync(~0u, (ld_acquire(c) & 0xffff) >= n);) { __nanosleep(32); spin_guard(spin); }
  fence_async_global();
}
__device__ __forceinline__ void prefetch_l2(const void* p, uint32_t bytes) {
  asm volatile("cp.async.bulk.prefetch.L2.global [%0], %1;" :: "l"(p), "r"(bytes) : "memory"); }

#define PLACE 3
__device__ __forceinline__ bool helper_sm() {
  uint32_t m; asm("mov.u32 %0, %%smid;" : "=r"(m));
  return m < 2 || m >= 124 || (m >= 92 && m < 104) || (m >= 106 && m < 118) || m == 120 || m == 121;
}

__device__ __forceinline__ uint8_t* pool_at(uint32_t off) {
  return reinterpret_cast<uint8_t*>((reinterpret_cast<uintptr_t>(g_pool) + 8191) & ~(uintptr_t)8191) + off; }
__device__ __forceinline__ uint32_t page_latency(uint32_t* w) {
  uint32_t best = ~0u;
  stg_strong32(w, 0u);
  for (int r = 0; r < 4; r++) {
    uint32_t t0, t1, v;
    asm volatile("mov.u32 %0, %%clock;" : "=r"(t0) :: "memory");
    asm volatile("atom.relaxed.gpu.global.exch.b32 %0, [%1], 0;" : "=r"(v) : "l"(w) : "memory");
    asm volatile("{.reg .u32 t; add.u32 t, %1, 1; mov.u32 %0, %%clock; sub.u32 %0, %0, %1;}" : "=r"(t1) : "r"(__shfl_sync(1u, v, 0)) : "memory");
    best = min(best, t1 - t0);
  }
  return best;
}
__device__ __forceinline__ void probe_slots(uint32_t scratch) {
  const int w = (threadIdx.x >> 6) & 1, slot = w == 0 ? NSLOT : blockIdx.x;
  if ((threadIdx.x & 31) == 0 && (w == 0 || slot < NSLOT)) {
    uint32_t* q = reinterpret_cast<uint32_t*>(pool_at(slot * 8192)) + (w == 0 ? (blockIdx.x & 31) * 32 + (blockIdx.x >> 5) : 0);
    sts32(scratch + w * 4, page_latency(q) < page_latency(q + 1024));
  }
  bar_sync(2, 64);
  if ((threadIdx.x & 31) == 0) {
    const int part = lds32(scratch) ? 1 : 2;
    if (w == 0) { uint32_t smid; asm("mov.u32 %0, %%smid;" : "=r"(smid)); stg_strong32(g_smpart + (smid & 255), part); }
    else if (slot < NSLOT) stg_strong32(g_orient + slot, lds32(scratch + 4) ? part : 3 - part);
  }
  __syncwarp();
}

struct ChainParams {
  CUtensorMap wq, wk, wv, wo;
  const __nv_bfloat16* mem0;
  uint32_t *sync, *other;
  int layer;
  int d1, d2, dn, dx, mode, zero;
};
constexpr int CH_WQ = 0, CH_WO = 81920, CH_X = CH_WO + 86016, CH_M = CH_X, CH_Q = CH_X + 34816, CH_KM = CH_Q + 2048, CH_VP = CH_KM + 2048,
              CH_K = CH_X + 40960, CH_O = CH_K, CH_KS = CH_K + 3072, CH_V = CH_K + 4096, CH_VX = CH_V + 12288, CH_R2 = CH_VX,
              CH_SX = CH_VX + 3072, CH_SO = CH_SX + 2048, CH_ID = CH_SO + 1024, CH_L = CH_ID + 256, CH_TAB = CH_L + 64, CH_BAR = CH_TAB + 384;
constexpr int CH_SMEM = CH_BAR + 144;
constexpr int MB_WO = CH_BAR, MB_WQ = CH_BAR + 8, MB_X = CH_BAR + 16, MB_V = CH_BAR + 24, MB_T = CH_BAR + 32, MB_F = CH_BAR + 40, MB_G = CH_BAR + 48, MB_W = CH_BAR + 56;
enum { NB_PROJ = 1, NB_O = 2, NB_W1 = 3, NB_PRE = 4, NB_ST = 5, NB_MEM = 6, NB_XFREE = 7, NB_H1 = 8, NB_PUB = 9, NB_W2 = 10, NB_PROJ2 = 11, NB_PRE2 = 12, NB_H2 = 13, NB_W1V = 14 };
#define CH_NQ 9
#define CH_LAG 0
#define CH_PUSH 1
#define CH_CHAIN 0
#define CH_GATE 1
#define CH_PA 6
#define CH_PB 10
#define CH_PC 12
#define CH_PL 3
#define CH_DBL 0x2108
#define CH_PD 2
#define CH_ZD 1
#define SCHED() asm volatile("griddepcontrol.launch_dependents;" ::: "memory")
__device__ __forceinline__ uint32_t opaque(uint32_t x) { return __shfl_sync(~0u, x, threadIdx.x & 31); }
__device__ __forceinline__ uint32_t nz(uint32_t x) { uint32_t r; asm("max.u32 %0, %1, 1;" : "=r"(r) : "r"(x)); return r; }
__device__ __forceinline__ uint32_t set_tag(uint32_t w, uint32_t tag) { uint32_t r; asm("lop3.b32 %0, %1, %2, 1, 0xD8;" : "=r"(r) : "r"(w), "r"(tag)); return r; }
__device__ __forceinline__ uint32_t pack_tag(float lo, float hi, uint32_t tag) { return set_tag(__byte_perm(__float_as_uint(lo) + tag, pack2(hi, hi), 0x7632), tag); }
__device__ __forceinline__ uint32_t differ(uint32_t a, uint32_t b, uint32_t t) { uint32_t r; asm("lop3.b32 %0, %1, %2, %3, 0x7E;" : "=r"(r) : "r"(a), "r"(b), "r"(t)); return r; }
__device__ __forceinline__ uint32_t clk64() { uint64_t c; asm volatile("mov.u64 %0, %%clock64;" : "=l"(c) :: "memory"); return (uint32_t)c; }
__device__ __forceinline__ void until(uint32_t t) { while ((int)(clk64() - t) < 0) {} }
__device__ __forceinline__ float rcp(float x) { float y; asm("rcp.approx.ftz.f32 %0, %1;" : "=f"(y) : "f"(x)); return y; }

__device__ __forceinline__ void push_values(uint32_t sb, int s, int j) {
  const int r1 = j == 2 ? 0 : j + 1, r2 = j == 0 ? 2 : j - 1;
  const uint32_t src = sb + CH_V + j * 4096;
  if (s < NSEG - 1) {
    fence_async();
    bulk_push(mapa(src, r1), src, 4096, mapa(sb + MB_V, r1));
    bulk_push(mapa(src, r2), src, 4096, mapa(sb + MB_V, r2));
  }
}

template <int WG>
__device__ __forceinline__ void chain_compute(const ChainParams& p, const uint32_t sb) {
  const int tid = threadIdx.x & 127, t4 = __shfl_sync(~0u, tid >> 5, 0), lane = tid & 31;
  const int cta = blockIdx.x, h = cta / 3, j = cta - 3 * h;
  uint32_t ak[80], av[80], tw[4 * CH_NQ];
  const uint32_t wq = opaque(sb + CH_WQ + (WG * 320 + (lane & 7) + (lane >> 4) * 8) * 128 + (((2 * t4 + ((lane >> 3) & 1)) ^ (lane & 7)) << 4));
#pragma unroll
  for (int k = 0; k < 20; k++) {
    if (k == 0 || (WG * 20 + k) % 8 == 0) mbar_wait(sb + MB_W + 8 * ((WG * 20 + k) / 8), 0);
    ldsm4t(&ak[4 * k], wq + k * 2048);
  }
  bar_arrive(NB_PROJ2, 384);
#pragma unroll
  for (int k = 0; k < 20; k++) {
    if (k == 0 || (WG * 20 + k) % 8 == 0) mbar_wait(sb + MB_W + 40 + 8 * ((WG * 20 + k) / 8), 0);
    ldsm4t(&av[4 * k], wq + CH_WO + k * 2048);
  }
  bar_arrive(NB_PRE2, 384);
  const int r1 = j == 2 ? 0 : j + 1, r2 = j == 0 ? 2 : j - 1;
  const uint32_t l16 = opaque(sb + lane * 16), l8 = opaque(sb + lane * 8), l4 = opaque(sb + lane * 4);
  const uint32_t t16 = l16 + t4 * 512, t8 = l8 + t4 * 256;
  auto refill = [&]() {
#pragma unroll
    for (int k = 0; k < CH_NQ; k++) ldsm4t(&tw[4 * k], wq + k * 2048);
  };
  auto batch = [&](float* d, const uint32_t (&a)[80], int acc, bool fill) {
    const uint64_t d0 = mkdesc(1024 + CH_X + WG * 20480, 128, 5120, 0);
    wg_fence();
#pragma unroll
    for (int k = 0; k < 20; k++) {
      if (fill && !(k & 1) && k / 2 < CH_NQ) {
        uint32_t w = wq;
        if (k > 0 && CH_CHAIN) asm volatile("lop3.b32 %0, %1, %2, %3, 0xF8;" : "=r"(w) : "r"(wq), "r"(tw[2 * k - 1]), "r"(p.zero));
        __syncwarp();
        ldsm4t(&tw[2 * k], w + k * 1024);
        __syncwarp();
      }
      wg_rs32_00(d, a[4 * k], a[4 * k + 1], a[4 * k + 2], a[4 * k + 3], d0 + k * 16, acc | k);
    }
    wg_commit();
    wg_wait<0>();
    reg_fence<16>(d);
  };
  auto tokens = [&](int s, auto first) {
    float d[16];
    mbar_wait(sb + MB_T, s & 1);
    batch(d, WG == 0 ? ak : av, 0, WG == 0 && !first.value);
    s--; TM(10); s++;
    if (WG == 1 && !first.value) mbar_wait(sb + MB_F, (s - 1) & 1);
    const uint32_t kt = t16 + CH_K, vt = t16 + CH_V + j * 4096;
#pragma unroll
    for (int i = 0; i < 2; i++)
      sts128((WG == 0 ? kt : vt) + i * 2048, make_uint4(pack2(d[8 * i], d[8 * i + 1]), pack2(d[8 * i + 2], d[8 * i + 3]), pack2(d[8 * i + 4], d[8 * i + 5]), pack2(d[8 * i + 6], d[8 * i + 7])));
    if (first.value || CH_GATE != 1) bar_sync(NB_H1, 256); else bar_sync(NB_PUB, 384);
    const uint32_t own = WG == 0 ? vt : kt;
#pragma unroll
    for (int i = 0; i < 2; i++) {
      const uint4 t = lds128(own + i * 2048);
      d[8 * i] = bf_lo(t.x); d[8 * i + 1] = bf_hi(t.x); d[8 * i + 2] = bf_lo(t.y); d[8 * i + 3] = bf_hi(t.y);
      d[8 * i + 4] = bf_lo(t.z); d[8 * i + 5] = bf_hi(t.z); d[8 * i + 6] = bf_lo(t.w); d[8 * i + 7] = bf_hi(t.w);
    }
    reg_fence<16>(d);
    if (!first.value && CH_GATE == 2) bar_sync(NB_PUB, 384);
    batch(d, WG == 0 ? av : ak, 1, WG == 1 && !first.value);
    s--; TM(11); s++;
    if (WG == 0) bar_arrive(NB_XFREE, 256);
#pragma unroll
    for (int i = 0; i < 2; i++) {
      const uint32_t w0 = pack2(d[8 * i], d[8 * i + 1]), w1 = pack2(d[8 * i + 2], d[8 * i + 3]), w2 = pack2(d[8 * i + 4], d[8 * i + 5]), w3 = pack2(d[8 * i + 6], d[8 * i + 7]);
      if (WG == 1) stsm4t(own + i * 2048, w0, w1, w2, w3); else stsm4(own + i * 2048, w0, w1, w2, w3);
    }
    if (CH_PUSH == 0 && WG == 0) {
      if (t4 == 0) {
        bar_sync(NB_H2, 128);
        if (elect()) push_values(sb, s, j);
        __syncwarp();
      } else {
        bar_arrive(NB_H2, 128);
      }
    }
    if (first.value) { mbar_wait(sb + MB_WQ, 0); refill(); mbar_wait(sb + MB_WO, 0); }
  };
  asm volatile("barrier.cluster.wait.aligned;" ::: "memory");
  tokens(0, Int<1>());
  uint32_t wo = opaque(sb + CH_WO + (WG == 0 ? (t4 >> 1) * 36864 : 73728 + t4 * 1024) + ((lane & 7) + (lane >> 4) * 8) * 64 +
                             (((((lane >> 3) & 1) + (WG == 0 ? (t4 & 1) * 2 : 0)) ^ ((lane >> 1) & 3)) << 4));
  const uint32_t kmul = __shfl_sync(~0u, tid & 32 ? -3 : 1, 0), ko0 = __shfl_sync(~0u, (tid >> 6) * 3072 + (tid & 32) * 24, 0),
                 ko1 = __shfl_sync(~0u, (tid >> 6) * 1024 + 1024 + (tid & 32) * 24, 0);
  uint32_t tag = opaque(1);
  const uint32_t o768 = __shfl_sync(~0u, (tid >> 5) * 768, 0);
  bar_sync(NB_ST, 384);
  uint8_t* pdst[WG == 0 ? 6 : 1];
#pragma unroll
  for (int i = 0; i < (WG == 0 ? 6 : 1); i++) {
    const int line = WG == 0 ? 24 * j + 12 * (t4 >> 1) + 2 * (t4 & 1) + 4 * (i >> 1) + (i & 1) : j == 0 ? 72 + t4 : 74 + 2 * j + (t4 & 1);
    pdst[i] = pool_at(__shfl_sync(~0u, lds32(sb + CH_TAB + line * 4), 0) + h * 128);
  }
  auto project = [&](int s, float (&dv)[4], uint4 (&kf)[2]) {
    float dq[4] = {}, dk[4] = {};
    uint32_t b[40], w[80];
#pragma unroll
    for (int i = 0; i < 4 * CH_NQ; i++) w[i] = tw[i];
    bar_sync(NB_MEM, 384);
    ldsm4t(&b[0], l16 + CH_M + WG * 5120);
    ldsm4t(&b[4], l16 + CH_M + WG * 5120 + 512);
    TMD(0, b[0]);
    int nw = CH_NQ, nb = 2;
#pragma unroll
    for (int k = 0; k < 20; k++) {
      SCHED();
      mma16(dq, w[4 * k], w[4 * k + 1], w[4 * k + 2], w[4 * k + 3], b[2 * k], b[2 * k + 1]);
      mma16(dk, ak[4 * k], ak[4 * k + 1], ak[4 * k + 2], ak[4 * k + 3], b[2 * k], b[2 * k + 1]);
      mma16(dv, av[4 * k], av[4 * k + 1], av[4 * k + 2], av[4 * k + 3], b[2 * k], b[2 * k + 1]);
#pragma unroll
      for (int i = 0; i < (CH_DBL >> k & 1) + 1; i++) {
        if (nb < 10 && 2 * nb <= nw) { ldsm4t(&b[4 * nb], l16 + CH_M + WG * 5120 + nb * 512); nb++; }
        else if (nw < 20) { ldsm4t(&w[4 * nw], wq + nw * 2048); nw++; }
        else if (WG == 1 && nw < 22) { kf[nw - 20] = ldsm4v(l16 + ((l16 ^ tag) & 256) * kmul + (nw == 20 ? ko0 : ko1) + CH_K); nw++; }
      }
    }
    const float k2 = 0.07216878364870322f * 1.44269504089f;
    sts32(l4 + t4 * 512 + CH_Q + WG * 128, pack2(dq[0] * k2, dq[1] * k2));
    sts32(l4 + t4 * 512 + CH_Q + WG * 128 + 256, pack2(dq[2] * k2, dq[3] * k2));
    stsm2t(t16 + CH_KM + WG * 256, pack2(dk[0], dk[1]), pack2(dk[2], dk[3]));
    if (WG == 1) sts128f(t16 + CH_VP, dv[0], dv[1], dv[2], dv[3]);
    TM(1);
  };
#pragma unroll 1
  for (int s = 0; s < NSEG - 1; s++) {
    float dv[4] = {};
    uint4 kf[2];
    project(s, dv, kf);
    bar_sync(NB_PROJ, 256);
    if (WG == 0) {
      const float4 pv = lds128f(t16 + CH_VP);
      const uint32_t v0 = pack2(dv[0] + pv.x, dv[1] + pv.y), v1 = pack2(dv[2] + pv.z, dv[3] + pv.w);
      const uint32_t xo = t8 + CH_VX + j * 1024;
      st_async64(mapa(xo, r1), v0, v1, mapa(sb + MB_X, r1));
      st_async64(mapa(xo, r2), v0, v1, mapa(sb + MB_X, r2));
      sts64(xo, v0, v1);
      __syncwarp();
      if (elect()) mbar_arrive(sb + MB_X);
      bar_arrive(NB_PROJ2, 256);
      TM(3);
      uint32_t w[144];
      auto tile_of = [](int n) { return n < 27 ? n % 3 : (0x26484 >> 2 * (n - 27)) & 3; };
      auto step_of = [](int n) { return n < 27 ? n / 3 : 9 + ((0x29610 >> 2 * (n - 27)) & 3); };
      auto wload = [&](int n) { ldsm4t(&w[4 * n], wo + tile_of(n) * 12288 + (step_of(n) % 3) * 4096 + (step_of(n) / 3) * 1024); };
#pragma unroll
      for (int n = 0; n < CH_PA; n++) wload(n);
      bar_sync(NB_PRE, 256);
#pragma unroll
      for (int n = CH_PA; n < CH_PB; n++) wload(n);
      bar_arrive(NB_PRE2, 256);
      if (CH_PC > CH_PB) {
        mbar_wait(sb + MB_X, s & 1);
        for (int i = 0; i < CH_PD; i++) wo = __shfl_xor_sync(~0u, wo, p.zero);
#pragma unroll
        for (int n = CH_PB; n < CH_PC; n++) wload(n);
      }
      TM(4);
      bar_sync(NB_O, 256);
      {
        float x[3][4] = {};
        uint32_t ob[24];
        float4 l;
        ldsm4t(&ob[0], l16 + CH_O);
        ldsm4t(&ob[4], l16 + CH_O + 512);
        TMD(7, ob[0]);
        int nw = CH_PC, no = 2;
        float i0, i1;
        uint8_t* dst[6];
        uint32_t lo[6], hi[6];
        auto pre = [&](int i) { lo[i] = __float_as_uint(x[i >> 1][2 * (i & 1)] * i0) + tag; hi[i] = pack2(0.f, x[i >> 1][2 * (i & 1) + 1] * i1); };
        auto emit = [&](int i) { stg_strong32(dst[i], set_tag(__byte_perm(lo[i], hi[i], 0x7632), tag)); };
#pragma unroll
        for (int n = 0; n < 36; n++) {
          SCHED();
          mma16(x[tile_of(n)], w[4 * n], w[4 * n + 1], w[4 * n + 2], w[4 * n + 3], ob[step_of(n) * 2], ob[step_of(n) * 2 + 1]);
          if (n >= CH_PL) {
            if (no < 6 && no * 2 <= step_of(min(nw, 35))) { ldsm4t(&ob[4 * no], l16 + CH_O + no * 512); no++; }
            else if (nw < 36) { wload(nw); nw++; }
          }
          if (n == 18) l = lds128f(sb + CH_L + ((l16 ^ tag) & 0x30));
          if (n == 26) { i0 = rcp(l.x + l.y); i1 = rcp(l.z + l.w); asm volatile("" : "+f"(i0), "+f"(i1)); }
          if (n >= 28 && n < 34) { dst[n - 28] = pdst[n - 28] + ((l4 ^ tag) & 0x7c); asm volatile("" : "+l"(dst[n - 28])); }
          if (n == 32) { for (int i = 0; i < 2; i++) { pre(i); asm volatile("" : "+r"(lo[i]), "+r"(hi[i])); } }
          if (n == 33) { emit(0); emit(1); }
        }
        for (int i = 2; i < 6; i++) pre(i);
        for (int i = 2; i < 6; i++) emit(i);
      }
      TM(8);
    } else {
      {
        float d0[4] = {}, d1[4] = {}, dm[4] = {};
        uint32_t q[16], km[4];
#pragma unroll
        for (int e = 0; e < 4; e++) {
          ldsm4t(&q[4 * e], l16 + (e ^ t4) * 512 + CH_Q);
          if (e == 1) ldsm4(km, t16 + CH_KM);
        }
        SCHED();
        mma16(d0, q[0], q[1], q[2], q[3], kf[0].x, kf[0].y);
        mma16(d1, q[4], q[5], q[6], q[7], kf[0].z, kf[0].w);
        mma16(dm, q[0], q[1], q[2], q[3], hadd2(km[0], km[2]), hadd2(km[1], km[3]));
        mma16(d0, q[8], q[9], q[10], q[11], kf[1].x, kf[1].y);
        mma16(d1, q[12], q[13], q[14], q[15], kf[1].z, kf[1].w);
        const uint32_t w0 = pack2((d0[0] + d0[2]) + (d1[0] + d1[2]), (d0[1] + d0[3]) + (d1[1] + d1[3])), w1 = pack2(dm[0] + dm[2], dm[1] + dm[3]);
        const uint32_t xo = l4 + t4 * 128, x1 = mapa(xo, r1), x2 = mapa(xo, r2);
        st_async32(x1 + CH_SX + 512, w1, mapa(sb + MB_X, r1));
        st_async32(x2 + CH_SX + 1536, w1, mapa(sb + MB_X, r2));
        st_async32(x1 + CH_SX, w0, mapa(sb + MB_X, r1));
        st_async32(x2 + CH_SX + 1024, w0, mapa(sb + MB_X, r2));
        sts32(xo + CH_SO, w0);
        sts32(xo + CH_SO + 512, w1);
      }
      TM(3);
      float sc[3][4] = {};
      uint32_t wd[12];
      float big;
      auto attend = [&](auto first) {
        uint4 vb[6];
        uint2 vm[3];
        float e[10];
        uint32_t ow[6];
        if (first.value) {
          const uint2 id = lds64(l8 + CH_ID);
          bar_sync(NB_W1V, 160);
          uint32_t r[8];
          ldsm4(r, l16 + CH_SO); ldsm4(r + 4, l16 + CH_SO + 512);
#pragma unroll
          for (int u = 0; u < 6; u++) vb[u] = ldsm4v(t16 + CH_V + u * 2048);
          bar_arrive(NB_PRE, 256);
          uint32_t sxa = l16 + ((l16 ^ tag) & 256) * 3;
          asm volatile("" : "+r"(sxa));
          sxa += CH_SX;
          SCHED();
          mma8(sc[0], r[0], r[1], id.x);
          mma8(sc[1], r[2], r[3], id.x);
          mma16(sc[2], r[4], r[5], r[6], r[7], id.x, id.y);
          TM(7);
          mbar_wait(sb + MB_X, s & 1);
          TM(4);
          uint32_t t[16];
          ldsm4(t, sxa); ldsm4(t + 4, sxa + 256); ldsm4(t + 8, sxa + 512);
          SCHED();
          mma16(sc[0], t[0], t[1], t[2], t[3], id.x, id.y);
          ldsm4(t + 12, sxa + 768);
          SCHED();
          mma16(sc[1], t[4], t[5], t[6], t[7], id.x, id.y);
#pragma unroll
          for (int u = 0; u < 2; u++) vm[u] = lds64(t8 + CH_VX + u * 1024);
          SCHED();
          e[0] = ex2(sc[0][0]);
          mma16(sc[2], t[8], t[9], t[10], t[11], id.x, id.y);
          vm[2] = lds64(t8 + CH_VX + 2048);
          SCHED();
          e[1] = ex2(sc[0][1]);
          ldsm4t(&wd[0], wo);
          SCHED();
          e[2] = ex2(sc[0][2]);
          SCHED();
          e[3] = ex2(sc[0][3]);
          mma16(sc[2], t[12], t[13], t[14], t[15], id.x, id.y);
          SCHED();
          e[4] = ex2(sc[1][0]);
          ldsm4t(&wd[4], wo + 4096);
          SCHED();
          e[5] = ex2(sc[1][1]);
        } else {
#pragma unroll
          for (int u = 0; u < 6; u++) vb[u] = ldsm4v(t16 + CH_V + u * 2048);
#pragma unroll
          for (int u = 0; u < 3; u++) vm[u] = lds64(t8 + CH_VX + u * 1024);
        }
        float o[3][4] = {};
        if (!first.value) {
#pragma unroll
          for (int i = 0; i < 6; i++) e[i] = ex2(sc[i >> 2][i & 3]);
        }
        const uint32_t p1 = pack2(e[0], e[1]), p2 = pack2(e[2], e[3]);
        float l = (e[0] + e[1]) + (e[2] + e[3]);
        asm volatile("" : "+f"(l));
        SCHED();
        e[6] = ex2(sc[1][2]);
        mma16(o[0], vb[0].x, vb[0].y, vb[0].z, vb[0].w, p1, p2);
        if (first.value) { sc[2][0] += sc[2][2]; sc[2][1] += sc[2][3]; }
        SCHED();
        e[7] = ex2(sc[1][3]);
        mma16(o[1], vb[2].x, vb[2].y, vb[2].z, vb[2].w, p1, p2);
        SCHED();
        e[8] = ex2(sc[2][0]);
        mma16(o[2], vb[4].x, vb[4].y, vb[4].z, vb[4].w, p1, p2);
        big = fmaxf(fmaxf(fmaxf(fabsf(sc[0][0]), fabsf(sc[0][1])), fmaxf(fabsf(sc[0][2]), fabsf(sc[0][3]))), fmaxf(fabsf(sc[2][0]), fabsf(sc[2][1])));
        SCHED();
        e[9] = ex2(sc[2][1]);
        const uint32_t p3 = pack2(e[4], e[5]), p4 = pack2(e[6], e[7]);
        l += (e[4] + e[5]) + (e[6] + e[7]);
#pragma unroll
        for (int u = 0; u < 3; u++) mma16(o[u], vb[2 * u + 1].x, vb[2 * u + 1].y, vb[2 * u + 1].z, vb[2 * u + 1].w, p3, p4);
        big = fmaxf(big, fmaxf(fmaxf(fabsf(sc[1][0]), fabsf(sc[1][1])), fmaxf(fabsf(sc[1][2]), fabsf(sc[1][3]))));
        SCHED();
        const uint32_t p0 = pack2(e[8], e[9]);
        l += e[8] + e[9];
        l += __shfl_xor_sync(~0u, l, 1);
        if (first.value) ldsm4t(&wd[8], wo + 8192);
#pragma unroll
        for (int u = 0; u < 3; u++) mma8(o[u], vm[u].x, vm[u].y, p0);
        SCHED();
#pragma unroll
        for (int u = 0; u < 3; u++) { ow[2 * u] = pack2(o[u][0], o[u][1]); ow[2 * u + 1] = pack2(o[u][2], o[u][3]); }
        stsm4(l16 + o768 + CH_O, ow[0], ow[1], ow[2], ow[3]);
        stsm2(l16 + o768 + CH_O + 512, ow[4], ow[5]);
        if (t4 == 0) sts32(sb + CH_L + (((l4 ^ tag) >> 1) & 0x3c), __float_as_uint(l));
      };
      attend(Int<1>());
      const uint32_t redo = __any_sync(~0u, big > 30.f);
      TM(6);
      asm volatile("{.reg .pred p; setp.eq.u32 p, %0, 0; @p bar.arrive 2, 256;}" :: "r"(redo) : "memory");
      if (redo) {
        float mx = fmaxf(sc[2][0], sc[2][1]);
#pragma unroll
        for (int i = 0; i < 4; i++) mx = fmaxf(mx, fmaxf(sc[0][i], sc[1][i]));
        mx = fmaxf(mx, __shfl_xor_sync(~0u, mx, 1));
        mx = fmaxf(mx, __shfl_xor_sync(~0u, mx, 2));
#pragma unroll
        for (int i = 0; i < 4; i++) { sc[0][i] -= mx; sc[1][i] -= mx; }
        sc[2][0] -= mx; sc[2][1] -= mx;
        attend(Int<0>());
        bar_arrive(NB_O, 256);
      }
      {
        float z[4] = {};
        const uint32_t scr = l8 + CH_V + r1 * 4096;
        uint32_t ow[6];
        __syncwarp();
        uint32_t oa = l16;
        for (int i = 0; i < CH_ZD; i++) oa = __shfl_xor_sync(~0u, oa, p.zero);
        ldsm4t(ow, oa + o768 + CH_O);
        ldsm2t(ow + 4, oa + o768 + CH_O + 512);
#pragma unroll
        for (int u = 0; u < 3; u++) mma16(z, wd[4 * u], wd[4 * u + 1], wd[4 * u + 2], wd[4 * u + 3], ow[2 * u], ow[2 * u + 1]);
        if (j == 0) {
          float y[4] = {};
          uint32_t we[12];
#pragma unroll
          for (int u = 0; u < 3; u++) ldsm4t(&we[4 * u], (wo ^ 32) + u * 4096);
#pragma unroll
          for (int u = 0; u < 3; u++) mma16(y, we[4 * u], we[4 * u + 1], we[4 * u + 2], we[4 * u + 3], ow[2 * u], ow[2 * u + 1]);
          sts64f(scr + t4 * 512 + 2048, y[0], y[1]); sts64f(scr + t4 * 512 + 2304, y[2], y[3]);
        }
        sts64f(scr + t4 * 512, z[0], z[1]); sts64f(scr + t4 * 512 + 256, z[2], z[3]);
        bar_sync(NB_W1, 128);
        if (j == 0 || t4 < 2) {
          float2 q[4];
          const float4 l = lds128f(sb + CH_L + ((l16 ^ tag) & 0x30));
#pragma unroll
          for (int i = 0; i < 4; i++) q[i] = lds64f(scr + (t4 >> 1) * 2048 + (t4 & 1) * 256 + i * 512);
          stg_strong32(pdst[0] + ((l4 ^ tag) & 0x7c), pack_tag(((q[0].x + q[1].x) + (q[2].x + q[3].x)) * rcp(l.x + l.y), ((q[0].y + q[1].y) + (q[2].y + q[3].y)) * rcp(l.z + l.w), tag));
        }
      }
      TM(2);
    }
    bar_sync(NB_ST, 384);
    tokens(s + 1, Int<0>());
    TM(9);
    tag ^= 0x10001;
  }
  {
    float dv[4] = {};
    uint4 kf[2];
    project(NSEG - 1, dv, kf);
    bar_sync(NB_PROJ, 256);
    if (WG == 0) {
      const float4 pv = lds128f(t16 + CH_VP);
      sts64(t8 + CH_VX + j * 1024, pack2(dv[0] + pv.x, dv[1] + pv.y), pack2(dv[2] + pv.z, dv[3] + pv.w));
      bar_arrive(NB_PROJ2, 256);
      bar_arrive(NB_PRE2, 256);
    }
  }
}

__device__ __forceinline__ void chain_comm(const ChainParams& p, const uint32_t sb) {
  [[maybe_unused]] constexpr int WG = 2;
  const int tid = threadIdx.x & 127, t4 = __shfl_sync(~0u, tid >> 5, 0), lane = tid & 31;
  const int cta = blockIdx.x, h = cta / 3, j = cta - 3 * h, colbase = cta * 64;
  const uint8_t* const xs = reinterpret_cast<const uint8_t*>(g_xn);
  auto xload = [&](int seg, int i, int off, int bytes) { bulk_load(sb + CH_X + i * 5120 + off, xs + (seg * 4 + (i & 3)) * 10240 + (i >> 2) * 5120 + off, bytes, sb + MB_T); };
  if (cta == 0) for (int i = tid; i < SY_N; i += 128) p.other[i] = 0;
  uint32_t smid; asm("mov.u32 %0, %%smid;" : "=r"(smid));
  const uint32_t part = max(ldg_strong32(g_smpart + (smid & 255)), 1u);
  if (tid == 64) stg_strong32(p.sync + SY_PART + cta, part);
  PRO(0);
  if (t4 == 3) {
    bar_arrive(NB_PROJ2, 384);
    bar_arrive(NB_PRE2, 384);
    if (elect()) {
      wait_count(p.sync + SY_P + 1, ln_items(p.layer, 0));
      fence_async_global();
      mbar_expect(sb + MB_T, 40960);
      for (int i = 0; i < 8; i++) xload(0, i, 0, 5120);
    }
    __syncwarp();
  } else {
  bar_sync(NB_PROJ2, 384);
  __syncwarp();
  PRO(1);
  if (t4 == 0 && elect()) {
    mbar_expect(sb + MB_WQ, 81920);
    for (int i = 0; i < 5; i++) tma_load(sb + CH_WQ + i * 16384, &p.wq, colbase, i * 128, sb + MB_WQ);
  }
  bar_sync(NB_PRE2, 384);
  __syncwarp();
  PRO(2);
  if (t4 == 0 && elect()) {
    mbar_expect(sb + MB_WO, 86016);
    for (int i = 0; i < 6; i++) tma_load(sb + CH_WO + i * 12288, &p.wo, j * 192 + i * 32, h * 192, sb + MB_WO);
    tma_load(sb + CH_WO + 73728, &p.wo, j == 0 ? 576 : 592 + j * 16, h * 192, sb + MB_WO);
  }
  }
  if (tid < NSLOT) {
    const uint32_t* part_of = p.sync + SY_PART + (tid >= 80 ? cta : tid);
    uint32_t reader = 0, orient = 0;
    int n = 0;
    while (reader == 0 || orient == 0) { reader = ldg_strong32(part_of); orient = ldg_strong32(g_orient + tid); spin_guard(n); }
    sts32(sb + CH_TAB + tid * 4, tid * 8192 + (orient == reader ? 0 : 4096));
    if (t4 == 0) {
      const uint32_t near = __ballot_sync(~0u, reader == part) & 0xffffff;
      if (lane == 0) sts32(sb + CH_TAB + NSLOT * 4, cta < 80 ? cta : near ? __fns(near, 0, 1 + cta % __popc(near)) : 0);
    }
  }
  __syncwarp();
  asm volatile("barrier.cluster.wait.aligned;" ::: "memory");
  const uint32_t l8 = opaque(sb + t4 * 256 + lane * 8);
  {
    const uint32_t* m0 = reinterpret_cast<const uint32_t*>(p.mem0) + (lane >> 2) * (DM / 2) + t4 * 80 + (lane & 3);
    uint32_t g[20];
#pragma unroll
    for (int i = 0; i < 20; i++) g[i] = transpose8(m0[i * 4]);
    const uint32_t id = (lane >> 3) == (lane & 3) ? ((lane & 4) ? 0x3f800000u : 0x00003f80u) : 0u;
    if (t4 == 0) sts64(l8 + CH_ID, id, id);
    bar_sync(NB_XFREE, 256);
#pragma unroll
    for (int i = 0; i < 20; i++) sts32(sb + CH_M + (t4 * 20 + i) * 128 + lane * 4, g[i]);
  }
  bar_sync(NB_ST, 384);
  uint8_t* const pool = pool_at(0);
  const uint8_t* const psrc = pool + opaque(lds32(sb + CH_TAB + lds32(sb + CH_TAB + NSLOT * 4) * 4) + t4 * 1024 + lane * 4);
  const uint32_t mdst = opaque((80 + cta / 20) * 8192 + (t4 & 1) * 4096 + (cta % 20) * 128 + lane * 4);
  int st = 0;
  uint32_t tag = opaque(1);
  bar_sync(NB_MEM, 384);
#pragma unroll 1
  for (int s = 0;; s++) {
    TM(0);
    STAT(0);
    if (t4 == 0) {
      if (elect()) {
        if (CH_PUSH == 1) push_values(sb, s, j);
        fence_async();
        uint8_t* dst = g_kv + ((s >> 2) * 96 + cta) * KV_BYTES + (s & 3) * 4096;
        (HINT & 8 ? bulk_store_stream : bulk_store)(dst + KV_K, sb + CH_K, 4096);
        (HINT & 8 ? bulk_store_stream : bulk_store)(dst + KV_V, sb + CH_V + j * 4096, 4096);
        bulk_commit();
        bulk_wait_read<0>();
      }
      __syncwarp();
    }
    if (t4 == 3 && (s & 3) == 2 && s < NSEG - 2) wait_count_uniform(p.sync + SY_P + 5 + (s & ~3), ln_items(p.layer, (s >> 2) + 1));
    if (t4 == 2 && s < NSEG - 1) { mbar_wait(sb + MB_V, s & 1); bar_arrive(NB_W1V, 160); }
    bar_sync(NB_PROJ2, 256);
    if (t4 == 0 && s < NSEG - 1 && elect()) {
      mbar_expect(sb + MB_X, 4096);
      mbar_expect(sb + MB_T, 40960);
#pragma unroll
      for (int i = 0; i < 7; i++) xload(s + 1, i, 0, i < 6 ? 5120 : 4096);
    }
    __syncwarp();
    STAT(1);
    TM(1);
    {
      const uint2 a = lds64(l8 + t4 * 256 + CH_KM), b = lds64(l8 + t4 * 256 + CH_KM + 256);
      sts64(l8 + CH_KS, hadd2(a.x, b.x), hadd2(a.y, b.y));
    }
    TM(4);
    bar_sync(NB_PRE2, 256);
    if (t4 == 0 && elect()) {
      if (s < NSEG - 1) { xload(s + 1, 6, 4096, 1024); xload(s + 1, 7, 0, 5120); }
      fence_async();
      uint8_t* dst = g_kv + ((s >> 2) * 96 + cta) * KV_BYTES + (s & 3) * 1024;
      bulk_store(dst + KV_KM, sb + CH_KS, 1024);
      bulk_store(dst + KV_VM, sb + CH_VX + j * 1024, 1024);
      bulk_commit();
      bulk_wait<0>();
      if ((s & 3) == 3) { fence_async_global(); atomicAdd(p.sync + (s >> 2) * 8 + 4, 1); }
    }
    __syncwarp();
    if (s == NSEG - 1) break;
    if (s == NSEG - 3 && cta == 95 && t4 == 2 && elect()) atomicAdd(p.sync + 15 * 8 + 4, 0x10000);
    __syncwarp();
    const uint8_t* ms = pool + (lds32(sb + CH_TAB + (80 + st * 4 + t4) * 4) + (l8 & 255));
    uint8_t* md = pool + (mdst + (t4 < 2 ? st : st == 2 ? 0 : st + 1) * 32768);
    asm volatile("" : "+l"(ms), "+l"(md));
    TM(2);
    bar_sync(NB_ST, 384);
    __syncwarp();
    uint32_t tg = clk32();
    if (t4 == 3 && elect()) {
      if (s < NSEG - 2) mbar_expect(sb + MB_V, 8192);
      mbar_arrive_remote(mapa(sb + MB_F, j == 2 ? 0 : j + 1));
      mbar_arrive_remote(mapa(sb + MB_F, j == 0 ? 2 : j - 1));
    }
    __syncwarp();
    STAT(2);
    {
      float2 q[4];
      uint32_t u[2][8];
      auto poll = [&](uint32_t (&v)[8], uint32_t flip) {
        const uint8_t* src = psrc + flip;
#pragma unroll
        for (int i = 0; i < 8; i++) v[i] = ldg_strong32(src + i * 128);
      };
      auto sum = [&](uint32_t (&v)[8]) {
        sts64f(l8 + CH_R2, ((bf_lo(v[0]) + bf_lo(v[1])) + (bf_lo(v[2]) + bf_lo(v[3]))) + ((bf_lo(v[4]) + bf_lo(v[5])) + (bf_lo(v[6]) + bf_lo(v[7]))),
               ((bf_hi(v[0]) + bf_hi(v[1])) + (bf_hi(v[2]) + bf_hi(v[3]))) + ((bf_hi(v[4]) + bf_hi(v[5])) + (bf_hi(v[6]) + bf_hi(v[7]))));
        uint32_t bad;
        asm volatile("{.reg .pred p, q; .reg .b32 a; lop3.b32 a, %1, %2, %3, 0xFE; lop3.b32 a, a, %4, 1, 0xA8; setp.ne.u32 p, a, 0;\n"
                     "bar.red.or.pred q, %5, 128, p; selp.u32 %0, 1, 0, q;}"
                     : "=r"(bad) : "r"(differ(v[0], v[1], tag)), "r"(differ(v[2], v[3], tag)), "r"(differ(v[4], v[5], tag)), "r"(differ(v[6], v[7], tag)), "n"((int)NB_W2) : "memory");
#pragma unroll
        for (int k = 0; k < 4; k++) asm volatile("ld.volatile.shared.v2.f32 {%0,%1}, [%2];" : "=f"(q[k].x), "=f"(q[k].y) : "r"(l8 - t4 * 256 + CH_R2 + k * 256) : "memory");
        return bad;
      };
      TM(3);
      until(tg + p.d1);
      poll(u[0], 0);
      SCHED();
      uint32_t lag = l8;
#pragma unroll
      for (int i = 0; i < CH_LAG; i++) asm volatile("mul.lo.u32 %0, %0, %1;" : "+r"(lag) : "r"(p.zero));
      if (CH_LAG) poll(u[1], lag);
      SCHED();
      if (sum(u[0])) {
        poll(u[0], CH_LAG ? u[1][7] & p.zero : 0);
        SCHED();
        if (!CH_LAG || sum(u[1])) {
          for (int n = 0; sum(u[0]) && (cta < 80 || n < 2); spin_guard(n)) poll(u[0], 0);
        }
      }
      if (CH_GATE) bar_arrive(NB_PUB, 384);
      SCHED();
      TM(9);
      if (cta < 80) stg_strong32(md, min(nz(pack2((q[0].x + q[1].x) + (q[2].x + q[3].x), (q[0].y + q[1].y) + (q[2].y + q[3].y))), t4 < 2 ? ~0u : 0u));
      tg = clk64() + p.d2;
      TM(8);
    }
    STAT(3);
    until(tg);
    TM(10);
    for (int n = 0;;) {
      uint2 g[10];
#pragma unroll
      for (int i = 0; i < 10; i++) g[i] = ldg_strong64(ms + i * 256);
      if (n == 0) bar_sync(NB_XFREE, 256);
      spin_guard(n);
      uint32_t m = ~0u;
#pragma unroll
      for (int i = 0; i < 10; i++) { sts64(l8 + CH_M + t4 * 2304 + i * 256, g[i].x, g[i].y); m = __vimin3_u32(m, g[i].x, g[i].y); }
      TMV(13, n - 1);
      if (!__any_sync(~0u, m == 0)) break;
    }
    TM(11);
    if (t4 == 0) bar_sync(NB_MEM, 384); else bar_arrive(NB_MEM, 384);
    if (++st == 3) st = 0;
    tag ^= 0x10001;
  }
  TRACE(2);
}

#define CH_R0 232
#define CH_R1 232
#define CH_R2N 40
__global__ void __launch_bounds__(384, 1) chain_kernel(const __grid_constant__ ChainParams p) {
  extern __shared__ __align__(1024) uint8_t smem_raw[];
  const uint32_t sb = s2u(smem_raw);
  const int wg = __shfl_sync(~0u, threadIdx.x >> 7, 0);
  if (threadIdx.x < 32 && elect()) {
    atomicAdd(p.sync + SY_UP, 1);
    if ((sb & 0xffffff) != 1024) __trap();
    mbar_init(sb + MB_WO, 1); mbar_init(sb + MB_WQ, 1); mbar_init(sb + MB_X, 5); mbar_init(sb + MB_V, 1); mbar_init(sb + MB_T, 1); mbar_init(sb + MB_F, 2); mbar_init(sb + MB_G, 2);
    for (int i = 0; i < 10; i++) mbar_init(sb + MB_W + 8 * i, 1);
    asm volatile("fence.mbarrier_init.release.cluster;" ::: "memory");
    mbar_expect(sb + MB_V, 8192);
    for (int i = 0; i < 10; i++) {
      const int n = i % 5 < 2 ? (i % 5) * 2 : i % 5 == 2 ? 1 : i % 5;
      const uint32_t bar = sb + MB_W + 8 * (n + (i < 5 ? 0 : 5));
      mbar_expect(bar, 16384);
      tma_load(sb + (i < 5 ? CH_WQ : CH_WO) + n * 16384, i < 5 ? &p.wk : &p.wv, blockIdx.x * 64, n * 128, bar);
    }
  }
  __syncthreads();
  asm volatile("barrier.cluster.arrive.relaxed.aligned;" ::: "memory");
  pdl_launch();
  if (wg == 2) {
    asm volatile("setmaxnreg.dec.sync.aligned.u32 %0;" :: "n"(CH_R2N));
    chain_comm(p, sb);
  } else if (wg == 0) {
    asm volatile("setmaxnreg.inc.sync.aligned.u32 %0;" :: "n"(CH_R0));
    chain_compute<0>(p, sb);
  } else {
    asm volatile("setmaxnreg.inc.sync.aligned.u32 %0;" :: "n"(CH_R1));
    chain_compute<1>(p, sb);
  }
}

struct WorkParams {
  CUtensorMap wq, wo, wb, wc, out, xn, xp;
  const __nv_bfloat16* x;
  uint32_t* sync;
  int kind, qa_end, idle;
};
#define GO_320 4
#define GO_192 6
enum { WK_FIRST = 0, WK_LEAD = 1, WK_JOIN = 2, WK_LAST = 3 };
constexpr int WK_SLOTS = 28, WK_BAR = WK_SLOTS * 8192, WK_SMEM = WK_BAR + 384 + 2048;
enum { IT_ATT = 0, IT_OP = 1, IT_FIN = 2, IT_BQ = 3, IT_BO = 4, IT_LN = 5, IT_Q = 6, IT_LN0 = 7, IT_OUT = 8 };
constexpr int C_EARLY = 1 << 20, C_LATE = 1 << 21, C_FREE = 1 << 22;

__device__ __forceinline__ uint32_t item_count(int type, int b) { return type == IT_ATT ? 32 : type == IT_OP ? op_tiles(b) * op_split(b) : type == IT_FIN ? fin_items(b) : bq_items(b); }
__device__ __forceinline__ uint32_t item_need(int type, int b) { return type == IT_ATT ? 96 : item_count(type - 1, b); }
__device__ __forceinline__ int item_cols(int type, int b) {
  return type == IT_ATT || type == IT_Q ? 192 : type == IT_OUT ? 80 : type == IT_BQ ? (b < BQ_12 ? 320 : b < BQ_24 ? 160 : 80) : type == IT_OP && b >= OP_N4 ? 160 : 320; }
__device__ __forceinline__ int item_groups(int type, int b) { return 16 / (type == IT_FIN ? fin_items(b) : ln_items(type == IT_LN, b)); }
#define RES_OP 15
constexpr int RES_N = (RES_OP < 15 ? op_tiles(14) * op_split(14) : 0) + op_tiles(15) * op_split(15), RES_BQ = (94 - RES_N) / 6;
__device__ __forceinline__ bool reserved(int type, int b) { return type == IT_OP ? b >= RES_OP : type == IT_BQ && b < RES_BQ; }
__device__ __forceinline__ int reserved_item(int i) {
  constexpr int n15 = op_tiles(15) * op_split(15);
  if (i < RES_BQ * 6) return C_FREE | IT_BQ << 16 | (i / 6) << 8 | i % 6;
  i -= RES_BQ * 6;
  return i < n15 ? C_FREE | IT_OP << 16 | 15 << 8 | i : i < RES_N ? C_FREE | IT_OP << 16 | 14 << 8 | (i - n15) : -1;
}
constexpr int LEAD1 = 12;
__device__ __forceinline__ int lead_item(int layer, int qa_end, int i) {
  if (layer == 2) return i < 128 ? C_EARLY | C_LATE | IT_OUT << 16 | (i >> 3) << 8 | (i & 7) : -1;
  if (layer == 0) {
    if (i < 32) return IT_LN0 << 16 | (i >> 4) << 8 | (i & 15);
    if (i < 88) return IT_LN0 << 16 | ((i - 24) >> 2) << 8 | (i & 3);
    i -= 88;
  } else {
    if (i < 4) return C_EARLY | IT_BO << 16 | (i >> 1) << 8 | (i & 1);
    if (i < 12) return C_EARLY | IT_LN << 16 | ((i - 4) >> 2) << 8 | (i & 3);
    if (i < 40) return C_EARLY | IT_BO << 16 | ((i - 8) >> 1) << 8 | (i & 1);
    if (i < 96) return C_EARLY | IT_LN << 16 | ((i - 32) >> 2) << 8 | (i & 3);
    i -= 96;
  }
  return i < (16 - qa_end) * 32 ? C_EARLY | IT_Q << 16 | (qa_end + (i >> 5)) << 8 | (i & 31) : -1;
}

struct Ring {
  uint32_t sb;
  int pos, seq;
  __device__ __forceinline__ uint32_t full() const { return sb + WK_BAR + 8 * (seq & 7); }
  __device__ __forceinline__ uint32_t take(int len) { if (pos + len > WK_SLOTS) pos = 0; pos += len; seq++; return sb + (pos - len) * 8192; }
  __device__ __forceinline__ uint32_t wait(int len) { mbar_wait_uniform(full(), (seq >> 3) & 1); return take(len); }
  __device__ __forceinline__ void release(int sq) const { if (elect()) mbar_arrive(sb + WK_BAR + 64 + 8 * (sq & 7)); }
};

struct Pending {
  uint32_t w[48], done;
  uint4* dst;
  __device__ __forceinline__ void store(int i) const { dst[(i >> 2) * 1024 + (i & 3) * 32] = make_uint4(w[4 * i], w[4 * i + 1], w[4 * i + 2], w[4 * i + 3]); }
  __device__ __forceinline__ void finish() { __syncwarp(); if (elect()) mbar_arrive(done); done = 0; }
  __device__ __forceinline__ void flush() {
    if (done) {
#pragma unroll
      for (int i = 0; i < 12; i++) store(i);
      finish();
    }
  }
};

template <int N>
__device__ __forceinline__ void gemm_item(float* d, Ring& r, int nkb, uint32_t go, Pending& pend) {
  const int warp = __shfl_sync(~0u, threadIdx.x >> 5, 0), wg = warp >> 2;
#pragma unroll 1
  for (int kb = 0; kb < nkb; kb++) {
    const uint32_t base = r.wait(2 + (N + 63) / 64);
    const uint64_t da = mkdesc(base + wg * 8192, 128, 1024, 0), db = mkdesc(base + 16384, 8192, 1024, 1);
    wg_fence();
#pragma unroll
    for (int kk = 0; kk < 4; kk++) {
      if (N == 80) wg_ss80_01(d, da + kk * 16, db + kk * 128, (kb | kk) != 0);
      else if (N == 160) wg_ss160_01(d, da + kk * 16, db + kk * 128, (kb | kk) != 0);
      else wg_ss192_01(d, da + kk * 16, db + kk * 128, (kb | kk) != 0);
      if (N == 320) wg_ss128_01(d + 96, da + kk * 16, db + kk * 128 + 3 * 512, (kb | kk) != 0);
    }
    wg_commit();
    if (kb == max(nkb - (N == 320 ? GO_320 : GO_192), 0) && go && warp == 0 && elect()) mbar_arrive(go);
    if (N == 192 && pend.done) {
#pragma unroll
      for (int i = 0; i < 12; i++) if (kb == i / 2) pend.store(i);
      if (kb == 5) pend.finish();
    }
    if (kb > 0) { wg_wait<1>(); r.release(r.seq - 2); }
  }
  wg_wait<0>();
  reg_fence<N / 2>(d);
  r.release(r.seq - 1);
}

template <int HALF>
__device__ __forceinline__ void attn_a_warp(Ring& r, Pending& pend, bool now) {
  uint32_t (&q)[48] = pend.w;
  constexpr int NT = HALF ? 5 : 3, NF = 8 * NT;
  const int lane = threadIdx.x & 31, g = lane >> 2, c = lane & 3, seg = (threadIdx.x >> 5) & 3;
  float sc[NT][4] = {};
  uint32_t base, f[2][NF];
  auto load_k = [&](int u) {
    base = u & 1 ? base + 20480 : r.wait(5) + seg * 1024;
#pragma unroll
    for (int kk = 0; kk < 4; kk++) {
      if (!(kk & 1)) ldsm4(&f[u & 1][2 * kk], base + KV_KM + kk * 256 + lane * 16);
#pragma unroll
      for (int t = 0; t <= HALF; t++) ldsm4(&f[u & 1][8 + 16 * t + 4 * kk], base + seg * 3072 + t * 2048 + kk * 512 + lane * 16);
    }
  };
  auto load_v = [&](int u) {
    base = u & 1 ? r.wait(5) + seg * 1024 : base + 20480;
#pragma unroll
    for (int n = 0; n < 4; n++) {
      const uint2 vm = lds64(base + KV_KM + n * 256 + lane * 8);
      f[~u & 1][2 * n] = vm.x; f[~u & 1][2 * n + 1] = vm.y;
#pragma unroll
      for (int t = 0; t <= HALF; t++)
        ldsm4(&f[~u & 1][8 + 16 * t + 4 * n], base + seg * 3072 + t * 2048 + n * 512 + (lane & 8) * 32 + (lane & 16) * 8 + (lane & 7) * 16);
    }
  };
  load_k(0);
#pragma unroll
  for (int u = 0; u < 3; u++) {
    if (u < 2) load_k(u + 1); else { r.release(r.seq - 2); load_v(0); }
    SCHED();
#pragma unroll
    for (int kk = 0; kk < 4; kk++) {
      const uint32_t *a = &q[16 * u + 4 * kk], *b = f[u & 1];
      mma16(sc[0], a[0], a[1], a[2], a[3], b[2 * kk], b[2 * kk + 1]);
#pragma unroll
      for (int n = 0; n < NT - 1; n++) mma16(sc[1 + n], a[0], a[1], a[2], a[3], b[8 + 16 * (n >> 1) + 4 * kk + 2 * (n & 1)], b[9 + 16 * (n >> 1) + 4 * kk + 2 * (n & 1)]);
    }
    SCHED();
  }
  load_v(1);
  SCHED();
  const float k2 = 0.07216878364870322f * 1.44269504089f, NEG = -INFINITY;
  if (2 * c > g) { sc[NT - 2][0] = NEG; sc[NT - 1][2] = NEG; }
  if (2 * c + 1 > g) { sc[NT - 2][1] = NEG; sc[NT - 1][3] = NEG; }
  sc[NT - 1][0] = sc[NT - 1][1] = NEG;
  uint32_t pp[NT][2]; float inv[2];
#pragma unroll
  for (int hh = 0; hh < 2; hh++) {
    float m = NEG, l = 0.f;
#pragma unroll
    for (int n = 0; n < NT; n++) m = fmaxf(m, fmaxf(sc[n][2 * hh], sc[n][2 * hh + 1]));
    m = fmaxf(m, __shfl_xor_sync(~0u, m, 1)); m = fmaxf(m, __shfl_xor_sync(~0u, m, 2));
#pragma unroll
    for (int n = 0; n < NT; n++) { const float x = ex2((sc[n][2 * hh] - m) * k2), y = ex2((sc[n][2 * hh + 1] - m) * k2); l += x + y; pp[n][hh] = pack2(x, y); }
    l += __shfl_xor_sync(~0u, l, 1); l += __shfl_xor_sync(~0u, l, 2);
    inv[hh] = rcp(l);
  }
#pragma unroll
  for (int u = 0; u < 3; u++) {
    float o[8][4] = {};
    const uint32_t* b = f[~u & 1];
#pragma unroll
    for (int n = 0; n < 8; n++) mma8(o[n], pp[0][0], pp[0][1], b[n]);
#pragma unroll
    for (int t = 0; t <= HALF; t++)
#pragma unroll
      for (int n = 0; n < 8; n++) mma16(o[n], pp[1 + 2 * t][0], pp[1 + 2 * t][1], pp[2 + 2 * t][0], pp[2 + 2 * t][1], b[8 + 16 * t + 2 * n], b[9 + 16 * t + 2 * n]);
    SCHED();
    if (u != 1) r.release(r.seq - 2 + u / 2);
    if (u == 0) { load_v(2); SCHED(); }
#pragma unroll
    for (int i = 0; i < 16; i++) q[16 * u + i] = pack2(o[i & 7][i >> 2 & 2] * inv[i >> 3], o[i & 7][(i >> 2 & 2) + 1] * inv[i >> 3]);
    if (now) {
#pragma unroll
      for (int i = 0; i < 4; i++) pend.store(4 * u + i);
    }
  }
}

template <int G>
__device__ __forceinline__ void ln_groups(Ring& ring, uint32_t scratch, bool input, int planes, int rg) {
  const int warp = threadIdx.x >> 5, lane = threadIdx.x & 31;
  const uint32_t id = (lane >> 3) == (lane & 3) ? ((lane & 4) ? 0x3f800000u : 0x00003f80u) : 0u;
  float v[G][5][4] = {};
#pragma unroll
  for (int r = 0; r < G; r++) {
    if (input) {
      const uint32_t a = ring.wait(2) + (lane >> 2) * 1280 + warp * 160 + (lane & 3) * 4;
#pragma unroll
      for (int i = 0; i < 5; i++) mma8(v[r][i], lds32(a + i * 32), lds32(a + i * 32 + 16), id);
      ring.release(ring.seq - 1);
    } else {
#pragma unroll 1
      for (int k = planes; k > 0; k -= 4) {
        const uint32_t a = ring.wait(min(k, 4) + 1) + (warp * 160 + lane) * 8;
        if (k == 1) {
#pragma unroll
          for (int i = 0; i < 5; i++) { const uint2 x = lds64(a + i * 256); mma8(v[r][i], x.x, x.y, id); }
        } else {
#pragma unroll
          for (int i = 0; i < 10; i++) {
            if (i == 5 && k < 4) break;
            const uint2 x = lds64(a + i / 5 * 20480 + i % 5 * 256), y = lds64(a + i / 5 * 20480 + 10240 + i % 5 * 256);
            mma16(v[r][i % 5], x.x, x.y, y.x, y.y, id, id);
          }
        }
        ring.release(ring.seq - 1);
      }
    }
  }
  uint2 xr[G][5];
  scratch += (lane >> 2) * 64;
#pragma unroll
  for (int r = 0; r < G; r++) {
    float m = 0.f, q = 0.f;
#pragma unroll
    for (int i = 0; i < 5; i++) {
      float* t = v[r][i];
      xr[r][i] = make_uint2(pack2(t[0], t[1]), pack2(t[2], t[3]));
      t[0] = bf_lo(xr[r][i].x); t[1] = bf_hi(xr[r][i].x); t[2] = bf_lo(xr[r][i].y); t[3] = bf_hi(xr[r][i].y);
      m += (t[0] + t[1]) + (t[2] + t[3]);
    }
    m += __shfl_xor_sync(~0u, m, 1); m += __shfl_xor_sync(~0u, m, 2);
    m *= 1.f / 80;
#pragma unroll
    for (int i = 0; i < 5; i++) { const float a = v[r][i][0] - m, b = v[r][i][1] - m, c = v[r][i][2] - m, d = v[r][i][3] - m; q += (a * a + b * b) + (c * c + d * d); }
    q += __shfl_xor_sync(~0u, q, 1); q += __shfl_xor_sync(~0u, q, 2);
    if ((lane & 3) == 0) sts64f(scratch + r * 512 + warp * 8, m, q);
  }
  bar_sync(1, 256);
#pragma unroll
  for (int r = 0; r < G; r++) {
    const float4 t = lds128f(scratch + r * 512 + (lane & 3) * 16);
    float mean = t.x + t.z;
    mean += __shfl_xor_sync(~0u, mean, 1); mean += __shfl_xor_sync(~0u, mean, 2);
    mean *= 0.125f;
    float var = (t.y + t.w) + 80.f * ((t.x - mean) * (t.x - mean) + (t.z - mean) * (t.z - mean));
    var += __shfl_xor_sync(~0u, var, 1); var += __shfl_xor_sync(~0u, var, 2);
    const float rs = rsqrtf(var * (1.f / DM) + 1e-5f);
#pragma unroll
    for (int i = 0; i < 20; i++) v[r][i >> 2][i & 3] = (v[r][i >> 2][i & 3] - mean) * rs;
  }
#pragma unroll
  for (int r = 0; r < G; r++) {
    uint32_t* xn = g_xn + (rg + r) * 2560 + warp * 320 + lane;
#pragma unroll
    for (int i = 0; i < 10; i++) xn[i * 32] = pack2(v[r][i >> 1][2 * (i & 1)], v[r][i >> 1][2 * (i & 1) + 1]);
#pragma unroll
    for (int i = 0; i < 5; i++) g_x[(rg + r) * 1280 + warp * 160 + i * 32 + lane] = xr[r][i];
  }
}

template <int NU>
__device__ __forceinline__ void store_partial(const float* d, int b, int split, int unit) {
  uint2* dst = g_part + (((b * 16 + split) * 16 + (threadIdx.x >> 5) * 2) * 40 + unit) * 32 + (threadIdx.x & 31);
#pragma unroll
  for (int u = 0; u < NU; u++) {
    dst[u * 32] = make_uint2(pack2(d[8 * u], d[8 * u + 1]), pack2(d[8 * u + 4], d[8 * u + 5]));
    dst[(40 + u) * 32] = make_uint2(pack2(d[8 * u + 2], d[8 * u + 3]), pack2(d[8 * u + 6], d[8 * u + 7]));
  }
}

template <int NH>
__device__ __forceinline__ void store_bqkv(const float* d, int b, int idx) {
  const int lane = threadIdx.x & 31, c = lane & 3, row = b * 128 + (threadIdx.x >> 5) * 16 + (lane >> 2), h0 = idx * NH;
  const float sc = h0 < 32 ? 0.22360679775f * 1.44269504089f : 1.f;
  const bool lo = c < 2;
  uint32_t* da = g_bqkv + (h0 * 256 + (row >> 3)) * 96 + lane;
  uint32_t* db = da + 256 * 96 + (lo ? 2 : -2);
#pragma unroll
  for (int r = 0; r < 2; r++) {
    const uint32_t pad = !(c & 1) && (h0 >= 64 || (h0 >= 32 && (row & 1) && poly_group((row >> 3) + r))) ? 0x00003f80u : 0u;
#pragma unroll
    for (int q = 0; q < NH / 2; q++) {
      uint32_t w[5];
#pragma unroll
      for (int i = 0; i < 5; i++) w[i] = pack2(d[20 * q + 4 * i + 2 * r] * sc, d[20 * q + 4 * i + 2 * r + 1] * sc);
      const int o = q * 2 * 256 * 96 + r * 96;
      da[o] = w[0]; da[o + 32] = w[1]; da[o + 64] = lo ? w[2] : pad;
      db[o] = lo ? w[3] : w[2]; db[o + 32] = lo ? w[4] : w[3]; db[o + 64] = lo ? pad : w[4];
    }
  }
}

template <bool WEIGHTS>
__device__ __forceinline__ void work_loader(const WorkParams& p, const uint32_t sb) {
  const uint32_t bars = sb + WK_BAR, bIF = bars + 128, bIE = bars + 160, bGo = bars + 256, slots = bars + 272;
  uint32_t* const sync = p.sync;
  int pos = 0, seq = 0, tail = 0, used = 0, normed = 0;
  uint32_t lens = 0, bar;
  const bool one = elect();
  auto alloc = [&](int len, uint32_t bytes) {
    const int skip = pos + len > WK_SLOTS ? WK_SLOTS - pos : 0, sh = 4 * (seq & 7);
    used += len + skip;
    while (used > WK_SLOTS || seq - tail >= 8) {
      mbar_wait_uniform(bars + 64 + 8 * (tail & 7), (tail >> 3) & 1);
      used -= (lens >> 4 * (tail & 7)) & 15;
      tail++;
    }
    lens = (lens & ~(15u << sh)) | (len + skip) << sh;
    bar = bars + 2 * sh;
    if (one) mbar_expect(bar, bytes);
    pos = (pos + len > WK_SLOTS ? 0 : pos) + len;
    seq++;
    return sb + (pos - len) * 8192;
  };
  for (int n = 0;; n++) {
    mbar_wait_uniform(bIF + 8 * (n & 3), (n >> 2) & 1);
    const int code = __shfl_sync(~0u, (int)lds32(slots + 4 * (n & 3)), 0);
    if (code < 0) break;
    const int type = (code >> 16) & 15, b = (code >> 8) & 255, idx = code & 255;
    if (one) mbar_arrive(bIE + 8 * (n & 3));
    const bool qa = type == IT_ATT && b < p.qa_end, tokens = qa || type == IT_Q, ln = type == IT_FIN || type == IT_LN || type == IT_LN0;
    auto inputs = [&]() {
      if (WEIGHTS || type == IT_LN0) return;
      if (type == IT_OUT || (type == IT_BO && b >= 2)) { if (p.kind != WK_JOIN) pdl_wait(); }
      else if (type == IT_BO) wait_count_uniform(sync + SY_OB, 32);
      else if (type == IT_LN) wait_count_uniform(sync + SY_P + b * 4, 2);
      else wait_count_uniform(sync + b * 8 + 4 + type, item_need(type, b));
    };
    if (type == IT_ATT && !qa) {
      if (!WEIGHTS) wait_count_uniform(sync + SY_P + b * 4 + 3, 32);
      const uint32_t dst = alloc(6, WEIGHTS ? 0 : 49152);
      if (!WEIGHTS && one) (HINT & 1 ? bulk_load_last : bulk_load)(dst, g_q + (b * 32 + idx) * 3072, 49152, bar);
    } else if (!ln) {
      const int cols = item_cols(type, b), nb = (cols + 63) >> 6, nkb = type == IT_OP ? 96 / op_split(b) : 10;
      const int kb0 = type == IT_OP ? (idx >> op_tiles(b) / 2) * nkb : 0, col = (type == IT_OP ? idx & (op_tiles(b) - 1) : idx) * cols;
      if (WEIGHTS) {
        if (type == IT_OP) {
          for (int kb = kb0; kb < kb0 + nkb; kb++) {
            const uint32_t dst = alloc(2 + nb, nb * 8192) + 16384;
            {
#pragma unroll
              for (int i = 0; i < 5; i++)
                if (i < nb && one) asm volatile("cp.async.bulk.tensor.5d.shared::cluster.global.mbarrier::complete_tx::bytes [%0], [%1, {%3, %5, %5, %5, %4}], [%2];"
                             :: "r"(dst + i * 8192), "l"(&p.wo), "r"(bar), "r"(col + i * 64), "r"(kb * 2), "r"(0) : "memory");
            }
          }
        } else {
          const CUtensorMap* m = tokens ? &p.wq : type == IT_BQ ? &p.wb : &p.wc;
          for (int kb = 0; kb < 10; kb++) {
            const uint32_t dst = alloc(2 + nb, nb * 8192) + 16384;
#pragma unroll
            for (int i = 0; i < 5; i++) if (i < nb && one) tma_load(dst + i * 8192, m, col + i * 64, kb * 64, bar);
          }
        }
      } else if (tokens || type == IT_BQ) {
        if (!tokens) inputs();
        else if (!(normed >> b & 1)) { wait_count_uniform(sync + SY_P + b * 4 + 1, ln_items(sync != g_sync, b)); normed |= 1 << b; }
        const CUtensorMap* m = tokens ? &p.xp : &p.xn;
        for (int kb = 0; kb < 10; kb++) {
          const uint32_t dst = alloc(2 + nb, 16384);
          if (one)
            asm volatile("cp.async.bulk.tensor.4d.shared::cluster.global.mbarrier::complete_tx::bytes [%0], [%1, {%3, %6, %4, %5}], [%2];"
                         :: "r"(dst), "l"(m), "r"(bar), "r"(kb * 128), "r"(tokens ? b * 4 : 0), "r"(tokens ? 0 : b * 4), "r"(0) : "memory");
        }
      } else {
        inputs();
        const uint8_t* a = type == IT_OP ? reinterpret_cast<const uint8_t*>(g_o) + (b * 96 + kb0) * 16384 : reinterpret_cast<const uint8_t*>(g_of) + b * 163840;
        for (int kb = 0; kb < nkb; kb++) {
          const uint32_t dst = alloc(2 + nb, 16384);
          if (one) (HINT & 2 ? bulk_load_last : bulk_load)(dst, a + kb * 16384, 16384, bar);
        }
      }
    }
    if (type == IT_ATT || ln) {
      inputs();
      if (!WEIGHTS && (!qa || (code & C_EARLY)) && !(code & C_LATE) && one) mbar_arrive(bGo);
    }
    if (type == IT_ATT) {
#pragma unroll
      for (int i = 0; i < 6; i += 2) {
        const uint32_t dst = alloc(5, WEIGHTS ? 0 : KV_BYTES);
        if (!WEIGHTS && one) {
#pragma unroll
          for (int u = i; u < i + 2; u++) (HINT & 1 ? bulk_load_last : bulk_load)(dst + (u - i) * 20480, g_kv + (b * 96 + idx * 3 + u % 3) * KV_BYTES + u / 3 * KV_V, 20480, bar);
        }
      }
    } else if (ln) {
      const int ng = item_groups(type, b), planes = type == IT_FIN ? op_split(b) + 1 : type == IT_LN ? 2 : 1;
      for (int rg = idx * ng; rg < (idx + 1) * ng; rg++) {
        const void* res = type == IT_LN0 ? static_cast<const void*>(p.x + (b * 16 + rg) * 8 * DM) : g_x + (b * 16 + rg) * 1280;
        for (int k = 0; k < planes; k += 4) {
          const int cnt = min(4, planes - k);
          const uint32_t dst = alloc(cnt + 1, WEIGHTS ? 0 : cnt * 10240);
          if (!WEIGHTS && one) {
#pragma unroll
            for (int i = 0; i < 4; i++)
              if (i < cnt) (HINT & 4 ? bulk_load_last : bulk_load)(dst + i * 10240, k + i + 1 < planes ? g_part + ((b * 16 + k + i) * 16 + rg) * 1280 : res, 10240, bar);
          }
        }
      }
    }
  }
}

__global__ void __launch_bounds__(384, 1) work_kernel(const __grid_constant__ WorkParams p) {
  extern __shared__ __align__(1024) uint8_t smem_raw[];
  const uint32_t sb = s2u(smem_raw), bars = sb + WK_BAR;
  const uint32_t bIF = bars + 128, bIE = bars + 160, done = bars + 192, bGo = bars + 256, slots = bars + 272, scratch = bars + 384;
  const int warp = __shfl_sync(~0u, threadIdx.x >> 5, 0), lane = threadIdx.x & 31;
  uint32_t* const sync = p.sync;
  XT(0);
  TRACE(0);
  pdl_launch();
  const bool keep = p.kind > WK_LEAD || helper_sm();
  if (!keep) {
    if (p.kind == WK_FIRST) { if (!(warp & 13)) probe_slots(bars + 320); TRACE(1); return; }
    if (__syncthreads_or(threadIdx.x == 0 && ldg_strong32(sync + SY_PRE + 1) >= LEAD1)) { pdl_wait(); return; }
  }
  const uint2 taken = p.kind == WK_JOIN && warp == 9 ? ldg_strong64(sync + SY_PRE) : make_uint2(0, 0);
  const uint32_t ending = p.kind == WK_JOIN && warp == 9 ? ldg_strong32(sync + 15 * 8 + 4) : 0;
  if (threadIdx.x < 33) {
    const int i = threadIdx.x;
    mbar_init(bars + 8 * i, i < 8 ? 2 : i < 16 ? 8 : i < 20 ? 1 : i < 24 ? 3 : i < 32 ? 8 : 1);
    asm volatile("fence.mbarrier_init.release.cluster;" ::: "memory");
  }
  __syncthreads();
  if (warp >= 8) {
    asm volatile("setmaxnreg.dec.sync.aligned.u32 56;");
    if (warp == 9) {
      XT(1);
      int own = p.kind == WK_JOIN ? reserved_item(blockIdx.x) : -1, n = 0;
      if (own >= 0 && ending) {
        if (lane == 0) { sts32(slots, own); mbar_arrive(bIF); }
        own = -1; n = 1;
      }
      XT(5);
      const int b = lane & 15, layer = p.kind == WK_LAST ? 2 : sync != g_sync;
      bool first = layer == 1 && taken.y < LEAD1, lead = first || p.kind != WK_JOIN || lead_item(layer, p.qa_end, taken.x + layer * LEAD1) >= 0;
      for (;; n++) {
        if (n > 0) mbar_wait_uniform(bGo, (n - 1) & 1);
        mbar_wait_uniform(bIE + 8 * (n & 3), ((n >> 2) & 1) ^ 1);
        int code = -1;
        if (lead) {
          int i = blockIdx.x + n * 256;
          if (first) { if (lane == 0) i = atomicAdd(sync + SY_PRE + 1, 1); i = __shfl_sync(~0u, i, 0); first = i < LEAD1; }
          if (layer < 2 && !first) {
            if (lane == 0) i = keep ? atomicAdd(sync + SY_PRE, 1) + layer * LEAD1 : 1 << 20;
            i = __shfl_sync(~0u, i, 0);
            if (!keep) pdl_wait();
          }
          code = lead_item(layer, p.qa_end, i);
          lead = code >= 0 || layer == 2 || !keep;
          if (!lead && p.kind <= WK_LEAD) {
            const uint32_t t0 = gtime();
            while (!lead && ldg_strong32(sync + SY_UP) < 96) lead = gtime() - t0 > 20000;
          }
        }
        if (!lead) {
          int spin = 0, ticket = 0;
          if (n == 0) XT(2);
          if (lane == 0) ticket = atomicAdd(sync + SY_T, 1);
          for (;;) {
            const uint4 hd = ldg_strong128(sync + b * 8), pr = ldg_strong128(sync + b * 8 + 4);
            const uint32_t hv[4] = {hd.x, hd.y, hd.z, hd.w}, pv[4] = {pr.x, pr.y, pr.z, pr.w};
            if (n == 0 && spin == 0 && hd.x + pr.x != 77777) XT(3);
            const uint32_t chain_done = __ballot_sync(~0u, (pr.x & 0xffff) >= 96);
            int left[4], avail[4], rdy = 0, claimed = 0, upstream = 0;
#pragma unroll
            for (int t = 0; t < 4; t++) {
              const int cnt = lane < 16 && !reserved(t, b) ? item_count(t, b) : 0;
              left[t] = max(cnt - (int)hv[t], 0);
              claimed += cnt - left[t];
              const bool ready = (pv[t] & 0xffff) >= item_need(t, b);
              rdy |= ready << t;
              bool ok = ready || (t == IT_ATT ? pr.x >= 0x10000 : !upstream || ((chain_done >> 15 & 1) && !left[t - 1] && (t < 2 || !left[t - 2])));
              if (t == IT_BQ && (chain_done >> 12 & 9) == 1) ok = false;
              avail[t] = ok ? left[t] : 0;
              upstream |= __any_sync(~0u, left[t] > 0);
            }
            if (own >= 0 && ((chain_done >> 15 & 1) || !upstream)) { code = own; own = -1; if (lane == 0) atomicSub(sync + SY_T, 1); break; }
            if (!upstream) { code = -1; break; }
            int rank = max(__shfl_sync(~0u, ticket, 0) - __reduce_add_sync(~0u, claimed), 0), type = -1, mine = 0;
#pragma unroll
            for (int c = 0; c < 7; c++) {
              const int t = c == 0 || c == 4 ? IT_FIN : c == 1 || c == 6 ? IT_ATT : c == 2 ? IT_OP : IT_BQ;
              int a = c == 1 || c == 2 || ((rdy >> t & 1) == (c < 4)) ? avail[t] : 0;
              if (c == 6) a = b < p.qa_end && !(rdy & 1) && ((chain_done << 1 | 1) >> b & 1) ? left[t] : 0;
              const int tot = __reduce_add_sync(~0u, a);
              if (type < 0) { if (rank < tot) { type = t; mine = a; } else rank -= tot; }
            }
            if (n == 0 && spin == 0) XT(4);
            if (type >= 0) {
#pragma unroll
              for (int o = 1; o < 16; o <<= 1) { const int y = __shfl_up_sync(~0u, mine, o); if (lane >= o) mine += y; }
              const int blk = __ffs(__ballot_sync(~0u, mine > rank)) - 1;
              const int early = !(__shfl_sync(~0u, rdy, blk) >> type & 1);
              uint32_t idx = 0;
              if (lane == 0) idx = atomicAdd(sync + blk * 8 + type, 1);
              idx = __shfl_sync(~0u, idx, 0);
              if (idx < item_count(type, blk)) { code = (chain_done >> 15 & 1) << 22 | early << 20 | type << 16 | blk << 8 | idx; break; }
            } else {
              __nanosleep(50);
            }
            spin_guard(spin);
          }
        }
        if (lane == 0) {
          sts32(slots + 4 * (n & 3), code);
          mbar_arrive(bIF + 8 * (n & 3));
        }
        __syncwarp();
        if (code < 0) break;
      }
    } else if (warp == 8) {
      if (p.kind == WK_FIRST) probe_slots(bars + 320);
      work_loader<true>(p, sb);
    } else if (warp == 11) {
      work_loader<false>(p, sb);
    } else {
      if (p.kind == WK_FIRST) probe_slots(bars + 320);
      for (int n = 0;; n++) {
        mbar_wait_uniform(bIF + 8 * (n & 3), (n >> 2) & 1);
        const int code = __shfl_sync(~0u, (int)lds32(slots + 4 * (n & 3)), 0);
        if (code < 0) break;
        const int type = (code >> 16) & 15, b = (code >> 8) & 255;
        mbar_wait_uniform(done + 8 * (n & 3), (n >> 2) & 1);
        if (elect()) {
          if (type != IT_OUT) red_release(sync + (type < IT_BQ ? b * 8 + 5 + type : SY_P + b * 4 + ((0x13102 >> 4 * (type - IT_BQ)) & 3)), 1);
          mbar_arrive(bIE + 8 * (n & 3));
        }
        __syncwarp();
      }
    }
  } else {
    asm volatile("setmaxnreg.inc.sync.aligned.u32 224;");
    Ring r{sb, 0, 0};
    Pending pend;
    pend.done = 0;
    int nln = 0;
    auto projects = [&](int n) {
      uint32_t here;
      asm volatile("{.reg .pred p; mbarrier.test_wait.parity.shared::cta.b64 p, [%1], %2; vote.sync.all.pred p, p, 0xffffffff; selp.u32 %0, 1, 0, p;}" : "=r"(here) : "r"(bIF + 8 * (n & 3)), "r"((n >> 2) & 1) : "memory");
      if (!here) return false;
      const int code = __shfl_sync(~0u, (int)lds32(slots + 4 * (n & 3)), 0);
      return code >= 0 && (((code >> 16) & 15) == IT_Q || (((code >> 16) & 15) == IT_ATT && ((code >> 8) & 255) < p.qa_end));
    };
#pragma unroll 1
    for (int n = 0;; n++) {
      if (pend.done && !projects(n)) pend.flush();
      mbar_wait_uniform(bIF + 8 * (n & 3), (n >> 2) & 1);
      const int code = __shfl_sync(~0u, (int)lds32(slots + 4 * (n & 3)), 0);
      if (code < 0) { TRACE(2); break; }
      const int type = (code >> 16) & 15, b = (code >> 8) & 255, idx = code & 255;
      const uint32_t go = (code & C_LATE) || (type == IT_ATT && (code & C_EARLY)) ? 0 : bGo;
      ITEM(code & 0xfffff, 0);
      if (type == IT_ATT || type == IT_Q) {
        if (type == IT_Q || b < p.qa_end) {
          float d[96] = {};
          reg_fence<96>(d);
          ITEM(9 << 16 | (code & 0xffff), 0);
          gemm_item<192>(d, r, 10, go, pend);
          ITEM(9 << 16 | (code & 0xffff), 1);
#pragma unroll
          for (int i = 0; i < 48; i++) pend.w[i] = pack2(d[2 * i], d[2 * i + 1]);
        } else {
          const uint32_t base = r.wait(6) + warp * 2048 + lane * 16;
#pragma unroll
          for (int i = 0; i < 12; i++) {
            const uint4 t = lds128(base + (i >> 2) * 16384 + (i & 3) * 512);
            pend.w[4 * i] = t.x; pend.w[4 * i + 1] = t.y; pend.w[4 * i + 2] = t.z; pend.w[4 * i + 3] = t.w;
          }
          __syncwarp();
          r.release(r.seq - 1);
        }
        const bool now = type == IT_ATT && !projects(n + 1);
        if (type == IT_Q) {
          pend.dst = g_q + (b * 32 + idx) * 3072 + warp * 128 + lane;
        } else {
          pend.dst = g_o + (b * 32 + idx) * 3072 + (warp & 3) * 256 + (warp >> 2) * 128 + (lane & 3) * 8 + (lane >> 2);
          if (warp < 4) attn_a_warp<0>(r, pend, now); else attn_a_warp<1>(r, pend, now);
        }
        pend.done = done + 8 * (n & 3);
        if (now) pend.finish();
      } else {
        if (type == IT_FIN || type == IT_LN || type == IT_LN0) {
          const int ng = item_groups(type, b);
          const int planes = type == IT_FIN ? op_split(b) + 1 : 2;
          if (ng == 1) {
            ln_groups<1>(r, scratch + (nln++ & 1) * 1024, type == IT_LN0, planes, b * 16 + idx);
          } else {
#pragma unroll 1
            for (int i = 0; i < ng; i += 2) ln_groups<2>(r, scratch + (nln++ & 1) * 1024, type == IT_LN0, planes, b * 16 + idx * ng + i);
          }
        } else if (item_cols(type, b) == 80) {
          float d[40] = {};
          uint2 y[10];
          if (type == IT_OUT) {
            const uint2* x = g_x + ((b * 16 + warp * 2) * 40 + idx * 5) * 32 + lane;
#pragma unroll
            for (int i = 0; i < 10; i++) y[i] = __ldcg(x + (i / 5 * 40 + i % 5) * 32);
          }
          reg_fence<40>(d);
          gemm_item<80>(d, r, 10, go, pend);
          if (type == IT_BQ) store_bqkv<4>(d, b, idx); else {
          bar_sync(1, 256);
          const uint32_t dst = sb + (warp * 16 + (lane & 15)) * 160 + (lane >> 4) * 16;
#pragma unroll
          for (int u = 0; u < 5; u++)
            stsm4(dst + u * 32, pack2(bf_lo(y[u].x) + d[8 * u], bf_hi(y[u].x) + d[8 * u + 1]), pack2(bf_lo(y[5 + u].x) + d[8 * u + 2], bf_hi(y[5 + u].x) + d[8 * u + 3]),
                  pack2(bf_lo(y[u].y) + d[8 * u + 4], bf_hi(y[u].y) + d[8 * u + 5]), pack2(bf_lo(y[5 + u].y) + d[8 * u + 6], bf_hi(y[5 + u].y) + d[8 * u + 7]));
          fence_async();
          __syncwarp();
          if (elect()) { tma_store(&p.out, sb + warp * 2560, idx * 80, b * 128 + warp * 16); bulk_commit(); bulk_wait<0>(); }
          }
        } else {
          if (item_cols(type, b) == 320) {
            float d[160] = {};
            reg_fence<160>(d);
            ITEM((type == IT_BQ ? 10 : 11) << 16 | (code & 0xffff), 0);
            gemm_item<320>(d, r, type == IT_OP ? 96 / op_split(b) : 10, go, pend);
            ITEM((type == IT_BQ ? 10 : 11) << 16 | (code & 0xffff), 1);
            if (warp >= 4) bar_sync(7, 256);
            if (type == IT_BQ) store_bqkv<16>(d, b, idx); else store_partial<20>(d, b, idx >> 1, (idx & 1) * 20);
          } else {
            float d[80] = {};
            reg_fence<80>(d);
            gemm_item<160>(d, r, type == IT_OP ? 96 / op_split(b) : 10, go, pend);
            if (warp >= 4) bar_sync(7, 256);
            if (type == IT_BQ) store_bqkv<8>(d, b, idx); else store_partial<10>(d, b, idx >> 2, (idx & 3) * 10);
          }
          if (warp < 4) bar_arrive(7, 256);
        }
        __syncwarp();
        if (elect()) mbar_arrive(done + 8 * (n & 3));
#pragma unroll
        for (int i = 0; i < 48; i++) pend.w[i] = 0;
      }
      if ((code & C_LATE) && warp == 4 && elect()) mbar_arrive(bGo);
      ITEM(code & 0xfffff, 1);
    }
  }
}

constexpr int AB_SMEM = 1024 + 2 * 98304 + 256;
#define AB_N 32
#define AB_WG 4
constexpr int AB_T = AB_WG * 128, AB_PASS = 8 / AB_WG;
__device__ __forceinline__ float ex2_poly(float t) {
  const uint32_t r = __float_as_uint(t) & 0xffff8000u;
  const float f = t - __uint_as_float(r);
  const float p = fmaf(fmaf(fmaf(-5.869912678e-38f, f, -1.700740250e-37f), f, -5.234869734e-37f), f, -7.522601252e-37f);
  uint32_t y;
  asm("mad.lo.u32 %0, %1, 256, %2;" : "=r"(y) : "r"(r), "r"(__float_as_uint(p)));
  return __uint_as_float(y);
}
__device__ __forceinline__ float sq2(uint32_t w) { const float a = bf_lo(w), b = bf_hi(w); return fmaf(a, a, b * b); }

__device__ __forceinline__ void attn_b_store(const float* o, int h, int row0, int lane) {
  const int g = lane >> 2, c = lane & 3;
  const float i0 = 1.f / __shfl_sync(~0u, o[8], (lane & ~3) | 2), i1 = 1.f / __shfl_sync(~0u, o[10], (lane & ~3) | 2);
#pragma unroll
  for (int jj = 0; jj < 3; jj++) {
    if (jj < 2 || c < 2) {
      const int col = h * 20 + 8 * jj + 2 * c;
      g_of[core_word(row0 + g, col)] = pack2(o[4 * jj] * i0, o[4 * jj + 1] * i0);
      g_of[core_word(row0 + g + 8, col)] = pack2(o[4 * jj + 2] * i1, o[4 * jj + 3] * i1);
    }
  }
}

__device__ __forceinline__ void attn_b_qk(float* s, uint32_t q0, uint32_t q1, uint32_t q2, uint32_t q3, uint32_t q4, uint32_t q5, uint32_t z0, uint32_t z1,
                                          uint64_t dk, uint64_t dk2) {
  wg_rs32_00(s, q0, q1, q2, q3, dk, 0);
  wg_rs32_00(s, q4, q5, z0, z1, dk2, 1);
}

struct AttnParams { const uint8_t* pf[4]; uint32_t *sync, *next; };
__global__ void __launch_bounds__(AB_T + 32, 1) attn_b_kernel(const __grid_constant__ AttnParams p) {
  extern __shared__ uint8_t smem_raw[];
  const uint32_t sb = (s2u(smem_raw) + 1023) & ~1023u, sK = sb, sV = sb + 98304, bars = sb + 2 * 98304;
  const int warp = __shfl_sync(~0u, threadIdx.x >> 5, 0), lane = threadIdx.x & 31;
  const int h = blockIdx.x >> 2, quarter = blockIdx.x & 3;
  TRACE(0);
  if (threadIdx.x == 0) {
    for (int i = 0; i < 8; i++) mbar_init(bars + 8 * i, 1);
    mbar_init(bars + 128, AB_T / 32);
    fence_async();
  }
  __syncthreads();
  if (warp == AB_T / 32) {
    const uint8_t* gk = reinterpret_cast<const uint8_t*>(g_bqkv + (32 + h) * 256 * 96);
    const uint8_t* gv = reinterpret_cast<const uint8_t*>(g_bqkv + (64 + h) * 256 * 96);
    uint32_t todo = 255;
    for (int spin = 0; todo;) {
      const uint32_t up = __ballot_sync(~0u, ld_acquire(p.sync + SY_P + (lane & 15) * 4 + 2) >= bq_items(lane & 15));
      fence_async_global();
      for (int i = 0; i < 8; i++) {
        if (!(todo >> i & 1) || (up >> 2 * i & 3) != 3) continue;
        todo &= ~(1u << i);
        if (elect()) {
          mbar_expect(bars + 8 * i, 24576);
          bulk_load(sK + i * 12288, gk + i * 12288, 12288, bars + 8 * i);
          bulk_load(sV + i * 12288, gv + i * 12288, 12288, bars + 8 * i);
        }
      }
      spin_guard(spin);
    }
    pdl_launch();
    TRACE(1);
    if (blockIdx.x < NSLOT) for (int i = lane; i < 512; i += 32) reinterpret_cast<uint4*>(pool_at(blockIdx.x * 8192))[i] = make_uint4(0, 0, 0, 0);
    if (!p.next && blockIdx.x == 127) for (int i = lane; i < 256; i += 32) { g_smpart[i] = 0; if (i < NSLOT) g_orient[i] = 0; }
    if (p.next) {
      mbar_wait_slow(bars + 128, 0);
      if (quarter == 0 && lane == 0) red_release(p.next + SY_OB, 1);
      for (int i = 0; i < 32; i++) {
        if (elect()) prefetch_l2(p.pf[i >> 3] + blockIdx.x * 61440 + (i & 7) * 7680, 7680);
        __nanosleep(300);
      }
    }
    return;
  }
  constexpr int NT = SEQ / AB_N, PER = 256 / AB_N;
#pragma unroll 1
  for (int pass = 0; pass < AB_PASS; pass++) {
    const int row0 = pass * 1024 + quarter * 256 + warp * 16;
    const uint32_t* gq = g_bqkv + (h * 256 + (row0 >> 3)) * 96 + lane;
    if (pass == 0) mbar_wait(bars + 8 * quarter, 0);
    const uint32_t q0 = __ldcg(gq), q1 = __ldcg(gq + 96), q2 = __ldcg(gq + 32), q3 = __ldcg(gq + 128);
    uint32_t q4 = __ldcg(gq + 64), q5 = __ldcg(gq + 160);
    const uint32_t z0 = __ldcg(gq + 64 + 3 - (lane & 3)), z1 = __ldcg(gq + 160 + 3 - (lane & 3));
    if ((lane & 3) == 2) { q4 = 0x43BCu; q5 = 0x43BCu; }
    float o[12];
    uint64_t dk = mkdesc(sK, 128, 384, 0), dk2 = mkdesc(sK + 256, 0, 384, 0), dv = mkdesc(sV, 384, 128, 0);
    float sa[AB_N / 2], sb2[AB_N / 2];
    uint32_t pa[AB_N / 4], pb[AB_N / 4];
    if (pass == 0) mbar_wait(bars, 0);
    wg_fence();
    attn_b_qk(sa, q0, q1, q2, q3, q4, q5, z0, z1, dk, dk2);
    wg_commit();
    attn_b_qk(sb2, q0, q1, q2, q3, q4, q5, z0, z1, dk + AB_N * 3, dk2 + AB_N * 3);
    wg_commit();
#pragma unroll 1
    for (int kt = 0; kt < NT; kt += 2) {
      const int nx = kt + 2 < NT ? kt + 2 : 0;
      if (pass == 0 && (nx & (PER - 1)) == 0) mbar_wait(bars + 8 * (nx / PER), 0);
      const uint64_t nk = dk + nx * (AB_N * 3), nk2 = dk2 + nx * (AB_N * 3);
      wg_wait<1>();
      reg_fence<AB_N / 2>(sa);
#pragma unroll
      for (int i = 0; i < AB_N / 4; i++) pa[i] = pack2(ex2(sa[2 * i]), poly_group(i >> 1) ? ex2_poly(sa[2 * i + 1]) : ex2(sa[2 * i + 1]));
      wg_fence();
#pragma unroll
      for (int kk = 0; kk < AB_N / 16; kk++) wg_rs24_01(o, pa[4 * kk], pa[4 * kk + 1], pa[4 * kk + 2], pa[4 * kk + 3], dv + kk * 48, kk | kt);
      attn_b_qk(sa, q0, q1, q2, q3, q4, q5, z0, z1, nk, nk2);
      wg_commit();
      wg_wait<1>();
      reg_fence<AB_N / 2>(sb2);
#pragma unroll
      for (int i = 0; i < AB_N / 4; i++) pb[i] = pack2(ex2(sb2[2 * i]), poly_group((i >> 1) + AB_N / 8) ? ex2_poly(sb2[2 * i + 1]) : ex2(sb2[2 * i + 1]));
      wg_fence();
#pragma unroll
      for (int kk = 0; kk < AB_N / 16; kk++) wg_rs24_01(o, pb[4 * kk], pb[4 * kk + 1], pb[4 * kk + 2], pb[4 * kk + 3], dv + AB_N * 3 + kk * 48, 1);
      attn_b_qk(sb2, q0, q1, q2, q3, q4, q5, z0, z1, nk + AB_N * 3, nk2 + AB_N * 3);
      wg_commit();
      dv += AB_N * 6;
    }
    wg_wait<0>();
    reg_fence<12>(o); reg_fence<AB_N / 2>(sa); reg_fence<AB_N / 2>(sb2);
    if (pass == 0) {
      float kmax = 0.f;
#pragma unroll
      for (int i = 0; i < SEQ / AB_T; i++) {
        const int key = threadIdx.x + AB_T * i;
        const uint32_t a = sK + (key >> 3) * 384 + (key & 7) * 16;
        const uint4 x = lds128(a), y = lds128(a + 128);
        const uint2 z = lds64(a + 256);
        const float n = ((sq2(x.x) + sq2(x.y)) + (sq2(x.z) + sq2(x.w))) + ((sq2(y.x) + sq2(y.y)) + (sq2(y.z) + sq2(y.w))) + (sq2(z.x) + sq2(z.y));
        kmax = (n > kmax || n != n) ? n : kmax;
      }
      const uint32_t kbits = __reduce_max_sync(~0u, __float_as_uint(kmax) & 0x7fffffffu);
      if (lane == 0) sts32(bars + 64 + warp * 4, kbits);
      bar_sync(1, AB_T);
    }
    const float kmax = __uint_as_float(__reduce_max_sync(~0u, lds32(bars + 64 + (lane & (AB_T / 32 - 1)) * 4)));
    if ((lane & 3) == 2) q4 = q5 = 0;
    float n0 = sq2(q0) + sq2(q2) + sq2(q4), n1 = sq2(q1) + sq2(q3) + sq2(q5);
    n0 += __shfl_xor_sync(~0u, n0, 1); n1 += __shfl_xor_sync(~0u, n1, 1);
    n0 += __shfl_xor_sync(~0u, n0, 2); n1 += __shfl_xor_sync(~0u, n1, 2);
    uint32_t redo;
    asm volatile("{.reg .pred p, q; setp.ne.u32 p, %1, 0; bar.red.or.pred q, %2, 128, p; selp.u32 %0, 1, 0, q;}"
                 : "=r"(redo) : "r"((uint32_t)!(n0 * kmax <= 10000.f && n1 * kmax <= 10000.f)), "r"(2 + (warp >> 2)) : "memory");
    if (redo) {
#pragma unroll
    for (int i = 0; i < 12; i++) o[i] = 0.f;
    float m0 = -INFINITY, m1 = -INFINITY;
#pragma unroll 1
    for (int kt = 0; kt < 32; kt++) {
      float s[32];
      const uint64_t dk = mkdesc(sK + kt * 3072, 128, 384, 0), dk2 = mkdesc(sK + kt * 3072 + 256, 0, 384, 0);
      wg_fence();
      wg_rs64_00(s, q0, q1, q2, q3, dk, 0);
      wg_rs64_00(s, q4, q5, z0, z1, dk2, 1);
      wg_commit();
      wg_wait<0>();
      reg_fence<32>(s); reg_fence<12>(o);
      float n0 = m0, n1 = m1;
#pragma unroll
      for (int jj = 0; jj < 8; jj++) { n0 = fmaxf(n0, fmaxf(s[4 * jj], s[4 * jj + 1])); n1 = fmaxf(n1, fmaxf(s[4 * jj + 2], s[4 * jj + 3])); }
      n0 = fmaxf(n0, __shfl_xor_sync(~0u, n0, 1)); n0 = fmaxf(n0, __shfl_xor_sync(~0u, n0, 2));
      n1 = fmaxf(n1, __shfl_xor_sync(~0u, n1, 1)); n1 = fmaxf(n1, __shfl_xor_sync(~0u, n1, 2));
      const float r0 = ex2(m0 - n0), r1 = ex2(m1 - n1);
      m0 = n0; m1 = n1;
#pragma unroll
      for (int jj = 0; jj < 3; jj++) { o[4 * jj] *= r0; o[4 * jj + 1] *= r0; o[4 * jj + 2] *= r1; o[4 * jj + 3] *= r1; }
      uint32_t pp[16];
#pragma unroll
      for (int jj = 0; jj < 8; jj++) {
        pp[2 * jj] = pack2(ex2(s[4 * jj] - m0), ex2(s[4 * jj + 1] - m0));
        pp[2 * jj + 1] = pack2(ex2(s[4 * jj + 2] - m1), ex2(s[4 * jj + 3] - m1));
      }
      const uint64_t dv = mkdesc(sV + kt * 3072, 384, 128, 0);
      wg_fence();
#pragma unroll
      for (int kk = 0; kk < 4; kk++) wg_rs24_01(o, pp[4 * kk], pp[4 * kk + 1], pp[4 * kk + 2], pp[4 * kk + 3], dv + kk * 48, 1);
      wg_commit();
    }
    wg_wait<0>();
    reg_fence<12>(o);
    }
    attn_b_store(o, h, row0, lane);
    __syncwarp();
    if (pass == 0 && lane == 0) mbar_arrive(bars + 128);
  }
  TRACE(2);
}

typedef CUresult (*EncodeFn)(CUtensorMap*, CUtensorMapDataType, cuuint32_t, void*, const cuuint64_t*, const cuuint64_t*,
                             const cuuint32_t*, const cuuint32_t*, CUtensorMapInterleave, CUtensorMapSwizzle,
                             CUtensorMapL2promotion, CUtensorMapFloatOOBfill);

void make_map(EncodeFn enc, CUtensorMap* m, const void* ptr, int cols, int rows, int box_rows, int box_cols = 64) {
  const cuuint64_t dims[2] = {(cuuint64_t)cols, (cuuint64_t)rows};
  const cuuint64_t strides[1] = {(cuuint64_t)cols * 2};
  const cuuint32_t box[2] = {(cuuint32_t)box_cols, (cuuint32_t)box_rows}, es[2] = {1, 1};
  enc(m, CU_TENSOR_MAP_DATA_TYPE_BFLOAT16, 2, const_cast<void*>(ptr), dims, strides, box, es, CU_TENSOR_MAP_INTERLEAVE_NONE,
      box_cols == 64 ? CU_TENSOR_MAP_SWIZZLE_128B : box_cols == 32 ? CU_TENSOR_MAP_SWIZZLE_64B : CU_TENSOR_MAP_SWIZZLE_NONE, CU_TENSOR_MAP_L2_PROMOTION_L2_256B, CU_TENSOR_MAP_FLOAT_OOB_FILL_NONE);
}
template <class... KA, class... A>
void launch(void (*kern)(KA...), int grid, int block, int smem, int cluster, bool pdl, A... args) {
  cudaFuncSetAttribute(kern, cudaFuncAttributeMaxDynamicSharedMemorySize, smem);
  cudaLaunchConfig_t cfg = {};
  cfg.gridDim = dim3(grid); cfg.blockDim = dim3(block); cfg.dynamicSmemBytes = smem; cfg.stream = cudaStreamPerThread;
  cudaLaunchAttribute at[2];
  int n = 0;
  if (cluster > 1) { at[n].id = cudaLaunchAttributeClusterDimension; at[n].val.clusterDim.x = cluster; at[n].val.clusterDim.y = 1; at[n].val.clusterDim.z = 1; n++; }
  if (pdl) { at[n].id = cudaLaunchAttributeProgrammaticStreamSerialization; at[n].val.programmaticStreamSerializationAllowed = 1; n++; }
  cfg.attrs = at; cfg.numAttrs = n;
  cudaLaunchKernelEx(&cfg, kern, args...);
}
template <class T> void* sym(T& s) { void* p = nullptr; cudaGetSymbolAddress(&p, s); return p; }

}

#define MODE(b) 0
extern "C" void kernel_launch(void* const* d_in, const int* in_sizes, int n_in, void* d_out, int out_size) {
  const __nv_bfloat16* x = (const __nv_bfloat16*)d_in[0];
  void* fn = nullptr; cudaDriverEntryPointQueryResult qr;
  cudaGetDriverEntryPoint("cuTensorMapEncodeTiled", &fn, cudaEnableDefault, &qr);
  EncodeFn enc = (EncodeFn)fn;

  ChainParams ch = {};
  WorkParams wk = {};
  AttnParams at = {};
  make_map(enc, &ch.wq, d_in[2], HD, DM, 128); make_map(enc, &ch.wk, d_in[3], HD, DM, 128); make_map(enc, &ch.wv, d_in[4], HD, DM, 128);
  make_map(enc, &ch.wo, d_in[5], DM, HD, 192, 32);
  ch.mem0 = (const __nv_bfloat16*)d_in[1];
  ch.d1 = 400; ch.d2 = 300; ch.dn = 0; ch.dx = 500;
  make_map(enc, &wk.wq, d_in[2], HD, DM, 64);
  make_map(enc, &wk.wb, d_in[8], 1920, DM, 64);
  make_map(enc, &wk.wc, d_in[9], DM, DM, 64);
  make_map(enc, &wk.out, d_out, DM, SEQ, 16, 80);
  {
    const cuuint64_t dims[5] = {DM, 2, 4, 4, HD / 32}, strides[4] = {DM * 2, DM * 16, DM * 4, DM * 64};
    const cuuint32_t box[5] = {64, 2, 4, 4, 2}, es[5] = {1, 1, 1, 1, 1};
    enc(&wk.wo, CU_TENSOR_MAP_DATA_TYPE_BFLOAT16, 5, d_in[5], dims, strides, box, es, CU_TENSOR_MAP_INTERLEAVE_NONE, CU_TENSOR_MAP_SWIZZLE_128B,
        CU_TENSOR_MAP_L2_PROMOTION_L2_256B, CU_TENSOR_MAP_FLOAT_OOB_FILL_NONE);
  }
  for (int i = 0; i < 2; i++) {
    const cuuint64_t dims[4] = {1280, 2, i ? 64u : 2u, i ? 2u : 64u}, strides[3] = {10240, i ? 40960u : 20480u, i ? 20480u : 40960u};
    const cuuint32_t box[4] = {128, 2, i ? 4u : 2u, i ? 2u : 4u}, es[4] = {1, 1, 1, 1};
    enc(i ? &wk.xp : &wk.xn, CU_TENSOR_MAP_DATA_TYPE_UINT64, 4, sym(g_xn), dims, strides, box, es, CU_TENSOR_MAP_INTERLEAVE_NONE, CU_TENSOR_MAP_SWIZZLE_NONE,
        CU_TENSOR_MAP_L2_PROMOTION_L2_256B, CU_TENSOR_MAP_FLOAT_OOB_FILL_NONE);
  }
  wk.x = x;
  for (int i = 0; i < 4; i++) at.pf[i] = (const uint8_t*)d_in[i < 2 ? 3 + i : i == 2 ? 2 : 5];
  int qa_end[2] = {12, 12};
  for (int layer = 0; layer < 2; layer++) {
    ch.sync = wk.sync = at.sync = (uint32_t*)sym(g_sync) + layer * SY_N;
    ch.other = (uint32_t*)sym(g_sync) + (1 - layer) * SY_N;
    ch.layer = layer;
    at.next = layer ? nullptr : ch.other;
    wk.qa_end = qa_end[layer];
    wk.kind = layer ? WK_LEAD : WK_FIRST;
    launch(work_kernel, 132, 384, WK_SMEM, 1, layer != 0, wk);
    launch(chain_kernel, 96, 384, CH_SMEM, 3, true, ch);
    wk.kind = WK_JOIN;
    launch(work_kernel, 96, 384, WK_SMEM, 1, true, wk);
    launch(attn_b_kernel, 128, AB_T + 32, AB_SMEM, 1, true, at);
  }
  wk.kind = WK_LAST;
  launch(work_kernel, 128, 384, WK_SMEM, 1, true, wk);
}
```

```cpp
#include <cuda_runtime.h>
#include <cuda_bf16.h>
#include <cuda.h>
#include <stdint.h>
#include <stdlib.h>

namespace {

constexpr int SEQ = 2048, DM = 640, HD = 6144, NSEG = 64;
constexpr int SPIN_LIMIT = 1 << 20;
#define HINT 7

__device__ __align__(128) uint2 g_x[SEQ * DM / 4];
__device__ __align__(128) uint32_t g_xn[SEQ * DM / 2];
__device__ __align__(128) uint32_t g_of[SEQ * DM / 2];
__device__ __align__(128) uint4 g_o[SEQ * HD / 8];
__device__ __align__(128) uint4 g_q[SEQ * HD / 8];
constexpr int KV_K = 0, KV_KM = 16384, KV_V = 20480, KV_VM = 36864, KV_BYTES = 40960;
__device__ __align__(128) uint8_t g_kv[16 * 96 * KV_BYTES];
#define OP_B8 11
#define OP_B16 14
#define OP_N4 16
#define BQ_12 12
#define BQ_24 14
#define FIN_16 12
__host__ __device__ constexpr int op_split(int b) { return b < OP_B8 ? 4 : b < OP_B16 ? 8 : 16; }
__host__ __device__ constexpr int op_tiles(int b) { return b < OP_N4 ? 2 : 4; }
__host__ __device__ constexpr int fin_items(int b) { return b < OP_B8 ? 4 : b < FIN_16 ? 8 : 16; }
__host__ __device__ constexpr int bq_items(int b) { return b < BQ_12 ? 6 : b < BQ_24 ? 12 : 24; }
__host__ __device__ constexpr int ln_items(int layer, int b) { return layer == 0 && b < 2 ? 16 : 4; }
__device__ __align__(128) uint2 g_part[16 * 16 * 16 * 40 * 32];
constexpr int SY_P = 128, SY_T = 192, SY_UP = 224, SY_OB = 225, SY_PRE = 256, SY_PART = 288, SY_N = 384;
__device__ __align__(128) uint32_t g_sync[2 * SY_N];
constexpr int NSLOT = 92;
__device__ uint32_t g_pool[(NSLOT + 2) * 2048];
__device__ uint32_t g_smpart[256], g_orient[NSLOT];
__device__ __align__(128) uint32_t g_bqkv[3 * 32 * 256 * 96];

#define XT(i)
#define BT(i)
#define MISS(k, n)
#define PRO(i)
#define TRACE(w)
#define ITEM(code, w)
#define STAT(k)
#define TMV(i, v)
#define TM(i)
#define TMD(i, dep)

__device__ __forceinline__ uint32_t gtime() { uint32_t c; asm volatile("mov.u32 %0, %%globaltimer_lo;" : "=r"(c) :: "memory"); return c; }
__device__ __forceinline__ uint32_t clk32() { uint32_t c; asm volatile("mov.u32 %0, %%clock;" : "=r"(c) :: "memory"); return c; }
__device__ __forceinline__ uint32_t s2u(const void* p) { return (uint32_t)__cvta_generic_to_shared(p); }
__device__ __forceinline__ uint32_t pack2(float a, float b) {
  uint32_t r; asm("cvt.rn.bf16x2.f32 %0, %1, %2;" : "=r"(r) : "f"(b), "f"(a)); return r; }
__device__ __forceinline__ float bf_lo(uint32_t w) { return __uint_as_float(w << 16); }
__device__ __forceinline__ float bf_hi(uint32_t w) { return __uint_as_float(w & 0xffff0000u); }
__device__ __forceinline__ float ex2(float x) { float y; asm("ex2.approx.ftz.f32 %0, %1;" : "=f"(y) : "f"(x)); return y; }

__device__ __forceinline__ void mbar_init(uint32_t bar, uint32_t n) {
  asm volatile("mbarrier.init.shared::cta.b64 [%0], %1;" :: "r"(bar), "r"(n) : "memory"); }
__device__ __forceinline__ void mbar_expect(uint32_t bar, uint32_t bytes) {
  asm volatile("mbarrier.arrive.expect_tx.shared::cta.b64 _, [%0], %1;" :: "r"(bar), "r"(bytes) : "memory"); }
__device__ __forceinline__ void mbar_arrive(uint32_t bar) {
  asm volatile("mbarrier.arrive.shared::cta.b64 _, [%0];" :: "r"(bar) : "memory"); }
__device__ __forceinline__ void mbar_arrive_remote(uint32_t bar) {
  asm volatile("mbarrier.arrive.shared::cluster.b64 _, [%0];" :: "r"(bar) : "memory"); }
__device__ __forceinline__ void mbar_wait_slow(uint32_t bar, uint32_t ph) {
  asm volatile("{.reg .pred p; .reg .u32 n; mov.u32 n, 0;\n"
               "W: mbarrier.try_wait.parity.shared::cta.b64 p, [%0], %1; @p bra D;\n"
               "add.u32 n, n, 1; setp.gt.u32 p, n, %2; @p trap; bra W;\n"
               "D: }" :: "r"(bar), "r"(ph), "n"(SPIN_LIMIT) : "memory");
}
__device__ __forceinline__ void mbar_wait(uint32_t bar, uint32_t ph) {
  uint32_t ok;
  asm volatile("{.reg .pred p; mbarrier.try_wait.parity.shared::cta.b64 p, [%1], %2; selp.u32 %0, 1, 0, p;}" : "=r"(ok) : "r"(bar), "r"(ph) : "memory");
  if (__builtin_expect(!ok, 0)) mbar_wait_slow(bar, ph);
}
__device__ __forceinline__ void mbar_wait_uniform(uint32_t bar, uint32_t ph) {
  asm volatile("{.reg .pred p; .reg .u32 n; mov.u32 n, 0;\n"
               "W: mbarrier.try_wait.parity.shared::cta.b64 p, [%0], %1; vote.sync.all.pred p, p, 0xffffffff; @p bra.uni D;\n"
               "add.u32 n, n, 1; setp.gt.u32 p, n, %2; @p trap; bra.uni W;\n"
               "D: }" :: "r"(bar), "r"(ph), "n"(SPIN_LIMIT) : "memory");
}
__device__ __forceinline__ bool elect() {
  uint32_t p; asm volatile("{.reg .pred q; elect.sync _|q, 0xffffffff; selp.u32 %0, 1, 0, q;}" : "=r"(p)); return p; }
__device__ __forceinline__ void mbar_wait_cluster(uint32_t bar, uint32_t ph) {
  asm volatile("{.reg .pred p; .reg .u32 n; mov.u32 n, 0;\n"
               "W: mbarrier.try_wait.parity.acquire.cluster.shared::cta.b64 p, [%0], %1; @p bra D;\n"
               "add.u32 n, n, 1; setp.gt.u32 p, n, %2; @p trap; bra W;\n"
               "D: }" :: "r"(bar), "r"(ph), "n"(SPIN_LIMIT) : "memory");
}
__device__ __forceinline__ void spin_guard(int& n) {
  asm volatile("{.reg .pred p; add.s32 %0, %0, 1; setp.gt.s32 p, %0, %1; @p trap;}" : "+r"(n) : "n"(SPIN_LIMIT));
}
__device__ __forceinline__ void pdl_wait() { asm volatile("griddepcontrol.wait;" ::: "memory"); TRACE(1); }
__device__ __forceinline__ void pdl_launch() { asm volatile("griddepcontrol.launch_dependents;" ::: "memory"); }
__device__ __forceinline__ uint32_t ld_acquire(const uint32_t* p) { uint32_t v; asm volatile("ld.acquire.gpu.global.u32 %0, [%1];" : "=r"(v) : "l"(p) : "memory"); return v; }
__device__ __forceinline__ void red_release(uint32_t* p, uint32_t v) { asm volatile("red.release.gpu.global.add.u32 [%0], %1;" :: "l"(p), "r"(v) : "memory"); }
__device__ __forceinline__ void fence_async_global() { asm volatile("fence.proxy.async.global;" ::: "memory"); }
__device__ __forceinline__ void fence_async() { asm volatile("fence.proxy.async.shared::cta;" ::: "memory"); }
__device__ __forceinline__ void bar_sync(int id, int n) { asm volatile("bar.sync %0, %1;" :: "r"(id), "r"(n) : "memory"); }
__device__ __forceinline__ void bar_arrive(int id, int n) { asm volatile("bar.arrive %0, %1;" :: "r"(id), "r"(n) : "memory"); }
__device__ __forceinline__ void tma_load(uint32_t dst, const CUtensorMap* m, int c0, int c1, uint32_t bar) {
  asm volatile("cp.async.bulk.tensor.2d.shared::cluster.global.mbarrier::complete_tx::bytes [%0], [%1, {%3, %4}], [%2];"
               :: "r"(dst), "l"(m), "r"(bar), "r"(c0), "r"(c1) : "memory"); }
__device__ __forceinline__ void tma_store(const CUtensorMap* m, uint32_t src, int c0, int c1) {
  asm volatile("cp.async.bulk.tensor.2d.global.shared::cta.bulk_group [%0, {%2, %3}], [%1];"
               :: "l"(m), "r"(src), "r"(c0), "r"(c1) : "memory"); }
__device__ __forceinline__ uint64_t evict_first() { uint64_t p; asm("createpolicy.fractional.L2::evict_first.b64 %0, 1.0;" : "=l"(p)); return p; }
__device__ __forceinline__ void bulk_load_last(uint32_t dst, const void* src, uint32_t bytes, uint32_t bar) {
  asm volatile("cp.async.bulk.shared::cluster.global.mbarrier::complete_tx::bytes.L2::cache_hint [%0], [%1], %2, [%3], %4;"
               :: "r"(dst), "l"(src), "r"(bytes), "r"(bar), "l"(evict_first()) : "memory"); }
__device__ __forceinline__ void bulk_store_stream(void* dst, uint32_t src, uint32_t bytes) {
  asm volatile("cp.async.bulk.global.shared::cta.bulk_group.L2::cache_hint [%0], [%1], %2, %3;" :: "l"(dst), "r"(src), "r"(bytes), "l"(evict_first()) : "memory"); }
__device__ __forceinline__ void bulk_load(uint32_t dst, const void* src, uint32_t bytes, uint32_t bar) {
  asm volatile("cp.async.bulk.shared::cluster.global.mbarrier::complete_tx::bytes [%0], [%1], %2, [%3];"
               :: "r"(dst), "l"(src), "r"(bytes), "r"(bar) : "memory"); }
__device__ __forceinline__ void bulk_push(uint32_t dst, uint32_t src, uint32_t bytes, uint32_t bar) {
  asm volatile("cp.async.bulk.shared::cluster.shared::cta.mbarrier::complete_tx::bytes [%0], [%1], %2, [%3];"
               :: "r"(dst), "r"(src), "r"(bytes), "r"(bar) : "memory"); }
__device__ __forceinline__ void bulk_store(void* dst, uint32_t src, uint32_t bytes) {
  asm volatile("cp.async.bulk.global.shared::cta.bulk_group [%0], [%1], %2;" :: "l"(dst), "r"(src), "r"(bytes) : "memory"); }
__device__ __forceinline__ void bulk_commit() { asm volatile("cp.async.bulk.commit_group;" ::: "memory"); }
template <int N> __device__ __forceinline__ void bulk_wait_read() { asm volatile("cp.async.bulk.wait_group.read %0;" :: "n"(N) : "memory"); }
template <int N> __device__ __forceinline__ void bulk_wait() { asm volatile("cp.async.bulk.wait_group %0;" :: "n"(N) : "memory"); }

__device__ __forceinline__ uint64_t mkdesc(uint32_t addr, uint32_t lbo, uint32_t sbo, uint32_t sw) {
  return (uint64_t)((addr & 0x3FFFF) >> 4) | ((uint64_t)(lbo >> 4) << 16) | ((uint64_t)(sbo >> 4) << 32) | ((uint64_t)sw << 62); }
__device__ __forceinline__ void wg_fence() { asm volatile("wgmma.fence.sync.aligned;" ::: "memory"); }
__device__ __forceinline__ void wg_commit() { asm volatile("wgmma.commit_group.sync.aligned;" ::: "memory"); }
template <int N> __device__ __forceinline__ void wg_wait() { asm volatile("wgmma.wait_group.sync.aligned %0;" :: "n"(N) : "memory"); }
template <int N> __device__ __forceinline__ void reg_fence(float* d) {
#pragma unroll
  for (int i = 0; i < N; i++) asm volatile("" : "+f"(d[i]) :: "memory");
}

__device__ __forceinline__ void mma16(float* d, uint32_t a0, uint32_t a1, uint32_t a2, uint32_t a3, uint32_t b0, uint32_t b1) {
  asm volatile("mma.sync.aligned.m16n8k16.row.col.f32.bf16.bf16.f32 {%0,%1,%2,%3},{%4,%5,%6,%7},{%8,%9},{%0,%1,%2,%3};"
               : "+f"(d[0]), "+f"(d[1]), "+f"(d[2]), "+f"(d[3]) : "r"(a0), "r"(a1), "r"(a2), "r"(a3), "r"(b0), "r"(b1)); }
__device__ __forceinline__ void mma8(float* d, uint32_t a0, uint32_t a1, uint32_t b0) {
  asm volatile("mma.sync.aligned.m16n8k8.row.col.f32.bf16.bf16.f32 {%0,%1,%2,%3},{%4,%5},{%6},{%0,%1,%2,%3};"
               : "+f"(d[0]), "+f"(d[1]), "+f"(d[2]), "+f"(d[3]) : "r"(a0), "r"(a1), "r"(b0)); }
__device__ __forceinline__ void ldsm4(uint32_t* r, uint32_t a) {
  asm volatile("ldmatrix.sync.aligned.m8n8.x4.shared.b16 {%0,%1,%2,%3},[%4];" : "=r"(r[0]), "=r"(r[1]), "=r"(r[2]), "=r"(r[3]) : "r"(a) : "memory"); }
__device__ __forceinline__ uint4 ldsm4v(uint32_t a) { uint32_t r[4]; ldsm4(r, a); return make_uint4(r[0], r[1], r[2], r[3]); }
__device__ __forceinline__ void ldsm4t(uint32_t* r, uint32_t a) {
  asm volatile("ldmatrix.sync.aligned.m8n8.x4.trans.shared.b16 {%0,%1,%2,%3},[%4];" : "=r"(r[0]), "=r"(r[1]), "=r"(r[2]), "=r"(r[3]) : "r"(a) : "memory"); }
__device__ __forceinline__ void ldsm2t(uint32_t* r, uint32_t a) {
  asm volatile("ldmatrix.sync.aligned.m8n8.x2.trans.shared.b16 {%0,%1},[%2];" : "=r"(r[0]), "=r"(r[1]) : "r"(a) : "memory"); }
__device__ __forceinline__ void stsm4(uint32_t a, uint32_t r0, uint32_t r1, uint32_t r2, uint32_t r3) {
  asm volatile("stmatrix.sync.aligned.m8n8.x4.shared.b16 [%0], {%1,%2,%3,%4};" :: "r"(a), "r"(r0), "r"(r1), "r"(r2), "r"(r3) : "memory"); }
__device__ __forceinline__ void stsm4t(uint32_t a, uint32_t r0, uint32_t r1, uint32_t r2, uint32_t r3) {
  asm volatile("stmatrix.sync.aligned.m8n8.x4.trans.shared.b16 [%0], {%1,%2,%3,%4};" :: "r"(a), "r"(r0), "r"(r1), "r"(r2), "r"(r3) : "memory"); }
__device__ __forceinline__ void stsm2(uint32_t a, uint32_t r0, uint32_t r1) {
  asm volatile("stmatrix.sync.aligned.m8n8.x2.shared.b16 [%0], {%1,%2};" :: "r"(a), "r"(r0), "r"(r1) : "memory"); }
__device__ __forceinline__ void stsm2t(uint32_t a, uint32_t r0, uint32_t r1) {
  asm volatile("stmatrix.sync.aligned.m8n8.x2.trans.shared.b16 [%0], {%1,%2};" :: "r"(a), "r"(r0), "r"(r1) : "memory"); }
__device__ __forceinline__ void sts32(uint32_t a, uint32_t v) { asm volatile("st.shared.b32 [%0], %1;" :: "r"(a), "r"(v) : "memory"); }
__device__ __forceinline__ void sts64f(uint32_t a, float x, float y) { asm volatile("st.shared.v2.f32 [%0], {%1,%2};" :: "r"(a), "f"(x), "f"(y) : "memory"); }
__device__ __forceinline__ void sts128(uint32_t a, uint4 v) {
  asm volatile("st.shared.v4.b32 [%0], {%1,%2,%3,%4};" :: "r"(a), "r"(v.x), "r"(v.y), "r"(v.z), "r"(v.w) : "memory"); }
__device__ __forceinline__ void sts128f(uint32_t a, float x, float y, float z, float w) {
  asm volatile("st.shared.v4.f32 [%0], {%1,%2,%3,%4};" :: "r"(a), "f"(x), "f"(y), "f"(z), "f"(w) : "memory"); }
__device__ __forceinline__ float lds32f(uint32_t a) { float v; asm volatile("ld.shared.f32 %0, [%1];" : "=f"(v) : "r"(a) : "memory"); return v; }
__device__ __forceinline__ float2 lds64f(uint32_t a) { float2 v; asm volatile("ld.shared.v2.f32 {%0,%1}, [%2];" : "=f"(v.x), "=f"(v.y) : "r"(a) : "memory"); return v; }
__device__ __forceinline__ float4 lds128f(uint32_t a) {
  float4 v; asm volatile("ld.shared.v4.f32 {%0,%1,%2,%3}, [%4];" : "=f"(v.x), "=f"(v.y), "=f"(v.z), "=f"(v.w) : "r"(a) : "memory"); return v; }
__device__ __forceinline__ uint4 lds128(uint32_t a) {
  uint4 v; asm volatile("ld.shared.v4.b32 {%0,%1,%2,%3}, [%4];" : "=r"(v.x), "=r"(v.y), "=r"(v.z), "=r"(v.w) : "r"(a) : "memory"); return v; }
__device__ __forceinline__ uint4 ldg_strong128(const void* p) {
  uint4 v; asm volatile("ld.relaxed.gpu.global.v4.u32 {%0,%1,%2,%3}, [%4];" : "=r"(v.x), "=r"(v.y), "=r"(v.z), "=r"(v.w) : "l"(p) : "memory"); return v; }
__device__ __forceinline__ uint2 ldg_strong64(const void* p) {
  uint2 v; asm volatile("ld.relaxed.gpu.global.v2.u32 {%0,%1}, [%2];" : "=r"(v.x), "=r"(v.y) : "l"(p) : "memory"); return v; }
__device__ __forceinline__ void stg_strong32(void* p, uint32_t v) { asm volatile("st.relaxed.gpu.global.u32 [%0], %1;" :: "l"(p), "r"(v) : "memory"); }
__device__ __forceinline__ void stg_strong128(void* p, uint4 v) {
  asm volatile("st.relaxed.gpu.global.v4.u32 [%0], {%1,%2,%3,%4};" :: "l"(p), "r"(v.x), "r"(v.y), "r"(v.z), "r"(v.w) : "memory"); }
__device__ __forceinline__ uint32_t mapa(uint32_t a, uint32_t r) {
  uint32_t o; asm("mapa.shared::cluster.u32 %0, %1, %2;" : "=r"(o) : "r"(a), "r"(r)); return o; }
__device__ __forceinline__ void st_async2f(uint32_t a, float x, float y, uint32_t bar) {
  asm volatile("st.async.shared::cluster.mbarrier::complete_tx::bytes.v2.f32 [%0], {%1,%2}, [%3];" :: "r"(a), "f"(x), "f"(y), "r"(bar) : "memory"); }
__device__ __forceinline__ void st_async32(uint32_t a, uint32_t x, uint32_t bar) {
  asm volatile("st.async.shared::cluster.mbarrier::complete_tx::bytes.b32 [%0], %1, [%2];" :: "r"(a), "r"(x), "r"(bar) : "memory"); }
__device__ __forceinline__ uint32_t lds32(uint32_t a) { uint32_t v; asm volatile("ld.shared.b32 %0, [%1];" : "=r"(v) : "r"(a) : "memory"); return v; }
__device__ __forceinline__ void st_async64(uint32_t a, uint32_t x, uint32_t y, uint32_t bar) {
  asm volatile("st.async.shared::cluster.mbarrier::complete_tx::bytes.v2.b32 [%0], {%1,%2}, [%3];" :: "r"(a), "r"(x), "r"(y), "r"(bar) : "memory"); }
__device__ __forceinline__ void st_async128(uint32_t a, uint4 v, uint32_t bar) {
  asm volatile("st.async.shared::cluster.mbarrier::complete_tx::bytes.v4.b32 [%0], {%1,%2,%3,%4}, [%5];" :: "r"(a), "r"(v.x), "r"(v.y), "r"(v.z), "r"(v.w), "r"(bar) : "memory"); }
__device__ __forceinline__ uint2 lds64(uint32_t a) { uint2 v; asm volatile("ld.shared.v2.b32 {%0,%1}, [%2];" : "=r"(v.x), "=r"(v.y) : "r"(a) : "memory"); return v; }
__device__ __forceinline__ void sts64(uint32_t a, uint32_t x, uint32_t y) { asm volatile("st.shared.v2.b32 [%0], {%1,%2};" :: "r"(a), "r"(x), "r"(y) : "memory"); }
__device__ __forceinline__ uint32_t ldg_strong32(const void* p) { uint32_t v; asm volatile("ld.relaxed.gpu.global.u32 %0, [%1];" : "=r"(v) : "l"(p) : "memory"); return v; }
__device__ __forceinline__ uint32_t transpose8(uint32_t x) { uint32_t r; asm volatile("movmatrix.sync.aligned.m8n8.trans.b16 %0, %1;" : "=r"(r) : "r"(x)); return r; }
__device__ __forceinline__ uint32_t hadd2(uint32_t a, uint32_t b) { uint32_t r; asm("add.rn.bf16x2 %0, %1, %2;" : "=r"(r) : "r"(a), "r"(b)); return r; }
__device__ __forceinline__ uint32_t min4(uint4 v) { return min(__vimin3_u32(v.x, v.y, v.z), v.w); }

__device__ __forceinline__ void wg_ss192_01(float* d, uint64_t da, uint64_t db, int sd) {
  asm volatile("{.reg .pred p; setp.ne.b32 p, %98, 0;\n"
    "wgmma.mma_async.sync.aligned.m64n192k16.f32.bf16.bf16 {%0,%1,%2,%3,%4,%5,%6,%7,%8,%9,%10,%11,%12,%13,%14,%15,%16,%17,%18,%19,%20,%21,%22,%23,%24,%25,%26,%27,%28,%29,%30,%31,%32,%33,%34,%35,%36,%37,%38,%39,%40,%41,%42,%43,%44,%45,%46,%47,%48,%49,%50,%51,%52,%53,%54,%55,%56,%57,%58,%59,%60,%61,%62,%63,%64,%65,%66,%67,%68,%69,%70,%71,%72,%73,%74,%75,%76,%77,%78,%79,%80,%81,%82,%83,%84,%85,%86,%87,%88,%89,%90,%91,%92,%93,%94,%95}, %96, %97, p, 1, 1, 0, 1;}"
    : "+f"(d[0]),"+f"(d[1]),"+f"(d[2]),"+f"(d[3]),"+f"(d[4]),"+f"(d[5]),"+f"(d[6]),"+f"(d[7]),"+f"(d[8]),"+f"(d[9]),"+f"(d[10]),"+f"(d[11]),"+f"(d[12]),"+f"(d[13]),"+f"(d[14]),"+f"(d[15]),"+f"(d[16]),"+f"(d[17]),"+f"(d[18]),"+f"(d[19]),"+f"(d[20]),"+f"(d[21]),"+f"(d[22]),"+f"(d[23]),"+f"(d[24]),"+f"(d[25]),"+f"(d[26]),"+f"(d[27]),"+f"(d[28]),"+f"(d[29]),"+f"(d[30]),"+f"(d[31]),"+f"(d[32]),"+f"(d[33]),"+f"(d[34]),"+f"(d[35]),"+f"(d[36]),"+f"(d[37]),"+f"(d[38]),"+f"(d[39]),"+f"(d[40]),"+f"(d[41]),"+f"(d[42]),"+f"(d[43]),"+f"(d[44]),"+f"(d[45]),"+f"(d[46]),"+f"(d[47]),"+f"(d[48]),"+f"(d[49]),"+f"(d[50]),"+f"(d[51]),"+f"(d[52]),"+f"(d[53]),"+f"(d[54]),"+f"(d[55]),"+f"(d[56]),"+f"(d[57]),"+f"(d[58]),"+f"(d[59]),"+f"(d[60]),"+f"(d[61]),"+f"(d[62]),"+f"(d[63]),"+f"(d[64]),"+f"(d[65]),"+f"(d[66]),"+f"(d[67]),"+f"(d[68]),"+f"(d[69]),"+f"(d[70]),"+f"(d[71]),"+f"(d[72]),"+f"(d[73]),"+f"(d[74]),"+f"(d[75]),"+f"(d[76]),"+f"(d[77]),"+f"(d[78]),"+f"(d[79]),"+f"(d[80]),"+f"(d[81]),"+f"(d[82]),"+f"(d[83]),"+f"(d[84]),"+f"(d[85]),"+f"(d[86]),"+f"(d[87]),"+f"(d[88]),"+f"(d[89]),"+f"(d[90]),"+f"(d[91]),"+f"(d[92]),"+f"(d[93]),"+f"(d[94]),"+f"(d[95])
    : "l"(da), "l"(db), "r"(sd));
}
__device__ __forceinline__ void wg_ss128_01(float* d, uint64_t da, uint64_t db, int sd) {
  asm volatile("{.reg .pred p; setp.ne.b32 p, %66, 0;\n"
    "wgmma.mma_async.sync.aligned.m64n128k16.f32.bf16.bf16 {%0,%1,%2,%3,%4,%5,%6,%7,%8,%9,%10,%11,%12,%13,%14,%15,%16,%17,%18,%19,%20,%21,%22,%23,%24,%25,%26,%27,%28,%29,%30,%31,%32,%33,%34,%35,%36,%37,%38,%39,%40,%41,%42,%43,%44,%45,%46,%47,%48,%49,%50,%51,%52,%53,%54,%55,%56,%57,%58,%59,%60,%61,%62,%63}, %64, %65, p, 1, 1, 0, 1;}"
    : "+f"(d[0]),"+f"(d[1]),"+f"(d[2]),"+f"(d[3]),"+f"(d[4]),"+f"(d[5]),"+f"(d[6]),"+f"(d[7]),"+f"(d[8]),"+f"(d[9]),"+f"(d[10]),"+f"(d[11]),"+f"(d[12]),"+f"(d[13]),"+f"(d[14]),"+f"(d[15]),"+f"(d[16]),"+f"(d[17]),"+f"(d[18]),"+f"(d[19]),"+f"(d[20]),"+f"(d[21]),"+f"(d[22]),"+f"(d[23]),"+f"(d[24]),"+f"(d[25]),"+f"(d[26]),"+f"(d[27]),"+f"(d[28]),"+f"(d[29]),"+f"(d[30]),"+f"(d[31]),"+f"(d[32]),"+f"(d[33]),"+f"(d[34]),"+f"(d[35]),"+f"(d[36]),"+f"(d[37]),"+f"(d[38]),"+f"(d[39]),"+f"(d[40]),"+f"(d[41]),"+f"(d[42]),"+f"(d[43]),"+f"(d[44]),"+f"(d[45]),"+f"(d[46]),"+f"(d[47]),"+f"(d[48]),"+f"(d[49]),"+f"(d[50]),"+f"(d[51]),"+f"(d[52]),"+f"(d[53]),"+f"(d[54]),"+f"(d[55]),"+f"(d[56]),"+f"(d[57]),"+f"(d[58]),"+f"(d[59]),"+f"(d[60]),"+f"(d[61]),"+f"(d[62]),"+f"(d[63])
    : "l"(da), "l"(db), "r"(sd));
}
__device__ __forceinline__ void wg_ss160_01(float* d, uint64_t da, uint64_t db, int sd) {
  asm volatile("{.reg .pred p; setp.ne.b32 p, %82, 0;\n"
    "wgmma.mma_async.sync.aligned.m64n160k16.f32.bf16.bf16 {%0,%1,%2,%3,%4,%5,%6,%7,%8,%9,%10,%11,%12,%13,%14,%15,%16,%17,%18,%19,%20,%21,%22,%23,%24,%25,%26,%27,%28,%29,%30,%31,%32,%33,%34,%35,%36,%37,%38,%39,%40,%41,%42,%43,%44,%45,%46,%47,%48,%49,%50,%51,%52,%53,%54,%55,%56,%57,%58,%59,%60,%61,%62,%63,%64,%65,%66,%67,%68,%69,%70,%71,%72,%73,%74,%75,%76,%77,%78,%79}, %80, %81, p, 1, 1, 0, 1;}"
    : "+f"(d[0]),"+f"(d[1]),"+f"(d[2]),"+f"(d[3]),"+f"(d[4]),"+f"(d[5]),"+f"(d[6]),"+f"(d[7]),"+f"(d[8]),"+f"(d[9]),"+f"(d[10]),"+f"(d[11]),"+f"(d[12]),"+f"(d[13]),"+f"(d[14]),"+f"(d[15]),"+f"(d[16]),"+f"(d[17]),"+f"(d[18]),"+f"(d[19]),"+f"(d[20]),"+f"(d[21]),"+f"(d[22]),"+f"(d[23]),"+f"(d[24]),"+f"(d[25]),"+f"(d[26]),"+f"(d[27]),"+f"(d[28]),"+f"(d[29]),"+f"(d[30]),"+f"(d[31]),"+f"(d[32]),"+f"(d[33]),"+f"(d[34]),"+f"(d[35]),"+f"(d[36]),"+f"(d[37]),"+f"(d[38]),"+f"(d[39]),"+f"(d[40]),"+f"(d[41]),"+f"(d[42]),"+f"(d[43]),"+f"(d[44]),"+f"(d[45]),"+f"(d[46]),"+f"(d[47]),"+f"(d[48]),"+f"(d[49]),"+f"(d[50]),"+f"(d[51]),"+f"(d[52]),"+f"(d[53]),"+f"(d[54]),"+f"(d[55]),"+f"(d[56]),"+f"(d[57]),"+f"(d[58]),"+f"(d[59]),"+f"(d[60]),"+f"(d[61]),"+f"(d[62]),"+f"(d[63]),"+f"(d[64]),"+f"(d[65]),"+f"(d[66]),"+f"(d[67]),"+f"(d[68]),"+f"(d[69]),"+f"(d[70]),"+f"(d[71]),"+f"(d[72]),"+f"(d[73]),"+f"(d[74]),"+f"(d[75]),"+f"(d[76]),"+f"(d[77]),"+f"(d[78]),"+f"(d[79])
    : "l"(da), "l"(db), "r"(sd));
}
__device__ __forceinline__ void wg_ss80_01(float* d, uint64_t da, uint64_t db, int sd) {
  asm volatile("{.reg .pred p; setp.ne.b32 p, %42, 0;\n"
    "wgmma.mma_async.sync.aligned.m64n80k16.f32.bf16.bf16 {%0,%1,%2,%3,%4,%5,%6,%7,%8,%9,%10,%11,%12,%13,%14,%15,%16,%17,%18,%19,%20,%21,%22,%23,%24,%25,%26,%27,%28,%29,%30,%31,%32,%33,%34,%35,%36,%37,%38,%39}, %40, %41, p, 1, 1, 0, 1;}"
    : "+f"(d[0]),"+f"(d[1]),"+f"(d[2]),"+f"(d[3]),"+f"(d[4]),"+f"(d[5]),"+f"(d[6]),"+f"(d[7]),"+f"(d[8]),"+f"(d[9]),"+f"(d[10]),"+f"(d[11]),"+f"(d[12]),"+f"(d[13]),"+f"(d[14]),"+f"(d[15]),"+f"(d[16]),"+f"(d[17]),"+f"(d[18]),"+f"(d[19]),"+f"(d[20]),"+f"(d[21]),"+f"(d[22]),"+f"(d[23]),"+f"(d[24]),"+f"(d[25]),"+f"(d[26]),"+f"(d[27]),"+f"(d[28]),"+f"(d[29]),"+f"(d[30]),"+f"(d[31]),"+f"(d[32]),"+f"(d[33]),"+f"(d[34]),"+f"(d[35]),"+f"(d[36]),"+f"(d[37]),"+f"(d[38]),"+f"(d[39])
    : "l"(da), "l"(db), "r"(sd));
}
__device__ __forceinline__ void wg_rs32_00(float* d, uint32_t a0, uint32_t a1, uint32_t a2, uint32_t a3, uint64_t db, int sd) {
  asm volatile("{.reg .pred p; setp.ne.b32 p, %21, 0;\n"
    "wgmma.mma_async.sync.aligned.m64n32k16.f32.bf16.bf16 {%0,%1,%2,%3,%4,%5,%6,%7,%8,%9,%10,%11,%12,%13,%14,%15}, {%16,%17,%18,%19}, %20, p, 1, 1, 0;}"
    : "+f"(d[0]),"+f"(d[1]),"+f"(d[2]),"+f"(d[3]),"+f"(d[4]),"+f"(d[5]),"+f"(d[6]),"+f"(d[7]),"+f"(d[8]),"+f"(d[9]),"+f"(d[10]),"+f"(d[11]),"+f"(d[12]),"+f"(d[13]),"+f"(d[14]),"+f"(d[15])
    : "r"(a0), "r"(a1), "r"(a2), "r"(a3), "l"(db), "r"(sd));
}
__device__ __forceinline__ void wg_rs64_00(float* d, uint32_t a0, uint32_t a1, uint32_t a2, uint32_t a3, uint64_t db, int sd) {
  asm volatile("{.reg .pred p; setp.ne.b32 p, %37, 0;\n"
    "wgmma.mma_async.sync.aligned.m64n64k16.f32.bf16.bf16 {%0,%1,%2,%3,%4,%5,%6,%7,%8,%9,%10,%11,%12,%13,%14,%15,%16,%17,%18,%19,%20,%21,%22,%23,%24,%25,%26,%27,%28,%29,%30,%31}, {%32,%33,%34,%35}, %36, p, 1, 1, 0;}"
    : "+f"(d[0]),"+f"(d[1]),"+f"(d[2]),"+f"(d[3]),"+f"(d[4]),"+f"(d[5]),"+f"(d[6]),"+f"(d[7]),"+f"(d[8]),"+f"(d[9]),"+f"(d[10]),"+f"(d[11]),"+f"(d[12]),"+f"(d[13]),"+f"(d[14]),"+f"(d[15]),"+f"(d[16]),"+f"(d[17]),"+f"(d[18]),"+f"(d[19]),"+f"(d[20]),"+f"(d[21]),"+f"(d[22]),"+f"(d[23]),"+f"(d[24]),"+f"(d[25]),"+f"(d[26]),"+f"(d[27]),"+f"(d[28]),"+f"(d[29]),"+f"(d[30]),"+f"(d[31])
    : "r"(a0), "r"(a1), "r"(a2), "r"(a3), "l"(db), "r"(sd));
}
__device__ __forceinline__ void wg_rs24_01(float* d, uint32_t a0, uint32_t a1, uint32_t a2, uint32_t a3, uint64_t db, int sd) {
  asm volatile("{.reg .pred p; setp.ne.b32 p, %17, 0;\n"
    "wgmma.mma_async.sync.aligned.m64n24k16.f32.bf16.bf16 {%0,%1,%2,%3,%4,%5,%6,%7,%8,%9,%10,%11}, {%12,%13,%14,%15}, %16, p, 1, 1, 1;}"
    : "+f"(d[0]),"+f"(d[1]),"+f"(d[2]),"+f"(d[3]),"+f"(d[4]),"+f"(d[5]),"+f"(d[6]),"+f"(d[7]),"+f"(d[8]),"+f"(d[9]),"+f"(d[10]),"+f"(d[11])
    : "r"(a0), "r"(a1), "r"(a2), "r"(a3), "l"(db), "r"(sd));
}

#define AB_POLY 0x77
__device__ __forceinline__ constexpr bool poly_group(int group) { return (AB_POLY >> (group & 7)) & 1; }

template <int V> struct Int { static constexpr int value = V; };

__device__ __forceinline__ int core_word(int row, int col) {
  return ((((row >> 7) * 10 + (col >> 6)) * 16 + ((row >> 3) & 15)) * 8 + ((col >> 3) & 7)) * 32 + (row & 7) * 4 + ((col & 7) >> 1);
}
__device__ __forceinline__ void wait_count(const uint32_t* c, uint32_t n) {
  int spin = 0;
  while ((ld_acquire(c) & 0xffff) < n) { __nanosleep(32); spin_guard(spin); }
}
__device__ __forceinline__ void wait_count_uniform(const uint32_t* c, uint32_t n) {
  for (int spin = 0; !__all_sync(~0u, (ld_acquire(c) & 0xffff) >= n);) { __nanosleep(32); spin_guard(spin); }
  fence_async_global();
}
__device__ __forceinline__ void prefetch_l2(const void* p, uint32_t bytes) {
  asm volatile("cp.async.bulk.prefetch.L2.global [%0], %1;" :: "l"(p), "r"(bytes) : "memory"); }

#define PLACE 3
__device__ __forceinline__ bool helper_sm() {
  uint32_t m; asm("mov.u32 %0, %%smid;" : "=r"(m));
  return m < 2 || m >= 124 || (m >= 92 && m < 104) || (m >= 106 && m < 118) || m == 120 || m == 121;
}

__device__ __forceinline__ uint8_t* pool_at(uint32_t off) {
  return reinterpret_cast<uint8_t*>((reinterpret_cast<uintptr_t>(g_pool) + 8191) & ~(uintptr_t)8191) + off; }
__device__ __forceinline__ uint32_t page_latency(uint32_t* w) {
  uint32_t best = ~0u;
  stg_strong32(w, 0u);
  for (int r = 0; r < 4; r++) {
    uint32_t t0, t1, v;
    asm volatile("mov.u32 %0, %%clock;" : "=r"(t0) :: "memory");
    asm volatile("atom.relaxed.gpu.global.exch.b32 %0, [%1], 0;" : "=r"(v) : "l"(w) : "memory");
    asm volatile("{.reg .u32 t; add.u32 t, %1, 1; mov.u32 %0, %%clock; sub.u32 %0, %0, %1;}" : "=r"(t1) : "r"(__shfl_sync(1u, v, 0)) : "memory");
    best = min(best, t1 - t0);
  }
  return best;
}
__device__ __forceinline__ void probe_slots(uint32_t scratch) {
  const int w = (threadIdx.x >> 6) & 1, slot = w == 0 ? NSLOT : blockIdx.x;
  if ((threadIdx.x & 31) == 0 && (w == 0 || slot < NSLOT)) {
    uint32_t* q = reinterpret_cast<uint32_t*>(pool_at(slot * 8192)) + (w == 0 ? (blockIdx.x & 31) * 32 + (blockIdx.x >> 5) : 0);
    sts32(scratch + w * 4, page_latency(q) < page_latency(q + 1024));
  }
  bar_sync(2, 64);
  if ((threadIdx.x & 31) == 0) {
    const int part = lds32(scratch) ? 1 : 2;
    if (w == 0) { uint32_t smid; asm("mov.u32 %0, %%smid;" : "=r"(smid)); stg_strong32(g_smpart + (smid & 255), part); }
    else if (slot < NSLOT) stg_strong32(g_orient + slot, lds32(scratch + 4) ? part : 3 - part);
  }
  __syncwarp();
}

struct ChainParams {
  CUtensorMap wq, wk, wv, wo;
  const __nv_bfloat16* mem0;
  uint32_t *sync, *other;
  int layer;
  int d1, d2, dn, dx, mode, zero;
};
constexpr int CH_WQ = 0, CH_WO = 81920, CH_X = CH_WO + 86016, CH_M = CH_X, CH_Q = CH_X + 34816, CH_KM = CH_Q + 2048, CH_VP = CH_KM + 2048,
              CH_K = CH_X + 40960, CH_O = CH_K, CH_KS = CH_K + 3072, CH_V = CH_K + 4096, CH_VX = CH_V + 12288, CH_R2 = CH_VX,
              CH_SX = CH_VX + 3072, CH_SO = CH_SX + 2048, CH_ID = CH_SO + 1024, CH_L = CH_ID + 256, CH_TAB = CH_L + 64, CH_BAR = CH_TAB + 384;
constexpr int CH_SMEM = CH_BAR + 144;
constexpr int MB_WO = CH_BAR, MB_WQ = CH_BAR + 8, MB_X = CH_BAR + 16, MB_V = CH_BAR + 24, MB_T = CH_BAR + 32, MB_F = CH_BAR + 40, MB_G = CH_BAR + 48, MB_W = CH_BAR + 56;
enum { NB_PROJ = 1, NB_O = 2, NB_W1 = 3, NB_PRE = 4, NB_ST = 5, NB_MEM = 6, NB_XFREE = 7, NB_H1 = 8, NB_PUB = 9, NB_W2 = 10, NB_PROJ2 = 11, NB_PRE2 = 12, NB_H2 = 13, NB_W1V = 14 };
#define CH_NQ 9
#define CH_LAG 0
#define CH_PUSH 1
#define CH_CHAIN 0
#define CH_GATE 1
#define CH_PA 6
#define CH_PB 10
#define CH_PC 12
#define CH_PL 3
#define CH_DBL 0x2108
#define CH_PD 2
#define CH_ZD 1
#define SCHED() asm volatile("griddepcontrol.launch_dependents;" ::: "memory")
__device__ __forceinline__ uint32_t opaque(uint32_t x) { return __shfl_sync(~0u, x, threadIdx.x & 31); }
__device__ __forceinline__ uint32_t nz(uint32_t x) { uint32_t r; asm("max.u32 %0, %1, 1;" : "=r"(r) : "r"(x)); return r; }
__device__ __forceinline__ uint32_t set_tag(uint32_t w, uint32_t tag) { uint32_t r; asm("lop3.b32 %0, %1, %2, 1, 0xD8;" : "=r"(r) : "r"(w), "r"(tag)); return r; }
__device__ __forceinline__ uint32_t pack_tag(float lo, float hi, uint32_t tag) { return set_tag(__byte_perm(__float_as_uint(lo) + tag, pack2(hi, hi), 0x7632), tag); }
__device__ __forceinline__ uint32_t differ(uint32_t a, uint32_t b, uint32_t t) { uint32_t r; asm("lop3.b32 %0, %1, %2, %3, 0x7E;" : "=r"(r) : "r"(a), "r"(b), "r"(t)); return r; }
__device__ __forceinline__ uint32_t clk64() { uint64_t c; asm volatile("mov.u64 %0, %%clock64;" : "=l"(c) :: "memory"); return (uint32_t)c; }
__device__ __forceinline__ void until(uint32_t t) { while ((int)(clk64() - t) < 0) {} }
__device__ __forceinline__ float rcp(float x) { float y; asm("rcp.approx.ftz.f32 %0, %1;" : "=f"(y) : "f"(x)); return y; }

__device__ __forceinline__ void push_values(uint32_t sb, int s, int j) {
  const int r1 = j == 2 ? 0 : j + 1, r2 = j == 0 ? 2 : j - 1;
  const uint32_t src = sb + CH_V + j * 4096;
  if (s < NSEG - 1) {
    fence_async();
    bulk_push(mapa(src, r1), src, 4096, mapa(sb + MB_V, r1));
    bulk_push(mapa(src, r2), src, 4096, mapa(sb + MB_V, r2));
  }
}

template <int WG>
__device__ __forceinline__ void chain_compute(const ChainParams& p, const uint32_t sb) {
  const int tid = threadIdx.x & 127, t4 = __shfl_sync(~0u, tid >> 5, 0), lane = tid & 31;
  const int cta = blockIdx.x, h = cta / 3, j = cta - 3 * h;
  uint32_t ak[80], av[80], tw[4 * CH_NQ];
  const uint32_t wq = opaque(sb + CH_WQ + (WG * 320 + (lane & 7) + (lane >> 4) * 8) * 128 + (((2 * t4 + ((lane >> 3) & 1)) ^ (lane & 7)) << 4));
#pragma unroll
  for (int k = 0; k < 20; k++) {
    if (k == 0 || (WG * 20 + k) % 8 == 0) mbar_wait(sb + MB_W + 8 * ((WG * 20 + k) / 8), 0);
    ldsm4t(&ak[4 * k], wq + k * 2048);
  }
  bar_arrive(NB_PROJ2, 384);
#pragma unroll
  for (int k = 0; k < 20; k++) {
    if (k == 0 || (WG * 20 + k) % 8 == 0) mbar_wait(sb + MB_W + 40 + 8 * ((WG * 20 + k) / 8), 0);
    ldsm4t(&av[4 * k], wq + CH_WO + k * 2048);
  }
  bar_arrive(NB_PRE2, 384);
  const int r1 = j == 2 ? 0 : j + 1, r2 = j == 0 ? 2 : j - 1;
  const uint32_t l16 = opaque(sb + lane * 16), l8 = opaque(sb + lane * 8), l4 = opaque(sb + lane * 4);
  const uint32_t t16 = l16 + t4 * 512, t8 = l8 + t4 * 256;
  auto refill = [&]() {
#pragma unroll
    for (int k = 0; k < CH_NQ; k++) ldsm4t(&tw[4 * k], wq + k * 2048);
  };
  auto batch = [&](float* d, const uint32_t (&a)[80], int acc, bool fill) {
    const uint64_t d0 = mkdesc(1024 + CH_X + WG * 20480, 128, 5120, 0);
    wg_fence();
#pragma unroll
    for (int k = 0; k < 20; k++) {
      if (fill && !(k & 1) && k / 2 < CH_NQ) {
        uint32_t w = wq;
        if (k > 0 && CH_CHAIN) asm volatile("lop3.b32 %0, %1, %2, %3, 0xF8;" : "=r"(w) : "r"(wq), "r"(tw[2 * k - 1]), "r"(p.zero));
        __syncwarp();
        ldsm4t(&tw[2 * k], w + k * 1024);
        __syncwarp();
      }
      wg_rs32_00(d, a[4 * k], a[4 * k + 1], a[4 * k + 2], a[4 * k + 3], d0 + k * 16, acc | k);
    }
    wg_commit();
    wg_wait<0>();
    reg_fence<16>(d);
  };
  auto tokens = [&](int s, auto first) {
    float d[16];
    mbar_wait(sb + MB_T, s & 1);
    batch(d, WG == 0 ? ak : av, 0, WG == 0 && !first.value);
    s--; TM(10); s++;
    if (WG == 1 && !first.value) mbar_wait(sb + MB_F, (s - 1) & 1);
    const uint32_t kt = t16 + CH_K, vt = t16 + CH_V + j * 4096;
#pragma unroll
    for (int i = 0; i < 2; i++)
      sts128((WG == 0 ? kt : vt) + i * 2048, make_uint4(pack2(d[8 * i], d[8 * i + 1]), pack2(d[8 * i + 2], d[8 * i + 3]), pack2(d[8 * i + 4], d[8 * i + 5]), pack2(d[8 * i + 6], d[8 * i + 7])));
    if (first.value || CH_GATE != 1) bar_sync(NB_H1, 256); else bar_sync(NB_PUB, 384);
    const uint32_t own = WG == 0 ? vt : kt;
#pragma unroll
    for (int i = 0; i < 2; i++) {
      const uint4 t = lds128(own + i * 2048);
      d[8 * i] = bf_lo(t.x); d[8 * i + 1] = bf_hi(t.x); d[8 * i + 2] = bf_lo(t.y); d[8 * i + 3] = bf_hi(t.y);
      d[8 * i + 4] = bf_lo(t.z); d[8 * i + 5] = bf_hi(t.z); d[8 * i + 6] = bf_lo(t.w); d[8 * i + 7] = bf_hi(t.w);
    }
    reg_fence<16>(d);
    if (!first.value && CH_GATE == 2) bar_sync(NB_PUB, 384);
    batch(d, WG == 0 ? av : ak, 1, WG == 1 && !first.value);
    s--; TM(11); s++;
    if (WG == 0) bar_arrive(NB_XFREE, 256);
#pragma unroll
    for (int i = 0; i < 2; i++) {
      const uint32_t w0 = pack2(d[8 * i], d[8 * i + 1]), w1 = pack2(d[8 * i + 2], d[8 * i + 3]), w2 = pack2(d[8 * i + 4], d[8 * i + 5]), w3 = pack2(d[8 * i + 6], d[8 * i + 7]);
      if (WG == 1) stsm4t(own + i * 2048, w0, w1, w2, w3); else stsm4(own + i * 2048, w0, w1, w2, w3);
    }
    if (CH_PUSH == 0 && WG == 0) {
      if (t4 == 0) {
        bar_sync(NB_H2, 128);
        if (elect()) push_values(sb, s, j);
        __syncwarp();
      } else {
        bar_arrive(NB_H2, 128);
      }
    }
    if (first.value) { mbar_wait(sb + MB_WQ, 0); refill(); mbar_wait(sb + MB_WO, 0); }
  };
  asm volatile("barrier.cluster.wait.aligned;" ::: "memory");
  tokens(0, Int<1>());
  uint32_t wo = opaque(sb + CH_WO + (WG == 0 ? (t4 >> 1) * 36864 : 73728 + t4 * 1024) + ((lane & 7) + (lane >> 4) * 8) * 64 +
                             (((((lane >> 3) & 1) + (WG == 0 ? (t4 & 1) * 2 : 0)) ^ ((lane >> 1) & 3)) << 4));
  const uint32_t kmul = __shfl_sync(~0u, tid & 32 ? -3 : 1, 0), ko0 = __shfl_sync(~0u, (tid >> 6) * 3072 + (tid & 32) * 24, 0),
                 ko1 = __shfl_sync(~0u, (tid >> 6) * 1024 + 1024 + (tid & 32) * 24, 0);
  uint32_t tag = opaque(1);
  const uint32_t o768 = __shfl_sync(~0u, (tid >> 5) * 768, 0);
  bar_sync(NB_ST, 384);
  uint8_t* pdst[WG == 0 ? 6 : 1];
#pragma unroll
  for (int i = 0; i < (WG == 0 ? 6 : 1); i++) {
    const int line = WG == 0 ? 24 * j + 12 * (t4 >> 1) + 2 * (t4 & 1) + 4 * (i >> 1) + (i & 1) : j == 0 ? 72 + t4 : 74 + 2 * j + (t4 & 1);
    pdst[i] = pool_at(__shfl_sync(~0u, lds32(sb + CH_TAB + line * 4), 0) + h * 128);
  }
  auto project = [&](int s, float (&dv)[4], uint4 (&kf)[2]) {
    float dq[4] = {}, dk[4] = {};
    uint32_t b[40], w[80];
#pragma unroll
    for (int i = 0; i < 4 * CH_NQ; i++) w[i] = tw[i];
    bar_sync(NB_MEM, 384);
    ldsm4t(&b[0], l16 + CH_M + WG * 5120);
    ldsm4t(&b[4], l16 + CH_M + WG * 5120 + 512);
    TMD(0, b[0]);
    int nw = CH_NQ, nb = 2;
#pragma unroll
    for (int k = 0; k < 20; k++) {
      SCHED();
      mma16(dq, w[4 * k], w[4 * k + 1], w[4 * k + 2], w[4 * k + 3], b[2 * k], b[2 * k + 1]);
      mma16(dk, ak[4 * k], ak[4 * k + 1], ak[4 * k + 2], ak[4 * k + 3], b[2 * k], b[2 * k + 1]);
      mma16(dv, av[4 * k], av[4 * k + 1], av[4 * k + 2], av[4 * k + 3], b[2 * k], b[2 * k + 1]);
#pragma unroll
      for (int i = 0; i < (CH_DBL >> k & 1) + 1; i++) {
        if (nb < 10 && 2 * nb <= nw) { ldsm4t(&b[4 * nb], l16 + CH_M + WG * 5120 + nb * 512); nb++; }
        else if (nw < 20) { ldsm4t(&w[4 * nw], wq + nw * 2048); nw++; }
        else if (WG == 1 && nw < 22) { kf[nw - 20] = ldsm4v(l16 + ((l16 ^ tag) & 256) * kmul + (nw == 20 ? ko0 : ko1) + CH_K); nw++; }
      }
    }
    const float k2 = 0.07216878364870322f * 1.44269504089f;
    sts32(l4 + t4 * 512 + CH_Q + WG * 128, pack2(dq[0] * k2, dq[1] * k2));
    sts32(l4 + t4 * 512 + CH_Q + WG * 128 + 256, pack2(dq[2] * k2, dq[3] * k2));
    stsm2t(t16 + CH_KM + WG * 256, pack2(dk[0], dk[1]), pack2(dk[2], dk[3]));
    if (WG == 1) sts128f(t16 + CH_VP, dv[0], dv[1], dv[2], dv[3]);
    TM(1);
  };
#pragma unroll 1
  for (int s = 0; s < NSEG - 1; s++) {
    float dv[4] = {};
    uint4 kf[2];
    project(s, dv, kf);
    bar_sync(NB_PROJ, 256);
    if (WG == 0) {
      const float4 pv = lds128f(t16 + CH_VP);
      const uint32_t v0 = pack2(dv[0] + pv.x, dv[1] + pv.y), v1 = pack2(dv[2] + pv.z, dv[3] + pv.w);
      const uint32_t xo = t8 + CH_VX + j * 1024;
      st_async64(mapa(xo, r1), v0, v1, mapa(sb + MB_X, r1));
      st_async64(mapa(xo, r2), v0, v1, mapa(sb + MB_X, r2));
      sts64(xo, v0, v1);
      __syncwarp();
      if (elect()) mbar_arrive(sb + MB_X);
      bar_arrive(NB_PROJ2, 256);
      TM(3);
      uint32_t w[144];
      auto tile_of = [](int n) { return n < 27 ? n % 3 : (0x26484 >> 2 * (n - 27)) & 3; };
      auto step_of = [](int n) { return n < 27 ? n / 3 : 9 + ((0x29610 >> 2 * (n - 27)) & 3); };
      auto wload = [&](int n) { ldsm4t(&w[4 * n], wo + tile_of(n) * 12288 + (step_of(n) % 3) * 4096 + (step_of(n) / 3) * 1024); };
#pragma unroll
      for (int n = 0; n < CH_PA; n++) wload(n);
      bar_sync(NB_PRE, 256);
#pragma unroll
      for (int n = CH_PA; n < CH_PB; n++) wload(n);
      bar_arrive(NB_PRE2, 256);
      if (CH_PC > CH_PB) {
        mbar_wait(sb + MB_X, s & 1);
        for (int i = 0; i < CH_PD; i++) wo = __shfl_xor_sync(~0u, wo, p.zero);
#pragma unroll
        for (int n = CH_PB; n < CH_PC; n++) wload(n);
      }
      TM(4);
      bar_sync(NB_O, 256);
      {
        float x[3][4] = {};
        uint32_t ob[24];
        float4 l;
        ldsm4t(&ob[0], l16 + CH_O);
        ldsm4t(&ob[4], l16 + CH_O + 512);
        TMD(7, ob[0]);
        int nw = CH_PC, no = 2;
        float i0, i1;
        uint8_t* dst[6];
        uint32_t lo[6], hi[6];
        auto pre = [&](int i) { lo[i] = __float_as_uint(x[i >> 1][2 * (i & 1)] * i0) + tag; hi[i] = pack2(0.f, x[i >> 1][2 * (i & 1) + 1] * i1); };
        auto emit = [&](int i) { stg_strong32(dst[i], set_tag(__byte_perm(lo[i], hi[i], 0x7632), tag)); };
#pragma unroll
        for (int n = 0; n < 36; n++) {
          SCHED();
          mma16(x[tile_of(n)], w[4 * n], w[4 * n + 1], w[4 * n + 2], w[4 * n + 3], ob[step_of(n) * 2], ob[step_of(n) * 2 + 1]);
          if (n >= CH_PL) {
            if (no < 6 && no * 2 <= step_of(min(nw, 35))) { ldsm4t(&ob[4 * no], l16 + CH_O + no * 512); no++; }
            else if (nw < 36) { wload(nw); nw++; }
          }
          if (n == 18) l = lds128f(sb + CH_L + ((l16 ^ tag) & 0x30));
          if (n == 26) { i0 = rcp(l.x + l.y); i1 = rcp(l.z + l.w); asm volatile("" : "+f"(i0), "+f"(i1)); }
          if (n >= 28 && n < 34) { dst[n - 28] = pdst[n - 28] + ((l4 ^ tag) & 0x7c); asm volatile("" : "+l"(dst[n - 28])); }
          if (n == 32) { for (int i = 0; i < 2; i++) { pre(i); asm volatile("" : "+r"(lo[i]), "+r"(hi[i])); } }
          if (n == 33) { emit(0); emit(1); }
        }
        for (int i = 2; i < 6; i++) pre(i);
        for (int i = 2; i < 6; i++) emit(i);
      }
      TM(8);
    } else {
      {
        float d0[4] = {}, d1[4] = {}, dm[4] = {};
        uint32_t q[16], km[4];
#pragma unroll
        for (int e = 0; e < 4; e++) {
          ldsm4t(&q[4 * e], l16 + (e ^ t4) * 512 + CH_Q);
          if (e == 1) ldsm4(km, t16 + CH_KM);
        }
        SCHED();
        mma16(d0, q[0], q[1], q[2], q[3], kf[0].x, kf[0].y);
        mma16(d1, q[4], q[5], q[6], q[7], kf[0].z, kf[0].w);
        mma16(dm, q[0], q[1], q[2], q[3], hadd2(km[0], km[2]), hadd2(km[1], km[3]));
        mma16(d0, q[8], q[9], q[10], q[11], kf[1].x, kf[1].y);
        mma16(d1, q[12], q[13], q[14], q[15], kf[1].z, kf[1].w);
        const uint32_t w0 = pack2((d0[0] + d0[2]) + (d1[0] + d1[2]), (d0[1] + d0[3]) + (d1[1] + d1[3])), w1 = pack2(dm[0] + dm[2], dm[1] + dm[3]);
        const uint32_t xo = l4 + t4 * 128, x1 = mapa(xo, r1), x2 = mapa(xo, r2);
        st_async32(x1 + CH_SX + 512, w1, mapa(sb + MB_X, r1));
        st_async32(x2 + CH_SX + 1536, w1, mapa(sb + MB_X, r2));
        st_async32(x1 + CH_SX, w0, mapa(sb + MB_X, r1));
        st_async32(x2 + CH_SX + 1024, w0, mapa(sb + MB_X, r2));
        sts32(xo + CH_SO, w0);
        sts32(xo + CH_SO + 512, w1);
      }
      TM(3);
      float sc[3][4] = {};
      uint32_t wd[12];
      float big;
      auto attend = [&](auto first) {
        uint4 vb[6];
        uint2 vm[3];
        float e[10];
        uint32_t ow[6];
        if (first.value) {
          const uint2 id = lds64(l8 + CH_ID);
          bar_sync(NB_W1V, 160);
          uint32_t r[8];
          ldsm4(r, l16 + CH_SO); ldsm4(r + 4, l16 + CH_SO + 512);
#pragma unroll
          for (int u = 0; u < 6; u++) vb[u] = ldsm4v(t16 + CH_V + u * 2048);
          bar_arrive(NB_PRE, 256);
          uint32_t sxa = l16 + ((l16 ^ tag) & 256) * 3;
          asm volatile("" : "+r"(sxa));
          sxa += CH_SX;
          SCHED();
          mma8(sc[0], r[0], r[1], id.x);
          mma8(sc[1], r[2], r[3], id.x);
          mma16(sc[2], r[4], r[5], r[6], r[7], id.x, id.y);
          TM(7);
          mbar_wait(sb + MB_X, s & 1);
          TM(4);
          uint32_t t[16];
          ldsm4(t, sxa); ldsm4(t + 4, sxa + 256); ldsm4(t + 8, sxa + 512);
          SCHED();
          mma16(sc[0], t[0], t[1], t[2], t[3], id.x, id.y);
          ldsm4(t + 12, sxa + 768);
          SCHED();
          mma16(sc[1], t[4], t[5], t[6], t[7], id.x, id.y);
#pragma unroll
          for (int u = 0; u < 2; u++) vm[u] = lds64(t8 + CH_VX + u * 1024);
          SCHED();
          e[0] = ex2(sc[0][0]);
          mma16(sc[2], t[8], t[9], t[10], t[11], id.x, id.y);
          vm[2] = lds64(t8 + CH_VX + 2048);
          SCHED();
          e[1] = ex2(sc[0][1]);
          ldsm4t(&wd[0], wo);
          SCHED();
          e[2] = ex2(sc[0][2]);
          SCHED();
          e[3] = ex2(sc[0][3]);
          mma16(sc[2], t[12], t[13], t[14], t[15], id.x, id.y);
          SCHED();
          e[4] = ex2(sc[1][0]);
          ldsm4t(&wd[4], wo + 4096);
          SCHED();
          e[5] = ex2(sc[1][1]);
        } else {
#pragma unroll
          for (int u = 0; u < 6; u++) vb[u] = ldsm4v(t16 + CH_V + u * 2048);
#pragma unroll
          for (int u = 0; u < 3; u++) vm[u] = lds64(t8 + CH_VX + u * 1024);
        }
        float o[3][4] = {};
        if (!first.value) {
#pragma unroll
          for (int i = 0; i < 6; i++) e[i] = ex2(sc[i >> 2][i & 3]);
        }
        const uint32_t p1 = pack2(e[0], e[1]), p2 = pack2(e[2], e[3]);
        float l = (e[0] + e[1]) + (e[2] + e[3]);
        asm volatile("" : "+f"(l));
        SCHED();
        e[6] = ex2(sc[1][2]);
        mma16(o[0], vb[0].x, vb[0].y, vb[0].z, vb[0].w, p1, p2);
        if (first.value) { sc[2][0] += sc[2][2]; sc[2][1] += sc[2][3]; }
        SCHED();
        e[7] = ex2(sc[1][3]);
        mma16(o[1], vb[2].x, vb[2].y, vb[2].z, vb[2].w, p1, p2);
        SCHED();
        e[8] = ex2(sc[2][0]);
        mma16(o[2], vb[4].x, vb[4].y, vb[4].z, vb[4].w, p1, p2);
        big = fmaxf(fmaxf(fmaxf(fabsf(sc[0][0]), fabsf(sc[0][1])), fmaxf(fabsf(sc[0][2]), fabsf(sc[0][3]))), fmaxf(fabsf(sc[2][0]), fabsf(sc[2][1])));
        SCHED();
        e[9] = ex2(sc[2][1]);
        const uint32_t p3 = pack2(e[4], e[5]), p4 = pack2(e[6], e[7]);
        l += (e[4] + e[5]) + (e[6] + e[7]);
#pragma unroll
        for (int u = 0; u < 3; u++) mma16(o[u], vb[2 * u + 1].x, vb[2 * u + 1].y, vb[2 * u + 1].z, vb[2 * u + 1].w, p3, p4);
        big = fmaxf(big, fmaxf(fmaxf(fabsf(sc[1][0]), fabsf(sc[1][1])), fmaxf(fabsf(sc[1][2]), fabsf(sc[1][3]))));
        SCHED();
        const uint32_t p0 = pack2(e[8], e[9]);
        l += e[8] + e[9];
        l += __shfl_xor_sync(~0u, l, 1);
        if (first.value) ldsm4t(&wd[8], wo + 8192);
#pragma unroll
        for (int u = 0; u < 3; u++) mma8(o[u], vm[u].x, vm[u].y, p0);
        SCHED();
#pragma unroll
        for (int u = 0; u < 3; u++) { ow[2 * u] = pack2(o[u][0], o[u][1]); ow[2 * u + 1] = pack2(o[u][2], o[u][3]); }
        stsm4(l16 + o768 + CH_O, ow[0], ow[1], ow[2], ow[3]);
        stsm2(l16 + o768 + CH_O + 512, ow[4], ow[5]);
        if (t4 == 0) sts32(sb + CH_L + (((l4 ^ tag) >> 1) & 0x3c), __float_as_uint(l));
      };
      attend(Int<1>());
      const uint32_t redo = __any_sync(~0u, big > 30.f);
      TM(6);
      asm volatile("{.reg .pred p; setp.eq.u32 p, %0, 0; @p bar.arrive 2, 256;}" :: "r"(redo) : "memory");
      if (redo) {
        float mx = fmaxf(sc[2][0], sc[2][1]);
#pragma unroll
        for (int i = 0; i < 4; i++) mx = fmaxf(mx, fmaxf(sc[0][i], sc[1][i]));
        mx = fmaxf(mx, __shfl_xor_sync(~0u, mx, 1));
        mx = fmaxf(mx, __shfl_xor_sync(~0u, mx, 2));
#pragma unroll
        for (int i = 0; i < 4; i++) { sc[0][i] -= mx; sc[1][i] -= mx; }
        sc[2][0] -= mx; sc[2][1] -= mx;
        attend(Int<0>());
        bar_arrive(NB_O, 256);
      }
      {
        float z[4] = {};
        const uint32_t scr = l8 + CH_V + r1 * 4096;
        uint32_t ow[6];
        __syncwarp();
        uint32_t oa = l16;
        for (int i = 0; i < CH_ZD; i++) oa = __shfl_xor_sync(~0u, oa, p.zero);
        ldsm4t(ow, oa + o768 + CH_O);
        ldsm2t(ow + 4, oa + o768 + CH_O + 512);
#pragma unroll
        for (int u = 0; u < 3; u++) mma16(z, wd[4 * u], wd[4 * u + 1], wd[4 * u + 2], wd[4 * u + 3], ow[2 * u], ow[2 * u + 1]);
        if (j == 0) {
          float y[4] = {};
          uint32_t we[12];
#pragma unroll
          for (int u = 0; u < 3; u++) ldsm4t(&we[4 * u], (wo ^ 32) + u * 4096);
#pragma unroll
          for (int u = 0; u < 3; u++) mma16(y, we[4 * u], we[4 * u + 1], we[4 * u + 2], we[4 * u + 3], ow[2 * u], ow[2 * u + 1]);
          sts64f(scr + t4 * 512 + 2048, y[0], y[1]); sts64f(scr + t4 * 512 + 2304, y[2], y[3]);
        }
        sts64f(scr + t4 * 512, z[0], z[1]); sts64f(scr + t4 * 512 + 256, z[2], z[3]);
        bar_sync(NB_W1, 128);
        if (j == 0 || t4 < 2) {
          float2 q[4];
          const float4 l = lds128f(sb + CH_L + ((l16 ^ tag) & 0x30));
#pragma unroll
          for (int i = 0; i < 4; i++) q[i] = lds64f(scr + (t4 >> 1) * 2048 + (t4 & 1) * 256 + i * 512);
          stg_strong32(pdst[0] + ((l4 ^ tag) & 0x7c), pack_tag(((q[0].x + q[1].x) + (q[2].x + q[3].x)) * rcp(l.x + l.y), ((q[0].y + q[1].y) + (q[2].y + q[3].y)) * rcp(l.z + l.w), tag));
        }
      }
      TM(2);
    }
    bar_sync(NB_ST, 384);
    tokens(s + 1, Int<0>());
    TM(9);
    tag ^= 0x10001;
  }
  {
    float dv[4] = {};
    uint4 kf[2];
    project(NSEG - 1, dv, kf);
    bar_sync(NB_PROJ, 256);
    if (WG == 0) {
      const float4 pv = lds128f(t16 + CH_VP);
      sts64(t8 + CH_VX + j * 1024, pack2(dv[0] + pv.x, dv[1] + pv.y), pack2(dv[2] + pv.z, dv[3] + pv.w));
      bar_arrive(NB_PROJ2, 256);
      bar_arrive(NB_PRE2, 256);
    }
  }
}

__device__ __forceinline__ void chain_comm(const ChainParams& p, const uint32_t sb) {
  [[maybe_unused]] constexpr int WG = 2;
  const int tid = threadIdx.x & 127, t4 = __shfl_sync(~0u, tid >> 5, 0), lane = tid & 31;
  const int cta = blockIdx.x, h = cta / 3, j = cta - 3 * h, colbase = cta * 64;
  const uint8_t* const xs = reinterpret_cast<const uint8_t*>(g_xn);
  auto xload = [&](int seg, int i, int off, int bytes) { bulk_load(sb + CH_X + i * 5120 + off, xs + (seg * 4 + (i & 3)) * 10240 + (i >> 2) * 5120 + off, bytes, sb + MB_T); };
  if (cta == 0) for (int i = tid; i < SY_N; i += 128) p.other[i] = 0;
  uint32_t smid; asm("mov.u32 %0, %%smid;" : "=r"(smid));
  const uint32_t part = max(ldg_strong32(g_smpart + (smid & 255)), 1u);
  if (tid == 64) stg_strong32(p.sync + SY_PART + cta, part);
  PRO(0);
  if (t4 == 3) {
    bar_arrive(NB_PROJ2, 384);
    bar_arrive(NB_PRE2, 384);
    if (elect()) {
      wait_count(p.sync + SY_P + 1, ln_items(p.layer, 0));
      fence_async_global();
      mbar_expect(sb + MB_T, 40960);
      for (int i = 0; i < 8; i++) xload(0, i, 0, 5120);
    }
    __syncwarp();
  } else {
  bar_sync(NB_PROJ2, 384);
  __syncwarp();
  PRO(1);
  if (t4 == 0 && elect()) {
    mbar_expect(sb + MB_WQ, 81920);
    for (int i = 0; i < 5; i++) tma_load(sb + CH_WQ + i * 16384, &p.wq, colbase, i * 128, sb + MB_WQ);
  }
  bar_sync(NB_PRE2, 384);
  __syncwarp();
  PRO(2);
  if (t4 == 0 && elect()) {
    mbar_expect(sb + MB_WO, 86016);
    for (int i = 0; i < 6; i++) tma_load(sb + CH_WO + i * 12288, &p.wo, j * 192 + i * 32, h * 192, sb + MB_WO);
    tma_load(sb + CH_WO + 73728, &p.wo, j == 0 ? 576 : 592 + j * 16, h * 192, sb + MB_WO);
  }
  }
  if (tid < NSLOT) {
    const uint32_t* part_of = p.sync + SY_PART + (tid >= 80 ? cta : tid);
    uint32_t reader = 0, orient = 0;
    int n = 0;
    while (reader == 0 || orient == 0) { reader = ldg_strong32(part_of); orient = ldg_strong32(g_orient + tid); spin_guard(n); }
    sts32(sb + CH_TAB + tid * 4, tid * 8192 + (orient == reader ? 0 : 4096));
    if (t4 == 0) {
      const uint32_t near = __ballot_sync(~0u, reader == part) & 0xffffff;
      if (lane == 0) sts32(sb + CH_TAB + NSLOT * 4, cta < 80 ? cta : near ? __fns(near, 0, 1 + cta % __popc(near)) : 0);
    }
  }
  __syncwarp();
  asm volatile("barrier.cluster.wait.aligned;" ::: "memory");
  const uint32_t l8 = opaque(sb + t4 * 256 + lane * 8);
  {
    const uint32_t* m0 = reinterpret_cast<const uint32_t*>(p.mem0) + (lane >> 2) * (DM / 2) + t4 * 80 + (lane & 3);
    uint32_t g[20];
#pragma unroll
    for (int i = 0; i < 20; i++) g[i] = transpose8(m0[i * 4]);
    const uint32_t id = (lane >> 3) == (lane & 3) ? ((lane & 4) ? 0x3f800000u : 0x00003f80u) : 0u;
    if (t4 == 0) sts64(l8 + CH_ID, id, id);
    bar_sync(NB_XFREE, 256);
#pragma unroll
    for (int i = 0; i < 20; i++) sts32(sb + CH_M + (t4 * 20 + i) * 128 + lane * 4, g[i]);
  }
  bar_sync(NB_ST, 384);
  uint8_t* const pool = pool_at(0);
  const uint8_t* const psrc = pool + opaque(lds32(sb + CH_TAB + lds32(sb + CH_TAB + NSLOT * 4) * 4) + t4 * 1024 + lane * 4);
  const uint32_t mdst = opaque((80 + cta / 20) * 8192 + (t4 & 1) * 4096 + (cta % 20) * 128 + lane * 4);
  int st = 0;
  uint32_t tag = opaque(1);
  bar_sync(NB_MEM, 384);
#pragma unroll 1
  for (int s = 0;; s++) {
    TM(0);
    STAT(0);
    if (t4 == 0) {
      if (elect()) {
        if (CH_PUSH == 1) push_values(sb, s, j);
        fence_async();
        uint8_t* dst = g_kv + ((s >> 2) * 96 + cta) * KV_BYTES + (s & 3) * 4096;
        (HINT & 8 ? bulk_store_stream : bulk_store)(dst + KV_K, sb + CH_K, 4096);
        (HINT & 8 ? bulk_store_stream : bulk_store)(dst + KV_V, sb + CH_V + j * 4096, 4096);
        bulk_commit();
        bulk_wait_read<0>();
      }
      __syncwarp();
    }
    if (t4 == 3 && (s & 3) == 2 && s < NSEG - 2) wait_count_uniform(p.sync + SY_P + 5 + (s & ~3), ln_items(p.layer, (s >> 2) + 1));
    if (t4 == 2 && s < NSEG - 1) { mbar_wait(sb + MB_V, s & 1); bar_arrive(NB_W1V, 160); }
    bar_sync(NB_PROJ2, 256);
    if (t4 == 0 && s < NSEG - 1 && elect()) {
      mbar_expect(sb + MB_X, 4096);
      mbar_expect(sb + MB_T, 40960);
#pragma unroll
      for (int i = 0; i < 7; i++) xload(s + 1, i, 0, i < 6 ? 5120 : 4096);
    }
    __syncwarp();
    STAT(1);
    TM(1);
    {
      const uint2 a = lds64(l8 + t4 * 256 + CH_KM), b = lds64(l8 + t4 * 256 + CH_KM + 256);
      sts64(l8 + CH_KS, hadd2(a.x, b.x), hadd2(a.y, b.y));
    }
    TM(4);
    bar_sync(NB_PRE2, 256);
    if (t4 == 0 && elect()) {
      if (s < NSEG - 1) { xload(s + 1, 6, 4096, 1024); xload(s + 1, 7, 0, 5120); }
      fence_async();
      uint8_t* dst = g_kv + ((s >> 2) * 96 + cta) * KV_BYTES + (s & 3) * 1024;
      bulk_store(dst + KV_KM, sb + CH_KS, 1024);
      bulk_store(dst + KV_VM, sb + CH_VX + j * 1024, 1024);
      bulk_commit();
      bulk_wait<0>();
      if ((s & 3) == 3) { fence_async_global(); atomicAdd(p.sync + (s >> 2) * 8 + 4, 1); }
    }
    __syncwarp();
    if (s == NSEG - 1) break;
    if (s == NSEG - 3 && cta == 95 && t4 == 2 && elect()) atomicAdd(p.sync + 15 * 8 + 4, 0x10000);
    __syncwarp();
    const uint8_t* ms = pool + (lds32(sb + CH_TAB + (80 + st * 4 + t4) * 4) + (l8 & 255));
    uint8_t* md = pool + (mdst + (t4 < 2 ? st : st == 2 ? 0 : st + 1) * 32768);
    asm volatile("" : "+l"(ms), "+l"(md));
    TM(2);
    bar_sync(NB_ST, 384);
    __syncwarp();
    uint32_t tg = clk32();
    if (t4 == 3 && elect()) {
      if (s < NSEG - 2) mbar_expect(sb + MB_V, 8192);
      mbar_arrive_remote(mapa(sb + MB_F, j == 2 ? 0 : j + 1));
      mbar_arrive_remote(mapa(sb + MB_F, j == 0 ? 2 : j - 1));
    }
    __syncwarp();
    STAT(2);
    {
      float2 q[4];
      uint32_t u[2][8];
      auto poll = [&](uint32_t (&v)[8], uint32_t flip) {
        const uint8_t* src = psrc + flip;
#pragma unroll
        for (int i = 0; i < 8; i++) v[i] = ldg_strong32(src + i * 128);
      };
      auto sum = [&](uint32_t (&v)[8]) {
        sts64f(l8 + CH_R2, ((bf_lo(v[0]) + bf_lo(v[1])) + (bf_lo(v[2]) + bf_lo(v[3]))) + ((bf_lo(v[4]) + bf_lo(v[5])) + (bf_lo(v[6]) + bf_lo(v[7]))),
               ((bf_hi(v[0]) + bf_hi(v[1])) + (bf_hi(v[2]) + bf_hi(v[3]))) + ((bf_hi(v[4]) + bf_hi(v[5])) + (bf_hi(v[6]) + bf_hi(v[7]))));
        uint32_t bad;
        asm volatile("{.reg .pred p, q; .reg .b32 a; lop3.b32 a, %1, %2, %3, 0xFE; lop3.b32 a, a, %4, 1, 0xA8; setp.ne.u32 p, a, 0;\n"
                     "bar.red.or.pred q, %5, 128, p; selp.u32 %0, 1, 0, q;}"
                     : "=r"(bad) : "r"(differ(v[0], v[1], tag)), "r"(differ(v[2], v[3], tag)), "r"(differ(v[4], v[5], tag)), "r"(differ(v[6], v[7], tag)), "n"((int)NB_W2) : "memory");
#pragma unroll
        for (int k = 0; k < 4; k++) asm volatile("ld.volatile.shared.v2.f32 {%0,%1}, [%2];" : "=f"(q[k].x), "=f"(q[k].y) : "r"(l8 - t4 * 256 + CH_R2 + k * 256) : "memory");
        return bad;
      };
      TM(3);
      until(tg + p.d1);
      poll(u[0], 0);
      SCHED();
      uint32_t lag = l8;
#pragma unroll
      for (int i = 0; i < CH_LAG; i++) asm volatile("mul.lo.u32 %0, %0, %1;" : "+r"(lag) : "r"(p.zero));
      if (CH_LAG) poll(u[1], lag);
      SCHED();
      if (sum(u[0])) {
        poll(u[0], CH_LAG ? u[1][7] & p.zero : 0);
        SCHED();
        if (!CH_LAG || sum(u[1])) {
          for (int n = 0; sum(u[0]) && (cta < 80 || n < 2); spin_guard(n)) poll(u[0], 0);
        }
      }
      if (CH_GATE) bar_arrive(NB_PUB, 384);
      SCHED();
      TM(9);
      if (cta < 80) stg_strong32(md, min(nz(pack2((q[0].x + q[1].x) + (q[2].x + q[3].x), (q[0].y + q[1].y) + (q[2].y + q[3].y))), t4 < 2 ? ~0u : 0u));
      tg = clk64() + p.d2;
      TM(8);
    }
    STAT(3);
    until(tg);
    TM(10);
    for (int n = 0;;) {
      uint2 g[10];
#pragma unroll
      for (int i = 0; i < 10; i++) g[i] = ldg_strong64(ms + i * 256);
      if (n == 0) bar_sync(NB_XFREE, 256);
      spin_guard(n);
      uint32_t m = ~0u;
#pragma unroll
      for (int i = 0; i < 10; i++) { sts64(l8 + CH_M + t4 * 2304 + i * 256, g[i].x, g[i].y); m = __vimin3_u32(m, g[i].x, g[i].y); }
      TMV(13, n - 1);
      if (!__any_sync(~0u, m == 0)) break;
    }
    TM(11);
    if (t4 == 0) bar_sync(NB_MEM, 384); else bar_arrive(NB_MEM, 384);
    if (++st == 3) st = 0;
    tag ^= 0x10001;
  }
  TRACE(2);
}

#define CH_R0 232
#define CH_R1 232
#define CH_R2N 40
__global__ void __launch_bounds__(384, 1) chain_kernel(const __grid_constant__ ChainParams p) {
  extern __shared__ __align__(1024) uint8_t smem_raw[];
  const uint32_t sb = s2u(smem_raw);
  const int wg = __shfl_sync(~0u, threadIdx.x >> 7, 0);
  if (threadIdx.x < 32 && elect()) {
    atomicAdd(p.sync + SY_UP, 1);
    if ((sb & 0xffffff) != 1024) __trap();
    mbar_init(sb + MB_WO, 1); mbar_init(sb + MB_WQ, 1); mbar_init(sb + MB_X, 5); mbar_init(sb + MB_V, 1); mbar_init(sb + MB_T, 1); mbar_init(sb + MB_F, 2); mbar_init(sb + MB_G, 2);
    for (int i = 0; i < 10; i++) mbar_init(sb + MB_W + 8 * i, 1);
    asm volatile("fence.mbarrier_init.release.cluster;" ::: "memory");
    mbar_expect(sb + MB_V, 8192);
    for (int i = 0; i < 10; i++) {
      const int n = i % 5 < 2 ? (i % 5) * 2 : i % 5 == 2 ? 1 : i % 5;
      const uint32_t bar = sb + MB_W + 8 * (n + (i < 5 ? 0 : 5));
      mbar_expect(bar, 16384);
      tma_load(sb + (i < 5 ? CH_WQ : CH_WO) + n * 16384, i < 5 ? &p.wk : &p.wv, blockIdx.x * 64, n * 128, bar);
    }
  }
  __syncthreads();
  asm volatile("barrier.cluster.arrive.relaxed.aligned;" ::: "memory");
  pdl_launch();
  if (wg == 2) {
    asm volatile("setmaxnreg.dec.sync.aligned.u32 %0;" :: "n"(CH_R2N));
    chain_comm(p, sb);
  } else if (wg == 0) {
    asm volatile("setmaxnreg.inc.sync.aligned.u32 %0;" :: "n"(CH_R0));
    chain_compute<0>(p, sb);
  } else {
    asm volatile("setmaxnreg.inc.sync.aligned.u32 %0;" :: "n"(CH_R1));
    chain_compute<1>(p, sb);
  }
}

struct WorkParams {
  CUtensorMap wq, wo, wb, wc, out, xn, xp;
  const __nv_bfloat16* x;
  uint32_t* sync;
  int kind, qa_end, idle;
};
#define GO_320 4
#define GO_192 6
enum { WK_FIRST = 0, WK_LEAD = 1, WK_JOIN = 2, WK_LAST = 3 };
constexpr int WK_SLOTS = 28, WK_BAR = WK_SLOTS * 8192, WK_SMEM = WK_BAR + 384 + 2048;
enum { IT_ATT = 0, IT_OP = 1, IT_FIN = 2, IT_BQ = 3, IT_BO = 4, IT_LN = 5, IT_Q = 6, IT_LN0 = 7, IT_OUT = 8 };
constexpr int C_EARLY = 1 << 20, C_LATE = 1 << 21, C_FREE = 1 << 22;

__device__ __forceinline__ uint32_t item_count(int type, int b) { return type == IT_ATT ? 32 : type == IT_OP ? op_tiles(b) * op_split(b) : type == IT_FIN ? fin_items(b) : bq_items(b); }
__device__ __forceinline__ uint32_t item_need(int type, int b) { return type == IT_ATT ? 96 : item_count(type - 1, b); }
__device__ __forceinline__ int item_cols(int type, int b) {
  return type == IT_ATT || type == IT_Q ? 192 : type == IT_OUT ? 80 : type == IT_BQ ? (b < BQ_12 ? 320 : b < BQ_24 ? 160 : 80) : type == IT_OP && b >= OP_N4 ? 160 : 320; }
__device__ __forceinline__ int item_groups(int type, int b) { return 16 / (type == IT_FIN ? fin_items(b) : ln_items(type == IT_LN, b)); }
#define RES_OP 15
constexpr int RES_N = (RES_OP < 15 ? op_tiles(14) * op_split(14) : 0) + op_tiles(15) * op_split(15), RES_BQ = (94 - RES_N) / 6;
__device__ __forceinline__ bool reserved(int type, int b) { return type == IT_OP ? b >= RES_OP : type == IT_BQ && b < RES_BQ; }
__device__ __forceinline__ int reserved_item(int i) {
  constexpr int n15 = op_tiles(15) * op_split(15);
  if (i < RES_BQ * 6) return C_FREE | IT_BQ << 16 | (i / 6) << 8 | i % 6;
  i -= RES_BQ * 6;
  return i < n15 ? C_FREE | IT_OP << 16 | 15 << 8 | i : i < RES_N ? C_FREE | IT_OP << 16 | 14 << 8 | (i - n15) : -1;
}
constexpr int LEAD1 = 12;
__device__ __forceinline__ int lead_item(int layer, int qa_end, int i) {
  if (layer == 2) return i < 128 ? C_EARLY | C_LATE | IT_OUT << 16 | (i >> 3) << 8 | (i & 7) : -1;
  if (layer == 0) {
    if (i < 32) return IT_LN0 << 16 | (i >> 4) << 8 | (i & 15);
    if (i < 88) return IT_LN0 << 16 | ((i - 24) >> 2) << 8 | (i & 3);
    i -= 88;
  } else {
    if (i < 4) return C_EARLY | IT_BO << 16 | (i >> 1) << 8 | (i & 1);
    if (i < 12) return C_EARLY | IT_LN << 16 | ((i - 4) >> 2) << 8 | (i & 3);
    if (i < 40) return C_EARLY | IT_BO << 16 | ((i - 8) >> 1) << 8 | (i & 1);
    if (i < 96) return C_EARLY | IT_LN << 16 | ((i - 32) >> 2) << 8 | (i & 3);
    i -= 96;
  }
  return i < (16 - qa_end) * 32 ? C_EARLY | IT_Q << 16 | (qa_end + (i >> 5)) << 8 | (i & 31) : -1;
}

struct Ring {
  uint32_t sb;
  int pos, seq;
  __device__ __forceinline__ uint32_t full() const { return sb + WK_BAR + 8 * (seq & 7); }
  __device__ __forceinline__ uint32_t take(int len) { if (pos + len > WK_SLOTS) pos = 0; pos += len; seq++; return sb + (pos - len) * 8192; }
  __device__ __forceinline__ uint32_t wait(int len) { mbar_wait_uniform(full(), (seq >> 3) & 1); return take(len); }
  __device__ __forceinline__ void release(int sq) const { if (elect()) mbar_arrive(sb + WK_BAR + 64 + 8 * (sq & 7)); }
};

struct Pending {
  uint32_t w[48], done;
  uint4* dst;
  __device__ __forceinline__ void store(int i) const { dst[(i >> 2) * 1024 + (i & 3) * 32] = make_uint4(w[4 * i], w[4 * i + 1], w[4 * i + 2], w[4 * i + 3]); }
  __device__ __forceinline__ void finish() { __syncwarp(); if (elect()) mbar_arrive(done); done = 0; }
  __device__ __forceinline__ void flush() {
    if (done) {
#pragma unroll
      for (int i = 0; i < 12; i++) store(i);
      finish();
    }
  }
};

template <int N>
__device__ __forceinline__ void gemm_item(float* d, Ring& r, int nkb, uint32_t go, Pending& pend) {
  const int warp = __shfl_sync(~0u, threadIdx.x >> 5, 0), wg = warp >> 2;
#pragma unroll 1
  for (int kb = 0; kb < nkb; kb++) {
    const uint32_t base = r.wait(2 + (N + 63) / 64);
    const uint64_t da = mkdesc(base + wg * 8192, 128, 1024, 0), db = mkdesc(base + 16384, 8192, 1024, 1);
    wg_fence();
#pragma unroll
    for (int kk = 0; kk < 4; kk++) {
      if (N == 80) wg_ss80_01(d, da + kk * 16, db + kk * 128, (kb | kk) != 0);
      else if (N == 160) wg_ss160_01(d, da + kk * 16, db + kk * 128, (kb | kk) != 0);
      else wg_ss192_01(d, da + kk * 16, db + kk * 128, (kb | kk) != 0);
      if (N == 320) wg_ss128_01(d + 96, da + kk * 16, db + kk * 128 + 3 * 512, (kb | kk) != 0);
    }
    wg_commit();
    if (kb == max(nkb - (N == 320 ? GO_320 : GO_192), 0) && go && warp == 0 && elect()) mbar_arrive(go);
    if (N == 192 && pend.done) {
#pragma unroll
      for (int i = 0; i < 12; i++) if (kb == i / 2) pend.store(i);
      if (kb == 5) pend.finish();
    }
    if (kb > 0) { wg_wait<1>(); r.release(r.seq - 2); }
  }
  wg_wait<0>();
  reg_fence<N / 2>(d);
  r.release(r.seq - 1);
}

template <int HALF>
__device__ __forceinline__ void attn_a_warp(Ring& r, Pending& pend, bool now) {
  uint32_t (&q)[48] = pend.w;
  constexpr int NT = HALF ? 5 : 3, NF = 8 * NT;
  const int lane = threadIdx.x & 31, g = lane >> 2, c = lane & 3, seg = (threadIdx.x >> 5) & 3;
  float sc[NT][4] = {};
  uint32_t base, f[2][NF];
  auto load_k = [&](int u) {
    base = u & 1 ? base + 20480 : r.wait(5) + seg * 1024;
#pragma unroll
    for (int kk = 0; kk < 4; kk++) {
      if (!(kk & 1)) ldsm4(&f[u & 1][2 * kk], base + KV_KM + kk * 256 + lane * 16);
#pragma unroll
      for (int t = 0; t <= HALF; t++) ldsm4(&f[u & 1][8 + 16 * t + 4 * kk], base + seg * 3072 + t * 2048 + kk * 512 + lane * 16);
    }
  };
  auto load_v = [&](int u) {
    base = u & 1 ? r.wait(5) + seg * 1024 : base + 20480;
#pragma unroll
    for (int n = 0; n < 4; n++) {
      const uint2 vm = lds64(base + KV_KM + n * 256 + lane * 8);
      f[~u & 1][2 * n] = vm.x; f[~u & 1][2 * n + 1] = vm.y;
#pragma unroll
      for (int t = 0; t <= HALF; t++)
        ldsm4(&f[~u & 1][8 + 16 * t + 4 * n], base + seg * 3072 + t * 2048 + n * 512 + (lane & 8) * 32 + (lane & 16) * 8 + (lane & 7) * 16);
    }
  };
  load_k(0);
#pragma unroll
  for (int u = 0; u < 3; u++) {
    if (u < 2) load_k(u + 1); else { r.release(r.seq - 2); load_v(0); }
    SCHED();
#pragma unroll
    for (int kk = 0; kk < 4; kk++) {
      const uint32_t *a = &q[16 * u + 4 * kk], *b = f[u & 1];
      mma16(sc[0], a[0], a[1], a[2], a[3], b[2 * kk], b[2 * kk + 1]);
#pragma unroll
      for (int n = 0; n < NT - 1; n++) mma16(sc[1 + n], a[0], a[1], a[2], a[3], b[8 + 16 * (n >> 1) + 4 * kk + 2 * (n & 1)], b[9 + 16 * (n >> 1) + 4 * kk + 2 * (n & 1)]);
    }
    SCHED();
  }
  load_v(1);
  SCHED();
  const float k2 = 0.07216878364870322f * 1.44269504089f, NEG = -INFINITY;
  if (2 * c > g) { sc[NT - 2][0] = NEG; sc[NT - 1][2] = NEG; }
  if (2 * c + 1 > g) { sc[NT - 2][1] = NEG; sc[NT - 1][3] = NEG; }
  sc[NT - 1][0] = sc[NT - 1][1] = NEG;
  uint32_t pp[NT][2]; float inv[2];
#pragma unroll
  for (int hh = 0; hh < 2; hh++) {
    float m = NEG, l = 0.f;
#pragma unroll
    for (int n = 0; n < NT; n++) m = fmaxf(m, fmaxf(sc[n][2 * hh], sc[n][2 * hh + 1]));
    m = fmaxf(m, __shfl_xor_sync(~0u, m, 1)); m = fmaxf(m, __shfl_xor_sync(~0u, m, 2));
#pragma unroll
    for (int n = 0; n < NT; n++) { const float x = ex2((sc[n][2 * hh] - m) * k2), y = ex2((sc[n][2 * hh + 1] - m) * k2); l += x + y; pp[n][hh] = pack2(x, y); }
    l += __shfl_xor_sync(~0u, l, 1); l += __shfl_xor_sync(~0u, l, 2);
    inv[hh] = rcp(l);
  }
#pragma unroll
  for (int u = 0; u < 3; u++) {
    float o[8][4] = {};
    const uint32_t* b = f[~u & 1];
#pragma unroll
    for (int n = 0; n < 8; n++) mma8(o[n], pp[0][0], pp[0][1], b[n]);
#pragma unroll
    for (int t = 0; t <= HALF; t++)
#pragma unroll
      for (int n = 0; n < 8; n++) mma16(o[n], pp[1 + 2 * t][0], pp[1 + 2 * t][1], pp[2 + 2 * t][0], pp[2 + 2 * t][1], b[8 + 16 * t + 2 * n], b[9 + 16 * t + 2 * n]);
    SCHED();
    if (u != 1) r.release(r.seq - 2 + u / 2);
    if (u == 0) { load_v(2); SCHED(); }
#pragma unroll
    for (int i = 0; i < 16; i++) q[16 * u + i] = pack2(o[i & 7][i >> 2 & 2] * inv[i >> 3], o[i & 7][(i >> 2 & 2) + 1] * inv[i >> 3]);
    if (now) {
#pragma unroll
      for (int i = 0; i < 4; i++) pend.store(4 * u + i);
    }
  }
}

template <int G>
__device__ __forceinline__ void ln_groups(Ring& ring, uint32_t scratch, bool input, int planes, int rg) {
  const int warp = threadIdx.x >> 5, lane = threadIdx.x & 31;
  const uint32_t id = (lane >> 3) == (lane & 3) ? ((lane & 4) ? 0x3f800000u : 0x00003f80u) : 0u;
  float v[G][5][4] = {};
#pragma unroll
  for (int r = 0; r < G; r++) {
    if (input) {
      const uint32_t a = ring.wait(2) + (lane >> 2) * 1280 + warp * 160 + (lane & 3) * 4;
#pragma unroll
      for (int i = 0; i < 5; i++) mma8(v[r][i], lds32(a + i * 32), lds32(a + i * 32 + 16), id);
      ring.release(ring.seq - 1);
    } else {
#pragma unroll 1
      for (int k = planes; k > 0; k -= 4) {
        const uint32_t a = ring.wait(min(k, 4) + 1) + (warp * 160 + lane) * 8;
        if (k == 1) {
#pragma unroll
          for (int i = 0; i < 5; i++) { const uint2 x = lds64(a + i * 256); mma8(v[r][i], x.x, x.y, id); }
        } else {
#pragma unroll
          for (int i = 0; i < 10; i++) {
            if (i == 5 && k < 4) break;
            const uint2 x = lds64(a + i / 5 * 20480 + i % 5 * 256), y = lds64(a + i / 5 * 20480 + 10240 + i % 5 * 256);
            mma16(v[r][i % 5], x.x, x.y, y.x, y.y, id, id);
          }
        }
        ring.release(ring.seq - 1);
      }
    }
  }
  uint2 xr[G][5];
  scratch += (lane >> 2) * 64;
#pragma unroll
  for (int r = 0; r < G; r++) {
    float m = 0.f, q = 0.f;
#pragma unroll
    for (int i = 0; i < 5; i++) {
      float* t = v[r][i];
      xr[r][i] = make_uint2(pack2(t[0], t[1]), pack2(t[2], t[3]));
      t[0] = bf_lo(xr[r][i].x); t[1] = bf_hi(xr[r][i].x); t[2] = bf_lo(xr[r][i].y); t[3] = bf_hi(xr[r][i].y);
      m += (t[0] + t[1]) + (t[2] + t[3]);
    }
    m += __shfl_xor_sync(~0u, m, 1); m += __shfl_xor_sync(~0u, m, 2);
    m *= 1.f / 80;
#pragma unroll
    for (int i = 0; i < 5; i++) { const float a = v[r][i][0] - m, b = v[r][i][1] - m, c = v[r][i][2] - m, d = v[r][i][3] - m; q += (a * a + b * b) + (c * c + d * d); }
    q += __shfl_xor_sync(~0u, q, 1); q += __shfl_xor_sync(~0u, q, 2);
    if ((lane & 3) == 0) sts64f(scratch + r * 512 + warp * 8, m, q);
  }
  bar_sync(1, 256);
#pragma unroll
  for (int r = 0; r < G; r++) {
    const float4 t = lds128f(scratch + r * 512 + (lane & 3) * 16);
    float mean = t.x + t.z;
    mean += __shfl_xor_sync(~0u, mean, 1); mean += __shfl_xor_sync(~0u, mean, 2);
    mean *= 0.125f;
    float var = (t.y + t.w) + 80.f * ((t.x - mean) * (t.x - mean) + (t.z - mean) * (t.z - mean));
    var += __shfl_xor_sync(~0u, var, 1); var += __shfl_xor_sync(~0u, var, 2);
    const float rs = rsqrtf(var * (1.f / DM) + 1e-5f);
#pragma unroll
    for (int i = 0; i < 20; i++) v[r][i >> 2][i & 3] = (v[r][i >> 2][i & 3] - mean) * rs;
  }
#pragma unroll
  for (int r = 0; r < G; r++) {
    uint32_t* xn = g_xn + (rg + r) * 2560 + warp * 320 + lane;
#pragma unroll
    for (int i = 0; i < 10; i++) xn[i * 32] = pack2(v[r][i >> 1][2 * (i & 1)], v[r][i >> 1][2 * (i & 1) + 1]);
#pragma unroll
    for (int i = 0; i < 5; i++) g_x[(rg + r) * 1280 + warp * 160 + i * 32 + lane] = xr[r][i];
  }
}

template <int NU>
__device__ __forceinline__ void store_partial(const float* d, int b, int split, int unit) {
  uint2* dst = g_part + (((b * 16 + split) * 16 + (threadIdx.x >> 5) * 2) * 40 + unit) * 32 + (threadIdx.x & 31);
#pragma unroll
  for (int u = 0; u < NU; u++) {
    dst[u * 32] = make_uint2(pack2(d[8 * u], d[8 * u + 1]), pack2(d[8 * u + 4], d[8 * u + 5]));
    dst[(40 + u) * 32] = make_uint2(pack2(d[8 * u + 2], d[8 * u + 3]), pack2(d[8 * u + 6], d[8 * u + 7]));
  }
}

template <int NH>
__device__ __forceinline__ void store_bqkv(const float* d, int b, int idx) {
  const int lane = threadIdx.x & 31, c = lane & 3, row = b * 128 + (threadIdx.x >> 5) * 16 + (lane >> 2), h0 = idx * NH;
  const float sc = h0 < 32 ? 0.22360679775f * 1.44269504089f : 1.f;
  const bool lo = c < 2;
  uint32_t* da = g_bqkv + (h0 * 256 + (row >> 3)) * 96 + lane;
  uint32_t* db = da + 256 * 96 + (lo ? 2 : -2);
#pragma unroll
  for (int r = 0; r < 2; r++) {
    const uint32_t pad = !(c & 1) && (h0 >= 64 || (h0 >= 32 && (row & 1) && poly_group((row >> 3) + r))) ? 0x00003f80u : 0u;
#pragma unroll
    for (int q = 0; q < NH / 2; q++) {
      uint32_t w[5];
#pragma unroll
      for (int i = 0; i < 5; i++) w[i] = pack2(d[20 * q + 4 * i + 2 * r] * sc, d[20 * q + 4 * i + 2 * r + 1] * sc);
      const int o = q * 2 * 256 * 96 + r * 96;
      da[o] = w[0]; da[o + 32] = w[1]; da[o + 64] = lo ? w[2] : pad;
      db[o] = lo ? w[3] : w[2]; db[o + 32] = lo ? w[4] : w[3]; db[o + 64] = lo ? pad : w[4];
    }
  }
}

template <bool WEIGHTS>
__device__ __forceinline__ void work_loader(const WorkParams& p, const uint32_t sb) {
  const uint32_t bars = sb + WK_BAR, bIF = bars + 128, bIE = bars + 160, bGo = bars + 256, slots = bars + 272;
  uint32_t* const sync = p.sync;
  int pos = 0, seq = 0, tail = 0, used = 0, normed = 0;
  uint32_t lens = 0, bar;
  const bool one = elect();
  auto alloc = [&](int len, uint32_t bytes) {
    const int skip = pos + len > WK_SLOTS ? WK_SLOTS - pos : 0, sh = 4 * (seq & 7);
    used += len + skip;
    while (used > WK_SLOTS || seq - tail >= 8) {
      mbar_wait_uniform(bars + 64 + 8 * (tail & 7), (tail >> 3) & 1);
      used -= (lens >> 4 * (tail & 7)) & 15;
      tail++;
    }
    lens = (lens & ~(15u << sh)) | (len + skip) << sh;
    bar = bars + 2 * sh;
    if (one) mbar_expect(bar, bytes);
    pos = (pos + len > WK_SLOTS ? 0 : pos) + len;
    seq++;
    return sb + (pos - len) * 8192;
  };
  for (int n = 0;; n++) {
    mbar_wait_uniform(bIF + 8 * (n & 3), (n >> 2) & 1);
    const int code = __shfl_sync(~0u, (int)lds32(slots + 4 * (n & 3)), 0);
    if (code < 0) break;
    const int type = (code >> 16) & 15, b = (code >> 8) & 255, idx = code & 255;
    if (one) mbar_arrive(bIE + 8 * (n & 3));
    const bool qa = type == IT_ATT && b < p.qa_end, tokens = qa || type == IT_Q, ln = type == IT_FIN || type == IT_LN || type == IT_LN0;
    auto inputs = [&]() {
      if (WEIGHTS || type == IT_LN0) return;
      if (type == IT_OUT || (type == IT_BO && b >= 2)) { if (p.kind != WK_JOIN) pdl_wait(); }
      else if (type == IT_BO) wait_count_uniform(sync + SY_OB, 32);
      else if (type == IT_LN) wait_count_uniform(sync + SY_P + b * 4, 2);
      else wait_count_uniform(sync + b * 8 + 4 + type, item_need(type, b));
    };
    if (type == IT_ATT && !qa) {
      if (!WEIGHTS) wait_count_uniform(sync + SY_P + b * 4 + 3, 32);
      const uint32_t dst = alloc(6, WEIGHTS ? 0 : 49152);
      if (!WEIGHTS && one) (HINT & 1 ? bulk_load_last : bulk_load)(dst, g_q + (b * 32 + idx) * 3072, 49152, bar);
    } else if (!ln) {
      const int cols = item_cols(type, b), nb = (cols + 63) >> 6, nkb = type == IT_OP ? 96 / op_split(b) : 10;
      const int kb0 = type == IT_OP ? (idx >> op_tiles(b) / 2) * nkb : 0, col = (type == IT_OP ? idx & (op_tiles(b) - 1) : idx) * cols;
      if (WEIGHTS) {
        if (type == IT_OP) {
          for (int kb = kb0; kb < kb0 + nkb; kb++) {
            const uint32_t dst = alloc(2 + nb, nb * 8192) + 16384;
            {
#pragma unroll
              for (int i = 0; i < 5; i++)
                if (i < nb && one) asm volatile("cp.async.bulk.tensor.5d.shared::cluster.global.mbarrier::complete_tx::bytes [%0], [%1, {%3, %5, %5, %5, %4}], [%2];"
                             :: "r"(dst + i * 8192), "l"(&p.wo), "r"(bar), "r"(col + i * 64), "r"(kb * 2), "r"(0) : "memory");
            }
          }
        } else {
          const CUtensorMap* m = tokens ? &p.wq : type == IT_BQ ? &p.wb : &p.wc;
          for (int kb = 0; kb < 10; kb++) {
            const uint32_t dst = alloc(2 + nb, nb * 8192) + 16384;
#pragma unroll
            for (int i = 0; i < 5; i++) if (i < nb && one) tma_load(dst + i * 8192, m, col + i * 64, kb * 64, bar);
          }
        }
      } else if (tokens || type == IT_BQ) {
        if (!tokens) inputs();
        else if (!(normed >> b & 1)) { wait_count_uniform(sync + SY_P + b * 4 + 1, ln_items(sync != g_sync, b)); normed |= 1 << b; }
        const CUtensorMap* m = tokens ? &p.xp : &p.xn;
        for (int kb = 0; kb < 10; kb++) {
          const uint32_t dst = alloc(2 + nb, 16384);
          if (one)
            asm volatile("cp.async.bulk.tensor.4d.shared::cluster.global.mbarrier::complete_tx::bytes [%0], [%1, {%3, %6, %4, %5}], [%2];"
                         :: "r"(dst), "l"(m), "r"(bar), "r"(kb * 128), "r"(tokens ? b * 4 : 0), "r"(tokens ? 0 : b * 4), "r"(0) : "memory");
        }
      } else {
        inputs();
        const uint8_t* a = type == IT_OP ? reinterpret_cast<const uint8_t*>(g_o) + (b * 96 + kb0) * 16384 : reinterpret_cast<const uint8_t*>(g_of) + b * 163840;
        for (int kb = 0; kb < nkb; kb++) {
          const uint32_t dst = alloc(2 + nb, 16384);
          if (one) (HINT & 2 ? bulk_load_last : bulk_load)(dst, a + kb * 16384, 16384, bar);
        }
      }
    }
    if (type == IT_ATT || ln) {
      inputs();
      if (!WEIGHTS && (!qa || (code & C_EARLY)) && !(code & C_LATE) && one) mbar_arrive(bGo);
    }
    if (type == IT_ATT) {
#pragma unroll
      for (int i = 0; i < 6; i += 2) {
        const uint32_t dst = alloc(5, WEIGHTS ? 0 : KV_BYTES);
        if (!WEIGHTS && one) {
#pragma unroll
          for (int u = i; u < i + 2; u++) (HINT & 1 ? bulk_load_last : bulk_load)(dst + (u - i) * 20480, g_kv + (b * 96 + idx * 3 + u % 3) * KV_BYTES + u / 3 * KV_V, 20480, bar);
        }
      }
    } else if (ln) {
      const int ng = item_groups(type, b), planes = type == IT_FIN ? op_split(b) + 1 : type == IT_LN ? 2 : 1;
      for (int rg = idx * ng; rg < (idx + 1) * ng; rg++) {
        const void* res = type == IT_LN0 ? static_cast<const void*>(p.x + (b * 16 + rg) * 8 * DM) : g_x + (b * 16 + rg) * 1280;
        for (int k = 0; k < planes; k += 4) {
          const int cnt = min(4, planes - k);
          const uint32_t dst = alloc(cnt + 1, WEIGHTS ? 0 : cnt * 10240);
          if (!WEIGHTS && one) {
#pragma unroll
            for (int i = 0; i < 4; i++)
              if (i < cnt) (HINT & 4 ? bulk_load_last : bulk_load)(dst + i * 10240, k + i + 1 < planes ? g_part + ((b * 16 + k + i) * 16 + rg) * 1280 : res, 10240, bar);
          }
        }
      }
    }
  }
}

__global__ void __launch_bounds__(384, 1) work_kernel(const __grid_constant__ WorkParams p) {
  extern __shared__ __align__(1024) uint8_t smem_raw[];
  const uint32_t sb = s2u(smem_raw), bars = sb + WK_BAR;
  const uint32_t bIF = bars + 128, bIE = bars + 160, done = bars + 192, bGo = bars + 256, slots = bars + 272, scratch = bars + 384;
  const int warp = __shfl_sync(~0u, threadIdx.x >> 5, 0), lane = threadIdx.x & 31;
  uint32_t* const sync = p.sync;
  XT(0);
  TRACE(0);
  pdl_launch();
  const bool keep = p.kind > WK_LEAD || helper_sm();
  if (!keep) {
    if (p.kind == WK_FIRST) { if (!(warp & 13)) probe_slots(bars + 320); TRACE(1); return; }
    if (__syncthreads_or(threadIdx.x == 0 && ldg_strong32(sync + SY_PRE + 1) >= LEAD1)) { pdl_wait(); return; }
  }
  const uint2 taken = p.kind == WK_JOIN && warp == 9 ? ldg_strong64(sync + SY_PRE) : make_uint2(0, 0);
  const uint32_t ending = p.kind == WK_JOIN && warp == 9 ? ldg_strong32(sync + 15 * 8 + 4) : 0;
  if (threadIdx.x < 33) {
    const int i = threadIdx.x;
    mbar_init(bars + 8 * i, i < 8 ? 2 : i < 16 ? 8 : i < 20 ? 1 : i < 24 ? 3 : i < 32 ? 8 : 1);
    asm volatile("fence.mbarrier_init.release.cluster;" ::: "memory");
  }
  __syncthreads();
  if (warp >= 8) {
    asm volatile("setmaxnreg.dec.sync.aligned.u32 56;");
    if (warp == 9) {
      XT(1);
      int own = p.kind == WK_JOIN ? reserved_item(blockIdx.x) : -1, n = 0;
      if (own >= 0 && ending) {
        if (lane == 0) { sts32(slots, own); mbar_arrive(bIF); }
        own = -1; n = 1;
      }
      XT(5);
      const int b = lane & 15, layer = p.kind == WK_LAST ? 2 : sync != g_sync;
      bool first = layer == 1 && taken.y < LEAD1, lead = first || p.kind != WK_JOIN || lead_item(layer, p.qa_end, taken.x + layer * LEAD1) >= 0;
      for (;; n++) {
        if (n > 0) mbar_wait_uniform(bGo, (n - 1) & 1);
        mbar_wait_uniform(bIE + 8 * (n & 3), ((n >> 2) & 1) ^ 1);
        int code = -1;
        if (lead) {
          int i = blockIdx.x + n * 256;
          if (first) { if (lane == 0) i = atomicAdd(sync + SY_PRE + 1, 1); i = __shfl_sync(~0u, i, 0); first = i < LEAD1; }
          if (layer < 2 && !first) {
            if (lane == 0) i = keep ? atomicAdd(sync + SY_PRE, 1) + layer * LEAD1 : 1 << 20;
            i = __shfl_sync(~0u, i, 0);
            if (!keep) pdl_wait();
          }
          code = lead_item(layer, p.qa_end, i);
          lead = code >= 0 || layer == 2 || !keep;
          if (!lead && p.kind <= WK_LEAD) {
            const uint32_t t0 = gtime();
            while (!lead && ldg_strong32(sync + SY_UP) < 96) lead = gtime() - t0 > 20000;
          }
        }
        if (!lead) {
          int spin = 0, ticket = 0;
          if (n == 0) XT(2);
          if (lane == 0) ticket = atomicAdd(sync + SY_T, 1);
          for (;;) {
            const uint4 hd = ldg_strong128(sync + b * 8), pr = ldg_strong128(sync + b * 8 + 4);
            const uint32_t hv[4] = {hd.x, hd.y, hd.z, hd.w}, pv[4] = {pr.x, pr.y, pr.z, pr.w};
            if (n == 0 && spin == 0 && hd.x + pr.x != 77777) XT(3);
            const uint32_t chain_done = __ballot_sync(~0u, (pr.x & 0xffff) >= 96);
            int left[4], avail[4], rdy = 0, claimed = 0, upstream = 0;
#pragma unroll
            for (int t = 0; t < 4; t++) {
              const int cnt = lane < 16 && !reserved(t, b) ? item_count(t, b) : 0;
              left[t] = max(cnt - (int)hv[t], 0);
              claimed += cnt - left[t];
              const bool ready = (pv[t] & 0xffff) >= item_need(t, b);
              rdy |= ready << t;
              bool ok = ready || (t == IT_ATT ? pr.x >= 0x10000 : !upstream || ((chain_done >> 15 & 1) && !left[t - 1] && (t < 2 || !left[t - 2])));
              if (t == IT_BQ && (chain_done >> 12 & 9) == 1) ok = false;
              avail[t] = ok ? left[t] : 0;
              upstream |= __any_sync(~0u, left[t] > 0);
            }
            if (own >= 0 && ((chain_done >> 15 & 1) || !upstream)) { code = own; own = -1; if (lane == 0) atomicSub(sync + SY_T, 1); break; }
            if (!upstream) { code = -1; break; }
            int rank = max(__shfl_sync(~0u, ticket, 0) - __reduce_add_sync(~0u, claimed), 0), type = -1, mine = 0;
#pragma unroll
            for (int c = 0; c < 7; c++) {
              const int t = c == 0 || c == 4 ? IT_FIN : c == 1 || c == 6 ? IT_ATT : c == 2 ? IT_OP : IT_BQ;
              int a = c == 1 || c == 2 || ((rdy >> t & 1) == (c < 4)) ? avail[t] : 0;
              if (c == 6) a = b < p.qa_end && !(rdy & 1) && ((chain_done << 1 | 1) >> b & 1) ? left[t] : 0;
              const int tot = __reduce_add_sync(~0u, a);
              if (type < 0) { if (rank < tot) { type = t; mine = a; } else rank -= tot; }
            }
            if (n == 0 && spin == 0) XT(4);
            if (type >= 0) {
#pragma unroll
              for (int o = 1; o < 16; o <<= 1) { const int y = __shfl_up_sync(~0u, mine, o); if (lane >= o) mine += y; }
              const int blk = __ffs(__ballot_sync(~0u, mine > rank)) - 1;
              const int early = !(__shfl_sync(~0u, rdy, blk) >> type & 1);
              uint32_t idx = 0;
              if (lane == 0) idx = atomicAdd(sync + blk * 8 + type, 1);
              idx = __shfl_sync(~0u, idx, 0);
              if (idx < item_count(type, blk)) { code = (chain_done >> 15 & 1) << 22 | early << 20 | type << 16 | blk << 8 | idx; break; }
            } else {
              __nanosleep(50);
            }
            spin_guard(spin);
          }
        }
        if (lane == 0) {
          sts32(slots + 4 * (n & 3), code);
          mbar_arrive(bIF + 8 * (n & 3));
        }
        __syncwarp();
        if (code < 0) break;
      }
    } else if (warp == 8) {
      if (p.kind == WK_FIRST) probe_slots(bars + 320);
      work_loader<true>(p, sb);
    } else if (warp == 11) {
      work_loader<false>(p, sb);
    } else {
      if (p.kind == WK_FIRST) probe_slots(bars + 320);
      for (int n = 0;; n++) {
        mbar_wait_uniform(bIF + 8 * (n & 3), (n >> 2) & 1);
        const int code = __shfl_sync(~0u, (int)lds32(slots + 4 * (n & 3)), 0);
        if (code < 0) break;
        const int type = (code >> 16) & 15, b = (code >> 8) & 255;
        mbar_wait_uniform(done + 8 * (n & 3), (n >> 2) & 1);
        if (elect()) {
          if (type != IT_OUT) red_release(sync + (type < IT_BQ ? b * 8 + 5 + type : SY_P + b * 4 + ((0x13102 >> 4 * (type - IT_BQ)) & 3)), 1);
          mbar_arrive(bIE + 8 * (n & 3));
        }
        __syncwarp();
      }
    }
  } else {
    asm volatile("setmaxnreg.inc.sync.aligned.u32 224;");
    Ring r{sb, 0, 0};
    Pending pend;
    pend.done = 0;
    int nln = 0;
    auto projects = [&](int n) {
      uint32_t here;
      asm volatile("{.reg .pred p; mbarrier.test_wait.parity.shared::cta.b64 p, [%1], %2; vote.sync.all.pred p, p, 0xffffffff; selp.u32 %0, 1, 0, p;}" : "=r"(here) : "r"(bIF + 8 * (n & 3)), "r"((n >> 2) & 1) : "memory");
      if (!here) return false;
      const int code = __shfl_sync(~0u, (int)lds32(slots + 4 * (n & 3)), 0);
      return code >= 0 && (((code >> 16) & 15) == IT_Q || (((code >> 16) & 15) == IT_ATT && ((code >> 8) & 255) < p.qa_end));
    };
#pragma unroll 1
    for (int n = 0;; n++) {
      if (pend.done && !projects(n)) pend.flush();
      mbar_wait_uniform(bIF + 8 * (n & 3), (n >> 2) & 1);
      const int code = __shfl_sync(~0u, (int)lds32(slots + 4 * (n & 3)), 0);
      if (code < 0) { TRACE(2); break; }
      const int type = (code >> 16) & 15, b = (code >> 8) & 255, idx = code & 255;
      const uint32_t go = (code & C_LATE) || (type == IT_ATT && (code & C_EARLY)) ? 0 : bGo;
      ITEM(code & 0xfffff, 0);
      if (type == IT_ATT || type == IT_Q) {
        if (type == IT_Q || b < p.qa_end) {
          float d[96] = {};
          reg_fence<96>(d);
          ITEM(9 << 16 | (code & 0xffff), 0);
          gemm_item<192>(d, r, 10, go, pend);
          ITEM(9 << 16 | (code & 0xffff), 1);
#pragma unroll
          for (int i = 0; i < 48; i++) pend.w[i] = pack2(d[2 * i], d[2 * i + 1]);
        } else {
          const uint32_t base = r.wait(6) + warp * 2048 + lane * 16;
#pragma unroll
          for (int i = 0; i < 12; i++) {
            const uint4 t = lds128(base + (i >> 2) * 16384 + (i & 3) * 512);
            pend.w[4 * i] = t.x; pend.w[4 * i + 1] = t.y; pend.w[4 * i + 2] = t.z; pend.w[4 * i + 3] = t.w;
          }
          __syncwarp();
          r.release(r.seq - 1);
        }
        const bool now = type == IT_ATT && !projects(n + 1);
        if (type == IT_Q) {
          pend.dst = g_q + (b * 32 + idx) * 3072 + warp * 128 + lane;
        } else {
          pend.dst = g_o + (b * 32 + idx) * 3072 + (warp & 3) * 256 + (warp >> 2) * 128 + (lane & 3) * 8 + (lane >> 2);
          if (warp < 4) attn_a_warp<0>(r, pend, now); else attn_a_warp<1>(r, pend, now);
        }
        pend.done = done + 8 * (n & 3);
        if (now) pend.finish();
      } else {
        if (type == IT_FIN || type == IT_LN || type == IT_LN0) {
          const int ng = item_groups(type, b);
          const int planes = type == IT_FIN ? op_split(b) + 1 : 2;
          if (ng == 1) {
            ln_groups<1>(r, scratch + (nln++ & 1) * 1024, type == IT_LN0, planes, b * 16 + idx);
          } else {
#pragma unroll 1
            for (int i = 0; i < ng; i += 2) ln_groups<2>(r, scratch + (nln++ & 1) * 1024, type == IT_LN0, planes, b * 16 + idx * ng + i);
          }
        } else if (item_cols(type, b) == 80) {
          float d[40] = {};
          uint2 y[10];
          if (type == IT_OUT) {
            const uint2* x = g_x + ((b * 16 + warp * 2) * 40 + idx * 5) * 32 + lane;
#pragma unroll
            for (int i = 0; i < 10; i++) y[i] = __ldcg(x + (i / 5 * 40 + i % 5) * 32);
          }
          reg_fence<40>(d);
          gemm_item<80>(d, r, 10, go, pend);
          if (type == IT_BQ) store_bqkv<4>(d, b, idx); else {
          bar_sync(1, 256);
          const uint32_t dst = sb + (warp * 16 + (lane & 15)) * 160 + (lane >> 4) * 16;
#pragma unroll
          for (int u = 0; u < 5; u++)
            stsm4(dst + u * 32, pack2(bf_lo(y[u].x) + d[8 * u], bf_hi(y[u].x) + d[8 * u + 1]), pack2(bf_lo(y[5 + u].x) + d[8 * u + 2], bf_hi(y[5 + u].x) + d[8 * u + 3]),
                  pack2(bf_lo(y[u].y) + d[8 * u + 4], bf_hi(y[u].y) + d[8 * u + 5]), pack2(bf_lo(y[5 + u].y) + d[8 * u + 6], bf_hi(y[5 + u].y) + d[8 * u + 7]));
          fence_async();
          __syncwarp();
          if (elect()) { tma_store(&p.out, sb + warp * 2560, idx * 80, b * 128 + warp * 16); bulk_commit(); bulk_wait<0>(); }
          }
        } else {
          if (item_cols(type, b) == 320) {
            float d[160] = {};
            reg_fence<160>(d);
            ITEM((type == IT_BQ ? 10 : 11) << 16 | (code & 0xffff), 0);
            gemm_item<320>(d, r, type == IT_OP ? 96 / op_split(b) : 10, go, pend);
            ITEM((type == IT_BQ ? 10 : 11) << 16 | (code & 0xffff), 1);
            if (warp >= 4) bar_sync(7, 256);
            if (type == IT_BQ) store_bqkv<16>(d, b, idx); else store_partial<20>(d, b, idx >> 1, (idx & 1) * 20);
          } else {
            float d[80] = {};
            reg_fence<80>(d);
            gemm_item<160>(d, r, type == IT_OP ? 96 / op_split(b) : 10, go, pend);
            if (warp >= 4) bar_sync(7, 256);
            if (type == IT_BQ) store_bqkv<8>(d, b, idx); else store_partial<10>(d, b, idx >> 2, (idx & 3) * 10);
          }
          if (warp < 4) bar_arrive(7, 256);
        }
        __syncwarp();
        if (elect()) mbar_arrive(done + 8 * (n & 3));
#pragma unroll
        for (int i = 0; i < 48; i++) pend.w[i] = 0;
      }
      if ((code & C_LATE) && warp == 4 && elect()) mbar_arrive(bGo);
      ITEM(code & 0xfffff, 1);
    }
  }
}

constexpr int AB_SMEM = 1024 + 2 * 98304 + 256;
#define AB_N 32
#define AB_WG 4
constexpr int AB_T = AB_WG * 128, AB_PASS = 8 / AB_WG;
__device__ __forceinline__ float ex2_poly(float t) {
  const uint32_t r = __float_as_uint(t) & 0xffff8000u;
  const float f = t - __uint_as_float(r);
  const float p = fmaf(fmaf(fmaf(-5.869912678e-38f, f, -1.700740250e-37f), f, -5.234869734e-37f), f, -7.522601252e-37f);
  uint32_t y;
  asm("mad.lo.u32 %0, %1, 256, %2;" : "=r"(y) : "r"(r), "r"(__float_as_uint(p)));
  return __uint_as_float(y);
}
__device__ __forceinline__ uint32_t hsq(uint32_t w, uint32_t c) { uint32_t r; asm("fma.rn.bf16x2 %0, %1, %1, %2;" : "=r"(r) : "r"(w), "r"(c)); return r; }
__device__ __forceinline__ float sq2(uint32_t w) { const float a = bf_lo(w), b = bf_hi(w); return fmaf(a, a, b * b); }

__device__ __forceinline__ void attn_b_store(const float* o, int h, int row0, int lane) {
  const int g = lane >> 2, c = lane & 3;
  const float i0 = 1.f / __shfl_sync(~0u, o[8], (lane & ~3) | 2), i1 = 1.f / __shfl_sync(~0u, o[10], (lane & ~3) | 2);
#pragma unroll
  for (int jj = 0; jj < 3; jj++) {
    if (jj < 2 || c < 2) {
      const int col = h * 20 + 8 * jj + 2 * c;
      g_of[core_word(row0 + g, col)] = pack2(o[4 * jj] * i0, o[4 * jj + 1] * i0);
      g_of[core_word(row0 + g + 8, col)] = pack2(o[4 * jj + 2] * i1, o[4 * jj + 3] * i1);
    }
  }
}

__device__ __forceinline__ void attn_b_qk(float* s, uint32_t q0, uint32_t q1, uint32_t q2, uint32_t q3, uint32_t q4, uint32_t q5, uint32_t z0, uint32_t z1,
                                          uint64_t dk, uint64_t dk2) {
  wg_rs32_00(s, q0, q1, q2, q3, dk, 0);
  wg_rs32_00(s, q4, q5, z0, z1, dk2, 1);
}

struct AttnParams { const uint8_t* pf[4]; uint32_t *sync, *next; };
__global__ void __launch_bounds__(AB_T + 128, 1) attn_b_kernel(const __grid_constant__ AttnParams p) {
  extern __shared__ uint8_t smem_raw[];
  const uint32_t sb = (s2u(smem_raw) + 1023) & ~1023u, sK = sb, sV = sb + 98304, bars = sb + 2 * 98304;
  const int warp = __shfl_sync(~0u, threadIdx.x >> 5, 0), lane = threadIdx.x & 31;
  const int h = blockIdx.x & 31, quarter = blockIdx.x >> 5;
  BT(0);
  TRACE(0);
  if (threadIdx.x == 0) {
    for (int i = 0; i < 8; i++) mbar_init(bars + 8 * i, 1);
    mbar_init(bars + 128, AB_T / 32);
    mbar_init(bars + 136, 2);
    asm volatile("fence.mbarrier_init.release.cluster;" ::: "memory");
  }
  __syncthreads();
  if (warp >= AB_T / 32) {
    asm volatile("setmaxnreg.dec.sync.aligned.u32 32;");
    if (warp == AB_T / 32 + 1) return;
    if (warp > AB_T / 32) {
      uint32_t kmax = 0;
#pragma unroll 1
      for (int i = 0; i < 32; i++) {
        if (!(i & 3)) mbar_wait_uniform(bars + 2 * i, 0);
        const uint32_t a = sK + i * 3072 + ((threadIdx.x >> 3) & 7) * 384 + (lane & 7) * 16;
        const uint4 x = lds128(a), y = lds128(a + 128);
        const uint2 z = lds64(a + 256);
        const uint32_t n = hadd2(hsq(x.x, hsq(x.y, hsq(x.z, hsq(x.w, hsq(z.x, 0))))), hsq(y.x, hsq(y.y, hsq(y.z, hsq(y.w, hsq(z.y, 0))))));
        kmax = max(kmax, __float_as_uint(bf_lo(n) + bf_hi(n)) & 0x7fffffffu);
      }
      const uint32_t kbits = __reduce_max_sync(~0u, kmax);
      if (lane == 0) { sts32(bars + 64 + (warp & 1) * 4, kbits); mbar_arrive(bars + 136); }
      return;
    }
    const uint8_t* gk = reinterpret_cast<const uint8_t*>(g_bqkv + (32 + h) * 256 * 96);
    const uint8_t* gv = reinterpret_cast<const uint8_t*>(g_bqkv + (64 + h) * 256 * 96);
    uint32_t todo = 255;
    for (int spin = 0; todo;) {
      const uint32_t up = __ballot_sync(~0u, ld_acquire(p.sync + SY_P + (lane & 15) * 4 + 2) >= bq_items(lane & 15));
      fence_async_global();
      for (int i = 0; i < 8; i++) {
        if (!(todo >> i & 1) || (up >> 2 * i & 3) != 3) continue;
        todo &= ~(1u << i);
        if (elect()) {
          mbar_expect(bars + 8 * i, 24576);
          bulk_load(sK + i * 12288, gk + i * 12288, 12288, bars + 8 * i);
          bulk_load(sV + i * 12288, gv + i * 12288, 12288, bars + 8 * i);
        }
      }
      spin_guard(spin);
    }
    pdl_launch();
    TRACE(1);
    if (blockIdx.x < NSLOT) for (int i = lane; i < 512; i += 32) reinterpret_cast<uint4*>(pool_at(blockIdx.x * 8192))[i] = make_uint4(0, 0, 0, 0);
    if (!p.next && blockIdx.x == 127) for (int i = lane; i < 256; i += 32) { g_smpart[i] = 0; if (i < NSLOT) g_orient[i] = 0; }
    if (p.next) {
      mbar_wait_uniform(bars + 128, 0);
      if (quarter == 0 && lane == 0) red_release(p.next + SY_OB, 1);
      for (int i = 0; i < 32; i++) {
        if (elect()) prefetch_l2(p.pf[i >> 3] + blockIdx.x * 61440 + (i & 7) * 7680, 7680);
        __nanosleep(300);
      }
    }
    return;
  }
  asm volatile("setmaxnreg.inc.sync.aligned.u32 112;");
  constexpr int NT = SEQ / AB_N, PER = 256 / AB_N;
  uint32_t qn[8];
  auto load_q = [&](int pass) {
    const uint32_t* gq = g_bqkv + (h * 256 + pass * 128 + quarter * 32 + warp * 2) * 96 + lane;
#pragma unroll
    for (int i = 0; i < 8; i++) qn[i] = __ldcg(gq + (i & 1) * 96 + min(i >> 1, 2) * 32 + (i < 6 ? 0 : 3 - (lane & 3)));
  };
  mbar_wait_uniform(bars + 8 * quarter, 0);
  load_q(0);
#pragma unroll 1
  for (int pass = 0; pass < AB_PASS; pass++) {
    const int row0 = pass * 1024 + quarter * 256 + warp * 16;
    const uint32_t q0 = qn[0], q1 = qn[1], q2 = qn[2], q3 = qn[3], z0 = qn[6], z1 = qn[7];
    uint32_t q4 = qn[4], q5 = qn[5];
    if ((lane & 3) == 2) { q4 = 0x43BCu; q5 = 0x43BCu; }
    float o[12];
    uint64_t dk = mkdesc(sK, 128, 384, 0), dk2 = mkdesc(sK + 256, 0, 384, 0), dv = mkdesc(sV, 384, 128, 0);
    float sa[AB_N / 2], sb2[AB_N / 2];
    uint32_t pa[AB_N / 4], pb[AB_N / 4];
    if (pass == 0) mbar_wait_uniform(bars, 0);
    BT(1 + 2 * pass);
    wg_fence();
    attn_b_qk(sa, q0, q1, q2, q3, q4, q5, z0, z1, dk, dk2);
    wg_commit();
    attn_b_qk(sb2, q0, q1, q2, q3, q4, q5, z0, z1, dk + AB_N * 3, dk2 + AB_N * 3);
    wg_commit();
#pragma unroll 1
    for (int kt = 0; kt < NT; kt += 2) {
      const int nx = kt + 2 < NT ? kt + 2 : 0;
      if (pass == 0 && (nx & (PER - 1)) == 0) mbar_wait_uniform(bars + 8 * (nx / PER), 0);
      const uint64_t nk = dk + nx * (AB_N * 3), nk2 = dk2 + nx * (AB_N * 3);
      wg_wait<1>();
      reg_fence<AB_N / 2>(sa);
#pragma unroll
      for (int i = 0; i < AB_N / 4; i++) pa[i] = pack2(ex2(sa[2 * i]), poly_group(i >> 1) ? ex2_poly(sa[2 * i + 1]) : ex2(sa[2 * i + 1]));
      wg_fence();
#pragma unroll
      for (int kk = 0; kk < AB_N / 16; kk++) wg_rs24_01(o, pa[4 * kk], pa[4 * kk + 1], pa[4 * kk + 2], pa[4 * kk + 3], dv + kk * 48, kk | kt);
      attn_b_qk(sa, q0, q1, q2, q3, q4, q5, z0, z1, nk, nk2);
      wg_commit();
      wg_wait<1>();
      reg_fence<AB_N / 2>(sb2);
#pragma unroll
      for (int i = 0; i < AB_N / 4; i++) pb[i] = pack2(ex2(sb2[2 * i]), poly_group((i >> 1) + AB_N / 8) ? ex2_poly(sb2[2 * i + 1]) : ex2(sb2[2 * i + 1]));
      wg_fence();
#pragma unroll
      for (int kk = 0; kk < AB_N / 16; kk++) wg_rs24_01(o, pb[4 * kk], pb[4 * kk + 1], pb[4 * kk + 2], pb[4 * kk + 3], dv + AB_N * 3 + kk * 48, 1);
      attn_b_qk(sb2, q0, q1, q2, q3, q4, q5, z0, z1, nk + AB_N * 3, nk2 + AB_N * 3);
      wg_commit();
      dv += AB_N * 6;
    }
    wg_wait<0>();
    reg_fence<12>(o); reg_fence<AB_N / 2>(sa); reg_fence<AB_N / 2>(sb2);
    BT(2 + 2 * pass);
    if (pass + 1 < AB_PASS) load_q(pass + 1);
    mbar_wait_uniform(bars + 136, 0);
    const uint2 kb = lds64(bars + 64);
    const float kmax = __uint_as_float(max(kb.x, kb.y));
    if ((lane & 3) == 2) q4 = q5 = 0;
    float n0 = sq2(q0) + sq2(q2) + sq2(q4), n1 = sq2(q1) + sq2(q3) + sq2(q5);
    n0 += __shfl_xor_sync(~0u, n0, 1); n1 += __shfl_xor_sync(~0u, n1, 1);
    n0 += __shfl_xor_sync(~0u, n0, 2); n1 += __shfl_xor_sync(~0u, n1, 2);
    uint32_t redo;
    asm volatile("{.reg .pred p, q; setp.ne.u32 p, %1, 0; bar.red.or.pred q, %2, 128, p; selp.u32 %0, 1, 0, q;}"
                 : "=r"(redo) : "r"((uint32_t)!(n0 * kmax <= 9500.f && n1 * kmax <= 9500.f)), "r"(2 + (warp >> 2)) : "memory");
    if (redo) {
#pragma unroll
      for (int i = 0; i < 12; i++) o[i] = 0.f;
      float m0 = -INFINITY, m1 = -INFINITY;
#pragma unroll 1
      for (int kt = 0; kt < 64; kt++) {
        float s[16];
        wg_fence();
        wg_rs32_00(s, q0, q1, q2, q3, dk + kt * 96, 0);
        wg_rs32_00(s, q4, q5, z0, z1, dk2 + kt * 96, 1);
        wg_commit();
        wg_wait<0>();
        reg_fence<16>(s); reg_fence<12>(o);
        float n0 = m0, n1 = m1;
#pragma unroll
        for (int jj = 0; jj < 4; jj++) { n0 = fmaxf(n0, fmaxf(s[4 * jj], s[4 * jj + 1])); n1 = fmaxf(n1, fmaxf(s[4 * jj + 2], s[4 * jj + 3])); }
        n0 = fmaxf(n0, __shfl_xor_sync(~0u, n0, 1)); n0 = fmaxf(n0, __shfl_xor_sync(~0u, n0, 2));
        n1 = fmaxf(n1, __shfl_xor_sync(~0u, n1, 1)); n1 = fmaxf(n1, __shfl_xor_sync(~0u, n1, 2));
        const float r0 = ex2(m0 - n0), r1 = ex2(m1 - n1);
        m0 = n0; m1 = n1;
#pragma unroll
        for (int jj = 0; jj < 3; jj++) { o[4 * jj] *= r0; o[4 * jj + 1] *= r0; o[4 * jj + 2] *= r1; o[4 * jj + 3] *= r1; }
        uint32_t pp[8];
#pragma unroll
        for (int jj = 0; jj < 4; jj++) {
          pp[2 * jj] = pack2(ex2(s[4 * jj] - m0), ex2(s[4 * jj + 1] - m0));
          pp[2 * jj + 1] = pack2(ex2(s[4 * jj + 2] - m1), ex2(s[4 * jj + 3] - m1));
        }
        reg_fence<12>(o);
        wg_fence();
#pragma unroll
        for (int kk = 0; kk < 2; kk++) wg_rs24_01(o, pp[4 * kk], pp[4 * kk + 1], pp[4 * kk + 2], pp[4 * kk + 3], mkdesc(sV, 384, 128, 0) + kt * 96 + kk * 48, 1);
        wg_commit();
      }
      wg_wait<0>();
      reg_fence<12>(o);
    }
    attn_b_store(o, h, row0, lane);
    __syncwarp();
    if (pass == 0 && lane == 0) mbar_arrive(bars + 128);
  }
  BT(5);
  TRACE(2);
}

typedef CUresult (*EncodeFn)(CUtensorMap*, CUtensorMapDataType, cuuint32_t, void*, const cuuint64_t*, const cuuint64_t*,
                             const cuuint32_t*, const cuuint32_t*, CUtensorMapInterleave, CUtensorMapSwizzle,
                             CUtensorMapL2promotion, CUtensorMapFloatOOBfill);

void make_map(EncodeFn enc, CUtensorMap* m, const void* ptr, int cols, int rows, int box_rows, int box_cols = 64) {
  const cuuint64_t dims[2] = {(cuuint64_t)cols, (cuuint64_t)rows};
  const cuuint64_t strides[1] = {(cuuint64_t)cols * 2};
  const cuuint32_t box[2] = {(cuuint32_t)box_cols, (cuuint32_t)box_rows}, es[2] = {1, 1};
  enc(m, CU_TENSOR_MAP_DATA_TYPE_BFLOAT16, 2, const_cast<void*>(ptr), dims, strides, box, es, CU_TENSOR_MAP_INTERLEAVE_NONE,
      box_cols == 64 ? CU_TENSOR_MAP_SWIZZLE_128B : box_cols == 32 ? CU_TENSOR_MAP_SWIZZLE_64B : CU_TENSOR_MAP_SWIZZLE_NONE, CU_TENSOR_MAP_L2_PROMOTION_L2_256B, CU_TENSOR_MAP_FLOAT_OOB_FILL_NONE);
}
template <class... KA, class... A>
void launch(void (*kern)(KA...), int grid, int block, int smem, int cluster, bool pdl, A... args) {
  cudaFuncSetAttribute(kern, cudaFuncAttributeMaxDynamicSharedMemorySize, smem);
  cudaLaunchConfig_t cfg = {};
  cfg.gridDim = dim3(grid); cfg.blockDim = dim3(block); cfg.dynamicSmemBytes = smem; cfg.stream = cudaStreamPerThread;
  cudaLaunchAttribute at[2];
  int n = 0;
  if (cluster > 1) { at[n].id = cudaLaunchAttributeClusterDimension; at[n].val.clusterDim.x = cluster; at[n].val.clusterDim.y = 1; at[n].val.clusterDim.z = 1; n++; }
  if (pdl) { at[n].id = cudaLaunchAttributeProgrammaticStreamSerialization; at[n].val.programmaticStreamSerializationAllowed = 1; n++; }
  cfg.attrs = at; cfg.numAttrs = n;
  cudaLaunchKernelEx(&cfg, kern, args...);
}
template <class T> void* sym(T& s) { void* p = nullptr; cudaGetSymbolAddress(&p, s); return p; }

}

#define MODE(b) 0
extern "C" void kernel_launch(void* const* d_in, const int* in_sizes, int n_in, void* d_out, int out_size) {
  const __nv_bfloat16* x = (const __nv_bfloat16*)d_in[0];
  void* fn = nullptr; cudaDriverEntryPointQueryResult qr;
  cudaGetDriverEntryPoint("cuTensorMapEncodeTiled", &fn, cudaEnableDefault, &qr);
  EncodeFn enc = (EncodeFn)fn;

  ChainParams ch = {};
  WorkParams wk = {};
  AttnParams at = {};
  make_map(enc, &ch.wq, d_in[2], HD, DM, 128); make_map(enc, &ch.wk, d_in[3], HD, DM, 128); make_map(enc, &ch.wv, d_in[4], HD, DM, 128);
  make_map(enc, &ch.wo, d_in[5], DM, HD, 192, 32);
  ch.mem0 = (const __nv_bfloat16*)d_in[1];
  ch.d1 = 400; ch.d2 = 300; ch.dn = 0; ch.dx = 500;
  make_map(enc, &wk.wq, d_in[2], HD, DM, 64);
  make_map(enc, &wk.wb, d_in[8], 1920, DM, 64);
  make_map(enc, &wk.wc, d_in[9], DM, DM, 64);
  make_map(enc, &wk.out, d_out, DM, SEQ, 16, 80);
  {
    const cuuint64_t dims[5] = {DM, 2, 4, 4, HD / 32}, strides[4] = {DM * 2, DM * 16, DM * 4, DM * 64};
    const cuuint32_t box[5] = {64, 2, 4, 4, 2}, es[5] = {1, 1, 1, 1, 1};
    enc(&wk.wo, CU_TENSOR_MAP_DATA_TYPE_BFLOAT16, 5, d_in[5], dims, strides, box, es, CU_TENSOR_MAP_INTERLEAVE_NONE, CU_TENSOR_MAP_SWIZZLE_128B,
        CU_TENSOR_MAP_L2_PROMOTION_L2_256B, CU_TENSOR_MAP_FLOAT_OOB_FILL_NONE);
  }
  for (int i = 0; i < 2; i++) {
    const cuuint64_t dims[4] = {1280, 2, i ? 64u : 2u, i ? 2u : 64u}, strides[3] = {10240, i ? 40960u : 20480u, i ? 20480u : 40960u};
    const cuuint32_t box[4] = {128, 2, i ? 4u : 2u, i ? 2u : 4u}, es[4] = {1, 1, 1, 1};
    enc(i ? &wk.xp : &wk.xn, CU_TENSOR_MAP_DATA_TYPE_UINT64, 4, sym(g_xn), dims, strides, box, es, CU_TENSOR_MAP_INTERLEAVE_NONE, CU_TENSOR_MAP_SWIZZLE_NONE,
        CU_TENSOR_MAP_L2_PROMOTION_L2_256B, CU_TENSOR_MAP_FLOAT_OOB_FILL_NONE);
  }
  wk.x = x;
  for (int i = 0; i < 4; i++) at.pf[i] = (const uint8_t*)d_in[i < 2 ? 3 + i : i == 2 ? 2 : 5];
  int qa_end[2] = {12, 12};
  for (int layer = 0; layer < 2; layer++) {
    ch.sync = wk.sync = at.sync = (uint32_t*)sym(g_sync) + layer * SY_N;
    ch.other = (uint32_t*)sym(g_sync) + (1 - layer) * SY_N;
    ch.layer = layer;
    at.next = layer ? nullptr : ch.other;
    wk.qa_end = qa_end[layer];
    wk.kind = layer ? WK_LEAD : WK_FIRST;
    launch(work_kernel, 132, 384, WK_SMEM, 1, layer != 0, wk);
    launch(chain_kernel, 96, 384, CH_SMEM, 3, true, ch);
    wk.kind = WK_JOIN;
    launch(work_kernel, 96, 384, WK_SMEM, 1, true, wk);
    launch(attn_b_kernel, 128, AB_T + 128, AB_SMEM, 1, true, at);
  }
  wk.kind = WK_LAST;
  launch(work_kernel, 128, 384, WK_SMEM, 1, true, wk);
}
```

```cpp
#include <cuda_runtime.h>
#include <cuda_bf16.h>
#include <cuda.h>
#include <stdint.h>
#include <stdlib.h>

namespace {

constexpr int SEQ = 2048, DM = 640, HD = 6144, NSEG = 64;
constexpr int SPIN_LIMIT = 1 << 20;
#define HINT 7

__device__ __align__(128) uint2 g_x[SEQ * DM / 4];
__device__ __align__(128) uint32_t g_xn[SEQ * DM / 2];
__device__ __align__(128) uint32_t g_of[SEQ * DM / 2];
__device__ __align__(128) uint4 g_o[SEQ * HD / 8];
__device__ __align__(128) uint4 g_q[SEQ * HD / 8];
constexpr int KV_K = 0, KV_KM = 16384, KV_V = 20480, KV_VM = 36864, KV_BYTES = 40960;
__device__ __align__(128) uint8_t g_kv[16 * 96 * KV_BYTES];
#define OP_B8 11
#define OP_B16 14
#define OP_N4 15
#define BQ_12 12
#define BQ_24 14
#define FIN_16 12
__host__ __device__ constexpr int op_split(int b) { return b < OP_B8 ? 4 : b < OP_B16 ? 8 : 16; }
__host__ __device__ constexpr int op_tiles(int b) { return b < OP_N4 ? 2 : 4; }
__host__ __device__ constexpr int fin_items(int b) { return b < OP_B8 ? 4 : b < FIN_16 ? 8 : 16; }
__host__ __device__ constexpr int bq_items(int b) { return b < BQ_12 ? 6 : b < BQ_24 ? 12 : 24; }
__host__ __device__ constexpr int ln_items(int layer, int b) { return layer == 0 && b < 2 ? 16 : 4; }
__device__ __align__(128) uint2 g_part[16 * 16 * 16 * 40 * 32];
constexpr int SY_P = 128, SY_T = 192, SY_UP = 224, SY_OB = 225, SY_PRE = 256, SY_PART = 288, SY_TIME = 384, SY_N = 448;
__device__ __align__(128) uint32_t g_sync[2 * SY_N];
constexpr int NSLOT = 92;
__device__ uint32_t g_pool[(NSLOT + 2) * 2048];
__device__ uint32_t g_smpart[256], g_orient[NSLOT];
__device__ __align__(128) uint32_t g_bqkv[3 * 32 * 256 * 96];

#define BT(i)
#define MISS(k, n)
#define PRO(i)
#define TRACE(w)
#define ITEM(code, w)
#define STAT(k)
#define TMV(i, v)
#define TM(i)
#define TMD(i, dep)

__device__ __forceinline__ uint32_t gtime() { uint32_t c; asm volatile("mov.u32 %0, %%globaltimer_lo;" : "=r"(c) :: "memory"); return c; }
__device__ __forceinline__ uint32_t clk32() { uint32_t c; asm volatile("mov.u32 %0, %%clock;" : "=r"(c) :: "memory"); return c; }
__device__ __forceinline__ uint32_t fresh_tid() { uint32_t t; asm volatile("mov.u32 %0, %%tid.x;" : "=r"(t)); return t; }
__device__ __forceinline__ uint32_t s2u(const void* p) { return (uint32_t)__cvta_generic_to_shared(p); }
__device__ __forceinline__ uint32_t pack2(float a, float b) {
  uint32_t r; asm("cvt.rn.bf16x2.f32 %0, %1, %2;" : "=r"(r) : "f"(b), "f"(a)); return r; }
__device__ __forceinline__ float bf_lo(uint32_t w) { return __uint_as_float(w << 16); }
__device__ __forceinline__ float bf_hi(uint32_t w) { return __uint_as_float(w & 0xffff0000u); }
__device__ __forceinline__ float ex2(float x) { float y; asm("ex2.approx.ftz.f32 %0, %1;" : "=f"(y) : "f"(x)); return y; }

__device__ __forceinline__ void mbar_init(uint32_t bar, uint32_t n) {
  asm volatile("mbarrier.init.shared::cta.b64 [%0], %1;" :: "r"(bar), "r"(n) : "memory"); }
__device__ __forceinline__ void mbar_expect(uint32_t bar, uint32_t bytes) {
  asm volatile("mbarrier.arrive.expect_tx.shared::cta.b64 _, [%0], %1;" :: "r"(bar), "r"(bytes) : "memory"); }
__device__ __forceinline__ void mbar_arrive(uint32_t bar) {
  asm volatile("mbarrier.arrive.shared::cta.b64 _, [%0];" :: "r"(bar) : "memory"); }
__device__ __forceinline__ void mbar_arrive_remote(uint32_t bar) {
  asm volatile("mbarrier.arrive.shared::cluster.b64 _, [%0];" :: "r"(bar) : "memory"); }
__device__ __forceinline__ void mbar_wait_slow(uint32_t bar, uint32_t ph) {
  asm volatile("{.reg .pred p; .reg .u32 n; mov.u32 n, 0;\n"
               "W: mbarrier.try_wait.parity.shared::cta.b64 p, [%0], %1; @p bra D;\n"
               "add.u32 n, n, 1; setp.gt.u32 p, n, %2; @p trap; bra W;\n"
               "D: }" :: "r"(bar), "r"(ph), "n"(SPIN_LIMIT) : "memory");
}
__device__ __forceinline__ void mbar_wait(uint32_t bar, uint32_t ph) {
  uint32_t ok;
  asm volatile("{.reg .pred p; mbarrier.try_wait.parity.shared::cta.b64 p, [%1], %2; selp.u32 %0, 1, 0, p;}" : "=r"(ok) : "r"(bar), "r"(ph) : "memory");
  if (__builtin_expect(!ok, 0)) mbar_wait_slow(bar, ph);
}
__device__ __forceinline__ void mbar_wait_uniform(uint32_t bar, uint32_t ph) {
  asm volatile("{.reg .pred p; .reg .u32 n; mov.u32 n, 0;\n"
               "W: mbarrier.try_wait.parity.shared::cta.b64 p, [%0], %1; vote.sync.all.pred p, p, 0xffffffff; @p bra.uni D;\n"
               "add.u32 n, n, 1; setp.gt.u32 p, n, %2; @p trap; bra.uni W;\n"
               "D: }" :: "r"(bar), "r"(ph), "n"(SPIN_LIMIT) : "memory");
}
__device__ __forceinline__ bool elect() {
  uint32_t p; asm volatile("{.reg .pred q; elect.sync _|q, 0xffffffff; selp.u32 %0, 1, 0, q;}" : "=r"(p)); return p; }
__device__ __forceinline__ void mbar_wait_cluster(uint32_t bar, uint32_t ph) {
  asm volatile("{.reg .pred p; .reg .u32 n; mov.u32 n, 0;\n"
               "W: mbarrier.try_wait.parity.acquire.cluster.shared::cta.b64 p, [%0], %1; @p bra D;\n"
               "add.u32 n, n, 1; setp.gt.u32 p, n, %2; @p trap; bra W;\n"
               "D: }" :: "r"(bar), "r"(ph), "n"(SPIN_LIMIT) : "memory");
}
__device__ __forceinline__ void spin_guard(int& n) {
  asm volatile("{.reg .pred p; add.s32 %0, %0, 1; setp.gt.s32 p, %0, %1; @p trap;}" : "+r"(n) : "n"(SPIN_LIMIT));
}
__device__ __forceinline__ void pdl_wait() { asm volatile("griddepcontrol.wait;" ::: "memory"); TRACE(1); }
__device__ __forceinline__ void pdl_launch() { asm volatile("griddepcontrol.launch_dependents;" ::: "memory"); }
__device__ __forceinline__ uint32_t ld_acquire(const uint32_t* p) { uint32_t v; asm volatile("ld.acquire.gpu.global.u32 %0, [%1];" : "=r"(v) : "l"(p) : "memory"); return v; }
__device__ __forceinline__ void red_release(uint32_t* p, uint32_t v) { asm volatile("red.release.gpu.global.add.u32 [%0], %1;" :: "l"(p), "r"(v) : "memory"); }
__device__ __forceinline__ void fence_async_global() { asm volatile("fence.proxy.async.global;" ::: "memory"); }
__device__ __forceinline__ void fence_async() { asm volatile("fence.proxy.async.shared::cta;" ::: "memory"); }
__device__ __forceinline__ void bar_sync(int id, int n) { asm volatile("bar.sync %0, %1;" :: "r"(id), "r"(n) : "memory"); }
__device__ __forceinline__ void bar_arrive(int id, int n) { asm volatile("bar.arrive %0, %1;" :: "r"(id), "r"(n) : "memory"); }
__device__ __forceinline__ void tma_load(uint32_t dst, const CUtensorMap* m, int c0, int c1, uint32_t bar) {
  asm volatile("cp.async.bulk.tensor.2d.shared::cluster.global.mbarrier::complete_tx::bytes [%0], [%1, {%3, %4}], [%2];"
               :: "r"(dst), "l"(m), "r"(bar), "r"(c0), "r"(c1) : "memory"); }
__device__ __forceinline__ void tma_store(const CUtensorMap* m, uint32_t src, int c0, int c1) {
  asm volatile("cp.async.bulk.tensor.2d.global.shared::cta.bulk_group [%0, {%2, %3}], [%1];"
               :: "l"(m), "r"(src), "r"(c0), "r"(c1) : "memory"); }
__device__ __forceinline__ uint64_t evict_first() { uint64_t p; asm("createpolicy.fractional.L2::evict_first.b64 %0, 1.0;" : "=l"(p)); return p; }
__device__ __forceinline__ void bulk_load_last(uint32_t dst, const void* src, uint32_t bytes, uint32_t bar) {
  asm volatile("cp.async.bulk.shared::cluster.global.mbarrier::complete_tx::bytes.L2::cache_hint [%0], [%1], %2, [%3], %4;"
               :: "r"(dst), "l"(src), "r"(bytes), "r"(bar), "l"(evict_first()) : "memory"); }
__device__ __forceinline__ void bulk_store_stream(void* dst, uint32_t src, uint32_t bytes) {
  asm volatile("cp.async.bulk.global.shared::cta.bulk_group.L2::cache_hint [%0], [%1], %2, %3;" :: "l"(dst), "r"(src), "r"(bytes), "l"(evict_first()) : "memory"); }
__device__ __forceinline__ void bulk_load(uint32_t dst, const void* src, uint32_t bytes, uint32_t bar) {
  asm volatile("cp.async.bulk.shared::cluster.global.mbarrier::complete_tx::bytes [%0], [%1], %2, [%3];"
               :: "r"(dst), "l"(src), "r"(bytes), "r"(bar) : "memory"); }
__device__ __forceinline__ void bulk_push(uint32_t dst, uint32_t src, uint32_t bytes, uint32_t bar) {
  asm volatile("cp.async.bulk.shared::cluster.shared::cta.mbarrier::complete_tx::bytes [%0], [%1], %2, [%3];"
               :: "r"(dst), "r"(src), "r"(bytes), "r"(bar) : "memory"); }
__device__ __forceinline__ void bulk_store(void* dst, uint32_t src, uint32_t bytes) {
  asm volatile("cp.async.bulk.global.shared::cta.bulk_group [%0], [%1], %2;" :: "l"(dst), "r"(src), "r"(bytes) : "memory"); }
__device__ __forceinline__ void bulk_commit() { asm volatile("cp.async.bulk.commit_group;" ::: "memory"); }
template <int N> __device__ __forceinline__ void bulk_wait_read() { asm volatile("cp.async.bulk.wait_group.read %0;" :: "n"(N) : "memory"); }
template <int N> __device__ __forceinline__ void bulk_wait() { asm volatile("cp.async.bulk.wait_group %0;" :: "n"(N) : "memory"); }

__device__ __forceinline__ uint64_t mkdesc(uint32_t addr, uint32_t lbo, uint32_t sbo, uint32_t sw) {
  return (uint64_t)((addr & 0x3FFFF) >> 4) | ((uint64_t)(lbo >> 4) << 16) | ((uint64_t)(sbo >> 4) << 32) | ((uint64_t)sw << 62); }
__device__ __forceinline__ void wg_fence() { asm volatile("wgmma.fence.sync.aligned;" ::: "memory"); }
__device__ __forceinline__ void wg_commit() { asm volatile("wgmma.commit_group.sync.aligned;" ::: "memory"); }
template <int N> __device__ __forceinline__ void wg_wait() { asm volatile("wgmma.wait_group.sync.aligned %0;" :: "n"(N) : "memory"); }
template <int N> __device__ __forceinline__ void reg_fence(float* d) {
#pragma unroll
  for (int i = 0; i < N; i++) asm volatile("" : "+f"(d[i]) :: "memory");
}

__device__ __forceinline__ void mma16(float* d, uint32_t a0, uint32_t a1, uint32_t a2, uint32_t a3, uint32_t b0, uint32_t b1) {
  asm volatile("mma.sync.aligned.m16n8k16.row.col.f32.bf16.bf16.f32 {%0,%1,%2,%3},{%4,%5,%6,%7},{%8,%9},{%0,%1,%2,%3};"
               : "+f"(d[0]), "+f"(d[1]), "+f"(d[2]), "+f"(d[3]) : "r"(a0), "r"(a1), "r"(a2), "r"(a3), "r"(b0), "r"(b1)); }
__device__ __forceinline__ void mma8(float* d, uint32_t a0, uint32_t a1, uint32_t b0) {
  asm volatile("mma.sync.aligned.m16n8k8.row.col.f32.bf16.bf16.f32 {%0,%1,%2,%3},{%4,%5},{%6},{%0,%1,%2,%3};"
               : "+f"(d[0]), "+f"(d[1]), "+f"(d[2]), "+f"(d[3]) : "r"(a0), "r"(a1), "r"(b0)); }
__device__ __forceinline__ void ldsm4(uint32_t* r, uint32_t a) {
  asm volatile("ldmatrix.sync.aligned.m8n8.x4.shared.b16 {%0,%1,%2,%3},[%4];" : "=r"(r[0]), "=r"(r[1]), "=r"(r[2]), "=r"(r[3]) : "r"(a) : "memory"); }
__device__ __forceinline__ uint4 ldsm4v(uint32_t a) { uint32_t r[4]; ldsm4(r, a); return make_uint4(r[0], r[1], r[2], r[3]); }
__device__ __forceinline__ void ldsm4t(uint32_t* r, uint32_t a) {
  asm volatile("ldmatrix.sync.aligned.m8n8.x4.trans.shared.b16 {%0,%1,%2,%3},[%4];" : "=r"(r[0]), "=r"(r[1]), "=r"(r[2]), "=r"(r[3]) : "r"(a) : "memory"); }
__device__ __forceinline__ void ldsm2t(uint32_t* r, uint32_t a) {
  asm volatile("ldmatrix.sync.aligned.m8n8.x2.trans.shared.b16 {%0,%1},[%2];" : "=r"(r[0]), "=r"(r[1]) : "r"(a) : "memory"); }
__device__ __forceinline__ void stsm4(uint32_t a, uint32_t r0, uint32_t r1, uint32_t r2, uint32_t r3) {
  asm volatile("stmatrix.sync.aligned.m8n8.x4.shared.b16 [%0], {%1,%2,%3,%4};" :: "r"(a), "r"(r0), "r"(r1), "r"(r2), "r"(r3) : "memory"); }
__device__ __forceinline__ void stsm4t(uint32_t a, uint32_t r0, uint32_t r1, uint32_t r2, uint32_t r3) {
  asm volatile("stmatrix.sync.aligned.m8n8.x4.trans.shared.b16 [%0], {%1,%2,%3,%4};" :: "r"(a), "r"(r0), "r"(r1), "r"(r2), "r"(r3) : "memory"); }
__device__ __forceinline__ void stsm2(uint32_t a, uint32_t r0, uint32_t r1) {
  asm volatile("stmatrix.sync.aligned.m8n8.x2.shared.b16 [%0], {%1,%2};" :: "r"(a), "r"(r0), "r"(r1) : "memory"); }
__device__ __forceinline__ void stsm2t(uint32_t a, uint32_t r0, uint32_t r1) {
  asm volatile("stmatrix.sync.aligned.m8n8.x2.trans.shared.b16 [%0], {%1,%2};" :: "r"(a), "r"(r0), "r"(r1) : "memory"); }
__device__ __forceinline__ void sts32(uint32_t a, uint32_t v) { asm volatile("st.shared.b32 [%0], %1;" :: "r"(a), "r"(v) : "memory"); }
__device__ __forceinline__ void sts64f(uint32_t a, float x, float y) { asm volatile("st.shared.v2.f32 [%0], {%1,%2};" :: "r"(a), "f"(x), "f"(y) : "memory"); }
__device__ __forceinline__ void sts128(uint32_t a, uint4 v) {
  asm volatile("st.shared.v4.b32 [%0], {%1,%2,%3,%4};" :: "r"(a), "r"(v.x), "r"(v.y), "r"(v.z), "r"(v.w) : "memory"); }
__device__ __forceinline__ void sts128f(uint32_t a, float x, float y, float z, float w) {
  asm volatile("st.shared.v4.f32 [%0], {%1,%2,%3,%4};" :: "r"(a), "f"(x), "f"(y), "f"(z), "f"(w) : "memory"); }
__device__ __forceinline__ float lds32f(uint32_t a) { float v; asm volatile("ld.shared.f32 %0, [%1];" : "=f"(v) : "r"(a) : "memory"); return v; }
__device__ __forceinline__ float2 lds64f(uint32_t a) { float2 v; asm volatile("ld.shared.v2.f32 {%0,%1}, [%2];" : "=f"(v.x), "=f"(v.y) : "r"(a) : "memory"); return v; }
__device__ __forceinline__ float4 lds128f(uint32_t a) {
  float4 v; asm volatile("ld.shared.v4.f32 {%0,%1,%2,%3}, [%4];" : "=f"(v.x), "=f"(v.y), "=f"(v.z), "=f"(v.w) : "r"(a) : "memory"); return v; }
__device__ __forceinline__ uint4 lds128(uint32_t a) {
  uint4 v; asm volatile("ld.shared.v4.b32 {%0,%1,%2,%3}, [%4];" : "=r"(v.x), "=r"(v.y), "=r"(v.z), "=r"(v.w) : "r"(a) : "memory"); return v; }
__device__ __forceinline__ uint4 ldg_strong128(const void* p) {
  uint4 v; asm volatile("ld.relaxed.gpu.global.v4.u32 {%0,%1,%2,%3}, [%4];" : "=r"(v.x), "=r"(v.y), "=r"(v.z), "=r"(v.w) : "l"(p) : "memory"); return v; }
__device__ __forceinline__ uint2 ldg_strong64(const void* p) {
  uint2 v; asm volatile("ld.relaxed.gpu.global.v2.u32 {%0,%1}, [%2];" : "=r"(v.x), "=r"(v.y) : "l"(p) : "memory"); return v; }
__device__ __forceinline__ void stg_strong32(void* p, uint32_t v) { asm volatile("st.relaxed.gpu.global.u32 [%0], %1;" :: "l"(p), "r"(v) : "memory"); }
__device__ __forceinline__ void stg_strong128(void* p, uint4 v) {
  asm volatile("st.relaxed.gpu.global.v4.u32 [%0], {%1,%2,%3,%4};" :: "l"(p), "r"(v.x), "r"(v.y), "r"(v.z), "r"(v.w) : "memory"); }
__device__ __forceinline__ uint32_t mapa(uint32_t a, uint32_t r) {
  uint32_t o; asm("mapa.shared::cluster.u32 %0, %1, %2;" : "=r"(o) : "r"(a), "r"(r)); return o; }
__device__ __forceinline__ void st_async2f(uint32_t a, float x, float y, uint32_t bar) {
  asm volatile("st.async.shared::cluster.mbarrier::complete_tx::bytes.v2.f32 [%0], {%1,%2}, [%3];" :: "r"(a), "f"(x), "f"(y), "r"(bar) : "memory"); }
__device__ __forceinline__ void st_async32(uint32_t a, uint32_t x, uint32_t bar) {
  asm volatile("st.async.shared::cluster.mbarrier::complete_tx::bytes.b32 [%0], %1, [%2];" :: "r"(a), "r"(x), "r"(bar) : "memory"); }
__device__ __forceinline__ uint32_t lds32(uint32_t a) { uint32_t v; asm volatile("ld.shared.b32 %0, [%1];" : "=r"(v) : "r"(a) : "memory"); return v; }
__device__ __forceinline__ void st_async64(uint32_t a, uint32_t x, uint32_t y, uint32_t bar) {
  asm volatile("st.async.shared::cluster.mbarrier::complete_tx::bytes.v2.b32 [%0], {%1,%2}, [%3];" :: "r"(a), "r"(x), "r"(y), "r"(bar) : "memory"); }
__device__ __forceinline__ void st_async128(uint32_t a, uint4 v, uint32_t bar) {
  asm volatile("st.async.shared::cluster.mbarrier::complete_tx::bytes.v4.b32 [%0], {%1,%2,%3,%4}, [%5];" :: "r"(a), "r"(v.x), "r"(v.y), "r"(v.z), "r"(v.w), "r"(bar) : "memory"); }
__device__ __forceinline__ uint2 lds64(uint32_t a) { uint2 v; asm volatile("ld.shared.v2.b32 {%0,%1}, [%2];" : "=r"(v.x), "=r"(v.y) : "r"(a) : "memory"); return v; }
__device__ __forceinline__ void sts64(uint32_t a, uint32_t x, uint32_t y) { asm volatile("st.shared.v2.b32 [%0], {%1,%2};" :: "r"(a), "r"(x), "r"(y) : "memory"); }
__device__ __forceinline__ uint32_t ldg_strong32(const void* p) { uint32_t v; asm volatile("ld.relaxed.gpu.global.u32 %0, [%1];" : "=r"(v) : "l"(p) : "memory"); return v; }
__device__ __forceinline__ uint32_t transpose8(uint32_t x) { uint32_t r; asm volatile("movmatrix.sync.aligned.m8n8.trans.b16 %0, %1;" : "=r"(r) : "r"(x)); return r; }
__device__ __forceinline__ uint32_t hadd2(uint32_t a, uint32_t b) { uint32_t r; asm("add.rn.bf16x2 %0, %1, %2;" : "=r"(r) : "r"(a), "r"(b)); return r; }
__device__ __forceinline__ uint32_t min4(uint4 v) { return min(__vimin3_u32(v.x, v.y, v.z), v.w); }

__device__ __forceinline__ void wg_ss192_01(float* d, uint64_t da, uint64_t db, int sd) {
  asm volatile("{.reg .pred p; setp.ne.b32 p, %98, 0;\n"
    "wgmma.mma_async.sync.aligned.m64n192k16.f32.bf16.bf16 {%0,%1,%2,%3,%4,%5,%6,%7,%8,%9,%10,%11,%12,%13,%14,%15,%16,%17,%18,%19,%20,%21,%22,%23,%24,%25,%26,%27,%28,%29,%30,%31,%32,%33,%34,%35,%36,%37,%38,%39,%40,%41,%42,%43,%44,%45,%46,%47,%48,%49,%50,%51,%52,%53,%54,%55,%56,%57,%58,%59,%60,%61,%62,%63,%64,%65,%66,%67,%68,%69,%70,%71,%72,%73,%74,%75,%76,%77,%78,%79,%80,%81,%82,%83,%84,%85,%86,%87,%88,%89,%90,%91,%92,%93,%94,%95}, %96, %97, p, 1, 1, 0, 1;}"
    : "+f"(d[0]),"+f"(d[1]),"+f"(d[2]),"+f"(d[3]),"+f"(d[4]),"+f"(d[5]),"+f"(d[6]),"+f"(d[7]),"+f"(d[8]),"+f"(d[9]),"+f"(d[10]),"+f"(d[11]),"+f"(d[12]),"+f"(d[13]),"+f"(d[14]),"+f"(d[15]),"+f"(d[16]),"+f"(d[17]),"+f"(d[18]),"+f"(d[19]),"+f"(d[20]),"+f"(d[21]),"+f"(d[22]),"+f"(d[23]),"+f"(d[24]),"+f"(d[25]),"+f"(d[26]),"+f"(d[27]),"+f"(d[28]),"+f"(d[29]),"+f"(d[30]),"+f"(d[31]),"+f"(d[32]),"+f"(d[33]),"+f"(d[34]),"+f"(d[35]),"+f"(d[36]),"+f"(d[37]),"+f"(d[38]),"+f"(d[39]),"+f"(d[40]),"+f"(d[41]),"+f"(d[42]),"+f"(d[43]),"+f"(d[44]),"+f"(d[45]),"+f"(d[46]),"+f"(d[47]),"+f"(d[48]),"+f"(d[49]),"+f"(d[50]),"+f"(d[51]),"+f"(d[52]),"+f"(d[53]),"+f"(d[54]),"+f"(d[55]),"+f"(d[56]),"+f"(d[57]),"+f"(d[58]),"+f"(d[59]),"+f"(d[60]),"+f"(d[61]),"+f"(d[62]),"+f"(d[63]),"+f"(d[64]),"+f"(d[65]),"+f"(d[66]),"+f"(d[67]),"+f"(d[68]),"+f"(d[69]),"+f"(d[70]),"+f"(d[71]),"+f"(d[72]),"+f"(d[73]),"+f"(d[74]),"+f"(d[75]),"+f"(d[76]),"+f"(d[77]),"+f"(d[78]),"+f"(d[79]),"+f"(d[80]),"+f"(d[81]),"+f"(d[82]),"+f"(d[83]),"+f"(d[84]),"+f"(d[85]),"+f"(d[86]),"+f"(d[87]),"+f"(d[88]),"+f"(d[89]),"+f"(d[90]),"+f"(d[91]),"+f"(d[92]),"+f"(d[93]),"+f"(d[94]),"+f"(d[95])
    : "l"(da), "l"(db), "r"(sd));
}
__device__ __forceinline__ void wg_ss128_01(float* d, uint64_t da, uint64_t db, int sd) {
  asm volatile("{.reg .pred p; setp.ne.b32 p, %66, 0;\n"
    "wgmma.mma_async.sync.aligned.m64n128k16.f32.bf16.bf16 {%0,%1,%2,%3,%4,%5,%6,%7,%8,%9,%10,%11,%12,%13,%14,%15,%16,%17,%18,%19,%20,%21,%22,%23,%24,%25,%26,%27,%28,%29,%30,%31,%32,%33,%34,%35,%36,%37,%38,%39,%40,%41,%42,%43,%44,%45,%46,%47,%48,%49,%50,%51,%52,%53,%54,%55,%56,%57,%58,%59,%60,%61,%62,%63}, %64, %65, p, 1, 1, 0, 1;}"
    : "+f"(d[0]),"+f"(d[1]),"+f"(d[2]),"+f"(d[3]),"+f"(d[4]),"+f"(d[5]),"+f"(d[6]),"+f"(d[7]),"+f"(d[8]),"+f"(d[9]),"+f"(d[10]),"+f"(d[11]),"+f"(d[12]),"+f"(d[13]),"+f"(d[14]),"+f"(d[15]),"+f"(d[16]),"+f"(d[17]),"+f"(d[18]),"+f"(d[19]),"+f"(d[20]),"+f"(d[21]),"+f"(d[22]),"+f"(d[23]),"+f"(d[24]),"+f"(d[25]),"+f"(d[26]),"+f"(d[27]),"+f"(d[28]),"+f"(d[29]),"+f"(d[30]),"+f"(d[31]),"+f"(d[32]),"+f"(d[33]),"+f"(d[34]),"+f"(d[35]),"+f"(d[36]),"+f"(d[37]),"+f"(d[38]),"+f"(d[39]),"+f"(d[40]),"+f"(d[41]),"+f"(d[42]),"+f"(d[43]),"+f"(d[44]),"+f"(d[45]),"+f"(d[46]),"+f"(d[47]),"+f"(d[48]),"+f"(d[49]),"+f"(d[50]),"+f"(d[51]),"+f"(d[52]),"+f"(d[53]),"+f"(d[54]),"+f"(d[55]),"+f"(d[56]),"+f"(d[57]),"+f"(d[58]),"+f"(d[59]),"+f"(d[60]),"+f"(d[61]),"+f"(d[62]),"+f"(d[63])
    : "l"(da), "l"(db), "r"(sd));
}
__device__ __forceinline__ void wg_ss160_01(float* d, uint64_t da, uint64_t db, int sd) {
  asm volatile("{.reg .pred p; setp.ne.b32 p, %82, 0;\n"
    "wgmma.mma_async.sync.aligned.m64n160k16.f32.bf16.bf16 {%0,%1,%2,%3,%4,%5,%6,%7,%8,%9,%10,%11,%12,%13,%14,%15,%16,%17,%18,%19,%20,%21,%22,%23,%24,%25,%26,%27,%28,%29,%30,%31,%32,%33,%34,%35,%36,%37,%38,%39,%40,%41,%42,%43,%44,%45,%46,%47,%48,%49,%50,%51,%52,%53,%54,%55,%56,%57,%58,%59,%60,%61,%62,%63,%64,%65,%66,%67,%68,%69,%70,%71,%72,%73,%74,%75,%76,%77,%78,%79}, %80, %81, p, 1, 1, 0, 1;}"
    : "+f"(d[0]),"+f"(d[1]),"+f"(d[2]),"+f"(d[3]),"+f"(d[4]),"+f"(d[5]),"+f"(d[6]),"+f"(d[7]),"+f"(d[8]),"+f"(d[9]),"+f"(d[10]),"+f"(d[11]),"+f"(d[12]),"+f"(d[13]),"+f"(d[14]),"+f"(d[15]),"+f"(d[16]),"+f"(d[17]),"+f"(d[18]),"+f"(d[19]),"+f"(d[20]),"+f"(d[21]),"+f"(d[22]),"+f"(d[23]),"+f"(d[24]),"+f"(d[25]),"+f"(d[26]),"+f"(d[27]),"+f"(d[28]),"+f"(d[29]),"+f"(d[30]),"+f"(d[31]),"+f"(d[32]),"+f"(d[33]),"+f"(d[34]),"+f"(d[35]),"+f"(d[36]),"+f"(d[37]),"+f"(d[38]),"+f"(d[39]),"+f"(d[40]),"+f"(d[41]),"+f"(d[42]),"+f"(d[43]),"+f"(d[44]),"+f"(d[45]),"+f"(d[46]),"+f"(d[47]),"+f"(d[48]),"+f"(d[49]),"+f"(d[50]),"+f"(d[51]),"+f"(d[52]),"+f"(d[53]),"+f"(d[54]),"+f"(d[55]),"+f"(d[56]),"+f"(d[57]),"+f"(d[58]),"+f"(d[59]),"+f"(d[60]),"+f"(d[61]),"+f"(d[62]),"+f"(d[63]),"+f"(d[64]),"+f"(d[65]),"+f"(d[66]),"+f"(d[67]),"+f"(d[68]),"+f"(d[69]),"+f"(d[70]),"+f"(d[71]),"+f"(d[72]),"+f"(d[73]),"+f"(d[74]),"+f"(d[75]),"+f"(d[76]),"+f"(d[77]),"+f"(d[78]),"+f"(d[79])
    : "l"(da), "l"(db), "r"(sd));
}
__device__ __forceinline__ void wg_ss80_01(float* d, uint64_t da, uint64_t db, int sd) {
  asm volatile("{.reg .pred p; setp.ne.b32 p, %42, 0;\n"
    "wgmma.mma_async.sync.aligned.m64n80k16.f32.bf16.bf16 {%0,%1,%2,%3,%4,%5,%6,%7,%8,%9,%10,%11,%12,%13,%14,%15,%16,%17,%18,%19,%20,%21,%22,%23,%24,%25,%26,%27,%28,%29,%30,%31,%32,%33,%34,%35,%36,%37,%38,%39}, %40, %41, p, 1, 1, 0, 1;}"
    : "+f"(d[0]),"+f"(d[1]),"+f"(d[2]),"+f"(d[3]),"+f"(d[4]),"+f"(d[5]),"+f"(d[6]),"+f"(d[7]),"+f"(d[8]),"+f"(d[9]),"+f"(d[10]),"+f"(d[11]),"+f"(d[12]),"+f"(d[13]),"+f"(d[14]),"+f"(d[15]),"+f"(d[16]),"+f"(d[17]),"+f"(d[18]),"+f"(d[19]),"+f"(d[20]),"+f"(d[21]),"+f"(d[22]),"+f"(d[23]),"+f"(d[24]),"+f"(d[25]),"+f"(d[26]),"+f"(d[27]),"+f"(d[28]),"+f"(d[29]),"+f"(d[30]),"+f"(d[31]),"+f"(d[32]),"+f"(d[33]),"+f"(d[34]),"+f"(d[35]),"+f"(d[36]),"+f"(d[37]),"+f"(d[38]),"+f"(d[39])
    : "l"(da), "l"(db), "r"(sd));
}
__device__ __forceinline__ void wg_rs32_00(float* d, uint32_t a0, uint32_t a1, uint32_t a2, uint32_t a3, uint64_t db, int sd) {
  asm volatile("{.reg .pred p; setp.ne.b32 p, %21, 0;\n"
    "wgmma.mma_async.sync.aligned.m64n32k16.f32.bf16.bf16 {%0,%1,%2,%3,%4,%5,%6,%7,%8,%9,%10,%11,%12,%13,%14,%15}, {%16,%17,%18,%19}, %20, p, 1, 1, 0;}"
    : "+f"(d[0]),"+f"(d[1]),"+f"(d[2]),"+f"(d[3]),"+f"(d[4]),"+f"(d[5]),"+f"(d[6]),"+f"(d[7]),"+f"(d[8]),"+f"(d[9]),"+f"(d[10]),"+f"(d[11]),"+f"(d[12]),"+f"(d[13]),"+f"(d[14]),"+f"(d[15])
    : "r"(a0), "r"(a1), "r"(a2), "r"(a3), "l"(db), "r"(sd));
}
__device__ __forceinline__ void wg_rs64_00(float* d, uint32_t a0, uint32_t a1, uint32_t a2, uint32_t a3, uint64_t db, int sd) {
  asm volatile("{.reg .pred p; setp.ne.b32 p, %37, 0;\n"
    "wgmma.mma_async.sync.aligned.m64n64k16.f32.bf16.bf16 {%0,%1,%2,%3,%4,%5,%6,%7,%8,%9,%10,%11,%12,%13,%14,%15,%16,%17,%18,%19,%20,%21,%22,%23,%24,%25,%26,%27,%28,%29,%30,%31}, {%32,%33,%34,%35}, %36, p, 1, 1, 0;}"
    : "+f"(d[0]),"+f"(d[1]),"+f"(d[2]),"+f"(d[3]),"+f"(d[4]),"+f"(d[5]),"+f"(d[6]),"+f"(d[7]),"+f"(d[8]),"+f"(d[9]),"+f"(d[10]),"+f"(d[11]),"+f"(d[12]),"+f"(d[13]),"+f"(d[14]),"+f"(d[15]),"+f"(d[16]),"+f"(d[17]),"+f"(d[18]),"+f"(d[19]),"+f"(d[20]),"+f"(d[21]),"+f"(d[22]),"+f"(d[23]),"+f"(d[24]),"+f"(d[25]),"+f"(d[26]),"+f"(d[27]),"+f"(d[28]),"+f"(d[29]),"+f"(d[30]),"+f"(d[31])
    : "r"(a0), "r"(a1), "r"(a2), "r"(a3), "l"(db), "r"(sd));
}
__device__ __forceinline__ void wg_rs24_01(float* d, uint32_t a0, uint32_t a1, uint32_t a2, uint32_t a3, uint64_t db, int sd) {
  asm volatile("{.reg .pred p; setp.ne.b32 p, %17, 0;\n"
    "wgmma.mma_async.sync.aligned.m64n24k16.f32.bf16.bf16 {%0,%1,%2,%3,%4,%5,%6,%7,%8,%9,%10,%11}, {%12,%13,%14,%15}, %16, p, 1, 1, 1;}"
    : "+f"(d[0]),"+f"(d[1]),"+f"(d[2]),"+f"(d[3]),"+f"(d[4]),"+f"(d[5]),"+f"(d[6]),"+f"(d[7]),"+f"(d[8]),"+f"(d[9]),"+f"(d[10]),"+f"(d[11])
    : "r"(a0), "r"(a1), "r"(a2), "r"(a3), "l"(db), "r"(sd));
}

#define AB_POLY 0x77
__device__ __forceinline__ constexpr bool poly_group(int group) { return (AB_POLY >> (group & 7)) & 1; }

template <int V> struct Int { static constexpr int value = V; };

__device__ __forceinline__ int core_word(int row, int col) {
  return ((((row >> 7) * 10 + (col >> 6)) * 16 + ((row >> 3) & 15)) * 8 + ((col >> 3) & 7)) * 32 + (row & 7) * 4 + ((col & 7) >> 1);
}
__device__ __forceinline__ void wait_count(const uint32_t* c, uint32_t n) {
  int spin = 0;
  while ((ld_acquire(c) & 0xffff) < n) { __nanosleep(32); spin_guard(spin); }
}
__device__ __forceinline__ void wait_count_uniform(const uint32_t* c, uint32_t n) {
  for (int spin = 0; !__all_sync(~0u, (ld_acquire(c) & 0xffff) >= n);) { __nanosleep(32); spin_guard(spin); }
  fence_async_global();
}
__device__ __forceinline__ void prefetch_l2(const void* p, uint32_t bytes) {
  asm volatile("cp.async.bulk.prefetch.L2.global [%0], %1;" :: "l"(p), "r"(bytes) : "memory"); }

#define PLACE 4
__device__ __forceinline__ bool helper_sm() {
  uint32_t m; asm volatile("mov.u32 %0, %%smid;" : "=r"(m));
  return m < 2 || m >= 120 || (m >= 92 && m < 102) || (m >= 106 && m < 117) || m == 118;
}

__device__ __forceinline__ uint8_t* pool_at(uint32_t off) {
  return reinterpret_cast<uint8_t*>((reinterpret_cast<uintptr_t>(g_pool) + 8191) & ~(uintptr_t)8191) + off; }
__device__ __forceinline__ uint32_t page_latency(uint32_t* w) {
  uint32_t best = ~0u;
  stg_strong32(w, 0u);
  for (int r = 0; r < 4; r++) {
    uint32_t t0, t1, v;
    asm volatile("mov.u32 %0, %%clock;" : "=r"(t0) :: "memory");
    asm volatile("atom.relaxed.gpu.global.exch.b32 %0, [%1], 0;" : "=r"(v) : "l"(w) : "memory");
    asm volatile("{.reg .u32 t; add.u32 t, %1, 1; mov.u32 %0, %%clock; sub.u32 %0, %0, %1;}" : "=r"(t1) : "r"(__shfl_sync(1u, v, 0)) : "memory");
    best = min(best, t1 - t0);
  }
  return best;
}
__device__ __forceinline__ void probe_slots(uint32_t scratch) {
  const int w = (threadIdx.x >> 6) & 1, slot = w == 0 ? NSLOT : blockIdx.x;
  if ((threadIdx.x & 31) == 0 && (w == 0 || slot < NSLOT)) {
    uint32_t* q = reinterpret_cast<uint32_t*>(pool_at(slot * 8192)) + (w == 0 ? (blockIdx.x & 31) * 32 + (blockIdx.x >> 5) : 0);
    sts32(scratch + w * 4, page_latency(q) < page_latency(q + 1024));
  }
  bar_sync(2, 64);
  if ((threadIdx.x & 31) == 0) {
    const int part = lds32(scratch) ? 1 : 2;
    if (w == 0) { uint32_t smid; asm("mov.u32 %0, %%smid;" : "=r"(smid)); stg_strong32(g_smpart + (smid & 255), part); }
    else if (slot < NSLOT) stg_strong32(g_orient + slot, lds32(scratch + 4) ? part : 3 - part);
  }
  __syncwarp();
}

constexpr int WK_SLOTS = 28, WK_BAR = WK_SLOTS * 8192;
__device__ __forceinline__ void work_init(uint32_t sb) {
  const int i = fresh_tid() & 31;
  mbar_init(sb + WK_BAR + 8 * i, i < 8 ? 2 : i < 16 ? 8 : i < 20 ? 1 : i < 24 ? 3 : i < 28 ? 8 : 1);
  asm volatile("fence.mbarrier_init.release.cluster;" ::: "memory");
}

struct ChainParams {
  CUtensorMap wq, wk, wv, wo;
  const __nv_bfloat16* mem0;
  const uint8_t* wb;
  uint32_t *sync, *other;
  int layer;
  int d1, d2, dn, dx, mode, zero;
};
constexpr int CH_WQ = 0, CH_WO = 81920, CH_X = CH_WO + 86016, CH_M = CH_X, CH_Q = CH_X + 34816, CH_KM = CH_Q + 2048, CH_VP = CH_KM + 2048,
              CH_K = CH_X + 40960, CH_O = CH_K, CH_KS = CH_K + 3072, CH_V = CH_K + 4096, CH_VX = CH_V + 12288, CH_R2 = CH_VX,
              CH_SX = CH_VX + 3072, CH_SO = CH_SX + 2048, CH_ID = CH_SO + 1024, CH_L = CH_ID + 256, CH_TAB = CH_L + 64, CH_BAR = CH_TAB + 384;
constexpr int CH_SMEM = CH_BAR + 144;
constexpr int MB_WO = CH_BAR, MB_WQ = CH_BAR + 8, MB_X = CH_BAR + 16, MB_V = CH_BAR + 24, MB_T = CH_BAR + 32, MB_F = CH_BAR + 40, MB_G = CH_BAR + 48, MB_W = CH_BAR + 56;
enum { NB_PROJ = 1, NB_O = 2, NB_W1 = 3, NB_PRE = 4, NB_ST = 5, NB_MEM = 6, NB_XFREE = 7, NB_H1 = 8, NB_PUB = 9, NB_W2 = 10, NB_PROJ2 = 11, NB_PRE2 = 12, NB_H2 = 13, NB_W1V = 14 };
#define CH_NQ 9
#define CH_VD 4
#define CH_TPRE 0
#define CH_XPF 1
#define CH_TPF 1
#define CH_LAG 0
#define CH_PUSH 1
#define CH_CHAIN 0
#define CH_GATE 1
#define CH_PA 6
#define CH_PB 10
#define CH_PC 12
#define CH_PL 3
#define CH_DBL 0x2108
#define CH_PD 2
#define CH_ZD 1
#define SCHED() asm volatile("griddepcontrol.launch_dependents;" ::: "memory")
__device__ __forceinline__ uint32_t opaque(uint32_t x) { return __shfl_sync(~0u, x, threadIdx.x & 31); }
__device__ __forceinline__ uint32_t nz(uint32_t x) { uint32_t r; asm("max.u32 %0, %1, 1;" : "=r"(r) : "r"(x)); return r; }
__device__ __forceinline__ uint32_t set_tag(uint32_t w, uint32_t tag) { uint32_t r; asm("lop3.b32 %0, %1, %2, 1, 0xD8;" : "=r"(r) : "r"(w), "r"(tag)); return r; }
__device__ __forceinline__ uint32_t pack_tag(float lo, float hi, uint32_t tag) { return set_tag(__byte_perm(__float_as_uint(lo) + tag, pack2(hi, hi), 0x7632), tag); }
__device__ __forceinline__ uint32_t differ(uint32_t a, uint32_t b, uint32_t t) { uint32_t r; asm("lop3.b32 %0, %1, %2, %3, 0x7E;" : "=r"(r) : "r"(a), "r"(b), "r"(t)); return r; }
__device__ __forceinline__ uint32_t clk64() { uint64_t c; asm volatile("mov.u64 %0, %%clock64;" : "=l"(c) :: "memory"); return (uint32_t)c; }
__device__ __forceinline__ void until(uint32_t t) { while ((int)(clk64() - t) < 0) {} }
__device__ __forceinline__ float rcp(float x) { float y; asm("rcp.approx.ftz.f32 %0, %1;" : "=f"(y) : "f"(x)); return y; }

__device__ __forceinline__ void push_values(uint32_t sb, int s, int j) {
  const int r1 = j == 2 ? 0 : j + 1, r2 = j == 0 ? 2 : j - 1;
  const uint32_t src = sb + CH_V + j * 4096;
  if (s < NSEG - 1) {
    fence_async();
    bulk_push(mapa(src, r1), src, 4096, mapa(sb + MB_V, r1));
    bulk_push(mapa(src, r2), src, 4096, mapa(sb + MB_V, r2));
  }
}

template <int WG>
__device__ __forceinline__ void chain_compute(const ChainParams& p, const uint32_t sb) {
  const int tid = threadIdx.x & 127, t4 = __shfl_sync(~0u, tid >> 5, 0), lane = tid & 31;
  const int cta = blockIdx.x, h = cta / 3, j = cta - 3 * h;
  uint32_t ak[80], av[80], tw[4 * CH_NQ];
  const uint32_t wq = opaque(sb + CH_WQ + (WG * 320 + (lane & 7) + (lane >> 4) * 8) * 128 + (((2 * t4 + ((lane >> 3) & 1)) ^ (lane & 7)) << 4));
#pragma unroll
  for (int k = 0; k < 20; k++) {
    if (k == 0 || (WG * 20 + k) % 8 == 0) mbar_wait(sb + MB_W + 8 * ((WG * 20 + k) / 8), 0);
    ldsm4t(&ak[4 * k], wq + k * 2048);
  }
  bar_arrive(NB_PROJ2, 384);
#pragma unroll
  for (int k = 0; k < 20; k++) {
    if (k == 0 || (WG * 20 + k) % 8 == 0) mbar_wait(sb + MB_W + 40 + 8 * ((WG * 20 + k) / 8), 0);
    ldsm4t(&av[4 * k], wq + CH_WO + k * 2048);
  }
  bar_arrive(NB_PRE2, 384);
  const int r1 = j == 2 ? 0 : j + 1, r2 = j == 0 ? 2 : j - 1;
  const uint32_t l8 = opaque(sb + lane * 8), l4 = opaque(sb + lane * 4);
  uint32_t l16 = opaque(sb + lane * 16), t16 = l16 + t4 * 512, t8 = l8 + t4 * 256;
  auto refill = [&]() {
#pragma unroll
    for (int k = 0; k < CH_NQ; k++) ldsm4t(&tw[4 * k], wq + k * 2048);
  };
  auto batch = [&](float* d, const uint32_t (&a)[80], int acc, bool fill) {
    const uint64_t d0 = mkdesc(1024 + CH_X + WG * 20480, 128, 5120, 0);
    wg_fence();
#pragma unroll
    for (int k = 0; k < 20; k++) {
      if (fill && !(k & 1) && k / 2 < CH_NQ) {
        __syncwarp();
        if (CH_CHAIN && k >= 2 * CH_CHAIN) { sts32(l4 + CH_SO, tw[CH_CHAIN ? 2 * k + 3 - 4 * CH_CHAIN : 0]); __syncwarp(); }
        ldsm4t(&tw[2 * k], wq + k * 1024);
        __syncwarp();
      }
      wg_rs32_00(d, a[4 * k], a[4 * k + 1], a[4 * k + 2], a[4 * k + 3], d0 + k * 16, acc | k);
    }
    wg_commit();
    wg_wait<0>();
    reg_fence<16>(d);
  };
  auto tokens = [&](int s, auto first) {
    float d[16];
    if (first.value || !CH_TPRE) mbar_wait(sb + MB_T, s & 1);
    batch(d, WG == 0 ? ak : av, 0, WG == 0 && !first.value);
    s--; TM(10); s++;
    if (WG == 1 && !first.value) mbar_wait(sb + MB_F, (s - 1) & 1);
    const uint32_t kt = t16 + CH_K, vt = t16 + CH_V + j * 4096;
#pragma unroll
    for (int i = 0; i < 2; i++)
      sts128((WG == 0 ? kt : vt) + i * 2048, make_uint4(pack2(d[8 * i], d[8 * i + 1]), pack2(d[8 * i + 2], d[8 * i + 3]), pack2(d[8 * i + 4], d[8 * i + 5]), pack2(d[8 * i + 6], d[8 * i + 7])));
    if (first.value || CH_GATE != 1) bar_sync(NB_H1, 256); else bar_sync(NB_PUB, 384);
    const uint32_t own = WG == 0 ? vt : kt;
#pragma unroll
    for (int i = 0; i < 2; i++) {
      const uint4 t = lds128(own + i * 2048);
      d[8 * i] = bf_lo(t.x); d[8 * i + 1] = bf_hi(t.x); d[8 * i + 2] = bf_lo(t.y); d[8 * i + 3] = bf_hi(t.y);
      d[8 * i + 4] = bf_lo(t.z); d[8 * i + 5] = bf_hi(t.z); d[8 * i + 6] = bf_lo(t.w); d[8 * i + 7] = bf_hi(t.w);
    }
    reg_fence<16>(d);
    if (!first.value && CH_GATE == 2) bar_sync(NB_PUB, 384);
    batch(d, WG == 0 ? av : ak, 1, WG == 1 && !first.value);
    s--; TM(11); s++;
    if (WG == 0) bar_arrive(NB_XFREE, 256);
#pragma unroll
    for (int i = 0; i < 2; i++) {
      const uint32_t w0 = pack2(d[8 * i], d[8 * i + 1]), w1 = pack2(d[8 * i + 2], d[8 * i + 3]), w2 = pack2(d[8 * i + 4], d[8 * i + 5]), w3 = pack2(d[8 * i + 6], d[8 * i + 7]);
      if (WG == 1) stsm4t(own + i * 2048, w0, w1, w2, w3); else stsm4(own + i * 2048, w0, w1, w2, w3);
    }
    if (CH_PUSH == 0 && WG == 0) {
      if (t4 == 0) {
        bar_sync(NB_H2, 128);
        if (elect()) push_values(sb, s, j);
        __syncwarp();
      } else {
        bar_arrive(NB_H2, 128);
      }
    }
    if (first.value) { mbar_wait(sb + MB_WQ, 0); refill(); mbar_wait(sb + MB_WO, 0); }
  };
  asm volatile("barrier.cluster.wait.aligned;" ::: "memory");
  tokens(0, Int<1>());
  uint32_t wo = opaque(sb + CH_WO + (WG == 0 ? (t4 >> 1) * 36864 : 73728 + t4 * 1024) + ((lane & 7) + (lane >> 4) * 8) * 64 +
                             (((((lane >> 3) & 1) + (WG == 0 ? (t4 & 1) * 2 : 0)) ^ ((lane >> 1) & 3)) << 4));
  const uint32_t ko0 = __shfl_sync(~0u, (tid >> 6) * 3072 + (tid & 32) * 8, 0), ko1 = __shfl_sync(~0u, (tid >> 6) * 1024 + 1024 + (tid & 32) * 8, 0);
  uint32_t tag = opaque(1);
  const uint32_t o768 = __shfl_sync(~0u, (tid >> 5) * 768, 0);
  bar_sync(NB_ST, 384);
  uint8_t* pdst[WG == 0 ? 6 : 1];
#pragma unroll
  for (int i = 0; i < (WG == 0 ? 6 : 1); i++) {
    const int line = WG == 0 ? 24 * j + 12 * (t4 >> 1) + 2 * (t4 & 1) + 4 * (i >> 1) + (i & 1) : j == 0 ? 72 + t4 : 74 + 2 * j + (t4 & 1);
    pdst[i] = pool_at(__shfl_sync(~0u, lds32(sb + CH_TAB + line * 4), 0) + h * 128);
  }
  auto project = [&](int s, float (&dv)[4], uint4 (&kf)[2], auto last) {
    float dq[4] = {}, dk[4] = {};
    uint32_t b[40], w[80];
#pragma unroll
    for (int i = 0; i < 4 * CH_NQ; i++) w[i] = tw[i];
    bar_sync(NB_MEM, 384);
    ldsm4t(&b[0], l16 + CH_M + WG * 5120);
    ldsm4t(&b[4], l16 + CH_M + WG * 5120 + 512);
    TMD(0, b[0]);
    int nw = last.value ? 22 : CH_NQ, nb = 2;
#pragma unroll
    for (int k = 0; k < 20; k++) {
      SCHED();
      if (!last.value) mma16(dq, w[4 * k], w[4 * k + 1], w[4 * k + 2], w[4 * k + 3], b[2 * k], b[2 * k + 1]);
      mma16(dk, ak[4 * k], ak[4 * k + 1], ak[4 * k + 2], ak[4 * k + 3], b[2 * k], b[2 * k + 1]);
      if (WG == 1 || k < 20 - CH_VD) mma16(dv, av[4 * k], av[4 * k + 1], av[4 * k + 2], av[4 * k + 3], b[2 * k], b[2 * k + 1]);
#pragma unroll
      for (int i = 0; i < (CH_DBL >> k & 1) + 1; i++) {
        if (nb < 10 && 2 * nb <= nw) { ldsm4t(&b[4 * nb], l16 + CH_M + WG * 5120 + nb * 512); nb++; }
        else if (nw < 20) { ldsm4t(&w[4 * nw], wq + nw * 2048); nw++; }
        else if (WG == 1 && nw < 22) { const uint32_t x = l16 ^ ((ko0 ^ tag) & 256); kf[nw - 20] = ldsm4v(x + (x & 256) + (nw == 20 ? ko0 : ko1) + CH_K); nw++; }
      }
    }
    const float k2 = 0.07216878364870322f * 1.44269504089f;
    if (!last.value) {
      sts32(l4 + t4 * 512 + CH_Q + WG * 128, pack2(dq[0] * k2, dq[1] * k2));
      sts32(l4 + t4 * 512 + CH_Q + WG * 128 + 256, pack2(dq[2] * k2, dq[3] * k2));
    }
    stsm2t(t16 + CH_KM + WG * 256, pack2(dk[0], dk[1]), pack2(dk[2], dk[3]));
    if (WG == 1) sts128f(t16 + CH_VP, dv[0], dv[1], dv[2], dv[3]);
    TM(1);
    bar_sync(NB_PROJ, 256);
    if (WG == 0) {
      float e[3][4] = {};
      SCHED();
#pragma unroll
      for (int k = 20 - CH_VD; k < 20; k++) {
        if (k == 18 - CH_VD / 2) { const float4 pv = lds128f(t16 + CH_VP); dk[0] = pv.x; dk[1] = pv.y; dk[2] = pv.z; dk[3] = pv.w; SCHED(); }
        mma16(k & 3 ? e[(k & 3) - 1] : dv, av[4 * k], av[4 * k + 1], av[4 * k + 2], av[4 * k + 3], b[2 * k], b[2 * k + 1]);
      }
#pragma unroll
      for (int i = 0; i < 4; i++) dv[i] = ((dv[i] + dk[i]) + e[0][i]) + (e[1][i] + e[2][i]);
    }
  };
#pragma unroll 1
  for (int s = 0; s < NSEG - 1; s++) {
    float dv[4] = {};
    uint4 kf[2];
    project(s, dv, kf, Int<0>());
    if (WG == 0) {
      const uint32_t v0 = pack2(dv[0], dv[1]), v1 = pack2(dv[2], dv[3]);
      const uint32_t xo = t8 + CH_VX + j * 1024;
      st_async64(mapa(xo, r1), v0, v1, mapa(sb + MB_X, r1));
      st_async64(mapa(xo, r2), v0, v1, mapa(sb + MB_X, r2));
      sts64(xo, v0, v1);
      __syncwarp();
      if (elect()) mbar_arrive(sb + MB_X);
      bar_arrive(NB_PROJ2, 256);
      TM(3);
      uint32_t w[144];
      auto tile_of = [](int n) { return n < 27 ? n % 3 : (0x26484 >> 2 * (n - 27)) & 3; };
      auto step_of = [](int n) { return n < 27 ? n / 3 : 9 + ((0x29610 >> 2 * (n - 27)) & 3); };
      auto wload = [&](int n) { ldsm4t(&w[4 * n], wo + tile_of(n) * 12288 + (step_of(n) % 3) * 4096 + (step_of(n) / 3) * 1024); };
#pragma unroll
      for (int n = 0; n < CH_PA; n++) wload(n);
      bar_sync(NB_PRE, 256);
#pragma unroll
      for (int n = CH_PA; n < CH_PB; n++) wload(n);
      bar_arrive(NB_PRE2, 256);
      if (CH_PC > CH_PB) {
        mbar_wait(sb + MB_X, s & 1);
        for (int i = 0; i < CH_PD; i++) wo = __shfl_xor_sync(~0u, wo, p.zero);
#pragma unroll
        for (int n = CH_PB; n < CH_PC; n++) wload(n);
      }
      TM(4);
      bar_sync(NB_O, 256);
      {
        float x[3][4] = {};
        uint32_t ob[24];
        float4 l;
        ldsm4t(&ob[0], l16 + CH_O);
        ldsm4t(&ob[4], l16 + CH_O + 512);
        TMD(7, ob[0]);
        int nw = CH_PC, no = 2;
        float i0, i1;
        uint8_t* dst[6];
        uint32_t lo[6], hi[6];
        auto pre = [&](int i) { lo[i] = __float_as_uint(x[i >> 1][2 * (i & 1)] * i0) + tag; hi[i] = pack2(0.f, x[i >> 1][2 * (i & 1) + 1] * i1); };
        auto emit = [&](int i) { stg_strong32(dst[i], set_tag(__byte_perm(lo[i], hi[i], 0x7632), tag)); };
#pragma unroll
        for (int n = 0; n < 36; n++) {
          SCHED();
          mma16(x[tile_of(n)], w[4 * n], w[4 * n + 1], w[4 * n + 2], w[4 * n + 3], ob[step_of(n) * 2], ob[step_of(n) * 2 + 1]);
          if (n >= CH_PL) {
            if (no < 6 && no * 2 <= step_of(min(nw, 35))) { ldsm4t(&ob[4 * no], l16 + CH_O + no * 512); no++; }
            else if (nw < 36) { wload(nw); nw++; }
          }
          if (n == 18) l = lds128f(sb + CH_L + ((l16 ^ tag) & 0x30));
          if (n == 26) { i0 = rcp(l.x + l.y); i1 = rcp(l.z + l.w); asm volatile("" : "+f"(i0), "+f"(i1)); }
          if (n >= 28 && n < 34) { dst[n - 28] = pdst[n - 28] + ((l4 ^ tag) & 0x7c); asm volatile("" : "+l"(dst[n - 28])); }
          if (n == 32) { for (int i = 0; i < 2; i++) { pre(i); asm volatile("" : "+r"(lo[i]), "+r"(hi[i])); } }
          if (n == 33) { emit(0); emit(1); }
        }
        for (int i = 2; i < 6; i++) pre(i);
        for (int i = 2; i < 6; i++) emit(i);
      }
      TM(8);
    } else {
      {
        float d0[4] = {}, d1[4] = {}, dm[4] = {};
        uint32_t q[16], km[4];
#pragma unroll
        for (int e = 0; e < 4; e++) {
          ldsm4t(&q[4 * e], l16 + (e ^ t4) * 512 + CH_Q);
          if (e == 1) ldsm4(km, t16 + CH_KM);
        }
        SCHED();
        mma16(d0, q[0], q[1], q[2], q[3], kf[0].x, kf[0].y);
        mma16(d1, q[4], q[5], q[6], q[7], kf[0].z, kf[0].w);
        mma16(dm, q[0], q[1], q[2], q[3], hadd2(km[0], km[2]), hadd2(km[1], km[3]));
        mma16(d0, q[8], q[9], q[10], q[11], kf[1].x, kf[1].y);
        mma16(d1, q[12], q[13], q[14], q[15], kf[1].z, kf[1].w);
        const uint32_t w0 = pack2((d0[0] + d0[2]) + (d1[0] + d1[2]), (d0[1] + d0[3]) + (d1[1] + d1[3])), w1 = pack2(dm[0] + dm[2], dm[1] + dm[3]);
        const uint32_t xo = l4 + t4 * 128, x1 = mapa(xo, r1), x2 = mapa(xo, r2);
        st_async32(x1 + CH_SX + 512, w1, mapa(sb + MB_X, r1));
        st_async32(x2 + CH_SX + 1536, w1, mapa(sb + MB_X, r2));
        st_async32(x1 + CH_SX, w0, mapa(sb + MB_X, r1));
        st_async32(x2 + CH_SX + 1024, w0, mapa(sb + MB_X, r2));
        sts32(xo + CH_SO, w0);
        sts32(xo + CH_SO + 512, w1);
      }
      TM(3);
      float sc[3][4] = {};
      uint32_t wd[12];
      uint32_t redo;
      auto attend = [&](auto first) {
        uint4 vb[6];
        uint2 vm[3];
        float e[10];
        uint32_t ow[6];
        if (first.value) {
          const uint2 id = lds64(l8 + CH_ID);
          bar_sync(NB_W1V, 160);
          uint32_t r[8];
          ldsm4(r, l16 + CH_SO); ldsm4(r + 4, l16 + CH_SO + 512);
#pragma unroll
          for (int u = 0; u < 6; u++) vb[u] = ldsm4v(t16 + CH_V + u * 2048);
          bar_arrive(NB_PRE, 256);
          uint32_t sxa = l16 + ((l16 ^ tag) & 256) * 3;
          asm volatile("" : "+r"(sxa));
          sxa += CH_SX;
          SCHED();
          mma8(sc[0], r[0], r[1], id.x);
          mma8(sc[1], r[2], r[3], id.x);
          mma16(sc[2], r[4], r[5], r[6], r[7], id.x, id.y);
          TM(7);
          mbar_wait(sb + MB_X, s & 1);
          TM(4);
          uint32_t t[16];
          ldsm4(t, sxa); ldsm4(t + 4, sxa + 256); ldsm4(t + 8, sxa + 512);
          SCHED();
          mma16(sc[0], t[0], t[1], t[2], t[3], id.x, id.y);
          ldsm4(t + 12, sxa + 768);
          SCHED();
          mma16(sc[1], t[4], t[5], t[6], t[7], id.x, id.y);
#pragma unroll
          for (int u = 0; u < 2; u++) vm[u] = lds64(t8 + CH_VX + u * 1024);
          SCHED();
          e[0] = ex2(sc[0][0]);
          mma16(sc[2], t[8], t[9], t[10], t[11], id.x, id.y);
          vm[2] = lds64(t8 + CH_VX + 2048);
          SCHED();
          e[1] = ex2(sc[0][1]);
          ldsm4t(&wd[0], wo);
          SCHED();
          e[2] = ex2(sc[0][2]);
          SCHED();
          e[3] = ex2(sc[0][3]);
          mma16(sc[2], t[12], t[13], t[14], t[15], id.x, id.y);
          SCHED();
          e[4] = ex2(sc[1][0]);
          ldsm4t(&wd[4], wo + 4096);
          SCHED();
          e[5] = ex2(sc[1][1]);
        } else {
#pragma unroll
          for (int u = 0; u < 6; u++) vb[u] = ldsm4v(t16 + CH_V + u * 2048);
#pragma unroll
          for (int u = 0; u < 3; u++) vm[u] = lds64(t8 + CH_VX + u * 1024);
        }
        float o[3][4] = {};
        if (!first.value) {
#pragma unroll
          for (int i = 0; i < 6; i++) e[i] = ex2(sc[i >> 2][i & 3]);
        }
        const uint32_t p1 = pack2(e[0], e[1]), p2 = pack2(e[2], e[3]);
        float l = (e[0] + e[1]) + (e[2] + e[3]);
        asm volatile("" : "+f"(l));
        SCHED();
        e[6] = ex2(sc[1][2]);
        mma16(o[0], vb[0].x, vb[0].y, vb[0].z, vb[0].w, p1, p2);
        if (first.value) { sc[2][0] += sc[2][2]; sc[2][1] += sc[2][3]; }
        SCHED();
        e[7] = ex2(sc[1][3]);
        mma16(o[1], vb[2].x, vb[2].y, vb[2].z, vb[2].w, p1, p2);
        SCHED();
        e[8] = ex2(sc[2][0]);
        mma16(o[2], vb[4].x, vb[4].y, vb[4].z, vb[4].w, p1, p2);
        SCHED();
        e[9] = ex2(sc[2][1]);
        SCHED();
        const uint32_t p3 = pack2(e[4], e[5]), p4 = pack2(e[6], e[7]);
        l += (e[4] + e[5]) + (e[6] + e[7]);
#pragma unroll
        for (int u = 0; u < 3; u++) mma16(o[u], vb[2 * u + 1].x, vb[2 * u + 1].y, vb[2 * u + 1].z, vb[2 * u + 1].w, p3, p4);
        SCHED();
        const uint32_t p0 = pack2(e[8], e[9]);
        l += e[8] + e[9];
        const float l2 = __shfl_xor_sync(~0u, l, 1);
        if (first.value) ldsm4t(&wd[8], wo + 8192);
#pragma unroll
        for (int u = 0; u < 3; u++) mma8(o[u], vm[u].x, vm[u].y, p0);
        redo = __any_sync(~0u, !(l > 1e-9f && l < 1e9f));
        uint32_t la = sb + CH_L + (((l4 ^ tag) >> 1) & 0x3c);
        asm volatile("" : "+r"(la));
        SCHED();
#pragma unroll
        for (int u = 0; u < 3; u++) { ow[2 * u] = pack2(o[u][0], o[u][1]); ow[2 * u + 1] = pack2(o[u][2], o[u][3]); }
        stsm4(l16 + o768 + CH_O, ow[0], ow[1], ow[2], ow[3]);
        stsm2(l16 + o768 + CH_O + 512, ow[4], ow[5]);
        if (t4 == 0) sts32(la, __float_as_uint(l + l2));
      };
      attend(Int<1>());
      TM(6);
      asm volatile("{.reg .pred p; setp.eq.u32 p, %0, 0; @p bar.arrive 2, 256;}" :: "r"(redo) : "memory");
      if (redo) {
        float mx = fmaxf(sc[2][0], sc[2][1]);
#pragma unroll
        for (int i = 0; i < 4; i++) mx = fmaxf(mx, fmaxf(sc[0][i], sc[1][i]));
        mx = fmaxf(mx, __shfl_xor_sync(~0u, mx, 1));
        mx = fmaxf(mx, __shfl_xor_sync(~0u, mx, 2));
#pragma unroll
        for (int i = 0; i < 4; i++) { sc[0][i] -= mx; sc[1][i] -= mx; }
        sc[2][0] -= mx; sc[2][1] -= mx;
        attend(Int<0>());
        bar_arrive(NB_O, 256);
      }
      {
        float z[4] = {};
        const uint32_t scr = l8 + CH_V + r1 * 4096;
        uint32_t ow[6], we[12];
        __syncwarp();
        ldsm4t(ow, l16 + o768 + CH_O);
        ldsm2t(ow + 4, l16 + o768 + CH_O + 512);
        if (j == 0) {
          float y[4] = {};
#pragma unroll
          for (int u = 0; u < 3; u++) ldsm4t(&we[4 * u], (wo ^ 32) + u * 4096);
          SCHED();
#pragma unroll
          for (int u = 0; u < 3; u++) {
            mma16(z, wd[4 * u], wd[4 * u + 1], wd[4 * u + 2], wd[4 * u + 3], ow[2 * u], ow[2 * u + 1]);
            mma16(y, we[4 * u], we[4 * u + 1], we[4 * u + 2], we[4 * u + 3], ow[2 * u], ow[2 * u + 1]);
          }
          sts64f(scr + t4 * 512 + 2048, y[0], y[1]); sts64f(scr + t4 * 512 + 2304, y[2], y[3]);
        } else {
#pragma unroll
          for (int u = 0; u < 3; u++) mma16(z, wd[4 * u], wd[4 * u + 1], wd[4 * u + 2], wd[4 * u + 3], ow[2 * u], ow[2 * u + 1]);
        }
        sts64f(scr + t4 * 512, z[0], z[1]); sts64f(scr + t4 * 512 + 256, z[2], z[3]);
        bar_sync(NB_W1, 128);
        if (j == 0 || t4 < 2) {
          float2 q[4];
          const float4 l = lds128f(sb + CH_L + ((l16 ^ tag) & 0x30));
#pragma unroll
          for (int i = 0; i < 4; i++) q[i] = lds64f(scr + (t4 >> 1) * 2048 + (t4 & 1) * 256 + i * 512);
          SCHED();
          stg_strong32(pdst[0] + ((l4 ^ tag) & 0x7c), pack_tag(((q[0].x + q[1].x) + (q[2].x + q[3].x)) * rcp(l.x + l.y), ((q[0].y + q[1].y) + (q[2].y + q[3].y)) * rcp(l.z + l.w), tag));
        }
      }
      TM(2);
      if (CH_TPRE) mbar_wait(sb + MB_T, ~s & 1);
    }
    bar_sync(NB_ST, 384);
    tokens(s + 1, Int<0>());
    TM(9);
    tag ^= 0x10001;
  }
  asm volatile("setmaxnreg.dec.sync.aligned.u32 224;");
  l16 = sb + (fresh_tid() & 31) * 16; t16 = sb + (fresh_tid() & 127) * 16; t8 = sb + (fresh_tid() & 127) * 8;
  float dv[4] = {};
  uint4 kf[2];
  project(NSEG - 1, dv, kf, Int<1>());
  if (WG == 0) {
    sts64(t8 + CH_VX + j * 1024, pack2(dv[0], dv[1]), pack2(dv[2], dv[3]));
  } else {
    const uint2 a = lds64(t8 + t4 * 256 + CH_KM), b = lds64(t8 + t4 * 256 + CH_KM + 256);
    sts64(t8 + CH_Q, hadd2(a.x, b.x), hadd2(a.y, b.y));
  }
  bar_arrive(NB_PRE2, 288);
}

__device__ __forceinline__ void chain_comm(const ChainParams& p, const uint32_t sb, const CUtensorMap* maps) {
  [[maybe_unused]] constexpr int WG = 2;
  const int tid = threadIdx.x & 127, t4 = __shfl_sync(~0u, tid >> 5, 0), lane = tid & 31;
  const int cta = blockIdx.x, h = cta / 3, j = cta - 3 * h, colbase = cta * 64;
  const uint8_t* const xs = reinterpret_cast<const uint8_t*>(g_xn);
  auto xload = [&](int seg, int i, int off, int bytes) { bulk_load(sb + CH_X + i * 5120 + off, xs + (seg * 4 + (i & 3)) * 10240 + (i >> 2) * 5120 + off, bytes, sb + MB_T); };
  if (cta == 0) for (int i = tid; i < SY_N; i += 128) p.other[i] = 0;
  uint32_t smid; asm("mov.u32 %0, %%smid;" : "=r"(smid));
  const uint32_t part = max(ldg_strong32(g_smpart + (smid & 255)), 1u);
  if (tid == 64) stg_strong32(p.sync + SY_PART + cta, part);
  PRO(0);
  if (t4 == 3) {
    bar_arrive(NB_PROJ2, 384);
    bar_arrive(NB_PRE2, 384);
    if (elect()) {
      wait_count(p.sync + SY_P + 1, ln_items(p.layer, 0));
      fence_async_global();
      mbar_expect(sb + MB_T, 40960);
      for (int i = 0; i < 8; i++) xload(0, i, 0, 5120);
    }
    __syncwarp();
  } else {
  bar_sync(NB_PROJ2, 384);
  __syncwarp();
  PRO(1);
  if (t4 == 0 && elect()) {
    mbar_expect(sb + MB_WQ, 81920);
    for (int i = 0; i < 5; i++) tma_load(sb + CH_WQ + i * 16384, &p.wq, colbase, i * 128, sb + MB_WQ);
  }
  bar_sync(NB_PRE2, 384);
  __syncwarp();
  PRO(2);
  if (t4 == 0 && elect()) {
    mbar_expect(sb + MB_WO, 86016);
    for (int i = 0; i < 6; i++) tma_load(sb + CH_WO + i * 12288, &p.wo, j * 192 + i * 32, h * 192, sb + MB_WO);
    tma_load(sb + CH_WO + 73728, &p.wo, j == 0 ? 576 : 592 + j * 16, h * 192, sb + MB_WO);
  }
  }
  if (tid < NSLOT) {
    const uint32_t* part_of = p.sync + SY_PART + (tid >= 80 ? cta : tid);
    uint32_t reader = 0, orient = 0;
    int n = 0;
    while (reader == 0 || orient == 0) { reader = ldg_strong32(part_of); orient = ldg_strong32(g_orient + tid); spin_guard(n); }
    sts32(sb + CH_TAB + tid * 4, tid * 8192 + (orient == reader ? 0 : 4096));
    if (t4 == 0) {
      const uint32_t near = __ballot_sync(~0u, reader == part) & 0xffffff;
      if (lane == 0) sts32(sb + CH_TAB + NSLOT * 4, cta < 80 ? cta : near ? __fns(near, 0, 1 + cta % __popc(near)) : 0);
    }
  }
  __syncwarp();
  asm volatile("barrier.cluster.wait.aligned;" ::: "memory");
  const uint32_t l8 = opaque(sb + t4 * 256 + lane * 8);
  {
    const uint32_t* m0 = reinterpret_cast<const uint32_t*>(p.mem0) + (lane >> 2) * (DM / 2) + t4 * 80 + (lane & 3);
    uint32_t g[20];
#pragma unroll
    for (int i = 0; i < 20; i++) g[i] = transpose8(m0[i * 4]);
    const uint32_t id = (lane >> 3) == (lane & 3) ? ((lane & 4) ? 0x3f800000u : 0x00003f80u) : 0u;
    if (t4 == 0) sts64(l8 + CH_ID, id, id);
    bar_sync(NB_XFREE, 256);
#pragma unroll
    for (int i = 0; i < 20; i++) sts32(sb + CH_M + (t4 * 20 + i) * 128 + lane * 4, g[i]);
  }
  bar_sync(NB_ST, 384);
  uint8_t* const pool = pool_at(0);
  const uint8_t* const psrc = pool + opaque(lds32(sb + CH_TAB + lds32(sb + CH_TAB + NSLOT * 4) * 4) + t4 * 1024 + lane * 4);
  const uint32_t mdst = opaque((80 + cta / 20) * 8192 + (t4 & 1) * 4096 + (cta % 20) * 128 + lane * 4);
  int st = 0;
  uint32_t tag = opaque(1), span = ~0u;
  bar_sync(NB_MEM, 384);
  auto send_tokens = [&](int s) {
    fence_async();
    uint8_t* dst = g_kv + ((s >> 2) * 96 + cta) * KV_BYTES + (s & 3) * 4096;
    bulk_store(dst + KV_K, sb + CH_K, 4096);
    bulk_store(dst + KV_V, sb + CH_V + j * 4096, 4096);
    bulk_commit();
  };
  auto send_memory = [&](int s, uint32_t km) {
    fence_async();
    uint8_t* dst = g_kv + ((s >> 2) * 96 + cta) * KV_BYTES + (s & 3) * 1024;
    bulk_store(dst + KV_KM, km, 1024);
    bulk_store(dst + KV_VM, sb + CH_VX + j * 1024, 1024);
    bulk_commit();
    bulk_wait<0>();
    if ((s & 3) == 3) { fence_async_global(); atomicAdd(p.sync + (s >> 2) * 8 + 4, 1); }
  };
#pragma unroll 1
  for (int s = 0; s < NSEG - 1; s++) {
    TM(0);
    STAT(0);
    if (t4 == 0) {
      if (elect()) {
        if (CH_PUSH == 1) push_values(sb, s, j);
        send_tokens(s);
        bulk_wait_read<0>();
      }
      __syncwarp();
    }
    uint32_t c0, g0;
    if (t4 == 1) {
      __syncwarp();
      c0 = clk32(); g0 = gtime();
      if (elect()) atomicMax(p.sync + SY_TIME + s, g0);
    }
    if (t4 == 3 && (s & 3) == 2 && s < NSEG - 2) wait_count_uniform(p.sync + SY_P + 5 + (s & ~3), ln_items(p.layer, (s >> 2) + 1));
    if (t4 == 2) { mbar_wait(sb + MB_V, s & 1); bar_arrive(NB_W1V, 160); }
    bar_sync(NB_PROJ2, 256);
    if (t4 == 0 && elect()) {
      mbar_expect(sb + MB_X, 4096);
      mbar_expect(sb + MB_T, 40960);
#pragma unroll
      for (int i = 0; i < 7; i++) xload(s + 1, i, 0, i < 6 ? 5120 : 4096);
    }
    __syncwarp();
    STAT(1);
    TM(1);
    {
      const uint2 a = lds64(l8 + t4 * 256 + CH_KM), b = lds64(l8 + t4 * 256 + CH_KM + 256);
      sts64(l8 + CH_KS, hadd2(a.x, b.x), hadd2(a.y, b.y));
    }
    TM(4);
    bar_sync(NB_PRE2, 256);
    if (t4 == 0 && elect()) {
      xload(s + 1, 6, 4096, 1024);
      xload(s + 1, 7, 0, 5120);
      if (CH_XPF && s < NSEG - 2) prefetch_l2(xs + (s + 2) * 40960 + cta % 20 * 2048, 2048);
      if (CH_TPF && s >= NSEG - 7) {
        const int i = s - (NSEG - 7);
        if (i < 2) prefetch_l2(p.wb + (cta * 2 + i) * 12800, 12800);
        else if (i < 4) prefetch_l2(xs + (cta * 2 + i - 2) * 8192, 8192);
        else prefetch_l2(g_q + 15 * 32 * 3072 + (cta * 2 + i - 4) * 512, 8192);
      }
      send_memory(s, sb + CH_KS);
    }
    __syncwarp();
    if (t4 == 1) {
      const uint32_t late = min(ldg_strong32(p.sync + SY_TIME + s) - g0, 640u);
      if (elect()) sts32(sb + CH_TAB + 380, c0 + span + (late * 115 >> 6) + (j ? 60 : 0) + p.d1);
    }
    bar_sync(NB_W2, 128);
    uint32_t due = lds32(sb + CH_TAB + 380);
    due = __shfl_sync(~0u, due, 0);
    const uint8_t* ms = pool + (lds32(sb + CH_TAB + (80 + st * 4 + t4) * 4) + (l8 & 255));
    uint8_t* md = pool + (mdst + (t4 < 2 ? st : st == 2 ? 0 : st + 1) * 32768);
    asm volatile("" : "+l"(ms), "+l"(md));
    TM(2);
    bar_sync(NB_ST, 384);
    __syncwarp();
    uint32_t tg = clk32();
    if (t4 == 3 && elect()) {
      if (s < NSEG - 2) mbar_expect(sb + MB_V, 8192);
      mbar_arrive_remote(mapa(sb + MB_F, j == 2 ? 0 : j + 1));
      mbar_arrive_remote(mapa(sb + MB_F, j == 0 ? 2 : j - 1));
    }
    if (t4 == 2 && s == NSEG - 2) {
      work_init(sb);
      if (elect()) for (int i = 0; i < 5; i++) asm volatile("prefetch.tensormap [%0];" :: "l"(maps + i) : "memory");
    }
    __syncwarp();
    STAT(2);
    {
      float2 q[4];
      uint32_t u[2][8];
      auto poll = [&](uint32_t (&v)[8], uint32_t flip) {
        const uint8_t* src = psrc + flip;
#pragma unroll
        for (int i = 0; i < 8; i++) v[i] = ldg_strong32(src + i * 128);
      };
      auto sum = [&](uint32_t (&v)[8]) {
        sts64f(l8 + CH_R2, ((bf_lo(v[0]) + bf_lo(v[1])) + (bf_lo(v[2]) + bf_lo(v[3]))) + ((bf_lo(v[4]) + bf_lo(v[5])) + (bf_lo(v[6]) + bf_lo(v[7]))),
               ((bf_hi(v[0]) + bf_hi(v[1])) + (bf_hi(v[2]) + bf_hi(v[3]))) + ((bf_hi(v[4]) + bf_hi(v[5])) + (bf_hi(v[6]) + bf_hi(v[7]))));
        uint32_t bad;
        asm volatile("{.reg .pred p, q; .reg .b32 a; lop3.b32 a, %1, %2, %3, 0xFE; lop3.b32 a, a, %4, 1, 0xA8; setp.ne.u32 p, a, 0;\n"
                     "bar.red.or.pred q, %5, 128, p; selp.u32 %0, 1, 0, q;}"
                     : "=r"(bad) : "r"(differ(v[0], v[1], tag)), "r"(differ(v[2], v[3], tag)), "r"(differ(v[4], v[5], tag)), "r"(differ(v[6], v[7], tag)), "n"((int)NB_W2) : "memory");
#pragma unroll
        for (int k = 0; k < 4; k++) asm volatile("ld.volatile.shared.v2.f32 {%0,%1}, [%2];" : "=f"(q[k].x), "=f"(q[k].y) : "r"(l8 - t4 * 256 + CH_R2 + k * 256) : "memory");
        return bad;
      };
      TM(3);
      if (t4 == 1) span = min(span, tg - c0);
      until(s < 2 ? tg + 400 : (int)(due - tg) > p.dn ? due : tg + p.dn);
      poll(u[0], 0);
      SCHED();
      uint32_t lag = l8;
#pragma unroll
      for (int i = 0; i < CH_LAG; i++) asm volatile("mul.lo.u32 %0, %0, %1;" : "+r"(lag) : "r"(p.zero));
      if (CH_LAG) poll(u[1], lag);
      SCHED();
      if (sum(u[0])) {
        poll(u[0], CH_LAG ? u[1][7] & p.zero : 0);
        SCHED();
        if (!CH_LAG || sum(u[1])) {
          for (int n = 0; sum(u[0]) && (cta < 80 || n < 2); spin_guard(n)) poll(u[0], 0);
        }
      }
      if (CH_GATE) bar_arrive(NB_PUB, 384);
      SCHED();
      TM(9);
      if (cta < 80) stg_strong32(md, min(nz(pack2((q[0].x + q[1].x) + (q[2].x + q[3].x), (q[0].y + q[1].y) + (q[2].y + q[3].y))), t4 < 2 ? ~0u : 0u));
      tg = clk64() + p.d2;
      if (s >= 2 && (int)(due + p.dx - tg) > 0) tg = due + p.dx;
      TM(8);
    }
    STAT(3);
    until(tg);
    TM(10);
    for (int n = 0;;) {
      uint2 g[10];
#pragma unroll
      for (int i = 0; i < 10; i++) g[i] = ldg_strong64(ms + i * 256);
      if (n == 0) bar_sync(NB_XFREE, 256);
      spin_guard(n);
      uint32_t m = ~0u;
#pragma unroll
      for (int i = 0; i < 10; i++) { sts64(l8 + CH_M + t4 * 2304 + i * 256, g[i].x, g[i].y); m = __vimin3_u32(m, g[i].x, g[i].y); }
      TMV(13, n - 1);
      if (!__any_sync(~0u, m == 0)) break;
    }
    TM(11);
    if (t4 < 2 || s == NSEG - 2) bar_sync(NB_MEM, 384); else bar_arrive(NB_MEM, 384);
    if (++st == 3) st = 0;
    tag ^= 0x10001;
  }
  asm volatile("setmaxnreg.inc.sync.aligned.u32 56;");
  if (t4 == 0) {
    if (elect()) send_tokens(NSEG - 1);
    __syncwarp();
    bar_sync(NB_PRE2, 288);
    if (elect()) {
      send_memory(NSEG - 1, sb + CH_Q);
      asm volatile("mbarrier.arrive.shared::cta.b64 _, [%0], 8;" :: "r"(sb + WK_BAR + 64) : "memory");
    }
    __syncwarp();
  }
}

__device__ __forceinline__ void chain_start(const ChainParams& p, const uint32_t sb) {
  if (threadIdx.x < 32 && elect()) {
    mbar_init(sb + MB_WO, 1); mbar_init(sb + MB_WQ, 1); mbar_init(sb + MB_X, 5); mbar_init(sb + MB_V, 1); mbar_init(sb + MB_T, 1); mbar_init(sb + MB_F, 2);
    for (int i = 0; i < 10; i++) mbar_init(sb + MB_W + 8 * i, 1);
    asm volatile("fence.mbarrier_init.release.cluster;" ::: "memory");
    mbar_expect(sb + MB_V, 8192);
    for (int i = 0; i < 10; i++) {
      const int n = i % 5 < 2 ? (i % 5) * 2 : i % 5 == 2 ? 1 : i % 5;
      const uint32_t bar = sb + MB_W + 8 * (n + (i < 5 ? 0 : 5));
      mbar_expect(bar, 16384);
      tma_load(sb + (i < 5 ? CH_WQ : CH_WO) + n * 16384, i < 5 ? &p.wk : &p.wv, blockIdx.x * 64, n * 128, bar);
    }
    atomicAdd(p.sync + SY_UP, 1);
    asm volatile("{.reg .pred p; setp.ne.u32 p, %0, 1024; @p trap;}" :: "r"(sb & 0xffffff));
  }
  __syncthreads();
  asm volatile("barrier.cluster.arrive.relaxed.aligned;" ::: "memory");
}

struct WorkParams {
  ChainParams ch;
  CUtensorMap wo, xn, wb[3], xp, wq, wc[2], out;
  const __nv_bfloat16* x;
  uint32_t* sync;
  int kind, qa_end, idle;
};
#define GO_320 4
#define GO_TAIL 1
enum { WK_FIRST = 0, WK_LEAD = 1, WK_CHAIN = 2, WK_LAST = 3 };
enum { IT_ATT = 0, IT_OP = 1, IT_FIN = 2, IT_BQ = 3, IT_BO = 4, IT_LN = 5, IT_Q = 6, IT_LN0 = 7, IT_OUT = 8 };
constexpr int C_EARLY = 1 << 20, C_LATE = 1 << 21, C_TAIL = 1 << 22;

__device__ __forceinline__ uint32_t item_count(int type, int b) { return type == IT_ATT ? 32 : type == IT_OP ? op_tiles(b) * op_split(b) : type == IT_FIN ? fin_items(b) : bq_items(b); }
__device__ __forceinline__ uint32_t item_need(int type, int b) { return type == IT_ATT ? 96 : item_count(type - 1, b); }
__device__ __forceinline__ int item_cols(int type, int b) {
  return type == IT_ATT || type == IT_Q ? 192 : type == IT_OUT ? 80 : type == IT_BQ ? (b < BQ_12 ? 320 : b < BQ_24 ? 160 : 80) : type == IT_OP && b >= OP_N4 ? 160 : 320; }
__device__ __forceinline__ int item_groups(int type, int b) { return 16 / (type == IT_FIN ? fin_items(b) : ln_items(type == IT_LN, b)); }
#define RES_OP 1
constexpr int RES_N = RES_OP ? op_tiles(14) * op_split(14) : 0, RES_BQ = (64 - RES_N) / 6;
__device__ __forceinline__ bool reserved(int type, int b) { return type == IT_ATT ? b == 15 : type == IT_OP ? RES_OP && b == 14 : type == IT_BQ && b < RES_BQ; }
__device__ __forceinline__ int reserved_item(int cta) {
  const int h = cta / 3, j = cta - 3 * h, i = h + (j - 1) * 32;
  if (j == 0) return C_EARLY | IT_ATT << 16 | 15 << 8 | h;
  return i < RES_N ? C_TAIL | IT_OP << 16 | 14 << 8 | i : i - RES_N < RES_BQ * 6 ? C_TAIL | IT_BQ << 16 | ((i - RES_N) / 6) << 8 | (i - RES_N) % 6 : -1;
}
constexpr int LEAD1 = 12;
__device__ __forceinline__ int lead_item(int layer, int qa_end, int i) {
  if (layer == 2) return i < 128 ? C_EARLY | C_LATE | IT_OUT << 16 | (i >> 3) << 8 | (i & 7) : -1;
  if (layer == 0) {
    if (i < 32) return IT_LN0 << 16 | (i >> 4) << 8 | (i & 15);
    if (i < 88) return IT_LN0 << 16 | ((i - 24) >> 2) << 8 | (i & 3);
    i -= 88;
  } else {
    if (i < 4) return C_EARLY | IT_BO << 16 | (i >> 1) << 8 | (i & 1);
    if (i < 12) return C_EARLY | IT_LN << 16 | ((i - 4) >> 2) << 8 | (i & 3);
    if (i < 40) return C_EARLY | IT_BO << 16 | ((i - 8) >> 1) << 8 | (i & 1);
    if (i < 96) return C_EARLY | IT_LN << 16 | ((i - 32) >> 2) << 8 | (i & 3);
    i -= 96;
  }
  return i < (16 - qa_end) * 32 ? C_EARLY | IT_Q << 16 | (qa_end + (i >> 5)) << 8 | (i & 31) : -1;
}

struct Ring {
  uint32_t sb;
  int pos, seq;
  __device__ __forceinline__ uint32_t full() const { return sb + WK_BAR + 8 * (seq & 7); }
  __device__ __forceinline__ uint32_t take(int len) { if (pos + len > WK_SLOTS) pos = 0; pos += len; seq++; return sb + (pos - len) * 8192; }
  __device__ __forceinline__ uint32_t wait(int len) { mbar_wait_uniform(full(), (seq >> 3) & 1); return take(len); }
  __device__ __forceinline__ void release(int sq) const { if (elect()) mbar_arrive(sb + WK_BAR + 64 + 8 * (sq & 7)); }
};

struct Pending {
  uint32_t w[48], done;
  uint4* dst;
  __device__ __forceinline__ void store(int i) const { dst[(i >> 2) * 1024 + (i & 3) * 32] = make_uint4(w[4 * i], w[4 * i + 1], w[4 * i + 2], w[4 * i + 3]); }
  __device__ __forceinline__ void finish() { __syncwarp(); if (elect()) mbar_arrive(done); done = 0; }
  __device__ __forceinline__ void flush() {
    if (done) {
#pragma unroll
      for (int i = 0; i < 12; i++) store(i);
      finish();
    }
  }
};

template <int N>
__device__ __forceinline__ void gemm_item(float* d, Ring& r, int nkb, uint32_t go, int ask, Pending& pend) {
  const int warp = __shfl_sync(~0u, fresh_tid() >> 5, 0), wg = warp >> 2;
#pragma unroll 1
  for (int kb = 0; kb < nkb; kb++) {
    const uint32_t base = r.wait(2 + (N + 63) / 64);
    const uint64_t da = mkdesc(base + wg * 8192, 128, 1024, 0), db = mkdesc(base + 16384, 8192, 1024, 1);
    wg_fence();
#pragma unroll
    for (int kk = 0; kk < 4; kk++) {
      if (N == 80) wg_ss80_01(d, da + kk * 16, db + kk * 128, (kb | kk) != 0);
      else if (N == 160) wg_ss160_01(d, da + kk * 16, db + kk * 128, (kb | kk) != 0);
      else wg_ss192_01(d, da + kk * 16, db + kk * 128, (kb | kk) != 0);
      if (N == 320) wg_ss128_01(d + 96, da + kk * 16, db + kk * 128 + 3 * 512, (kb | kk) != 0);
    }
    wg_commit();
    if (kb == ask && go && warp == 0 && elect()) mbar_arrive(go);
    if (N == 192 && pend.done) {
#pragma unroll
      for (int i = 0; i < 12; i++) if (kb == i / 2) pend.store(i);
      if (kb == 5) pend.finish();
    }
    if (kb > 0) { wg_wait<1>(); r.release(r.seq - 2); }
  }
  wg_wait<0>();
  reg_fence<N / 2>(d);
  r.release(r.seq - 1);
}

template <int HALF>
__device__ __forceinline__ void attn_a_warp(Ring& r, Pending& pend, bool now) {
  uint32_t (&q)[48] = pend.w;
  constexpr int NT = HALF ? 5 : 3, NF = 8 * NT;
  const int lane = fresh_tid() & 31, g = lane >> 2, c = lane & 3, seg = (fresh_tid() >> 5) & 3;
  float sc[NT][4] = {};
  uint32_t base, f[2][NF];
  auto load_k = [&](int u) {
    base = u & 1 ? base + 20480 : r.wait(5) + seg * 1024;
#pragma unroll
    for (int kk = 0; kk < 4; kk++) {
      if (!(kk & 1)) ldsm4(&f[u & 1][2 * kk], base + KV_KM + kk * 256 + lane * 16);
#pragma unroll
      for (int t = 0; t <= HALF; t++) ldsm4(&f[u & 1][8 + 16 * t + 4 * kk], base + seg * 3072 + t * 2048 + kk * 512 + lane * 16);
    }
  };
  auto load_v = [&](int u) {
    base = u & 1 ? r.wait(5) + seg * 1024 : base + 20480;
#pragma unroll
    for (int n = 0; n < 4; n++) {
      const uint2 vm = lds64(base + KV_KM + n * 256 + lane * 8);
      f[~u & 1][2 * n] = vm.x; f[~u & 1][2 * n + 1] = vm.y;
#pragma unroll
      for (int t = 0; t <= HALF; t++)
        ldsm4(&f[~u & 1][8 + 16 * t + 4 * n], base + seg * 3072 + t * 2048 + n * 512 + (lane & 8) * 32 + (lane & 16) * 8 + (lane & 7) * 16);
    }
  };
  load_k(0);
#pragma unroll
  for (int u = 0; u < 3; u++) {
    if (u < 2) load_k(u + 1); else { r.release(r.seq - 2); load_v(0); }
    SCHED();
#pragma unroll
    for (int kk = 0; kk < 4; kk++) {
      const uint32_t *a = &q[16 * u + 4 * kk], *b = f[u & 1];
      mma16(sc[0], a[0], a[1], a[2], a[3], b[2 * kk], b[2 * kk + 1]);
#pragma unroll
      for (int n = 0; n < NT - 1; n++) mma16(sc[1 + n], a[0], a[1], a[2], a[3], b[8 + 16 * (n >> 1) + 4 * kk + 2 * (n & 1)], b[9 + 16 * (n >> 1) + 4 * kk + 2 * (n & 1)]);
    }
    SCHED();
  }
  load_v(1);
  SCHED();
  const float k2 = 0.07216878364870322f * 1.44269504089f, NEG = -INFINITY;
  if (2 * c > g) { sc[NT - 2][0] = NEG; sc[NT - 1][2] = NEG; }
  if (2 * c + 1 > g) { sc[NT - 2][1] = NEG; sc[NT - 1][3] = NEG; }
  sc[NT - 1][0] = sc[NT - 1][1] = NEG;
  uint32_t pp[NT][2]; float inv[2];
#pragma unroll
  for (int hh = 0; hh < 2; hh++) {
    float m = NEG, l = 0.f;
#pragma unroll
    for (int n = 0; n < NT; n++) m = fmaxf(m, fmaxf(sc[n][2 * hh], sc[n][2 * hh + 1]));
    m = fmaxf(m, __shfl_xor_sync(~0u, m, 1)); m = fmaxf(m, __shfl_xor_sync(~0u, m, 2));
#pragma unroll
    for (int n = 0; n < NT; n++) { const float x = ex2((sc[n][2 * hh] - m) * k2), y = ex2((sc[n][2 * hh + 1] - m) * k2); l += x + y; pp[n][hh] = pack2(x, y); }
    l += __shfl_xor_sync(~0u, l, 1); l += __shfl_xor_sync(~0u, l, 2);
    inv[hh] = rcp(l);
  }
#pragma unroll
  for (int u = 0; u < 3; u++) {
    float o[8][4] = {};
    const uint32_t* b = f[~u & 1];
#pragma unroll
    for (int n = 0; n < 8; n++) mma8(o[n], pp[0][0], pp[0][1], b[n]);
#pragma unroll
    for (int t = 0; t <= HALF; t++)
#pragma unroll
      for (int n = 0; n < 8; n++) mma16(o[n], pp[1 + 2 * t][0], pp[1 + 2 * t][1], pp[2 + 2 * t][0], pp[2 + 2 * t][1], b[8 + 16 * t + 2 * n], b[9 + 16 * t + 2 * n]);
    SCHED();
    if (u != 1) r.release(r.seq - 2 + u / 2);
    if (u == 0) { load_v(2); SCHED(); }
#pragma unroll
    for (int i = 0; i < 16; i++) q[16 * u + i] = pack2(o[i & 7][i >> 2 & 2] * inv[i >> 3], o[i & 7][(i >> 2 & 2) + 1] * inv[i >> 3]);
    if (now) {
#pragma unroll
      for (int i = 0; i < 4; i++) pend.store(4 * u + i);
    }
  }
}

template <int G>
__device__ __forceinline__ void ln_groups(Ring& ring, uint32_t scratch, bool input, int planes, int rg) {
  const int warp = fresh_tid() >> 5, lane = fresh_tid() & 31;
  const uint32_t id = (lane >> 3) == (lane & 3) ? ((lane & 4) ? 0x3f800000u : 0x00003f80u) : 0u;
  float v[G][5][4] = {};
#pragma unroll
  for (int r = 0; r < G; r++) {
    if (input) {
      const uint32_t a = ring.wait(2) + (lane >> 2) * 1280 + warp * 160 + (lane & 3) * 4;
#pragma unroll
      for (int i = 0; i < 5; i++) mma8(v[r][i], lds32(a + i * 32), lds32(a + i * 32 + 16), id);
      ring.release(ring.seq - 1);
    } else {
#pragma unroll 1
      for (int k = planes; k > 0; k -= 4) {
        const uint32_t a = ring.wait(min(k, 4) + 1) + (warp * 160 + lane) * 8;
        if (k == 1) {
#pragma unroll
          for (int i = 0; i < 5; i++) { const uint2 x = lds64(a + i * 256); mma8(v[r][i], x.x, x.y, id); }
        } else {
#pragma unroll
          for (int i = 0; i < 10; i++) {
            if (i == 5 && k < 4) break;
            const uint2 x = lds64(a + i / 5 * 20480 + i % 5 * 256), y = lds64(a + i / 5 * 20480 + 10240 + i % 5 * 256);
            mma16(v[r][i % 5], x.x, x.y, y.x, y.y, id, id);
          }
        }
        ring.release(ring.seq - 1);
      }
    }
  }
  uint2 xr[G][5];
  scratch += (lane >> 2) * 64;
#pragma unroll
  for (int r = 0; r < G; r++) {
    float m = 0.f, q = 0.f;
#pragma unroll
    for (int i = 0; i < 5; i++) {
      float* t = v[r][i];
      xr[r][i] = make_uint2(pack2(t[0], t[1]), pack2(t[2], t[3]));
      t[0] = bf_lo(xr[r][i].x); t[1] = bf_hi(xr[r][i].x); t[2] = bf_lo(xr[r][i].y); t[3] = bf_hi(xr[r][i].y);
      m += (t[0] + t[1]) + (t[2] + t[3]);
    }
    m += __shfl_xor_sync(~0u, m, 1); m += __shfl_xor_sync(~0u, m, 2);
    m *= 1.f / 80;
#pragma unroll
    for (int i = 0; i < 5; i++) { const float a = v[r][i][0] - m, b = v[r][i][1] - m, c = v[r][i][2] - m, d = v[r][i][3] - m; q += (a * a + b * b) + (c * c + d * d); }
    q += __shfl_xor_sync(~0u, q, 1); q += __shfl_xor_sync(~0u, q, 2);
    if ((lane & 3) == 0) sts64f(scratch + r * 512 + warp * 8, m, q);
  }
  bar_sync(1, 256);
#pragma unroll
  for (int r = 0; r < G; r++) {
    const float4 t = lds128f(scratch + r * 512 + (lane & 3) * 16);
    float mean = t.x + t.z;
    mean += __shfl_xor_sync(~0u, mean, 1); mean += __shfl_xor_sync(~0u, mean, 2);
    mean *= 0.125f;
    float var = (t.y + t.w) + 80.f * ((t.x - mean) * (t.x - mean) + (t.z - mean) * (t.z - mean));
    var += __shfl_xor_sync(~0u, var, 1); var += __shfl_xor_sync(~0u, var, 2);
    const float rs = rsqrtf(var * (1.f / DM) + 1e-5f);
#pragma unroll
    for (int i = 0; i < 20; i++) v[r][i >> 2][i & 3] = (v[r][i >> 2][i & 3] - mean) * rs;
  }
#pragma unroll
  for (int r = 0; r < G; r++) {
    uint32_t* xn = g_xn + (rg + r) * 2560 + warp * 320 + lane;
#pragma unroll
    for (int i = 0; i < 10; i++) xn[i * 32] = pack2(v[r][i >> 1][2 * (i & 1)], v[r][i >> 1][2 * (i & 1) + 1]);
#pragma unroll
    for (int i = 0; i < 5; i++) g_x[(rg + r) * 1280 + warp * 160 + i * 32 + lane] = xr[r][i];
  }
}

__device__ __forceinline__ void store_partial(const float* d, int b, int split, int unit, int nu) {
  uint2* dst = g_part + (((b * 16 + split) * 16 + (fresh_tid() >> 5) * 2) * 40 + unit) * 32 + (fresh_tid() & 31);
#pragma unroll
  for (int u = 0; u < 20; u++) {
    if (u == 10 && nu == 10) break;
    dst[u * 32] = make_uint2(pack2(d[8 * u], d[8 * u + 1]), pack2(d[8 * u + 4], d[8 * u + 5]));
    dst[(40 + u) * 32] = make_uint2(pack2(d[8 * u + 2], d[8 * u + 3]), pack2(d[8 * u + 6], d[8 * u + 7]));
  }
}

__device__ __forceinline__ void store_bqkv(const float* d, int b, int idx, int nh) {
  const int lane = fresh_tid() & 31, c = lane & 3, rg = b * 16 + (fresh_tid() >> 5) * 2, h0 = idx * nh;
  const float sc = h0 < 32 ? 0.22360679775f * 1.44269504089f : 1.f;
  const bool lo = c < 2;
  uint32_t* da = g_bqkv + (h0 * 256 + rg) * 96 + lane;
  uint32_t* db = da + 256 * 96 + (lo ? 2 : -2);
  uint32_t pad[2];
#pragma unroll
  for (int r = 0; r < 2; r++) pad[r] = !(c & 1) && (h0 >= 64 || (h0 >= 32 && (lane & 4) && poly_group(rg + r))) ? 0x00003f80u : 0u;
#pragma unroll
  for (int q = 0; q < 8; q++) {
    if ((q == 2 || q == 4) && nh == 2 * q) break;
#pragma unroll
    for (int r = 0; r < 2; r++) {
      uint32_t w[5];
#pragma unroll
      for (int i = 0; i < 5; i++) w[i] = pack2(d[20 * q + 4 * i + 2 * r] * sc, d[20 * q + 4 * i + 2 * r + 1] * sc);
      const int o = q * 2 * 256 * 96 + r * 96;
      da[o] = w[0]; da[o + 32] = w[1]; da[o + 64] = lo ? w[2] : pad[r];
      db[o] = lo ? w[3] : w[2]; db[o + 32] = lo ? w[4] : w[3]; db[o + 64] = lo ? pad[r] : w[4];
    }
  }
}

template <bool WEIGHTS>
__device__ __forceinline__ void work_loader(const WorkParams& p, const uint32_t sb) {
  const uint32_t bars = sb + WK_BAR, bIF = bars + 128, bIE = bars + 160, bGo = bars + 224, slots = bars + 272;
  uint32_t* const sync = p.sync;
  int pos = 0, seq = 0, tail = 0, used = 0, normed = 0;
  uint32_t lens = 0, bar;
  const bool one = elect();
  if (p.kind == WK_CHAIN) {
    seq = 1; used = lens = 8;
    if (one) mbar_arrive(bars);
  }
  auto alloc = [&](int len, uint32_t bytes) {
    const int skip = pos + len > WK_SLOTS ? WK_SLOTS - pos : 0, sh = 4 * (seq & 7);
    used += len + skip;
    while (used > WK_SLOTS || seq - tail >= 8) {
      mbar_wait_uniform(bars + 64 + 8 * (tail & 7), (tail >> 3) & 1);
      used -= (lens >> 4 * (tail & 7)) & 15;
      tail++;
    }
    lens = (lens & ~(15u << sh)) | (len + skip) << sh;
    bar = bars + 2 * sh;
    if (one) mbar_expect(bar, bytes);
    pos = (pos + len > WK_SLOTS ? 0 : pos) + len;
    seq++;
    return sb + (pos - len) * 8192;
  };
  for (int n = 0;; n++) {
    mbar_wait_uniform(bIF + 8 * (n & 3), (n >> 2) & 1);
    const int code = __shfl_sync(~0u, (int)lds32(slots + 4 * (n & 3)), 0);
    if (code < 0) break;
    const int type = (code >> 16) & 15, b = (code >> 8) & 255, idx = code & 255;
    if (one) mbar_arrive(bIE + 8 * (n & 3));
    const bool qa = type == IT_ATT && b < p.qa_end, tokens = qa || type == IT_Q, ln = type == IT_FIN || type == IT_LN || type == IT_LN0;
    auto inputs = [&]() {
      if (WEIGHTS || type == IT_LN0) return;
      if (type == IT_OUT || (type == IT_BO && b >= 2)) pdl_wait();
      else if (type == IT_BO) wait_count_uniform(sync + SY_OB, 32);
      else if (type == IT_LN) wait_count_uniform(sync + SY_P + b * 4, 2);
      else wait_count_uniform(sync + b * 8 + 4 + type, item_need(type, b));
    };
    if (type == IT_ATT && !qa) {
      if (!WEIGHTS) wait_count_uniform(sync + SY_P + b * 4 + 3, 32);
      const uint32_t dst = alloc(6, WEIGHTS ? 0 : 49152);
      if (!WEIGHTS && one) (HINT & 1 ? bulk_load_last : bulk_load)(dst, g_q + (b * 32 + idx) * 3072, 49152, bar);
    } else if (!ln) {
      const int cols = item_cols(type, b), nb = (cols + 63) >> 6, nkb = type == IT_OP ? 96 / op_split(b) : 10;
      const int kb0 = type == IT_OP ? (idx >> op_tiles(b) / 2) * nkb : 0, col = (idx & (op_tiles(b) - 1)) * cols;
      if (WEIGHTS) {
        if (type == IT_OP) {
          for (int kb = kb0; kb < kb0 + nkb; kb++) {
            const uint32_t dst = alloc(2 + nb, nb * 8192) + 16384;
            {
#pragma unroll
              for (int i = 0; i < 5; i++)
                if (i < nb && one) asm volatile("cp.async.bulk.tensor.5d.shared::cluster.global.mbarrier::complete_tx::bytes [%0], [%1, {%3, %5, %5, %5, %4}], [%2];"
                             :: "r"(dst + i * 8192), "l"(&p.wo), "r"(bar), "r"(col + i * 64), "r"(kb * 2), "r"(0) : "memory");
            }
          }
        } else {
          const CUtensorMap* m = tokens ? &p.wq : type == IT_BQ ? &p.wb[cols / 160] : &p.wc[cols / 320];
          for (int kb = 0; kb < 10; kb++) {
            const uint32_t dst = alloc(2 + nb, nb * 8192) + 16384;
#pragma unroll
            for (int i = 0; i < 5; i++)
              if (i < nb && one)
                asm volatile("cp.async.bulk.tensor.3d.shared::cluster.global.mbarrier::complete_tx::bytes [%0], [%1, {%3, %4, %5}], [%2];"
                             :: "r"(dst + i * 8192), "l"(m), "r"(bar), "r"(i * 64), "r"(kb * 64), "r"(idx) : "memory");
          }
        }
      } else if (tokens || type == IT_BQ) {
        if (!tokens) inputs();
        else if (!(normed >> b & 1)) { wait_count_uniform(sync + SY_P + b * 4 + 1, ln_items(sync != g_sync, b)); normed |= 1 << b; }
        const CUtensorMap* m = tokens ? &p.xp : &p.xn;
        for (int kb = 0; kb < 10; kb++) {
          const uint32_t dst = alloc(2 + nb, 16384);
          if (one)
            asm volatile("cp.async.bulk.tensor.4d.shared::cluster.global.mbarrier::complete_tx::bytes [%0], [%1, {%3, %6, %4, %5}], [%2];"
                         :: "r"(dst), "l"(m), "r"(bar), "r"(kb * 128), "r"(tokens ? b * 4 : 0), "r"(tokens ? 0 : b * 4), "r"(0) : "memory");
        }
      } else {
        inputs();
        const uint8_t* a = type == IT_OP ? reinterpret_cast<const uint8_t*>(g_o) + (b * 96 + kb0) * 16384 : reinterpret_cast<const uint8_t*>(g_of) + b * 163840;
        for (int kb = 0; kb < nkb; kb++) {
          const uint32_t dst = alloc(2 + nb, 16384);
          if (one) (HINT & 2 ? bulk_load_last : bulk_load)(dst, a + kb * 16384, 16384, bar);
        }
      }
    }
    if (type == IT_ATT || ln) {
      inputs();
      if (!WEIGHTS && (!qa || (code & C_EARLY)) && !(code & C_LATE) && one) mbar_arrive(bGo);
    }
    if (type == IT_ATT) {
#pragma unroll
      for (int i = 0; i < 6; i += 2) {
        const uint32_t dst = alloc(5, WEIGHTS ? 0 : KV_BYTES);
        if (!WEIGHTS && one) {
#pragma unroll
          for (int u = i; u < i + 2; u++) (HINT & 1 ? bulk_load_last : bulk_load)(dst + (u - i) * 20480, g_kv + (b * 96 + idx * 3 + u % 3) * KV_BYTES + u / 3 * KV_V, 20480, bar);
        }
      }
    } else if (ln) {
      const int ng = item_groups(type, b), planes = type == IT_FIN ? op_split(b) + 1 : type == IT_LN ? 2 : 1;
      for (int rg = idx * ng; rg < (idx + 1) * ng; rg++) {
        const void* res = type == IT_LN0 ? static_cast<const void*>(p.x + (b * 16 + rg) * 8 * DM) : g_x + (b * 16 + rg) * 1280;
        for (int k = 0; k < planes; k += 4) {
          const int cnt = min(4, planes - k);
          const uint32_t dst = alloc(cnt + 1, WEIGHTS ? 0 : cnt * 10240);
          if (!WEIGHTS && one) {
#pragma unroll
            for (int i = 0; i < 4; i++)
              if (i < cnt) (HINT & 4 ? bulk_load_last : bulk_load)(dst + i * 10240, k + i + 1 < planes ? g_part + ((b * 16 + k + i) * 16 + rg) * 1280 : res, 10240, bar);
          }
        }
      }
    }
  }
}

__global__ void __launch_bounds__(384, 1) work_kernel(const __grid_constant__ WorkParams p) {
  extern __shared__ __align__(1024) uint8_t smem_raw[];
  const uint32_t sb = s2u(smem_raw), bars = sb + WK_BAR;
  const uint32_t bIF = bars + 128, bIE = bars + 160, done = bars + 192, bGo = bars + 224, slots = bars + 272, scratch = bars + 384;
  const int warp = __shfl_sync(~0u, threadIdx.x >> 5, 0);
  uint32_t* const sync = p.sync;
  TRACE(0);
  pdl_launch();
  if (p.kind <= WK_LEAD && !helper_sm()) {
    if (p.kind == WK_FIRST) { if (!(warp & 13)) probe_slots(bars + 320); TRACE(1); return; }
    if (__syncthreads_or(threadIdx.x == 0 && ldg_strong32(sync + SY_PRE + 1) >= LEAD1)) { pdl_wait(); return; }
  }
  if (p.kind == WK_CHAIN) {
    chain_start(p.ch, sb);
  } else {
    if (warp == 0) work_init(sb);
    __syncthreads();
  }
  if (warp >= 8) {
    if (p.kind == WK_CHAIN) {
      asm volatile("setmaxnreg.dec.sync.aligned.u32 40;");
      chain_comm(p.ch, sb, &p.wo);
    } else {
      asm volatile("setmaxnreg.dec.sync.aligned.u32 56;");
    }
    const int warp = __shfl_sync(~0u, fresh_tid() >> 5, 0), lane = fresh_tid() & 31;
    if (warp == 9) {
      const bool keep = p.kind > WK_LEAD || helper_sm();
      int n = 0;
      if (p.kind == WK_CHAIN && reserved_item(blockIdx.x) >= 0) {
        if (lane == 0) { sts32(slots, reserved_item(blockIdx.x)); mbar_arrive(bIF); }
        n = 1;
      }
      const int b = lane & 15, layer = p.kind == WK_LAST ? 2 : sync != g_sync;
      bool first = layer == 1, lead = p.kind != WK_CHAIN;
      for (;; n++) {
        if (n > 0) mbar_wait_uniform(bGo, (n - 1) & 1);
        mbar_wait_uniform(bIE + 8 * (n & 3), ((n >> 2) & 1) ^ 1);
        int code = -1;
        if (lead) {
          int i = blockIdx.x + n * 256;
          if (first) { if (lane == 0) i = atomicAdd(sync + SY_PRE + 1, 1); i = __shfl_sync(~0u, i, 0); first = i < LEAD1; }
          if (layer < 2 && !first) {
            if (lane == 0) i = keep ? atomicAdd(sync + SY_PRE, 1) + layer * LEAD1 : 1 << 20;
            i = __shfl_sync(~0u, i, 0);
            if (!keep) pdl_wait();
          }
          code = lead_item(layer, p.qa_end, i);
          lead = code >= 0 || layer == 2 || !keep;
          if (!lead && p.kind <= WK_LEAD) {
            const uint32_t t0 = gtime();
            while (!lead && ldg_strong32(sync + SY_UP) < 96) lead = gtime() - t0 > 20000;
          }
        }
        if (!lead) {
          int spin = 0, ticket = 0;
          if (lane == 0) ticket = atomicAdd(sync + SY_T, 1);
          for (;;) {
            const uint4 hd = ldg_strong128(sync + b * 8), pr = ldg_strong128(sync + b * 8 + 4);
            const uint32_t hv[4] = {hd.x, hd.y, hd.z, hd.w}, pv[4] = {pr.x, pr.y, pr.z, pr.w};
            const uint32_t chain_done = __ballot_sync(~0u, (pr.x & 0xffff) >= 96);
            int left[4], avail[4], rdy = 0, claimed = 0, upstream = 0;
#pragma unroll
            for (int t = 0; t < 4; t++) {
              const int cnt = lane < 16 && !reserved(t, b) ? item_count(t, b) : 0;
              left[t] = max(cnt - (int)hv[t], 0);
              claimed += cnt - left[t];
              const bool ready = (pv[t] & 0xffff) >= item_need(t, b);
              rdy |= ready << t;
              bool ok = ready || (t != IT_ATT && (chain_done >> 15 & 1) && !left[t - 1] && (t < 2 || !left[t - 2]));
              if (t == IT_BQ && (chain_done >> 12 & 9) == 1) ok = false;
              avail[t] = ok ? left[t] : 0;
              upstream |= __any_sync(~0u, left[t] > 0);
            }
            if (!upstream) { code = -1; break; }
            int rank = max(__shfl_sync(~0u, ticket, 0) - __reduce_add_sync(~0u, claimed), 0), type = -1, mine = 0;
#pragma unroll
            for (int c = 0; c < 7; c++) {
              const int t = c == 0 || c == 4 ? IT_FIN : c == 1 || c == 6 ? IT_ATT : c == 2 ? IT_OP : IT_BQ;
              int a = c == 1 || c == 2 || ((rdy >> t & 1) == (c < 4)) ? avail[t] : 0;
              if (c == 6) a = b < p.qa_end && !(rdy & 1) && ((chain_done << 1 | 1) >> b & 1) ? left[t] : 0;
              const int tot = __reduce_add_sync(~0u, a);
              if (type < 0) { if (rank < tot) { type = t; mine = a; } else rank -= tot; }
            }
            if (type >= 0) {
#pragma unroll
              for (int o = 1; o < 16; o <<= 1) { const int y = __shfl_up_sync(~0u, mine, o); if (lane >= o) mine += y; }
              const int blk = __ffs(__ballot_sync(~0u, mine > rank)) - 1;
              const int early = !(__shfl_sync(~0u, rdy, blk) >> type & 1);
              uint32_t idx = 0;
              if (lane == 0) idx = atomicAdd(sync + blk * 8 + type, 1);
              idx = __shfl_sync(~0u, idx, 0);
              if (idx < item_count(type, blk)) { code = (chain_done >> 14 & 1) << 22 | early << 20 | type << 16 | blk << 8 | idx; break; }
            } else {
              __nanosleep(50);
            }
            spin_guard(spin);
          }
        }
        if (lane == 0) {
          sts32(slots + 4 * (n & 3), code);
          mbar_arrive(bIF + 8 * (n & 3));
        }
        __syncwarp();
        if (code < 0) break;
      }
    } else if (warp == 10) {
      if (p.kind == WK_FIRST) probe_slots(bars + 320);
      work_loader<true>(p, sb);
    } else if (warp == 11) {
      work_loader<false>(p, sb);
    } else {
      if (p.kind == WK_FIRST) probe_slots(bars + 320);
      for (int n = 0;; n++) {
        mbar_wait_uniform(bIF + 8 * (n & 3), (n >> 2) & 1);
        const int code = __shfl_sync(~0u, (int)lds32(slots + 4 * (n & 3)), 0);
        if (code < 0) break;
        const int type = (code >> 16) & 15, b = (code >> 8) & 255;
        mbar_wait_uniform(done + 8 * (n & 3), (n >> 2) & 1);
        if (elect()) {
          if (type != IT_OUT) red_release(sync + (type < IT_BQ ? b * 8 + 5 + type : SY_P + b * 4 + ((0x13102 >> 4 * (type - IT_BQ)) & 3)), 1);
          mbar_arrive(bIE + 8 * (n & 3));
        }
        __syncwarp();
      }
    }
  } else {
    if (p.kind == WK_CHAIN) {
      asm volatile("setmaxnreg.inc.sync.aligned.u32 232;");
      if (warp < 4) chain_compute<0>(p.ch, sb); else chain_compute<1>(p.ch, sb);
    } else {
      asm volatile("setmaxnreg.inc.sync.aligned.u32 224;");
    }
    const int warp = __shfl_sync(~0u, fresh_tid() >> 5, 0), lane = fresh_tid() & 31;
    Ring r{sb, 0, p.kind == WK_CHAIN};
    Pending pend;
    pend.done = 0;
    int nln = 0;
    auto projects = [&](int n) {
      uint32_t here;
      asm volatile("{.reg .pred p; mbarrier.test_wait.parity.shared::cta.b64 p, [%1], %2; vote.sync.all.pred p, p, 0xffffffff; selp.u32 %0, 1, 0, p;}" : "=r"(here) : "r"(bIF + 8 * (n & 3)), "r"((n >> 2) & 1) : "memory");
      if (!here) return false;
      const int code = __shfl_sync(~0u, (int)lds32(slots + 4 * (n & 3)), 0);
      return code >= 0 && (((code >> 16) & 15) == IT_Q || (((code >> 16) & 15) == IT_ATT && ((code >> 8) & 255) < p.qa_end));
    };
#pragma unroll 1
    for (int n = 0;; n++) {
      if (pend.done && !projects(n)) pend.flush();
      mbar_wait_uniform(bIF + 8 * (n & 3), (n >> 2) & 1);
      const int code = __shfl_sync(~0u, (int)lds32(slots + 4 * (n & 3)), 0);
      if (code < 0) { TRACE(2); break; }
      const int type = (code >> 16) & 15, b = (code >> 8) & 255, idx = code & 255;
      const uint32_t go = (code & C_LATE) || (type == IT_ATT && (code & C_EARLY)) ? 0 : bGo;
      ITEM(code & 0xfffff, 0);
      if (type == IT_ATT || type == IT_Q) {
        if (type == IT_Q || b < p.qa_end) {
          float d[96] = {};
          reg_fence<96>(d);
          ITEM(9 << 16 | (code & 0xffff), 0);
          gemm_item<192>(d, r, 10, go, 4, pend);
          ITEM(9 << 16 | (code & 0xffff), 1);
#pragma unroll
          for (int i = 0; i < 48; i++) pend.w[i] = pack2(d[2 * i], d[2 * i + 1]);
        } else {
          const uint32_t base = r.wait(6) + warp * 2048 + lane * 16;
#pragma unroll
          for (int i = 0; i < 12; i++) {
            const uint4 t = lds128(base + (i >> 2) * 16384 + (i & 3) * 512);
            pend.w[4 * i] = t.x; pend.w[4 * i + 1] = t.y; pend.w[4 * i + 2] = t.z; pend.w[4 * i + 3] = t.w;
          }
          __syncwarp();
          r.release(r.seq - 1);
        }
        const bool now = type == IT_ATT && !projects(n + 1);
        if (type == IT_Q) {
          pend.dst = g_q + (b * 32 + idx) * 3072 + warp * 128 + lane;
        } else {
          pend.dst = g_o + (b * 32 + idx) * 3072 + (warp & 3) * 256 + (warp >> 2) * 128 + (lane & 3) * 8 + (lane >> 2);
          if (warp < 4) attn_a_warp<0>(r, pend, now); else attn_a_warp<1>(r, pend, now);
        }
        pend.done = done + 8 * (n & 3);
        if (now) pend.finish();
      } else {
        if (type == IT_FIN || type == IT_LN || type == IT_LN0) {
          const int ng = item_groups(type, b);
          const int planes = type == IT_FIN ? op_split(b) + 1 : 2;
          if (ng == 1) {
            ln_groups<1>(r, scratch + (nln++ & 1) * 1024, type == IT_LN0, planes, b * 16 + idx);
          } else {
#pragma unroll 1
            for (int i = 0; i < ng; i += 2) ln_groups<2>(r, scratch + (nln++ & 1) * 1024, type == IT_LN0, planes, b * 16 + idx * ng + i);
          }
        } else {
          const int cols = item_cols(type, b), nkb = type == IT_OP ? 96 / op_split(b) : 10;
          float d[160] = {};
          if (type == IT_OUT) {
            const uint2* x = g_x + ((b * 16 + warp * 2) * 40 + idx * 5) * 32 + lane;
#pragma unroll
            for (int i = 0; i < 10; i++) { const uint2 y = __ldcg(x + (i / 5 * 40 + i % 5) * 32); d[40 + 2 * i] = __uint_as_float(y.x); d[41 + 2 * i] = __uint_as_float(y.y); }
          }
          reg_fence<160>(d);
          if (type != IT_OUT) ITEM((type == IT_BQ ? 10 : 11) << 16 | (code & 0xffff), 0);
          const int ask = max(nkb - (code & C_TAIL ? GO_TAIL : GO_320) * 320 / cols, 0);
          if (cols == 320) gemm_item<320>(d, r, nkb, go, ask, pend);
          else if (cols == 160) gemm_item<160>(d, r, nkb, go, ask, pend);
          else gemm_item<80>(d, r, nkb, go, ask, pend);
          if (type != IT_OUT) ITEM((type == IT_BQ ? 10 : 11) << 16 | (code & 0xffff), 1);
          reg_fence<160>(d);
          if (type == IT_OUT) {
            bar_sync(1, 256);
            const uint32_t dst = sb + (warp * 16 + (lane & 15)) * 160 + (lane >> 4) * 16;
#pragma unroll
            for (int u = 0; u < 5; u++) {
              uint32_t w[4];
#pragma unroll
              for (int i = 0; i < 4; i++) { const uint32_t y = __float_as_uint(d[40 + (i & 1) * 10 + 2 * u + (i >> 1)]); w[i] = pack2(bf_lo(y) + d[8 * u + 2 * i], bf_hi(y) + d[8 * u + 2 * i + 1]); }
              stsm4(dst + u * 32, w[0], w[1], w[2], w[3]);
            }
            fence_async();
            __syncwarp();
            if (elect()) { tma_store(&p.out, sb + warp * 2560, idx * 80, b * 128 + warp * 16); bulk_commit(); bulk_wait<0>(); }
          } else {
            if (warp >= 4) bar_sync(7, 256);
            if (type == IT_BQ) store_bqkv(d, b, idx, cols / 20);
            else store_partial(d, b, cols == 320 ? idx >> 1 : idx >> 2, cols == 320 ? (idx & 1) * 20 : (idx & 3) * 10, cols >> 4);
            if (warp < 4) bar_arrive(7, 256);
          }
        }
        __syncwarp();
        if (elect()) mbar_arrive(done + 8 * (n & 3));
#pragma unroll
        for (int i = 0; i < 48; i++) pend.w[i] = 0;
      }
      if ((code & C_LATE) && warp == 4 && elect()) mbar_arrive(bGo);
      ITEM(code & 0xfffff, 1);
    }
  }
}

constexpr int AB_SMEM = 1024 + 2 * 98304 + 256;
#define AB_N 32
#define AB_WG 4
constexpr int AB_T = AB_WG * 128, AB_PASS = 8 / AB_WG;
__device__ __forceinline__ float ex2_poly(float t) {
  const uint32_t r = __float_as_uint(t) & 0xffff8000u;
  const float f = t - __uint_as_float(r);
  const float p = fmaf(fmaf(fmaf(-5.869912678e-38f, f, -1.700740250e-37f), f, -5.234869734e-37f), f, -7.522601252e-37f);
  uint32_t y;
  asm("mad.lo.u32 %0, %1, 256, %2;" : "=r"(y) : "r"(r), "r"(__float_as_uint(p)));
  return __uint_as_float(y);
}
__device__ __forceinline__ uint32_t hsq(uint32_t w, uint32_t c) { uint32_t r; asm("fma.rn.bf16x2 %0, %1, %1, %2;" : "=r"(r) : "r"(w), "r"(c)); return r; }
__device__ __forceinline__ float sq2(uint32_t w) { const float a = bf_lo(w), b = bf_hi(w); return fmaf(a, a, b * b); }

__device__ __forceinline__ void attn_b_store(const float* o, int h, int row0, int lane) {
  const int g = lane >> 2, c = lane & 3;
  const float i0 = 1.f / __shfl_sync(~0u, o[8], (lane & ~3) | 2), i1 = 1.f / __shfl_sync(~0u, o[10], (lane & ~3) | 2);
#pragma unroll
  for (int jj = 0; jj < 3; jj++) {
    if (jj < 2 || c < 2) {
      const int col = h * 20 + 8 * jj + 2 * c;
      g_of[core_word(row0 + g, col)] = pack2(o[4 * jj] * i0, o[4 * jj + 1] * i0);
      g_of[core_word(row0 + g + 8, col)] = pack2(o[4 * jj + 2] * i1, o[4 * jj + 3] * i1);
    }
  }
}

__device__ __forceinline__ void attn_b_qk(float* s, uint32_t q0, uint32_t q1, uint32_t q2, uint32_t q3, uint32_t q4, uint32_t q5, uint32_t z0, uint32_t z1,
                                          uint64_t dk, uint64_t dk2) {
  wg_rs32_00(s, q0, q1, q2, q3, dk, 0);
  wg_rs32_00(s, q4, q5, z0, z1, dk2, 1);
}

struct AttnParams { const uint8_t* pf[4]; uint32_t *sync, *next; };
__global__ void __launch_bounds__(AB_T + 128, 1) attn_b_kernel(const __grid_constant__ AttnParams p) {
  extern __shared__ uint8_t smem_raw[];
  const uint32_t sb = (s2u(smem_raw) + 1023) & ~1023u, sK = sb, sV = sb + 98304, bars = sb + 2 * 98304;
  const int warp = __shfl_sync(~0u, threadIdx.x >> 5, 0), lane = threadIdx.x & 31;
  const int h = blockIdx.x & 31, quarter = blockIdx.x >> 5;
  BT(0);
  TRACE(0);
  if (threadIdx.x == 0) {
    for (int i = 0; i < 8; i++) mbar_init(bars + 8 * i, 1);
    mbar_init(bars + 128, AB_T / 32);
    mbar_init(bars + 136, 2);
    asm volatile("fence.mbarrier_init.release.cluster;" ::: "memory");
  }
  __syncthreads();
  if (warp >= AB_T / 32) {
    asm volatile("setmaxnreg.dec.sync.aligned.u32 32;");
    if (warp == AB_T / 32 + 1) return;
    if (warp > AB_T / 32) {
      uint32_t kmax = 0;
#pragma unroll 1
      for (int i = 0; i < 32; i++) {
        if (!(i & 3)) mbar_wait_uniform(bars + 2 * i, 0);
        const uint32_t a = sK + i * 3072 + ((threadIdx.x >> 3) & 7) * 384 + (lane & 7) * 16;
        const uint4 x = lds128(a), y = lds128(a + 128);
        const uint2 z = lds64(a + 256);
        const uint32_t n = hadd2(hsq(x.x, hsq(x.y, hsq(x.z, hsq(x.w, hsq(z.x, 0))))), hsq(y.x, hsq(y.y, hsq(y.z, hsq(y.w, hsq(z.y, 0))))));
        kmax = max(kmax, __float_as_uint(bf_lo(n) + bf_hi(n)) & 0x7fffffffu);
      }
      const uint32_t kbits = __reduce_max_sync(~0u, kmax);
      if (lane == 0) { sts32(bars + 64 + (warp & 1) * 4, kbits); mbar_arrive(bars + 136); }
      return;
    }
    const uint8_t* gk = reinterpret_cast<const uint8_t*>(g_bqkv + (32 + h) * 256 * 96);
    const uint8_t* gv = reinterpret_cast<const uint8_t*>(g_bqkv + (64 + h) * 256 * 96);
    uint32_t todo = 255;
    for (int spin = 0; todo;) {
      const uint32_t up = __ballot_sync(~0u, ld_acquire(p.sync + SY_P + (lane & 15) * 4 + 2) >= bq_items(lane & 15));
      fence_async_global();
      for (int i = 0; i < 8; i++) {
        if (!(todo >> i & 1) || (up >> 2 * i & 3) != 3) continue;
        todo &= ~(1u << i);
        if (elect()) {
          mbar_expect(bars + 8 * i, 24576);
          bulk_load(sK + i * 12288, gk + i * 12288, 12288, bars + 8 * i);
          bulk_load(sV + i * 12288, gv + i * 12288, 12288, bars + 8 * i);
        }
      }
      spin_guard(spin);
    }
    pdl_launch();
    TRACE(1);
    if (blockIdx.x < NSLOT) for (int i = lane; i < 512; i += 32) reinterpret_cast<uint4*>(pool_at(blockIdx.x * 8192))[i] = make_uint4(0, 0, 0, 0);
    if (!p.next && blockIdx.x == 127) for (int i = lane; i < 256; i += 32) { g_smpart[i] = 0; if (i < NSLOT) g_orient[i] = 0; }
    if (p.next) {
      mbar_wait_uniform(bars + 128, 0);
      if (quarter == 0 && lane == 0) red_release(p.next + SY_OB, 1);
      for (int i = 0; i < 32; i++) {
        if (elect()) prefetch_l2(p.pf[i >> 3] + blockIdx.x * 61440 + (i & 7) * 7680, 7680);
        __nanosleep(300);
      }
    }
    return;
  }
  asm volatile("setmaxnreg.inc.sync.aligned.u32 112;");
  constexpr int NT = SEQ / AB_N, PER = 256 / AB_N;
  uint32_t qn[8];
  auto load_q = [&](int pass) {
    const uint32_t* gq = g_bqkv + (h * 256 + pass * 128 + quarter * 32 + warp * 2) * 96 + lane;
#pragma unroll
    for (int i = 0; i < 8; i++) qn[i] = __ldcg(gq + (i & 1) * 96 + min(i >> 1, 2) * 32 + (i < 6 ? 0 : 3 - (lane & 3)));
  };
  mbar_wait_uniform(bars + 8 * quarter, 0);
  load_q(0);
#pragma unroll 1
  for (int pass = 0; pass < AB_PASS; pass++) {
    const int row0 = pass * 1024 + quarter * 256 + warp * 16;
    const uint32_t q0 = qn[0], q1 = qn[1], q2 = qn[2], q3 = qn[3], z0 = qn[6], z1 = qn[7];
    uint32_t q4 = qn[4], q5 = qn[5];
    if ((lane & 3) == 2) { q4 = 0x43BCu; q5 = 0x43BCu; }
    float o[12];
    uint64_t dk = mkdesc(sK, 128, 384, 0), dk2 = mkdesc(sK + 256, 0, 384, 0), dv = mkdesc(sV, 384, 128, 0);
    float sa[AB_N / 2], sb2[AB_N / 2];
    uint32_t pa[AB_N / 4], pb[AB_N / 4];
    if (pass == 0) mbar_wait_uniform(bars, 0);
    BT(1 + 2 * pass);
    wg_fence();
    attn_b_qk(sa, q0, q1, q2, q3, q4, q5, z0, z1, dk, dk2);
    wg_commit();
    attn_b_qk(sb2, q0, q1, q2, q3, q4, q5, z0, z1, dk + AB_N * 3, dk2 + AB_N * 3);
    wg_commit();
#pragma unroll 1
    for (int kt = 0; kt < NT; kt += 2) {
      const int nx = kt + 2 < NT ? kt + 2 : 0;
      if (pass == 0 && (nx & (PER - 1)) == 0) mbar_wait_uniform(bars + 8 * (nx / PER), 0);
      const uint64_t nk = dk + nx * (AB_N * 3), nk2 = dk2 + nx * (AB_N * 3);
      wg_wait<1>();
      reg_fence<AB_N / 2>(sa);
#pragma unroll
      for (int i = 0; i < AB_N / 4; i++) pa[i] = pack2(ex2(sa[2 * i]), poly_group(i >> 1) ? ex2_poly(sa[2 * i + 1]) : ex2(sa[2 * i + 1]));
      wg_fence();
#pragma unroll
      for (int kk = 0; kk < AB_N / 16; kk++) wg_rs24_01(o, pa[4 * kk], pa[4 * kk + 1], pa[4 * kk + 2], pa[4 * kk + 3], dv + kk * 48, kk | kt);
      attn_b_qk(sa, q0, q1, q2, q3, q4, q5, z0, z1, nk, nk2);
      wg_commit();
      wg_wait<1>();
      reg_fence<AB_N / 2>(sb2);
#pragma unroll
      for (int i = 0; i < AB_N / 4; i++) pb[i] = pack2(ex2(sb2[2 * i]), poly_group((i >> 1) + AB_N / 8) ? ex2_poly(sb2[2 * i + 1]) : ex2(sb2[2 * i + 1]));
      wg_fence();
#pragma unroll
      for (int kk = 0; kk < AB_N / 16; kk++) wg_rs24_01(o, pb[4 * kk], pb[4 * kk + 1], pb[4 * kk + 2], pb[4 * kk + 3], dv + AB_N * 3 + kk * 48, 1);
      attn_b_qk(sb2, q0, q1, q2, q3, q4, q5, z0, z1, nk + AB_N * 3, nk2 + AB_N * 3);
      wg_commit();
      dv += AB_N * 6;
    }
    wg_wait<0>();
    reg_fence<12>(o); reg_fence<AB_N / 2>(sa); reg_fence<AB_N / 2>(sb2);
    BT(2 + 2 * pass);
    if (pass + 1 < AB_PASS) load_q(pass + 1);
    mbar_wait_uniform(bars + 136, 0);
    const uint2 kb = lds64(bars + 64);
    const float kmax = __uint_as_float(max(kb.x, kb.y));
    if ((lane & 3) == 2) q4 = q5 = 0;
    float n0 = sq2(q0) + sq2(q2) + sq2(q4), n1 = sq2(q1) + sq2(q3) + sq2(q5);
    n0 += __shfl_xor_sync(~0u, n0, 1); n1 += __shfl_xor_sync(~0u, n1, 1);
    n0 += __shfl_xor_sync(~0u, n0, 2); n1 += __shfl_xor_sync(~0u, n1, 2);
    uint32_t redo;
    asm volatile("{.reg .pred p, q; setp.ne.u32 p, %1, 0; bar.red.or.pred q, %2, 128, p; selp.u32 %0, 1, 0, q;}"
                 : "=r"(redo) : "r"((uint32_t)!(n0 * kmax <= 9500.f && n1 * kmax <= 9500.f)), "r"(2 + (warp >> 2)) : "memory");
    if (redo) {
#pragma unroll
      for (int i = 0; i < 12; i++) o[i] = 0.f;
      float m0 = -INFINITY, m1 = -INFINITY;
#pragma unroll 1
      for (int kt = 0; kt < 64; kt++) {
        float s[16];
        wg_fence();
        wg_rs32_00(s, q0, q1, q2, q3, dk + kt * 96, 0);
        wg_rs32_00(s, q4, q5, z0, z1, dk2 + kt * 96, 1);
        wg_commit();
        wg_wait<0>();
        reg_fence<16>(s); reg_fence<12>(o);
        float n0 = m0, n1 = m1;
#pragma unroll
        for (int jj = 0; jj < 4; jj++) { n0 = fmaxf(n0, fmaxf(s[4 * jj], s[4 * jj + 1])); n1 = fmaxf(n1, fmaxf(s[4 * jj + 2], s[4 * jj + 3])); }
        n0 = fmaxf(n0, __shfl_xor_sync(~0u, n0, 1)); n0 = fmaxf(n0, __shfl_xor_sync(~0u, n0, 2));
        n1 = fmaxf(n1, __shfl_xor_sync(~0u, n1, 1)); n1 = fmaxf(n1, __shfl_xor_sync(~0u, n1, 2));
        const float r0 = ex2(m0 - n0), r1 = ex2(m1 - n1);
        m0 = n0; m1 = n1;
#pragma unroll
        for (int jj = 0; jj < 3; jj++) { o[4 * jj] *= r0; o[4 * jj + 1] *= r0; o[4 * jj + 2] *= r1; o[4 * jj + 3] *= r1; }
        uint32_t pp[8];
#pragma unroll
        for (int jj = 0; jj < 4; jj++) {
          pp[2 * jj] = pack2(ex2(s[4 * jj] - m0), ex2(s[4 * jj + 1] - m0));
          pp[2 * jj + 1] = pack2(ex2(s[4 * jj + 2] - m1), ex2(s[4 * jj + 3] - m1));
        }
        reg_fence<12>(o);
        wg_fence();
#pragma unroll
        for (int kk = 0; kk < 2; kk++) wg_rs24_01(o, pp[4 * kk], pp[4 * kk + 1], pp[4 * kk + 2], pp[4 * kk + 3], mkdesc(sV, 384, 128, 0) + kt * 96 + kk * 48, 1);
        wg_commit();
      }
      wg_wait<0>();
      reg_fence<12>(o);
    }
    attn_b_store(o, h, row0, lane);
    __syncwarp();
    if (pass == 0 && lane == 0) mbar_arrive(bars + 128);
  }
  BT(5);
  TRACE(2);
}

typedef CUresult (*EncodeFn)(CUtensorMap*, CUtensorMapDataType, cuuint32_t, void*, const cuuint64_t*, const cuuint64_t*,
                             const cuuint32_t*, const cuuint32_t*, CUtensorMapInterleave, CUtensorMapSwizzle,
                             CUtensorMapL2promotion, CUtensorMapFloatOOBfill);

void make_map(EncodeFn enc, CUtensorMap* m, const void* ptr, int cols, int rows, int box_rows, int box_cols = 64) {
  const cuuint64_t dims[2] = {(cuuint64_t)cols, (cuuint64_t)rows};
  const cuuint64_t strides[1] = {(cuuint64_t)cols * 2};
  const cuuint32_t box[2] = {(cuuint32_t)box_cols, (cuuint32_t)box_rows}, es[2] = {1, 1};
  enc(m, CU_TENSOR_MAP_DATA_TYPE_BFLOAT16, 2, const_cast<void*>(ptr), dims, strides, box, es, CU_TENSOR_MAP_INTERLEAVE_NONE,
      box_cols == 64 ? CU_TENSOR_MAP_SWIZZLE_128B : box_cols == 32 ? CU_TENSOR_MAP_SWIZZLE_64B : CU_TENSOR_MAP_SWIZZLE_NONE, CU_TENSOR_MAP_L2_PROMOTION_L2_256B, CU_TENSOR_MAP_FLOAT_OOB_FILL_NONE);
}
void make_tiles(EncodeFn enc, CUtensorMap* m, const void* ptr, int cols, int tile) {
  const cuuint64_t dims[3] = {(cuuint64_t)tile, DM, (cuuint64_t)(cols / tile)}, strides[2] = {(cuuint64_t)cols * 2, (cuuint64_t)tile * 2};
  const cuuint32_t box[3] = {64, 64, 1}, es[3] = {1, 1, 1};
  enc(m, CU_TENSOR_MAP_DATA_TYPE_BFLOAT16, 3, const_cast<void*>(ptr), dims, strides, box, es, CU_TENSOR_MAP_INTERLEAVE_NONE,
      CU_TENSOR_MAP_SWIZZLE_128B, tile % 64 ? CU_TENSOR_MAP_L2_PROMOTION_L2_128B : CU_TENSOR_MAP_L2_PROMOTION_L2_256B, CU_TENSOR_MAP_FLOAT_OOB_FILL_NONE);
}
template <class... KA, class... A>
void launch(void (*kern)(KA...), int grid, int block, int smem, int cluster, bool pdl, A... args) {
  cudaFuncSetAttribute(kern, cudaFuncAttributeMaxDynamicSharedMemorySize, smem);
  cudaLaunchConfig_t cfg = {};
  cfg.gridDim = dim3(grid); cfg.blockDim = dim3(block); cfg.dynamicSmemBytes = smem; cfg.stream = cudaStreamPerThread;
  cudaLaunchAttribute at[2];
  int n = 0;
  if (cluster > 1) { at[n].id = cudaLaunchAttributeClusterDimension; at[n].val.clusterDim.x = cluster; at[n].val.clusterDim.y = 1; at[n].val.clusterDim.z = 1; n++; }
  if (pdl) { at[n].id = cudaLaunchAttributeProgrammaticStreamSerialization; at[n].val.programmaticStreamSerializationAllowed = 1; n++; }
  cfg.attrs = at; cfg.numAttrs = n;
  cudaLaunchKernelEx(&cfg, kern, args...);
}
template <class T> void* sym(T& s) { void* p = nullptr; cudaGetSymbolAddress(&p, s); return p; }

}

#define MODE(b) 0
extern "C" void kernel_launch(void* const* d_in, const int* in_sizes, int n_in, void* d_out, int out_size) {
  const __nv_bfloat16* x = (const __nv_bfloat16*)d_in[0];
  void* fn = nullptr; cudaDriverEntryPointQueryResult qr;
  cudaGetDriverEntryPoint("cuTensorMapEncodeTiled", &fn, cudaEnableDefault, &qr);
  EncodeFn enc = (EncodeFn)fn;

  WorkParams wk = {};
  ChainParams& ch = wk.ch;
  AttnParams at = {};
  make_map(enc, &ch.wq, d_in[2], HD, DM, 128); make_map(enc, &ch.wk, d_in[3], HD, DM, 128); make_map(enc, &ch.wv, d_in[4], HD, DM, 128);
  make_map(enc, &ch.wo, d_in[5], DM, HD, 192, 32);
  ch.mem0 = (const __nv_bfloat16*)d_in[1];
  ch.wb = (const uint8_t*)d_in[8];
  ch.d1 = 300; ch.d2 = 300; ch.dn = 250; ch.dx = 900;
  make_tiles(enc, &wk.wq, d_in[2], HD, 192);
  for (int i = 0; i < 3; i++) make_tiles(enc, &wk.wb[i], d_in[8], 1920, 80 << i);
  for (int i = 0; i < 2; i++) make_tiles(enc, &wk.wc[i], d_in[9], DM, 80 << 2 * i);
  make_map(enc, &wk.out, d_out, DM, SEQ, 16, 80);
  {
    const cuuint64_t dims[5] = {DM, 2, 4, 4, HD / 32}, strides[4] = {DM * 2, DM * 16, DM * 4, DM * 64};
    const cuuint32_t box[5] = {64, 2, 4, 4, 2}, es[5] = {1, 1, 1, 1, 1};
    enc(&wk.wo, CU_TENSOR_MAP_DATA_TYPE_BFLOAT16, 5, d_in[5], dims, strides, box, es, CU_TENSOR_MAP_INTERLEAVE_NONE, CU_TENSOR_MAP_SWIZZLE_128B,
        CU_TENSOR_MAP_L2_PROMOTION_L2_256B, CU_TENSOR_MAP_FLOAT_OOB_FILL_NONE);
  }
  for (int i = 0; i < 2; i++) {
    const cuuint64_t dims[4] = {1280, 2, i ? 64u : 2u, i ? 2u : 64u}, strides[3] = {10240, i ? 40960u : 20480u, i ? 20480u : 40960u};
    const cuuint32_t box[4] = {128, 2, i ? 4u : 2u, i ? 2u : 4u}, es[4] = {1, 1, 1, 1};
    enc(i ? &wk.xp : &wk.xn, CU_TENSOR_MAP_DATA_TYPE_UINT64, 4, sym(g_xn), dims, strides, box, es, CU_TENSOR_MAP_INTERLEAVE_NONE, CU_TENSOR_MAP_SWIZZLE_NONE,
        CU_TENSOR_MAP_L2_PROMOTION_L2_256B, CU_TENSOR_MAP_FLOAT_OOB_FILL_NONE);
  }
  wk.x = x;
  for (int i = 0; i < 4; i++) at.pf[i] = (const uint8_t*)d_in[i < 2 ? 3 + i : i == 2 ? 2 : 5];
  int qa_end[2] = {12, 12};
  for (int layer = 0; layer < 2; layer++) {
    ch.sync = wk.sync = at.sync = (uint32_t*)sym(g_sync) + layer * SY_N;
    ch.other = (uint32_t*)sym(g_sync) + (1 - layer) * SY_N;
    ch.layer = layer;
    at.next = layer ? nullptr : ch.other;
    wk.qa_end = qa_end[layer];
    wk.kind = layer ? WK_LEAD : WK_FIRST;
    launch(work_kernel, 132, 384, CH_SMEM, 1, layer != 0, wk);
    wk.kind = WK_CHAIN;
    launch(work_kernel, 96, 384, CH_SMEM, 3, true, wk);
    launch(attn_b_kernel, 128, AB_T + 128, AB_SMEM, 1, true, at);
  }
  wk.kind = WK_LAST;
  launch(work_kernel, 128, 384, CH_SMEM, 1, true, wk);
}
```

```cpp
#include <cuda_runtime.h>
#include <cuda_bf16.h>
#include <cuda.h>
#include <stdint.h>
#include <stdlib.h>

namespace {

constexpr int SEQ = 2048, DM = 640, HD = 6144, NSEG = 64;
constexpr int SPIN_LIMIT = 1 << 20;

__device__ __align__(128) uint2 g_x[256 * 17 * 1280];
__device__ __align__(128) uint32_t g_xn[SEQ * DM / 2];
__device__ __align__(128) uint32_t g_of[SEQ * DM / 2];
__device__ __align__(128) uint4 g_o[SEQ * HD / 8];
__device__ __align__(128) uint4 g_q[SEQ * HD / 8];
constexpr int KV_M = 16384, KV_PART = 20480, KV_V = 3 * KV_PART;
__device__ __align__(128) uint8_t g_kv[16 * 32 * 6 * KV_PART];
#define OP_B8 11
#define OP_B16 14
#define OP_N4 15
#define BQ_12 12
#define BQ_24 14
#define FIN_16 12
__host__ __device__ constexpr int op_split(int b) { return b < OP_B8 ? 4 : b < OP_B16 ? 8 : 16; }
__host__ __device__ constexpr int op_tiles(int b) { return b < OP_N4 ? 2 : 4; }
__host__ __device__ constexpr int fin_items(int b) { return b < OP_B8 ? 4 : b < FIN_16 ? 8 : 16; }
__host__ __device__ constexpr int bq_items(int b) { return b < BQ_12 ? 6 : b < BQ_24 ? 12 : 24; }
__host__ __device__ constexpr int ln_items(int layer, int b) { return layer == 0 && b < 2 ? 16 : 4; }
constexpr int SY_P = 128, SY_T = 192, SY_UP = 224, SY_OB = 225, SY_PRE = 256, SY_PART = 288, SY_TIME = 384, SY_N = 448;
__device__ __align__(128) uint32_t g_sync[2 * SY_N];
constexpr int NSLOT = 92;
__device__ uint32_t g_pool[(NSLOT + 2) * 2048];
__device__ uint32_t g_smpart[256], g_orient[NSLOT];
__device__ __align__(128) uint32_t g_bqkv[3 * 32 * 256 * 96];

#define BT(i)
#define MISS(k, n)
#define PRO(i)
#define TRACE(w)
#define ITEM(code, w)
#define STAT(k)
#define TMV(i, v)
#define TM(i)
#define TMD(i, dep)

__device__ __forceinline__ uint32_t gtime() { uint32_t c; asm volatile("mov.u32 %0, %%globaltimer_lo;" : "=r"(c) :: "memory"); return c; }
__device__ __forceinline__ uint32_t clk32() { uint32_t c; asm volatile("mov.u32 %0, %%clock;" : "=r"(c) :: "memory"); return c; }
__device__ __forceinline__ uint32_t fresh_tid() { uint32_t t; asm volatile("mov.u32 %0, %%tid.x;" : "=r"(t)); return t; }
__device__ __forceinline__ uint32_t s2u(const void* p) { return (uint32_t)__cvta_generic_to_shared(p); }
__device__ __forceinline__ uint32_t pack2(float a, float b) {
  uint32_t r; asm("cvt.rn.bf16x2.f32 %0, %1, %2;" : "=r"(r) : "f"(b), "f"(a)); return r; }
__device__ __forceinline__ float bf_lo(uint32_t w) { return __uint_as_float(w << 16); }
__device__ __forceinline__ float bf_hi(uint32_t w) { return __uint_as_float(w & 0xffff0000u); }
__device__ __forceinline__ float ex2(float x) { float y; asm("ex2.approx.ftz.f32 %0, %1;" : "=f"(y) : "f"(x)); return y; }

__device__ __forceinline__ void mbar_init(uint32_t bar, uint32_t n) {
  asm volatile("mbarrier.init.shared::cta.b64 [%0], %1;" :: "r"(bar), "r"(n) : "memory"); }
__device__ __forceinline__ void mbar_expect(uint32_t bar, uint32_t bytes) {
  asm volatile("mbarrier.arrive.expect_tx.shared::cta.b64 _, [%0], %1;" :: "r"(bar), "r"(bytes) : "memory"); }
__device__ __forceinline__ void mbar_arrive(uint32_t bar) {
  asm volatile("mbarrier.arrive.shared::cta.b64 _, [%0];" :: "r"(bar) : "memory"); }
__device__ __forceinline__ void mbar_arrive_remote(uint32_t bar) {
  asm volatile("mbarrier.arrive.shared::cluster.b64 _, [%0];" :: "r"(bar) : "memory"); }
__device__ __forceinline__ void mbar_wait_slow(uint32_t bar, uint32_t ph) {
  asm volatile("{.reg .pred p; .reg .u32 n; mov.u32 n, 0;\n"
               "W: mbarrier.try_wait.parity.shared::cta.b64 p, [%0], %1; @p bra D;\n"
               "add.u32 n, n, 1; setp.gt.u32 p, n, %2; @p trap; bra W;\n"
               "D: }" :: "r"(bar), "r"(ph), "n"(SPIN_LIMIT) : "memory");
}
__device__ __forceinline__ void mbar_wait(uint32_t bar, uint32_t ph) {
  uint32_t ok;
  asm volatile("{.reg .pred p; mbarrier.try_wait.parity.shared::cta.b64 p, [%1], %2; selp.u32 %0, 1, 0, p;}" : "=r"(ok) : "r"(bar), "r"(ph) : "memory");
  if (__builtin_expect(!ok, 0)) mbar_wait_slow(bar, ph);
}
__device__ __forceinline__ void mbar_wait_uniform(uint32_t bar, uint32_t ph) {
  asm volatile("{.reg .pred p; .reg .u32 n; mov.u32 n, 0;\n"
               "W: mbarrier.try_wait.parity.shared::cta.b64 p, [%0], %1; vote.sync.all.pred p, p, 0xffffffff; @p bra.uni D;\n"
               "add.u32 n, n, 1; setp.gt.u32 p, n, %2; @p trap; bra.uni W;\n"
               "D: }" :: "r"(bar), "r"(ph), "n"(SPIN_LIMIT) : "memory");
}
__device__ __forceinline__ bool elect() {
  uint32_t p; asm volatile("{.reg .pred q; elect.sync _|q, 0xffffffff; selp.u32 %0, 1, 0, q;}" : "=r"(p)); return p; }
__device__ __forceinline__ void mbar_wait_cluster(uint32_t bar, uint32_t ph) {
  asm volatile("{.reg .pred p; .reg .u32 n; mov.u32 n, 0;\n"
               "W: mbarrier.try_wait.parity.acquire.cluster.shared::cta.b64 p, [%0], %1; @p bra D;\n"
               "add.u32 n, n, 1; setp.gt.u32 p, n, %2; @p trap; bra W;\n"
               "D: }" :: "r"(bar), "r"(ph), "n"(SPIN_LIMIT) : "memory");
}
__device__ __forceinline__ void spin_guard(int& n) {
  asm volatile("{.reg .pred p; add.s32 %0, %0, 1; setp.gt.s32 p, %0, %1; @p trap;}" : "+r"(n) : "n"(SPIN_LIMIT));
}
__device__ __forceinline__ void pdl_wait() { asm volatile("griddepcontrol.wait;" ::: "memory"); TRACE(1); }
__device__ __forceinline__ void pdl_launch() { asm volatile("griddepcontrol.launch_dependents;" ::: "memory"); }
__device__ __forceinline__ uint32_t ld_acquire(const uint32_t* p) { uint32_t v; asm volatile("ld.acquire.gpu.global.u32 %0, [%1];" : "=r"(v) : "l"(p) : "memory"); return v; }
__device__ __forceinline__ void red_release(uint32_t* p, uint32_t v) { asm volatile("red.release.gpu.global.add.u32 [%0], %1;" :: "l"(p), "r"(v) : "memory"); }
__device__ __forceinline__ void fence_async_global() { asm volatile("fence.proxy.async.global;" ::: "memory"); }
__device__ __forceinline__ void fence_async() { asm volatile("fence.proxy.async.shared::cta;" ::: "memory"); }
__device__ __forceinline__ void bar_sync(int id, int n) { asm volatile("bar.sync %0, %1;" :: "r"(id), "r"(n) : "memory"); }
__device__ __forceinline__ void bar_arrive(int id, int n) { asm volatile("bar.arrive %0, %1;" :: "r"(id), "r"(n) : "memory"); }
__device__ __forceinline__ void tma_load(uint32_t dst, const CUtensorMap* m, int c0, int c1, uint32_t bar) {
  asm volatile("cp.async.bulk.tensor.2d.shared::cluster.global.mbarrier::complete_tx::bytes [%0], [%1, {%3, %4}], [%2];"
               :: "r"(dst), "l"(m), "r"(bar), "r"(c0), "r"(c1) : "memory"); }
__device__ __forceinline__ void tma_store(const CUtensorMap* m, uint32_t src, int c0, int c1) {
  asm volatile("cp.async.bulk.tensor.2d.global.shared::cta.bulk_group [%0, {%2, %3}], [%1];"
               :: "l"(m), "r"(src), "r"(c0), "r"(c1) : "memory"); }
__device__ __forceinline__ uint64_t evict_first() { uint64_t p; asm("createpolicy.fractional.L2::evict_first.b64 %0, 1.0;" : "=l"(p)); return p; }
__device__ __forceinline__ void bulk_load_last(uint32_t dst, const void* src, uint32_t bytes, uint32_t bar) {
  asm volatile("cp.async.bulk.shared::cluster.global.mbarrier::complete_tx::bytes.L2::cache_hint [%0], [%1], %2, [%3], %4;"
               :: "r"(dst), "l"(src), "r"(bytes), "r"(bar), "l"(evict_first()) : "memory"); }
__device__ __forceinline__ void bulk_store_stream(void* dst, uint32_t src, uint32_t bytes) {
  asm volatile("cp.async.bulk.global.shared::cta.bulk_group.L2::cache_hint [%0], [%1], %2, %3;" :: "l"(dst), "r"(src), "r"(bytes), "l"(evict_first()) : "memory"); }
__device__ __forceinline__ void bulk_load(uint32_t dst, const void* src, uint32_t bytes, uint32_t bar) {
  asm volatile("cp.async.bulk.shared::cluster.global.mbarrier::complete_tx::bytes [%0], [%1], %2, [%3];"
               :: "r"(dst), "l"(src), "r"(bytes), "r"(bar) : "memory"); }
__device__ __forceinline__ void bulk_push(uint32_t dst, uint32_t src, uint32_t bytes, uint32_t bar) {
  asm volatile("cp.async.bulk.shared::cluster.shared::cta.mbarrier::complete_tx::bytes [%0], [%1], %2, [%3];"
               :: "r"(dst), "r"(src), "r"(bytes), "r"(bar) : "memory"); }
__device__ __forceinline__ void bulk_store(void* dst, uint32_t src, uint32_t bytes) {
  asm volatile("cp.async.bulk.global.shared::cta.bulk_group [%0], [%1], %2;" :: "l"(dst), "r"(src), "r"(bytes) : "memory"); }
__device__ __forceinline__ void bulk_commit() { asm volatile("cp.async.bulk.commit_group;" ::: "memory"); }
template <int N> __device__ __forceinline__ void bulk_wait_read() { asm volatile("cp.async.bulk.wait_group.read %0;" :: "n"(N) : "memory"); }
template <int N> __device__ __forceinline__ void bulk_wait() { asm volatile("cp.async.bulk.wait_group %0;" :: "n"(N) : "memory"); }

__device__ __forceinline__ uint64_t mkdesc(uint32_t addr, uint32_t lbo, uint32_t sbo, uint32_t sw) {
  return (uint64_t)((addr & 0x3FFFF) >> 4) | ((uint64_t)(lbo >> 4) << 16) | ((uint64_t)(sbo >> 4) << 32) | ((uint64_t)sw << 62); }
__device__ __forceinline__ void wg_fence() { asm volatile("wgmma.fence.sync.aligned;" ::: "memory"); }
__device__ __forceinline__ void wg_commit() { asm volatile("wgmma.commit_group.sync.aligned;" ::: "memory"); }
template <int N> __device__ __forceinline__ void wg_wait() { asm volatile("wgmma.wait_group.sync.aligned %0;" :: "n"(N) : "memory"); }
template <int N> __device__ __forceinline__ void reg_fence(float* d) {
#pragma unroll
  for (int i = 0; i < N; i++) asm volatile("" : "+f"(d[i]) :: "memory");
}

__device__ __forceinline__ void mma16(float* d, uint32_t a0, uint32_t a1, uint32_t a2, uint32_t a3, uint32_t b0, uint32_t b1) {
  asm volatile("mma.sync.aligned.m16n8k16.row.col.f32.bf16.bf16.f32 {%0,%1,%2,%3},{%4,%5,%6,%7},{%8,%9},{%0,%1,%2,%3};"
               : "+f"(d[0]), "+f"(d[1]), "+f"(d[2]), "+f"(d[3]) : "r"(a0), "r"(a1), "r"(a2), "r"(a3), "r"(b0), "r"(b1)); }
__device__ __forceinline__ void mma8(float* d, uint32_t a0, uint32_t a1, uint32_t b0) {
  asm volatile("mma.sync.aligned.m16n8k8.row.col.f32.bf16.bf16.f32 {%0,%1,%2,%3},{%4,%5},{%6},{%0,%1,%2,%3};"
               : "+f"(d[0]), "+f"(d[1]), "+f"(d[2]), "+f"(d[3]) : "r"(a0), "r"(a1), "r"(b0)); }
__device__ __forceinline__ void ldsm4(uint32_t* r, uint32_t a) {
  asm volatile("ldmatrix.sync.aligned.m8n8.x4.shared.b16 {%0,%1,%2,%3},[%4];" : "=r"(r[0]), "=r"(r[1]), "=r"(r[2]), "=r"(r[3]) : "r"(a) : "memory"); }
__device__ __forceinline__ uint4 ldsm4v(uint32_t a) { uint32_t r[4]; ldsm4(r, a); return make_uint4(r[0], r[1], r[2], r[3]); }
__device__ __forceinline__ void ldsm4t(uint32_t* r, uint32_t a) {
  asm volatile("ldmatrix.sync.aligned.m8n8.x4.trans.shared.b16 {%0,%1,%2,%3},[%4];" : "=r"(r[0]), "=r"(r[1]), "=r"(r[2]), "=r"(r[3]) : "r"(a) : "memory"); }
__device__ __forceinline__ void ldsm2t(uint32_t* r, uint32_t a) {
  asm volatile("ldmatrix.sync.aligned.m8n8.x2.trans.shared.b16 {%0,%1},[%2];" : "=r"(r[0]), "=r"(r[1]) : "r"(a) : "memory"); }
__device__ __forceinline__ void stsm4(uint32_t a, uint32_t r0, uint32_t r1, uint32_t r2, uint32_t r3) {
  asm volatile("stmatrix.sync.aligned.m8n8.x4.shared.b16 [%0], {%1,%2,%3,%4};" :: "r"(a), "r"(r0), "r"(r1), "r"(r2), "r"(r3) : "memory"); }
__device__ __forceinline__ void stsm4t(uint32_t a, uint32_t r0, uint32_t r1, uint32_t r2, uint32_t r3) {
  asm volatile("stmatrix.sync.aligned.m8n8.x4.trans.shared.b16 [%0], {%1,%2,%3,%4};" :: "r"(a), "r"(r0), "r"(r1), "r"(r2), "r"(r3) : "memory"); }
__device__ __forceinline__ void stsm2(uint32_t a, uint32_t r0, uint32_t r1) {
  asm volatile("stmatrix.sync.aligned.m8n8.x2.shared.b16 [%0], {%1,%2};" :: "r"(a), "r"(r0), "r"(r1) : "memory"); }
__device__ __forceinline__ void stsm2t(uint32_t a, uint32_t r0, uint32_t r1) {
  asm volatile("stmatrix.sync.aligned.m8n8.x2.trans.shared.b16 [%0], {%1,%2};" :: "r"(a), "r"(r0), "r"(r1) : "memory"); }
__device__ __forceinline__ void sts32(uint32_t a, uint32_t v) { asm volatile("st.shared.b32 [%0], %1;" :: "r"(a), "r"(v) : "memory"); }
__device__ __forceinline__ void sts64f(uint32_t a, float x, float y) { asm volatile("st.shared.v2.f32 [%0], {%1,%2};" :: "r"(a), "f"(x), "f"(y) : "memory"); }
__device__ __forceinline__ void sts128(uint32_t a, uint4 v) {
  asm volatile("st.shared.v4.b32 [%0], {%1,%2,%3,%4};" :: "r"(a), "r"(v.x), "r"(v.y), "r"(v.z), "r"(v.w) : "memory"); }
__device__ __forceinline__ void sts128f(uint32_t a, float x, float y, float z, float w) {
  asm volatile("st.shared.v4.f32 [%0], {%1,%2,%3,%4};" :: "r"(a), "f"(x), "f"(y), "f"(z), "f"(w) : "memory"); }
__device__ __forceinline__ float lds32f(uint32_t a) { float v; asm volatile("ld.shared.f32 %0, [%1];" : "=f"(v) : "r"(a) : "memory"); return v; }
__device__ __forceinline__ float2 lds64f(uint32_t a) { float2 v; asm volatile("ld.shared.v2.f32 {%0,%1}, [%2];" : "=f"(v.x), "=f"(v.y) : "r"(a) : "memory"); return v; }
__device__ __forceinline__ float4 lds128f(uint32_t a) {
  float4 v; asm volatile("ld.shared.v4.f32 {%0,%1,%2,%3}, [%4];" : "=f"(v.x), "=f"(v.y), "=f"(v.z), "=f"(v.w) : "r"(a) : "memory"); return v; }
__device__ __forceinline__ uint4 lds128(uint32_t a) {
  uint4 v; asm volatile("ld.shared.v4.b32 {%0,%1,%2,%3}, [%4];" : "=r"(v.x), "=r"(v.y), "=r"(v.z), "=r"(v.w) : "r"(a) : "memory"); return v; }
__device__ __forceinline__ uint4 ldg_strong128(const void* p) {
  uint4 v; asm volatile("ld.relaxed.gpu.global.v4.u32 {%0,%1,%2,%3}, [%4];" : "=r"(v.x), "=r"(v.y), "=r"(v.z), "=r"(v.w) : "l"(p) : "memory"); return v; }
__device__ __forceinline__ uint2 ldg_strong64(const void* p) {
  uint2 v; asm volatile("ld.relaxed.gpu.global.v2.u32 {%0,%1}, [%2];" : "=r"(v.x), "=r"(v.y) : "l"(p) : "memory"); return v; }
__device__ __forceinline__ void stg_strong32(void* p, uint32_t v) { asm volatile("st.relaxed.gpu.global.u32 [%0], %1;" :: "l"(p), "r"(v) : "memory"); }
__device__ __forceinline__ void stg_strong128(void* p, uint4 v) {
  asm volatile("st.relaxed.gpu.global.v4.u32 [%0], {%1,%2,%3,%4};" :: "l"(p), "r"(v.x), "r"(v.y), "r"(v.z), "r"(v.w) : "memory"); }
__device__ __forceinline__ uint32_t mapa(uint32_t a, uint32_t r) {
  uint32_t o; asm("mapa.shared::cluster.u32 %0, %1, %2;" : "=r"(o) : "r"(a), "r"(r)); return o; }
__device__ __forceinline__ void st_async2f(uint32_t a, float x, float y, uint32_t bar) {
  asm volatile("st.async.shared::cluster.mbarrier::complete_tx::bytes.v2.f32 [%0], {%1,%2}, [%3];" :: "r"(a), "f"(x), "f"(y), "r"(bar) : "memory"); }
__device__ __forceinline__ void st_async32(uint32_t a, uint32_t x, uint32_t bar) {
  asm volatile("st.async.shared::cluster.mbarrier::complete_tx::bytes.b32 [%0], %1, [%2];" :: "r"(a), "r"(x), "r"(bar) : "memory"); }
__device__ __forceinline__ uint32_t lds32(uint32_t a) { uint32_t v; asm volatile("ld.shared.b32 %0, [%1];" : "=r"(v) : "r"(a) : "memory"); return v; }
__device__ __forceinline__ void st_async64(uint32_t a, uint32_t x, uint32_t y, uint32_t bar) {
  asm volatile("st.async.shared::cluster.mbarrier::complete_tx::bytes.v2.b32 [%0], {%1,%2}, [%3];" :: "r"(a), "r"(x), "r"(y), "r"(bar) : "memory"); }
__device__ __forceinline__ void st_async128(uint32_t a, uint4 v, uint32_t bar) {
  asm volatile("st.async.shared::cluster.mbarrier::complete_tx::bytes.v4.b32 [%0], {%1,%2,%3,%4}, [%5];" :: "r"(a), "r"(v.x), "r"(v.y), "r"(v.z), "r"(v.w), "r"(bar) : "memory"); }
__device__ __forceinline__ uint2 lds64(uint32_t a) { uint2 v; asm volatile("ld.shared.v2.b32 {%0,%1}, [%2];" : "=r"(v.x), "=r"(v.y) : "r"(a) : "memory"); return v; }
__device__ __forceinline__ void sts64(uint32_t a, uint32_t x, uint32_t y) { asm volatile("st.shared.v2.b32 [%0], {%1,%2};" :: "r"(a), "r"(x), "r"(y) : "memory"); }
__device__ __forceinline__ uint32_t ldg_strong32(const void* p) { uint32_t v; asm volatile("ld.relaxed.gpu.global.u32 %0, [%1];" : "=r"(v) : "l"(p) : "memory"); return v; }
__device__ __forceinline__ uint32_t transpose8(uint32_t x) { uint32_t r; asm volatile("movmatrix.sync.aligned.m8n8.trans.b16 %0, %1;" : "=r"(r) : "r"(x)); return r; }
__device__ __forceinline__ uint32_t hadd2(uint32_t a, uint32_t b) { uint32_t r; asm("add.rn.bf16x2 %0, %1, %2;" : "=r"(r) : "r"(a), "r"(b)); return r; }
__device__ __forceinline__ uint32_t min4(uint4 v) { return min(__vimin3_u32(v.x, v.y, v.z), v.w); }

__device__ __forceinline__ void wg_ss192_01(float* d, uint64_t da, uint64_t db, int sd) {
  asm volatile("{.reg .pred p; setp.ne.b32 p, %98, 0;\n"
    "wgmma.mma_async.sync.aligned.m64n192k16.f32.bf16.bf16 {%0,%1,%2,%3,%4,%5,%6,%7,%8,%9,%10,%11,%12,%13,%14,%15,%16,%17,%18,%19,%20,%21,%22,%23,%24,%25,%26,%27,%28,%29,%30,%31,%32,%33,%34,%35,%36,%37,%38,%39,%40,%41,%42,%43,%44,%45,%46,%47,%48,%49,%50,%51,%52,%53,%54,%55,%56,%57,%58,%59,%60,%61,%62,%63,%64,%65,%66,%67,%68,%69,%70,%71,%72,%73,%74,%75,%76,%77,%78,%79,%80,%81,%82,%83,%84,%85,%86,%87,%88,%89,%90,%91,%92,%93,%94,%95}, %96, %97, p, 1, 1, 0, 1;}"
    : "+f"(d[0]),"+f"(d[1]),"+f"(d[2]),"+f"(d[3]),"+f"(d[4]),"+f"(d[5]),"+f"(d[6]),"+f"(d[7]),"+f"(d[8]),"+f"(d[9]),"+f"(d[10]),"+f"(d[11]),"+f"(d[12]),"+f"(d[13]),"+f"(d[14]),"+f"(d[15]),"+f"(d[16]),"+f"(d[17]),"+f"(d[18]),"+f"(d[19]),"+f"(d[20]),"+f"(d[21]),"+f"(d[22]),"+f"(d[23]),"+f"(d[24]),"+f"(d[25]),"+f"(d[26]),"+f"(d[27]),"+f"(d[28]),"+f"(d[29]),"+f"(d[30]),"+f"(d[31]),"+f"(d[32]),"+f"(d[33]),"+f"(d[34]),"+f"(d[35]),"+f"(d[36]),"+f"(d[37]),"+f"(d[38]),"+f"(d[39]),"+f"(d[40]),"+f"(d[41]),"+f"(d[42]),"+f"(d[43]),"+f"(d[44]),"+f"(d[45]),"+f"(d[46]),"+f"(d[47]),"+f"(d[48]),"+f"(d[49]),"+f"(d[50]),"+f"(d[51]),"+f"(d[52]),"+f"(d[53]),"+f"(d[54]),"+f"(d[55]),"+f"(d[56]),"+f"(d[57]),"+f"(d[58]),"+f"(d[59]),"+f"(d[60]),"+f"(d[61]),"+f"(d[62]),"+f"(d[63]),"+f"(d[64]),"+f"(d[65]),"+f"(d[66]),"+f"(d[67]),"+f"(d[68]),"+f"(d[69]),"+f"(d[70]),"+f"(d[71]),"+f"(d[72]),"+f"(d[73]),"+f"(d[74]),"+f"(d[75]),"+f"(d[76]),"+f"(d[77]),"+f"(d[78]),"+f"(d[79]),"+f"(d[80]),"+f"(d[81]),"+f"(d[82]),"+f"(d[83]),"+f"(d[84]),"+f"(d[85]),"+f"(d[86]),"+f"(d[87]),"+f"(d[88]),"+f"(d[89]),"+f"(d[90]),"+f"(d[91]),"+f"(d[92]),"+f"(d[93]),"+f"(d[94]),"+f"(d[95])
    : "l"(da), "l"(db), "r"(sd));
}
__device__ __forceinline__ void wg_ss128_01(float* d, uint64_t da, uint64_t db, int sd) {
  asm volatile("{.reg .pred p; setp.ne.b32 p, %66, 0;\n"
    "wgmma.mma_async.sync.aligned.m64n128k16.f32.bf16.bf16 {%0,%1,%2,%3,%4,%5,%6,%7,%8,%9,%10,%11,%12,%13,%14,%15,%16,%17,%18,%19,%20,%21,%22,%23,%24,%25,%26,%27,%28,%29,%30,%31,%32,%33,%34,%35,%36,%37,%38,%39,%40,%41,%42,%43,%44,%45,%46,%47,%48,%49,%50,%51,%52,%53,%54,%55,%56,%57,%58,%59,%60,%61,%62,%63}, %64, %65, p, 1, 1, 0, 1;}"
    : "+f"(d[0]),"+f"(d[1]),"+f"(d[2]),"+f"(d[3]),"+f"(d[4]),"+f"(d[5]),"+f"(d[6]),"+f"(d[7]),"+f"(d[8]),"+f"(d[9]),"+f"(d[10]),"+f"(d[11]),"+f"(d[12]),"+f"(d[13]),"+f"(d[14]),"+f"(d[15]),"+f"(d[16]),"+f"(d[17]),"+f"(d[18]),"+f"(d[19]),"+f"(d[20]),"+f"(d[21]),"+f"(d[22]),"+f"(d[23]),"+f"(d[24]),"+f"(d[25]),"+f"(d[26]),"+f"(d[27]),"+f"(d[28]),"+f"(d[29]),"+f"(d[30]),"+f"(d[31]),"+f"(d[32]),"+f"(d[33]),"+f"(d[34]),"+f"(d[35]),"+f"(d[36]),"+f"(d[37]),"+f"(d[38]),"+f"(d[39]),"+f"(d[40]),"+f"(d[41]),"+f"(d[42]),"+f"(d[43]),"+f"(d[44]),"+f"(d[45]),"+f"(d[46]),"+f"(d[47]),"+f"(d[48]),"+f"(d[49]),"+f"(d[50]),"+f"(d[51]),"+f"(d[52]),"+f"(d[53]),"+f"(d[54]),"+f"(d[55]),"+f"(d[56]),"+f"(d[57]),"+f"(d[58]),"+f"(d[59]),"+f"(d[60]),"+f"(d[61]),"+f"(d[62]),"+f"(d[63])
    : "l"(da), "l"(db), "r"(sd));
}
__device__ __forceinline__ void wg_ss160_01(float* d, uint64_t da, uint64_t db, int sd) {
  asm volatile("{.reg .pred p; setp.ne.b32 p, %82, 0;\n"
    "wgmma.mma_async.sync.aligned.m64n160k16.f32.bf16.bf16 {%0,%1,%2,%3,%4,%5,%6,%7,%8,%9,%10,%11,%12,%13,%14,%15,%16,%17,%18,%19,%20,%21,%22,%23,%24,%25,%26,%27,%28,%29,%30,%31,%32,%33,%34,%35,%36,%37,%38,%39,%40,%41,%42,%43,%44,%45,%46,%47,%48,%49,%50,%51,%52,%53,%54,%55,%56,%57,%58,%59,%60,%61,%62,%63,%64,%65,%66,%67,%68,%69,%70,%71,%72,%73,%74,%75,%76,%77,%78,%79}, %80, %81, p, 1, 1, 0, 1;}"
    : "+f"(d[0]),"+f"(d[1]),"+f"(d[2]),"+f"(d[3]),"+f"(d[4]),"+f"(d[5]),"+f"(d[6]),"+f"(d[7]),"+f"(d[8]),"+f"(d[9]),"+f"(d[10]),"+f"(d[11]),"+f"(d[12]),"+f"(d[13]),"+f"(d[14]),"+f"(d[15]),"+f"(d[16]),"+f"(d[17]),"+f"(d[18]),"+f"(d[19]),"+f"(d[20]),"+f"(d[21]),"+f"(d[22]),"+f"(d[23]),"+f"(d[24]),"+f"(d[25]),"+f"(d[26]),"+f"(d[27]),"+f"(d[28]),"+f"(d[29]),"+f"(d[30]),"+f"(d[31]),"+f"(d[32]),"+f"(d[33]),"+f"(d[34]),"+f"(d[35]),"+f"(d[36]),"+f"(d[37]),"+f"(d[38]),"+f"(d[39]),"+f"(d[40]),"+f"(d[41]),"+f"(d[42]),"+f"(d[43]),"+f"(d[44]),"+f"(d[45]),"+f"(d[46]),"+f"(d[47]),"+f"(d[48]),"+f"(d[49]),"+f"(d[50]),"+f"(d[51]),"+f"(d[52]),"+f"(d[53]),"+f"(d[54]),"+f"(d[55]),"+f"(d[56]),"+f"(d[57]),"+f"(d[58]),"+f"(d[59]),"+f"(d[60]),"+f"(d[61]),"+f"(d[62]),"+f"(d[63]),"+f"(d[64]),"+f"(d[65]),"+f"(d[66]),"+f"(d[67]),"+f"(d[68]),"+f"(d[69]),"+f"(d[70]),"+f"(d[71]),"+f"(d[72]),"+f"(d[73]),"+f"(d[74]),"+f"(d[75]),"+f"(d[76]),"+f"(d[77]),"+f"(d[78]),"+f"(d[79])
    : "l"(da), "l"(db), "r"(sd));
}
__device__ __forceinline__ void wg_ss80_01(float* d, uint64_t da, uint64_t db, int sd) {
  asm volatile("{.reg .pred p; setp.ne.b32 p, %42, 0;\n"
    "wgmma.mma_async.sync.aligned.m64n80k16.f32.bf16.bf16 {%0,%1,%2,%3,%4,%5,%6,%7,%8,%9,%10,%11,%12,%13,%14,%15,%16,%17,%18,%19,%20,%21,%22,%23,%24,%25,%26,%27,%28,%29,%30,%31,%32,%33,%34,%35,%36,%37,%38,%39}, %40, %41, p, 1, 1, 0, 1;}"
    : "+f"(d[0]),"+f"(d[1]),"+f"(d[2]),"+f"(d[3]),"+f"(d[4]),"+f"(d[5]),"+f"(d[6]),"+f"(d[7]),"+f"(d[8]),"+f"(d[9]),"+f"(d[10]),"+f"(d[11]),"+f"(d[12]),"+f"(d[13]),"+f"(d[14]),"+f"(d[15]),"+f"(d[16]),"+f"(d[17]),"+f"(d[18]),"+f"(d[19]),"+f"(d[20]),"+f"(d[21]),"+f"(d[22]),"+f"(d[23]),"+f"(d[24]),"+f"(d[25]),"+f"(d[26]),"+f"(d[27]),"+f"(d[28]),"+f"(d[29]),"+f"(d[30]),"+f"(d[31]),"+f"(d[32]),"+f"(d[33]),"+f"(d[34]),"+f"(d[35]),"+f"(d[36]),"+f"(d[37]),"+f"(d[38]),"+f"(d[39])
    : "l"(da), "l"(db), "r"(sd));
}
__device__ __forceinline__ void wg_rs32_00(float* d, uint32_t a0, uint32_t a1, uint32_t a2, uint32_t a3, uint64_t db, int sd) {
  asm volatile("{.reg .pred p; setp.ne.b32 p, %21, 0;\n"
    "wgmma.mma_async.sync.aligned.m64n32k16.f32.bf16.bf16 {%0,%1,%2,%3,%4,%5,%6,%7,%8,%9,%10,%11,%12,%13,%14,%15}, {%16,%17,%18,%19}, %20, p, 1, 1, 0;}"
    : "+f"(d[0]),"+f"(d[1]),"+f"(d[2]),"+f"(d[3]),"+f"(d[4]),"+f"(d[5]),"+f"(d[6]),"+f"(d[7]),"+f"(d[8]),"+f"(d[9]),"+f"(d[10]),"+f"(d[11]),"+f"(d[12]),"+f"(d[13]),"+f"(d[14]),"+f"(d[15])
    : "r"(a0), "r"(a1), "r"(a2), "r"(a3), "l"(db), "r"(sd));
}
__device__ __forceinline__ void wg_rs64_00(float* d, uint32_t a0, uint32_t a1, uint32_t a2, uint32_t a3, uint64_t db, int sd) {
  asm volatile("{.reg .pred p; setp.ne.b32 p, %37, 0;\n"
    "wgmma.mma_async.sync.aligned.m64n64k16.f32.bf16.bf16 {%0,%1,%2,%3,%4,%5,%6,%7,%8,%9,%10,%11,%12,%13,%14,%15,%16,%17,%18,%19,%20,%21,%22,%23,%24,%25,%26,%27,%28,%29,%30,%31}, {%32,%33,%34,%35}, %36, p, 1, 1, 0;}"
    : "+f"(d[0]),"+f"(d[1]),"+f"(d[2]),"+f"(d[3]),"+f"(d[4]),"+f"(d[5]),"+f"(d[6]),"+f"(d[7]),"+f"(d[8]),"+f"(d[9]),"+f"(d[10]),"+f"(d[11]),"+f"(d[12]),"+f"(d[13]),"+f"(d[14]),"+f"(d[15]),"+f"(d[16]),"+f"(d[17]),"+f"(d[18]),"+f"(d[19]),"+f"(d[20]),"+f"(d[21]),"+f"(d[22]),"+f"(d[23]),"+f"(d[24]),"+f"(d[25]),"+f"(d[26]),"+f"(d[27]),"+f"(d[28]),"+f"(d[29]),"+f"(d[30]),"+f"(d[31])
    : "r"(a0), "r"(a1), "r"(a2), "r"(a3), "l"(db), "r"(sd));
}
__device__ __forceinline__ void wg_rs24_01(float* d, uint32_t a0, uint32_t a1, uint32_t a2, uint32_t a3, uint64_t db, int sd) {
  asm volatile("{.reg .pred p; setp.ne.b32 p, %17, 0;\n"
    "wgmma.mma_async.sync.aligned.m64n24k16.f32.bf16.bf16 {%0,%1,%2,%3,%4,%5,%6,%7,%8,%9,%10,%11}, {%12,%13,%14,%15}, %16, p, 1, 1, 1;}"
    : "+f"(d[0]),"+f"(d[1]),"+f"(d[2]),"+f"(d[3]),"+f"(d[4]),"+f"(d[5]),"+f"(d[6]),"+f"(d[7]),"+f"(d[8]),"+f"(d[9]),"+f"(d[10]),"+f"(d[11])
    : "r"(a0), "r"(a1), "r"(a2), "r"(a3), "l"(db), "r"(sd));
}

#define AB_POLY 0x77
__device__ __forceinline__ constexpr bool poly_group(int group) { return (AB_POLY >> (group & 7)) & 1; }

template <int V> struct Int { static constexpr int value = V; };

__device__ __forceinline__ int core_word(int row, int col) {
  return ((((row >> 7) * 10 + (col >> 6)) * 16 + ((row >> 3) & 15)) * 8 + ((col >> 3) & 7)) * 32 + (row & 7) * 4 + ((col & 7) >> 1);
}
__device__ __forceinline__ void wait_count(const uint32_t* c, uint32_t n) {
  int spin = 0;
  while ((ld_acquire(c) & 0xffff) < n) { __nanosleep(32); spin_guard(spin); }
}
__device__ __forceinline__ void wait_count_uniform(const uint32_t* c, uint32_t n) {
  for (int spin = 0; !__all_sync(~0u, (ld_acquire(c) & 0xffff) >= n);) { __nanosleep(32); spin_guard(spin); }
  fence_async_global();
}
__device__ __forceinline__ void prefetch_l2(const void* p, uint32_t bytes) {
  asm volatile("cp.async.bulk.prefetch.L2.global [%0], %1;" :: "l"(p), "r"(bytes) : "memory"); }

#define PLACE 4
__device__ __forceinline__ bool helper_sm() {
  uint32_t m; asm volatile("mov.u32 %0, %%smid;" : "=r"(m));
  return m < 2 || m >= 120 || (m >= 92 && m < 102) || (m >= 106 && m < 117) || m == 118;
}

__device__ __forceinline__ uint8_t* pool_at(uint32_t off) {
  return reinterpret_cast<uint8_t*>((reinterpret_cast<uintptr_t>(g_pool) + 8191) & ~(uintptr_t)8191) + off; }
__device__ __forceinline__ uint32_t page_latency(uint32_t* w) {
  uint32_t best = ~0u;
  stg_strong32(w, 0u);
#pragma unroll 1
  for (int r = 0; r < 4; r++) {
    uint32_t t0, t1, v;
    asm volatile("mov.u32 %0, %%clock;" : "=r"(t0) :: "memory");
    asm volatile("atom.relaxed.gpu.global.exch.b32 %0, [%1], 0;" : "=r"(v) : "l"(w) : "memory");
    asm volatile("{.reg .u32 t; add.u32 t, %1, 1; mov.u32 %0, %%clock; sub.u32 %0, %0, %1;}" : "=r"(t1) : "r"(__shfl_sync(1u, v, 0)) : "memory");
    best = min(best, t1 - t0);
  }
  return best;
}
__device__ __forceinline__ void probe_slots(uint32_t scratch) {
  const int w = (threadIdx.x >> 6) & 1, slot = w == 0 ? NSLOT : blockIdx.x;
  if ((threadIdx.x & 31) == 0 && (w == 0 || slot < NSLOT)) {
    uint32_t* q = reinterpret_cast<uint32_t*>(pool_at(slot * 8192)) + (w == 0 ? (blockIdx.x & 31) * 32 + (blockIdx.x >> 5) : 0);
    sts32(scratch + w * 4, page_latency(q) < page_latency(q + 1024));
  }
  bar_sync(2, 64);
  if ((threadIdx.x & 31) == 0) {
    const int part = lds32(scratch) ? 1 : 2;
    if (w == 0) { uint32_t smid; asm("mov.u32 %0, %%smid;" : "=r"(smid)); stg_strong32(g_smpart + (smid & 255), part); }
    else if (slot < NSLOT) stg_strong32(g_orient + slot, lds32(scratch + 4) ? part : 3 - part);
  }
  __syncwarp();
}

constexpr int WK_SLOTS = 28, WK_BAR = WK_SLOTS * 8192;
__device__ __forceinline__ void work_init(uint32_t sb) {
  const int i = fresh_tid() & 31;
  mbar_init(sb + WK_BAR + 8 * i, i < 8 ? 2 : i < 16 ? 8 : i < 20 ? 1 : i < 24 ? 3 : i < 28 ? 8 : 1);
  asm volatile("fence.mbarrier_init.release.cluster;" ::: "memory");
}

struct ChainParams {
  CUtensorMap wq, wk, wv, wo;
  const __nv_bfloat16* mem0;
  const uint8_t* wb;
  uint32_t *sync, *other;
  int layer;
  int d1, d2, dn, dx, mode, zero;
};
constexpr int CH_WQ = 0, CH_WO = 81920, CH_X = CH_WO + 86016, CH_M = CH_X, CH_Q = CH_X + 34816, CH_KM = CH_Q + 2048, CH_VP = CH_KM + 2048,
              CH_K = CH_X + 40960, CH_O = CH_K, CH_KS = CH_K + 3072, CH_V = CH_K + 4096, CH_VX = CH_V + 12288, CH_R2 = CH_VX,
              CH_SX = CH_VX + 3072, CH_SO = CH_SX + 2048, CH_ID = CH_SO + 1024, CH_L = CH_ID + 256, CH_TAB = CH_L + 64, CH_BAR = CH_TAB + 384;
constexpr int CH_SMEM = CH_BAR + 144;
constexpr int MB_WO = CH_BAR, MB_WQ = CH_BAR + 8, MB_X = CH_BAR + 16, MB_V = CH_BAR + 24, MB_T = CH_BAR + 32, MB_F = CH_BAR + 40, MB_G = CH_BAR + 48, MB_W = CH_BAR + 56;
enum { NB_PROJ = 1, NB_O = 2, NB_W1 = 3, NB_PRE = 4, NB_ST = 5, NB_MEM = 6, NB_XFREE = 7, NB_H1 = 8, NB_PUB = 9, NB_W2 = 10, NB_PROJ2 = 11, NB_PRE2 = 12, NB_H2 = 13, NB_W1V = 14 };
#define CH_NQ 9
#define CH_VD 4
#define CH_TPRE 0
#define CH_XPF 1
#define CH_TPF 1
#define CH_LAG 0
#define CH_PUSH 1
#define CH_CHAIN 0
#define CH_GATE 1
#define CH_PA 6
#define CH_PB 10
#define CH_PC 12
#define CH_PL 3
#define CH_DBL 0x2108
#define CH_PD 2
#define CH_ZD 1
#define SCHED() asm volatile("griddepcontrol.launch_dependents;" ::: "memory")
__device__ __forceinline__ uint32_t opaque(uint32_t x) { return __shfl_sync(~0u, x, threadIdx.x & 31); }
__device__ __forceinline__ uint32_t nz(uint32_t x) { uint32_t r; asm("max.u32 %0, %1, 1;" : "=r"(r) : "r"(x)); return r; }
__device__ __forceinline__ uint32_t set_tag(uint32_t w, uint32_t tag) { uint32_t r; asm("lop3.b32 %0, %1, %2, 1, 0xD8;" : "=r"(r) : "r"(w), "r"(tag)); return r; }
__device__ __forceinline__ uint32_t pack_tag(float lo, float hi, uint32_t tag) { return set_tag(__byte_perm(__float_as_uint(lo) + tag, pack2(hi, hi), 0x7632), tag); }
__device__ __forceinline__ uint32_t differ(uint32_t a, uint32_t b, uint32_t t) { uint32_t r; asm("lop3.b32 %0, %1, %2, %3, 0x7E;" : "=r"(r) : "r"(a), "r"(b), "r"(t)); return r; }
__device__ __forceinline__ uint32_t clk64() { uint64_t c; asm volatile("mov.u64 %0, %%clock64;" : "=l"(c) :: "memory"); return (uint32_t)c; }
__device__ __forceinline__ void until(uint32_t t) { while ((int)(clk64() - t) < 0) {} }
__device__ __forceinline__ float rcp(float x) { float y; asm("rcp.approx.ftz.f32 %0, %1;" : "=f"(y) : "f"(x)); return y; }

__device__ __forceinline__ void push_values(uint32_t sb, int s, int j) {
  const int r1 = j == 2 ? 0 : j + 1, r2 = j == 0 ? 2 : j - 1;
  const uint32_t src = sb + CH_V + j * 4096;
  if (s < NSEG - 1) {
    fence_async();
    bulk_push(mapa(src, r1), src, 4096, mapa(sb + MB_V, r1));
    bulk_push(mapa(src, r2), src, 4096, mapa(sb + MB_V, r2));
  }
}

template <int WG>
__device__ __forceinline__ void chain_compute(const ChainParams& p, const uint32_t sb) {
  const int tid = threadIdx.x & 127, t4 = __shfl_sync(~0u, tid >> 5, 0), lane = tid & 31;
  const int cta = blockIdx.x, h = cta / 3, j = cta - 3 * h;
  uint32_t ak[80], av[80], tw[4 * CH_NQ];
  const uint32_t wq = opaque(sb + CH_WQ + (WG * 320 + (lane & 7) + (lane >> 4) * 8) * 128 + (((2 * t4 + ((lane >> 3) & 1)) ^ (lane & 7)) << 4));
#pragma unroll
  for (int k = 0; k < 20; k++) {
    if (k == 0 || (WG * 20 + k) % 8 == 0) mbar_wait(sb + MB_W + 8 * ((WG * 20 + k) / 8), 0);
    ldsm4t(&ak[4 * k], wq + k * 2048);
  }
  bar_arrive(NB_PROJ2, 384);
#pragma unroll
  for (int k = 0; k < 20; k++) {
    if (k == 0 || (WG * 20 + k) % 8 == 0) mbar_wait(sb + MB_W + 40 + 8 * ((WG * 20 + k) / 8), 0);
    ldsm4t(&av[4 * k], wq + CH_WO + k * 2048);
  }
  bar_arrive(NB_PRE2, 384);
  const int r1 = j == 2 ? 0 : j + 1, r2 = j == 0 ? 2 : j - 1;
  const uint32_t l8 = opaque(sb + lane * 8), l4 = opaque(sb + lane * 4);
  uint32_t l16 = opaque(sb + lane * 16), t16 = l16 + t4 * 512, t8 = l8 + t4 * 256;
  auto refill = [&]() {
#pragma unroll
    for (int k = 0; k < CH_NQ; k++) ldsm4t(&tw[4 * k], wq + k * 2048);
  };
  auto batch = [&](float* d, const uint32_t (&a)[80], int acc, bool fill) {
    const uint64_t d0 = mkdesc(1024 + CH_X + WG * 20480, 128, 5120, 0);
    wg_fence();
#pragma unroll
    for (int k = 0; k < 20; k++) {
      if (fill && !(k & 1) && k / 2 < CH_NQ) {
        __syncwarp();
        if (CH_CHAIN && k >= 2 * CH_CHAIN) { sts32(l4 + CH_SO, tw[CH_CHAIN ? 2 * k + 3 - 4 * CH_CHAIN : 0]); __syncwarp(); }
        ldsm4t(&tw[2 * k], wq + k * 1024);
        __syncwarp();
      }
      wg_rs32_00(d, a[4 * k], a[4 * k + 1], a[4 * k + 2], a[4 * k + 3], d0 + k * 16, acc | k);
    }
    wg_commit();
    wg_wait<0>();
    reg_fence<16>(d);
  };
  auto tokens = [&](int s, auto first) {
    float d[16];
    if (first.value || !CH_TPRE) mbar_wait(sb + MB_T, s & 1);
    batch(d, WG == 0 ? ak : av, 0, WG == 0 && !first.value);
    s--; TM(10); s++;
    if (WG == 1 && !first.value) mbar_wait(sb + MB_F, (s - 1) & 1);
    const uint32_t kt = t16 + CH_K, vt = t16 + CH_V + j * 4096;
#pragma unroll
    for (int i = 0; i < 2; i++)
      sts128((WG == 0 ? kt : vt) + i * 2048, make_uint4(pack2(d[8 * i], d[8 * i + 1]), pack2(d[8 * i + 2], d[8 * i + 3]), pack2(d[8 * i + 4], d[8 * i + 5]), pack2(d[8 * i + 6], d[8 * i + 7])));
    if (first.value || CH_GATE != 1) bar_sync(NB_H1, 256); else bar_sync(NB_PUB, 384);
    const uint32_t own = WG == 0 ? vt : kt;
#pragma unroll
    for (int i = 0; i < 2; i++) {
      const uint4 t = lds128(own + i * 2048);
      d[8 * i] = bf_lo(t.x); d[8 * i + 1] = bf_hi(t.x); d[8 * i + 2] = bf_lo(t.y); d[8 * i + 3] = bf_hi(t.y);
      d[8 * i + 4] = bf_lo(t.z); d[8 * i + 5] = bf_hi(t.z); d[8 * i + 6] = bf_lo(t.w); d[8 * i + 7] = bf_hi(t.w);
    }
    reg_fence<16>(d);
    if (!first.value && CH_GATE == 2) bar_sync(NB_PUB, 384);
    batch(d, WG == 0 ? av : ak, 1, WG == 1 && !first.value);
    s--; TM(11); s++;
    if (WG == 0) bar_arrive(NB_XFREE, 256);
#pragma unroll
    for (int i = 0; i < 2; i++) {
      const uint32_t w0 = pack2(d[8 * i], d[8 * i + 1]), w1 = pack2(d[8 * i + 2], d[8 * i + 3]), w2 = pack2(d[8 * i + 4], d[8 * i + 5]), w3 = pack2(d[8 * i + 6], d[8 * i + 7]);
      if (WG == 1) stsm4t(own + i * 2048, w0, w1, w2, w3); else stsm4(own + i * 2048, w0, w1, w2, w3);
    }
    if (CH_PUSH == 0 && WG == 0) {
      if (t4 == 0) {
        bar_sync(NB_H2, 128);
        if (elect()) push_values(sb, s, j);
        __syncwarp();
      } else {
        bar_arrive(NB_H2, 128);
      }
    }
    if (first.value) { mbar_wait(sb + MB_WQ, 0); refill(); mbar_wait(sb + MB_WO, 0); }
  };
  asm volatile("barrier.cluster.wait.aligned;" ::: "memory");
  tokens(0, Int<1>());
  uint32_t wo = opaque(sb + CH_WO + (WG == 0 ? (t4 >> 1) * 36864 : 73728 + t4 * 1024) + ((lane & 7) + (lane >> 4) * 8) * 64 +
                             (((((lane >> 3) & 1) + (WG == 0 ? (t4 & 1) * 2 : 0)) ^ ((lane >> 1) & 3)) << 4));
  const uint32_t ko0 = __shfl_sync(~0u, (tid >> 6) * 3072 + (tid & 32) * 8, 0), ko1 = __shfl_sync(~0u, (tid >> 6) * 1024 + 1024 + (tid & 32) * 8, 0);
  uint32_t tag = opaque(1);
  const uint32_t o768 = __shfl_sync(~0u, (tid >> 5) * 768, 0);
  bar_sync(NB_ST, 384);
  uint8_t* pdst[WG == 0 ? 6 : 1];
#pragma unroll
  for (int i = 0; i < (WG == 0 ? 6 : 1); i++) {
    const int line = WG == 0 ? 24 * j + 12 * (t4 >> 1) + 2 * (t4 & 1) + 4 * (i >> 1) + (i & 1) : j == 0 ? 72 + t4 : 74 + 2 * j + (t4 & 1);
    pdst[i] = pool_at(__shfl_sync(~0u, lds32(sb + CH_TAB + line * 4), 0) + h * 128);
  }
  auto project = [&](int s, float (&dv)[4], uint4 (&kf)[2], auto last) {
    float dq[4] = {}, dk[4] = {};
    uint32_t b[40], w[80];
#pragma unroll
    for (int i = 0; i < 4 * CH_NQ; i++) w[i] = tw[i];
    bar_sync(NB_MEM, 384);
    ldsm4t(&b[0], l16 + CH_M + WG * 5120);
    ldsm4t(&b[4], l16 + CH_M + WG * 5120 + 512);
    TMD(0, b[0]);
    int nw = last.value ? 22 : CH_NQ, nb = 2;
#pragma unroll
    for (int k = 0; k < 20; k++) {
      SCHED();
      if (!last.value) mma16(dq, w[4 * k], w[4 * k + 1], w[4 * k + 2], w[4 * k + 3], b[2 * k], b[2 * k + 1]);
      mma16(dk, ak[4 * k], ak[4 * k + 1], ak[4 * k + 2], ak[4 * k + 3], b[2 * k], b[2 * k + 1]);
      if (WG == 1 || k < 20 - CH_VD) mma16(dv, av[4 * k], av[4 * k + 1], av[4 * k + 2], av[4 * k + 3], b[2 * k], b[2 * k + 1]);
#pragma unroll
      for (int i = 0; i < (CH_DBL >> k & 1) + 1; i++) {
        if (nb < 10 && 2 * nb <= nw) { ldsm4t(&b[4 * nb], l16 + CH_M + WG * 5120 + nb * 512); nb++; }
        else if (nw < 20) { ldsm4t(&w[4 * nw], wq + nw * 2048); nw++; }
        else if (WG == 1 && nw < 22) { const uint32_t x = l16 ^ ((ko0 ^ tag) & 256); kf[nw - 20] = ldsm4v(x + (x & 256) + (nw == 20 ? ko0 : ko1) + CH_K); nw++; }
      }
    }
    const float k2 = 0.07216878364870322f * 1.44269504089f;
    if (!last.value) {
      sts32(l4 + t4 * 512 + CH_Q + WG * 128, pack2(dq[0] * k2, dq[1] * k2));
      sts32(l4 + t4 * 512 + CH_Q + WG * 128 + 256, pack2(dq[2] * k2, dq[3] * k2));
    }
    stsm2t(t16 + CH_KM + WG * 256, pack2(dk[0], dk[1]), pack2(dk[2], dk[3]));
    if (WG == 1) sts128f(t16 + CH_VP, dv[0], dv[1], dv[2], dv[3]);
    TM(1);
    bar_sync(NB_PROJ, 256);
    if (WG == 0) {
      float e[3][4] = {};
      SCHED();
#pragma unroll
      for (int k = 20 - CH_VD; k < 20; k++) {
        if (k == 18 - CH_VD / 2) { const float4 pv = lds128f(t16 + CH_VP); dk[0] = pv.x; dk[1] = pv.y; dk[2] = pv.z; dk[3] = pv.w; SCHED(); }
        mma16(k & 3 ? e[(k & 3) - 1] : dv, av[4 * k], av[4 * k + 1], av[4 * k + 2], av[4 * k + 3], b[2 * k], b[2 * k + 1]);
      }
#pragma unroll
      for (int i = 0; i < 4; i++) dv[i] = ((dv[i] + dk[i]) + e[0][i]) + (e[1][i] + e[2][i]);
    }
  };
#pragma unroll 1
  for (int s = 0; s < NSEG - 1; s++) {
    float dv[4] = {};
    uint4 kf[2];
    project(s, dv, kf, Int<0>());
    if (WG == 0) {
      const uint32_t v0 = pack2(dv[0], dv[1]), v1 = pack2(dv[2], dv[3]);
      const uint32_t xo = t8 + CH_VX + j * 1024;
      st_async64(mapa(xo, r1), v0, v1, mapa(sb + MB_X, r1));
      st_async64(mapa(xo, r2), v0, v1, mapa(sb + MB_X, r2));
      sts64(xo, v0, v1);
      __syncwarp();
      if (elect()) mbar_arrive(sb + MB_X);
      bar_arrive(NB_PROJ2, 256);
      TM(3);
      uint32_t w[144];
      auto tile_of = [](int n) { return n < 27 ? n % 3 : (0x26484 >> 2 * (n - 27)) & 3; };
      auto step_of = [](int n) { return n < 27 ? n / 3 : 9 + ((0x29610 >> 2 * (n - 27)) & 3); };
      auto wload = [&](int n) { ldsm4t(&w[4 * n], wo + tile_of(n) * 12288 + (step_of(n) % 3) * 4096 + (step_of(n) / 3) * 1024); };
#pragma unroll
      for (int n = 0; n < CH_PA; n++) wload(n);
      bar_sync(NB_PRE, 256);
#pragma unroll
      for (int n = CH_PA; n < CH_PB; n++) wload(n);
      bar_arrive(NB_PRE2, 256);
      if (CH_PC > CH_PB) {
        mbar_wait(sb + MB_X, s & 1);
        for (int i = 0; i < CH_PD; i++) wo = __shfl_xor_sync(~0u, wo, p.zero);
#pragma unroll
        for (int n = CH_PB; n < CH_PC; n++) wload(n);
      }
      TM(4);
      bar_sync(NB_O, 256);
      {
        float x[3][4] = {};
        uint32_t ob[24];
        float4 l;
        ldsm4t(&ob[0], l16 + CH_O);
        ldsm4t(&ob[4], l16 + CH_O + 512);
        TMD(7, ob[0]);
        int nw = CH_PC, no = 2;
        float i0, i1;
        uint8_t* dst[6];
        uint32_t lo[6], hi[6];
        auto pre = [&](int i) { lo[i] = __float_as_uint(x[i >> 1][2 * (i & 1)] * i0) + tag; hi[i] = pack2(0.f, x[i >> 1][2 * (i & 1) + 1] * i1); };
        auto emit = [&](int i) { stg_strong32(dst[i], set_tag(__byte_perm(lo[i], hi[i], 0x7632), tag)); };
#pragma unroll
        for (int n = 0; n < 36; n++) {
          SCHED();
          mma16(x[tile_of(n)], w[4 * n], w[4 * n + 1], w[4 * n + 2], w[4 * n + 3], ob[step_of(n) * 2], ob[step_of(n) * 2 + 1]);
          if (n >= CH_PL) {
            if (no < 6 && no * 2 <= step_of(min(nw, 35))) { ldsm4t(&ob[4 * no], l16 + CH_O + no * 512); no++; }
            else if (nw < 36) { wload(nw); nw++; }
          }
          if (n == 18) l = lds128f(sb + CH_L + ((l16 ^ tag) & 0x30));
          if (n == 26) { i0 = rcp(l.x + l.y); i1 = rcp(l.z + l.w); asm volatile("" : "+f"(i0), "+f"(i1)); }
          if (n >= 28 && n < 34) { dst[n - 28] = pdst[n - 28] + ((l4 ^ tag) & 0x7c); asm volatile("" : "+l"(dst[n - 28])); }
          if (n == 32) { for (int i = 0; i < 2; i++) { pre(i); asm volatile("" : "+r"(lo[i]), "+r"(hi[i])); } }
          if (n == 33) { emit(0); emit(1); }
        }
        for (int i = 2; i < 6; i++) pre(i);
        for (int i = 2; i < 6; i++) emit(i);
      }
      TM(8);
    } else {
      {
        float d0[4] = {}, d1[4] = {}, dm[4] = {};
        uint32_t q[16], km[4];
#pragma unroll
        for (int e = 0; e < 4; e++) {
          ldsm4t(&q[4 * e], l16 + (e ^ t4) * 512 + CH_Q);
          if (e == 1) ldsm4(km, t16 + CH_KM);
        }
        SCHED();
        mma16(d0, q[0], q[1], q[2], q[3], kf[0].x, kf[0].y);
        mma16(d1, q[4], q[5], q[6], q[7], kf[0].z, kf[0].w);
        mma16(dm, q[0], q[1], q[2], q[3], hadd2(km[0], km[2]), hadd2(km[1], km[3]));
        mma16(d0, q[8], q[9], q[10], q[11], kf[1].x, kf[1].y);
        mma16(d1, q[12], q[13], q[14], q[15], kf[1].z, kf[1].w);
        const uint32_t w0 = pack2((d0[0] + d0[2]) + (d1[0] + d1[2]), (d0[1] + d0[3]) + (d1[1] + d1[3])), w1 = pack2(dm[0] + dm[2], dm[1] + dm[3]);
        const uint32_t xo = l4 + t4 * 128, x1 = mapa(xo, r1), x2 = mapa(xo, r2);
        st_async32(x1 + CH_SX + 512, w1, mapa(sb + MB_X, r1));
        st_async32(x2 + CH_SX + 1536, w1, mapa(sb + MB_X, r2));
        st_async32(x1 + CH_SX, w0, mapa(sb + MB_X, r1));
        st_async32(x2 + CH_SX + 1024, w0, mapa(sb + MB_X, r2));
        sts32(xo + CH_SO, w0);
        sts32(xo + CH_SO + 512, w1);
      }
      TM(3);
      float sc[3][4] = {};
      uint32_t wd[12];
      uint32_t redo;
      auto attend = [&](auto first) {
        uint4 vb[6];
        uint2 vm[3];
        float e[10];
        uint32_t ow[6];
        if (first.value) {
          const uint2 id = lds64(l8 + CH_ID);
          bar_sync(NB_W1V, 160);
          uint32_t r[8];
          ldsm4(r, l16 + CH_SO); ldsm4(r + 4, l16 + CH_SO + 512);
#pragma unroll
          for (int u = 0; u < 6; u++) vb[u] = ldsm4v(t16 + CH_V + u * 2048);
          bar_arrive(NB_PRE, 256);
          uint32_t sxa = l16 + ((l16 ^ tag) & 256) * 3;
          asm volatile("" : "+r"(sxa));
          sxa += CH_SX;
          SCHED();
          mma8(sc[0], r[0], r[1], id.x);
          mma8(sc[1], r[2], r[3], id.x);
          mma16(sc[2], r[4], r[5], r[6], r[7], id.x, id.y);
          TM(7);
          mbar_wait(sb + MB_X, s & 1);
          TM(4);
          uint32_t t[16];
          ldsm4(t, sxa); ldsm4(t + 4, sxa + 256); ldsm4(t + 8, sxa + 512);
          SCHED();
          mma16(sc[0], t[0], t[1], t[2], t[3], id.x, id.y);
          ldsm4(t + 12, sxa + 768);
          SCHED();
          mma16(sc[1], t[4], t[5], t[6], t[7], id.x, id.y);
#pragma unroll
          for (int u = 0; u < 2; u++) vm[u] = lds64(t8 + CH_VX + u * 1024);
          SCHED();
          e[0] = ex2(sc[0][0]);
          mma16(sc[2], t[8], t[9], t[10], t[11], id.x, id.y);
          vm[2] = lds64(t8 + CH_VX + 2048);
          SCHED();
          e[1] = ex2(sc[0][1]);
          ldsm4t(&wd[0], wo);
          SCHED();
          e[2] = ex2(sc[0][2]);
          SCHED();
          e[3] = ex2(sc[0][3]);
          mma16(sc[2], t[12], t[13], t[14], t[15], id.x, id.y);
          SCHED();
          e[4] = ex2(sc[1][0]);
          ldsm4t(&wd[4], wo + 4096);
          SCHED();
          e[5] = ex2(sc[1][1]);
        } else {
#pragma unroll
          for (int u = 0; u < 6; u++) vb[u] = ldsm4v(t16 + CH_V + u * 2048);
#pragma unroll
          for (int u = 0; u < 3; u++) vm[u] = lds64(t8 + CH_VX + u * 1024);
        }
        float o[3][4] = {};
        if (!first.value) {
#pragma unroll
          for (int i = 0; i < 6; i++) e[i] = ex2(sc[i >> 2][i & 3]);
        }
        const uint32_t p1 = pack2(e[0], e[1]), p2 = pack2(e[2], e[3]);
        float l = (e[0] + e[1]) + (e[2] + e[3]);
        asm volatile("" : "+f"(l));
        SCHED();
        e[6] = ex2(sc[1][2]);
        mma16(o[0], vb[0].x, vb[0].y, vb[0].z, vb[0].w, p1, p2);
        if (first.value) { sc[2][0] += sc[2][2]; sc[2][1] += sc[2][3]; }
        SCHED();
        e[7] = ex2(sc[1][3]);
        mma16(o[1], vb[2].x, vb[2].y, vb[2].z, vb[2].w, p1, p2);
        SCHED();
        e[8] = ex2(sc[2][0]);
        mma16(o[2], vb[4].x, vb[4].y, vb[4].z, vb[4].w, p1, p2);
        SCHED();
        e[9] = ex2(sc[2][1]);
        SCHED();
        const uint32_t p3 = pack2(e[4], e[5]), p4 = pack2(e[6], e[7]);
        l += (e[4] + e[5]) + (e[6] + e[7]);
#pragma unroll
        for (int u = 0; u < 3; u++) mma16(o[u], vb[2 * u + 1].x, vb[2 * u + 1].y, vb[2 * u + 1].z, vb[2 * u + 1].w, p3, p4);
        SCHED();
        const uint32_t p0 = pack2(e[8], e[9]);
        l += e[8] + e[9];
        const float l2 = __shfl_xor_sync(~0u, l, 1);
        if (first.value) ldsm4t(&wd[8], wo + 8192);
#pragma unroll
        for (int u = 0; u < 3; u++) mma8(o[u], vm[u].x, vm[u].y, p0);
        redo = __any_sync(~0u, !(l > 1e-9f && l < 1e9f));
        uint32_t la = sb + CH_L + (((l4 ^ tag) >> 1) & 0x3c);
        asm volatile("" : "+r"(la));
        SCHED();
#pragma unroll
        for (int u = 0; u < 3; u++) { ow[2 * u] = pack2(o[u][0], o[u][1]); ow[2 * u + 1] = pack2(o[u][2], o[u][3]); }
        stsm4(l16 + o768 + CH_O, ow[0], ow[1], ow[2], ow[3]);
        stsm2(l16 + o768 + CH_O + 512, ow[4], ow[5]);
        if (t4 == 0) sts32(la, __float_as_uint(l + l2));
      };
      attend(Int<1>());
      TM(6);
      asm volatile("{.reg .pred p; setp.eq.u32 p, %0, 0; @p bar.arrive 2, 256;}" :: "r"(redo) : "memory");
      if (redo) {
        float mx = fmaxf(sc[2][0], sc[2][1]);
#pragma unroll
        for (int i = 0; i < 4; i++) mx = fmaxf(mx, fmaxf(sc[0][i], sc[1][i]));
        mx = fmaxf(mx, __shfl_xor_sync(~0u, mx, 1));
        mx = fmaxf(mx, __shfl_xor_sync(~0u, mx, 2));
#pragma unroll
        for (int i = 0; i < 4; i++) { sc[0][i] -= mx; sc[1][i] -= mx; }
        sc[2][0] -= mx; sc[2][1] -= mx;
        attend(Int<0>());
        bar_arrive(NB_O, 256);
      }
      {
        float z[4] = {};
        const uint32_t scr = l8 + CH_V + r1 * 4096;
        uint32_t ow[6], we[12];
        __syncwarp();
        ldsm4t(ow, l16 + o768 + CH_O);
        ldsm2t(ow + 4, l16 + o768 + CH_O + 512);
        if (j == 0) {
          float y[4] = {};
#pragma unroll
          for (int u = 0; u < 3; u++) ldsm4t(&we[4 * u], (wo ^ 32) + u * 4096);
          SCHED();
#pragma unroll
          for (int u = 0; u < 3; u++) {
            mma16(z, wd[4 * u], wd[4 * u + 1], wd[4 * u + 2], wd[4 * u + 3], ow[2 * u], ow[2 * u + 1]);
            mma16(y, we[4 * u], we[4 * u + 1], we[4 * u + 2], we[4 * u + 3], ow[2 * u], ow[2 * u + 1]);
          }
          sts64f(scr + t4 * 512 + 2048, y[0], y[1]); sts64f(scr + t4 * 512 + 2304, y[2], y[3]);
        } else {
#pragma unroll
          for (int u = 0; u < 3; u++) mma16(z, wd[4 * u], wd[4 * u + 1], wd[4 * u + 2], wd[4 * u + 3], ow[2 * u], ow[2 * u + 1]);
        }
        sts64f(scr + t4 * 512, z[0], z[1]); sts64f(scr + t4 * 512 + 256, z[2], z[3]);
        bar_sync(NB_W1, 128);
        if (j == 0 || t4 < 2) {
          float2 q[4];
          const float4 l = lds128f(sb + CH_L + ((l16 ^ tag) & 0x30));
#pragma unroll
          for (int i = 0; i < 4; i++) q[i] = lds64f(scr + (t4 >> 1) * 2048 + (t4 & 1) * 256 + i * 512);
          SCHED();
          stg_strong32(pdst[0] + ((l4 ^ tag) & 0x7c), pack_tag(((q[0].x + q[1].x) + (q[2].x + q[3].x)) * rcp(l.x + l.y), ((q[0].y + q[1].y) + (q[2].y + q[3].y)) * rcp(l.z + l.w), tag));
        }
      }
      TM(2);
      if (CH_TPRE) mbar_wait(sb + MB_T, ~s & 1);
    }
    bar_sync(NB_ST, 384);
    tokens(s + 1, Int<0>());
    TM(9);
    tag ^= 0x10001;
  }
  asm volatile("setmaxnreg.dec.sync.aligned.u32 224;");
  l16 = sb + (fresh_tid() & 31) * 16; t16 = sb + (fresh_tid() & 127) * 16; t8 = sb + (fresh_tid() & 127) * 8;
  float dv[4] = {};
  uint4 kf[2];
  project(NSEG - 1, dv, kf, Int<1>());
  if (WG == 0) {
    sts64(t8 + CH_VX + j * 1024, pack2(dv[0], dv[1]), pack2(dv[2], dv[3]));
  } else {
    const uint2 a = lds64(t8 + t4 * 256 + CH_KM), b = lds64(t8 + t4 * 256 + CH_KM + 256);
    sts64(t8 + CH_Q, hadd2(a.x, b.x), hadd2(a.y, b.y));
  }
  bar_arrive(NB_PRE2, 288);
}

__device__ __forceinline__ void chain_comm(const ChainParams& p, const uint32_t sb, const CUtensorMap* maps) {
  [[maybe_unused]] constexpr int WG = 2;
  const int tid = threadIdx.x & 127, t4 = __shfl_sync(~0u, tid >> 5, 0), lane = tid & 31;
  const int cta = blockIdx.x, h = cta / 3, j = cta - 3 * h, colbase = cta * 64;
  const uint8_t* const xs = reinterpret_cast<const uint8_t*>(g_xn);
  auto xload = [&](int seg, int i, int off, int bytes) { bulk_load(sb + CH_X + i * 5120 + off, xs + (seg * 4 + (i & 3)) * 10240 + (i >> 2) * 5120 + off, bytes, sb + MB_T); };
  if (cta == 0) for (int i = tid; i < SY_N; i += 128) p.other[i] = 0;
  uint32_t smid; asm("mov.u32 %0, %%smid;" : "=r"(smid));
  const uint32_t part = max(ldg_strong32(g_smpart + (smid & 255)), 1u);
  if (tid == 64) stg_strong32(p.sync + SY_PART + cta, part);
  PRO(0);
  if (t4 == 3) {
    bar_arrive(NB_PROJ2, 384);
    bar_arrive(NB_PRE2, 384);
    if (elect()) {
      wait_count(p.sync + SY_P + 1, ln_items(p.layer, 0));
      fence_async_global();
      mbar_expect(sb + MB_T, 40960);
      for (int i = 0; i < 8; i++) xload(0, i, 0, 5120);
    }
    __syncwarp();
  } else {
  bar_sync(NB_PROJ2, 384);
  __syncwarp();
  PRO(1);
  if (t4 == 0 && elect()) {
    mbar_expect(sb + MB_WQ, 81920);
    for (int i = 0; i < 5; i++) tma_load(sb + CH_WQ + i * 16384, &p.wq, colbase, i * 128, sb + MB_WQ);
  }
  bar_sync(NB_PRE2, 384);
  __syncwarp();
  PRO(2);
  if (t4 == 0 && elect()) {
    mbar_expect(sb + MB_WO, 86016);
    for (int i = 0; i < 6; i++) tma_load(sb + CH_WO + i * 12288, &p.wo, j * 192 + i * 32, h * 192, sb + MB_WO);
    tma_load(sb + CH_WO + 73728, &p.wo, j == 0 ? 576 : 592 + j * 16, h * 192, sb + MB_WO);
  }
  }
  if (tid < NSLOT) {
    const uint32_t* part_of = p.sync + SY_PART + (tid >= 80 ? cta : tid);
    uint32_t reader = 0, orient = 0;
    int n = 0;
    while (reader == 0 || orient == 0) { reader = ldg_strong32(part_of); orient = ldg_strong32(g_orient + tid); spin_guard(n); }
    sts32(sb + CH_TAB + tid * 4, tid * 8192 + (orient == reader ? 0 : 4096));
    if (t4 == 0) {
      const uint32_t near = __ballot_sync(~0u, reader == part) & 0xffffff;
      if (lane == 0) sts32(sb + CH_TAB + NSLOT * 4, cta < 80 ? cta : near ? __fns(near, 0, 1 + cta % __popc(near)) : 0);
    }
  }
  __syncwarp();
  asm volatile("barrier.cluster.wait.aligned;" ::: "memory");
  const uint32_t l8 = opaque(sb + t4 * 256 + lane * 8);
  {
    const uint32_t* m0 = reinterpret_cast<const uint32_t*>(p.mem0) + (lane >> 2) * (DM / 2) + t4 * 80 + (lane & 3);
    uint32_t g[20];
#pragma unroll
    for (int i = 0; i < 20; i++) g[i] = transpose8(m0[i * 4]);
    const uint32_t id = (lane >> 3) == (lane & 3) ? ((lane & 4) ? 0x3f800000u : 0x00003f80u) : 0u;
    if (t4 == 0) sts64(l8 + CH_ID, id, id);
    bar_sync(NB_XFREE, 256);
#pragma unroll
    for (int i = 0; i < 20; i++) sts32(sb + CH_M + (t4 * 20 + i) * 128 + lane * 4, g[i]);
  }
  bar_sync(NB_ST, 384);
  uint8_t* const pool = pool_at(0);
  const uint8_t* const psrc = pool + opaque(lds32(sb + CH_TAB + lds32(sb + CH_TAB + NSLOT * 4) * 4) + t4 * 1024 + lane * 4);
  const uint32_t mdst = opaque((80 + cta / 20) * 8192 + (t4 & 1) * 4096 + (cta % 20) * 128 + lane * 4);
  int st = 0;
  uint32_t tag = opaque(1), span = ~0u;
  bar_sync(NB_MEM, 384);
  auto send_tokens = [&](int s) {
    fence_async();
    uint8_t* dst = g_kv + ((s >> 2) * 192 + cta + 3 * h) * KV_PART + (s & 3) * 4096;
    bulk_store(dst, sb + CH_K, 4096);
    bulk_store(dst + KV_V, sb + CH_V + j * 4096, 4096);
    bulk_commit();
  };
  auto send_memory = [&](int s, uint32_t km) {
    fence_async();
    uint8_t* dst = g_kv + ((s >> 2) * 192 + cta + 3 * h) * KV_PART + KV_M + (s & 3) * 1024;
    bulk_store(dst, km, 1024);
    bulk_store(dst + KV_V, sb + CH_VX + j * 1024, 1024);
    bulk_commit();
    bulk_wait<0>();
    if ((s & 3) == 3) { fence_async_global(); atomicAdd(p.sync + (s >> 2) * 8 + 4, 1); }
  };
#pragma unroll 1
  for (int s = 0; s < NSEG - 1; s++) {
    TM(0);
    STAT(0);
    if (t4 == 0) {
      if (elect()) {
        if (CH_PUSH == 1) push_values(sb, s, j);
        send_tokens(s);
        bulk_wait_read<0>();
      }
      __syncwarp();
    }
    uint32_t c0, g0;
    if (t4 == 1) {
      __syncwarp();
      c0 = clk32(); g0 = gtime();
      if (elect()) atomicMax(p.sync + SY_TIME + s, g0);
    }
    if (t4 == 3 && (s & 3) == 2 && s < NSEG - 2) wait_count_uniform(p.sync + SY_P + 5 + (s & ~3), ln_items(p.layer, (s >> 2) + 1));
    if (t4 == 2) { mbar_wait(sb + MB_V, s & 1); bar_arrive(NB_W1V, 160); }
    bar_sync(NB_PROJ2, 256);
    if (t4 == 0 && elect()) {
      mbar_expect(sb + MB_X, 4096);
      mbar_expect(sb + MB_T, 40960);
#pragma unroll
      for (int i = 0; i < 7; i++) xload(s + 1, i, 0, i < 6 ? 5120 : 4096);
    }
    __syncwarp();
    STAT(1);
    TM(1);
    {
      const uint2 a = lds64(l8 + t4 * 256 + CH_KM), b = lds64(l8 + t4 * 256 + CH_KM + 256);
      sts64(l8 + CH_KS, hadd2(a.x, b.x), hadd2(a.y, b.y));
    }
    TM(4);
    bar_sync(NB_PRE2, 256);
    if (t4 == 0 && elect()) {
      xload(s + 1, 6, 4096, 1024);
      xload(s + 1, 7, 0, 5120);
      if (CH_XPF && s < NSEG - 2) prefetch_l2(xs + (s + 2) * 40960 + cta % 20 * 2048, 2048);
      if (CH_TPF && s >= NSEG - 7) {
        const int i = s - (NSEG - 7);
        if (i < 2) prefetch_l2(p.wb + (cta * 2 + i) * 12800, 12800);
        else if (i < 4) prefetch_l2(xs + (cta * 2 + i - 2) * 8192, 8192);
        else prefetch_l2(g_q + 15 * 32 * 3072 + (cta * 2 + i - 4) * 512, 8192);
      }
      send_memory(s, sb + CH_KS);
    }
    __syncwarp();
    if (t4 == 1) {
      const uint32_t late = min(ldg_strong32(p.sync + SY_TIME + s) - g0, 640u);
      if (elect()) sts32(sb + CH_TAB + 380, c0 + span + (late * 115 >> 6) + (j ? 60 : 0) + p.d1);
    }
    bar_sync(NB_W2, 128);
    uint32_t due = lds32(sb + CH_TAB + 380);
    due = __shfl_sync(~0u, due, 0);
    const uint8_t* ms = pool + (lds32(sb + CH_TAB + (80 + st * 4 + t4) * 4) + (l8 & 255));
    uint8_t* md = pool + (mdst + (t4 < 2 ? st : st == 2 ? 0 : st + 1) * 32768);
    asm volatile("" : "+l"(ms), "+l"(md));
    TM(2);
    bar_sync(NB_ST, 384);
    __syncwarp();
    uint32_t tg = clk32();
    if (t4 == 3 && elect()) {
      if (s < NSEG - 2) mbar_expect(sb + MB_V, 8192);
      mbar_arrive_remote(mapa(sb + MB_F, j == 2 ? 0 : j + 1));
      mbar_arrive_remote(mapa(sb + MB_F, j == 0 ? 2 : j - 1));
    }
    if (t4 == 2 && s == NSEG - 2) {
      work_init(sb);
      if (elect()) for (int i = 0; i < 5; i++) asm volatile("prefetch.tensormap [%0];" :: "l"(maps + i) : "memory");
    }
    __syncwarp();
    STAT(2);
    {
      float2 q[4];
      uint32_t u[2][8];
      auto poll = [&](uint32_t (&v)[8], uint32_t flip) {
        const uint8_t* src = psrc + flip;
#pragma unroll
        for (int i = 0; i < 8; i++) v[i] = ldg_strong32(src + i * 128);
      };
      auto sum = [&](uint32_t (&v)[8]) {
        sts64f(l8 + CH_R2, ((bf_lo(v[0]) + bf_lo(v[1])) + (bf_lo(v[2]) + bf_lo(v[3]))) + ((bf_lo(v[4]) + bf_lo(v[5])) + (bf_lo(v[6]) + bf_lo(v[7]))),
               ((bf_hi(v[0]) + bf_hi(v[1])) + (bf_hi(v[2]) + bf_hi(v[3]))) + ((bf_hi(v[4]) + bf_hi(v[5])) + (bf_hi(v[6]) + bf_hi(v[7]))));
        uint32_t bad;
        asm volatile("{.reg .pred p, q; .reg .b32 a; lop3.b32 a, %1, %2, %3, 0xFE; lop3.b32 a, a, %4, 1, 0xA8; setp.ne.u32 p, a, 0;\n"
                     "bar.red.or.pred q, %5, 128, p; selp.u32 %0, 1, 0, q;}"
                     : "=r"(bad) : "r"(differ(v[0], v[1], tag)), "r"(differ(v[2], v[3], tag)), "r"(differ(v[4], v[5], tag)), "r"(differ(v[6], v[7], tag)), "n"((int)NB_W2) : "memory");
#pragma unroll
        for (int k = 0; k < 4; k++) asm volatile("ld.volatile.shared.v2.f32 {%0,%1}, [%2];" : "=f"(q[k].x), "=f"(q[k].y) : "r"(l8 - t4 * 256 + CH_R2 + k * 256) : "memory");
        return bad;
      };
      TM(3);
      if (t4 == 1) span = min(span, tg - c0);
      until(s < 2 ? tg + 400 : (int)(due - tg) > p.dn ? due : tg + p.dn);
      poll(u[0], 0);
      SCHED();
      uint32_t lag = l8;
#pragma unroll
      for (int i = 0; i < CH_LAG; i++) asm volatile("mul.lo.u32 %0, %0, %1;" : "+r"(lag) : "r"(p.zero));
      if (CH_LAG) poll(u[1], lag);
      SCHED();
      if (sum(u[0])) {
        poll(u[0], CH_LAG ? u[1][7] & p.zero : 0);
        SCHED();
        if (!CH_LAG || sum(u[1])) {
          for (int n = 0; sum(u[0]) && (cta < 80 || n < 2); spin_guard(n)) poll(u[0], 0);
        }
      }
      if (CH_GATE) bar_arrive(NB_PUB, 384);
      SCHED();
      TM(9);
      if (cta < 80) stg_strong32(md, min(nz(pack2((q[0].x + q[1].x) + (q[2].x + q[3].x), (q[0].y + q[1].y) + (q[2].y + q[3].y))), t4 < 2 ? ~0u : 0u));
      tg = clk64() + p.d2;
      if (s >= 2 && (int)(due + p.dx - tg) > 0) tg = due + p.dx;
      TM(8);
    }
    STAT(3);
    until(tg);
    TM(10);
    for (int n = 0;;) {
      uint2 g[10];
#pragma unroll
      for (int i = 0; i < 10; i++) g[i] = ldg_strong64(ms + i * 256);
      if (n == 0) bar_sync(NB_XFREE, 256);
      spin_guard(n);
      uint32_t m = ~0u;
#pragma unroll
      for (int i = 0; i < 10; i++) { sts64(l8 + CH_M + t4 * 2304 + i * 256, g[i].x, g[i].y); m = __vimin3_u32(m, g[i].x, g[i].y); }
      TMV(13, n - 1);
      if (!__any_sync(~0u, m == 0)) break;
    }
    TM(11);
    if (t4 < 2 || s == NSEG - 2) bar_sync(NB_MEM, 384); else bar_arrive(NB_MEM, 384);
    if (++st == 3) st = 0;
    tag ^= 0x10001;
  }
  asm volatile("setmaxnreg.inc.sync.aligned.u32 56;");
  if (t4 == 0) {
    if (elect()) send_tokens(NSEG - 1);
    __syncwarp();
    bar_sync(NB_PRE2, 288);
    if (elect()) {
      send_memory(NSEG - 1, sb + CH_Q);
      asm volatile("mbarrier.arrive.shared::cta.b64 _, [%0], 8;" :: "r"(sb + WK_BAR + 64) : "memory");
    }
    __syncwarp();
  }
}

__device__ __forceinline__ void chain_start(const ChainParams& p, const uint32_t sb) {
  if (threadIdx.x < 32 && elect()) {
    mbar_init(sb + MB_WO, 1); mbar_init(sb + MB_WQ, 1); mbar_init(sb + MB_X, 5); mbar_init(sb + MB_V, 1); mbar_init(sb + MB_T, 1); mbar_init(sb + MB_F, 2);
    for (int i = 0; i < 10; i++) mbar_init(sb + MB_W + 8 * i, 1);
    asm volatile("fence.mbarrier_init.release.cluster;" ::: "memory");
    mbar_expect(sb + MB_V, 8192);
    for (int i = 0; i < 10; i++) {
      const int n = i % 5 < 2 ? (i % 5) * 2 : i % 5 == 2 ? 1 : i % 5;
      const uint32_t bar = sb + MB_W + 8 * (n + (i < 5 ? 0 : 5));
      mbar_expect(bar, 16384);
      tma_load(sb + (i < 5 ? CH_WQ : CH_WO) + n * 16384, i < 5 ? &p.wk : &p.wv, blockIdx.x * 64, n * 128, bar);
    }
    atomicAdd(p.sync + SY_UP, 1);
    asm volatile("{.reg .pred p; setp.ne.u32 p, %0, 1024; @p trap;}" :: "r"(sb & 0xffffff));
  }
  __syncthreads();
  asm volatile("barrier.cluster.arrive.relaxed.aligned;" ::: "memory");
}

struct WorkParams {
  ChainParams ch;
  CUtensorMap wo, xn, wb[3], xp, wq, wc[2], out;
  const __nv_bfloat16* x;
  uint32_t* sync;
  int kind, qa_end, idle;
};
#define GO_320 4
#define GO_TAIL 1
enum { WK_FIRST = 0, WK_LEAD = 1, WK_CHAIN = 2, WK_LAST = 3 };
enum { IT_ATT = 0, IT_OP = 1, IT_FIN = 2, IT_BQ = 3, IT_BO = 4, IT_LN = 5, IT_Q = 6, IT_LN0 = 7, IT_OUT = 8 };
constexpr int C_EARLY = 1 << 20, C_LATE = 1 << 21, C_TAIL = 1 << 22;

__device__ __forceinline__ uint32_t item_count(int type, int b) { return type == IT_ATT ? 32 : type == IT_OP ? op_tiles(b) * op_split(b) : type == IT_FIN ? fin_items(b) : bq_items(b); }
__device__ __forceinline__ uint32_t item_need(int type, int b) { return type == IT_ATT ? 96 : item_count(type - 1, b); }
__device__ __forceinline__ int item_cols(int type, int b) {
  return type == IT_ATT || type == IT_Q ? 192 : type == IT_OUT ? 80 : type == IT_BQ ? (b < BQ_12 ? 320 : b < BQ_24 ? 160 : 80) : type == IT_OP && b >= OP_N4 ? 160 : 320; }
__device__ __forceinline__ int item_groups(int type, int b) { return 16 / (type == IT_FIN ? fin_items(b) : ln_items(type == IT_LN, b)); }
#define RES_OP 1
constexpr int RES_N = RES_OP ? op_tiles(14) * op_split(14) : 0, RES_BQ = (64 - RES_N) / 6;
__device__ __forceinline__ bool reserved(int type, int b) { return type == IT_ATT ? b == 15 : type == IT_OP ? RES_OP && b == 14 : type == IT_BQ && b < RES_BQ; }
__device__ __forceinline__ int reserved_item(int cta) {
  const int h = cta / 3, j = cta - 3 * h, i = h + (j - 1) * 32;
  if (j == 0) return C_EARLY | IT_ATT << 16 | 15 << 8 | h;
  return i < RES_N ? C_TAIL | IT_OP << 16 | 14 << 8 | i : i - RES_N < RES_BQ * 6 ? C_TAIL | IT_BQ << 16 | ((i - RES_N) / 6) << 8 | (i - RES_N) % 6 : -1;
}
constexpr int LEAD1 = 12;
__device__ __forceinline__ int lead_item(int layer, int qa_end, int i) {
  if (layer == 2) return i < 128 ? C_EARLY | C_LATE | IT_OUT << 16 | (i >> 3) << 8 | (i & 7) : -1;
  if (layer == 0) {
    if (i < 32) return IT_LN0 << 16 | (i >> 4) << 8 | (i & 15);
    if (i < 88) return IT_LN0 << 16 | ((i - 24) >> 2) << 8 | (i & 3);
    i -= 88;
  } else {
    if (i < 4) return C_EARLY | IT_BO << 16 | (i >> 1) << 8 | (i & 1);
    if (i < 12) return C_EARLY | IT_LN << 16 | ((i - 4) >> 2) << 8 | (i & 3);
    if (i < 40) return C_EARLY | IT_BO << 16 | ((i - 8) >> 1) << 8 | (i & 1);
    if (i < 96) return C_EARLY | IT_LN << 16 | ((i - 32) >> 2) << 8 | (i & 3);
    i -= 96;
  }
  return i < (16 - qa_end) * 32 ? C_EARLY | IT_Q << 16 | (qa_end + (i >> 5)) << 8 | (i & 31) : -1;
}

struct Ring {
  uint32_t sb;
  int pos, seq;
  __device__ __forceinline__ uint32_t full() const { return sb + WK_BAR + 8 * (seq & 7); }
  __device__ __forceinline__ uint32_t take(int len) { if (pos + len > WK_SLOTS) pos = 0; pos += len; seq++; return sb + (pos - len) * 8192; }
  __device__ __forceinline__ uint32_t wait(int len) { mbar_wait_uniform(full(), (seq >> 3) & 1); return take(len); }
  __device__ __forceinline__ void release(int sq) const { if (elect()) mbar_arrive(sb + WK_BAR + 64 + 8 * (sq & 7)); }
};

struct Pending {
  uint32_t w[48], done;
  uint4* dst;
  __device__ __forceinline__ void store(int i) const { dst[(i >> 2) * 1024 + (i & 3) * 32] = make_uint4(w[4 * i], w[4 * i + 1], w[4 * i + 2], w[4 * i + 3]); }
  __device__ __forceinline__ void finish() { __syncwarp(); if (elect()) mbar_arrive(done); done = 0; }
  __device__ __forceinline__ void flush() {
    if (done) {
#pragma unroll
      for (int i = 0; i < 12; i++) store(i);
      finish();
    }
  }
};

template <int N>
__device__ __forceinline__ void gemm_item(float* d, Ring& r, int nkb, uint32_t go, int ask, Pending& pend) {
  const int warp = __shfl_sync(~0u, fresh_tid() >> 5, 0), wg = warp >> 2;
#pragma unroll 1
  for (int kb = 0; kb < nkb; kb++) {
    const uint32_t base = r.wait(2 + (N + 63) / 64);
    const uint64_t da = mkdesc(base + wg * 8192, 128, 1024, 0), db = mkdesc(base + 16384, 8192, 1024, 1);
    wg_fence();
#pragma unroll
    for (int kk = 0; kk < 4; kk++) {
      if (N == 80) wg_ss80_01(d, da + kk * 16, db + kk * 128, (kb | kk) != 0);
      else if (N == 160) wg_ss160_01(d, da + kk * 16, db + kk * 128, (kb | kk) != 0);
      else wg_ss192_01(d, da + kk * 16, db + kk * 128, (kb | kk) != 0);
      if (N == 320) wg_ss128_01(d + 96, da + kk * 16, db + kk * 128 + 3 * 512, (kb | kk) != 0);
    }
    wg_commit();
    if (kb == ask && go && warp == 0 && elect()) mbar_arrive(go);
    if (N == 192 && pend.done) {
#pragma unroll
      for (int i = 0; i < 12; i++) if (kb == i / 2) pend.store(i);
      if (kb == 5) pend.finish();
    }
    if (kb > 0) { wg_wait<1>(); r.release(r.seq - 2); }
  }
  wg_wait<0>();
  reg_fence<N / 2>(d);
  r.release(r.seq - 1);
}

__device__ __forceinline__ void attn_a_warp(Ring& r, Pending& pend, bool now, const int warp) {
  uint32_t (&q)[48] = pend.w;
  const int lane = fresh_tid() & 31, g = lane >> 2, c = lane & 3, seg = warp & 3;
  const bool half = warp >= 4;
  const float k2 = 0.07216878364870322f * 1.44269504089f, NEG = -INFINITY;
  float sc[5][4] = {};
#pragma unroll
  for (int i = 0; i < 8; i++) sc[3 + (i >> 2)][i & 3] = half ? 0.f : NEG;
  uint32_t base, f[2][40] = {};
  const uint32_t ka = seg * 4096 + lane * 16, va = seg * 4096 + (lane & 8) * 32 + (lane & 16) * 8 + (lane & 7) * 16;
  auto load = [&](int n) {
    uint32_t* d = f[n & 1];
    base = n & 1 ? base + KV_PART : r.wait(5);
    const uint32_t a = base + (n < 3 ? ka : va), m = base + KV_M + seg * 1024;
#pragma unroll
    for (int i = 0; i < 4; i++) {
      if (n >= 3) { const uint2 vm = lds64(m + i * 256 + lane * 8); d[2 * i] = vm.x; d[2 * i + 1] = vm.y; }
      else if (!(i & 1)) ldsm4(&d[2 * i], m + i * 256 + lane * 16);
      ldsm4(&d[8 + 4 * i], a + half * 2048 + i * 512);
    }
    if (half) {
#pragma unroll
      for (int i = 0; i < 4; i++) ldsm4(&d[24 + 4 * i], a + i * 512);
    }
  };
  load(0);
#pragma unroll
  for (int u = 0; u < 3; u++) {
    if (u == 2) r.release(r.seq - 2);
    load(u + 1);
    SCHED();
    const uint32_t* b = f[u & 1];
#pragma unroll
    for (int kk = 0; kk < 4; kk++) {
      const uint32_t* a = &q[16 * u + 4 * kk];
      mma16(sc[0], a[0], a[1], a[2], a[3], b[2 * kk], b[2 * kk + 1]);
      mma16(sc[1], a[0], a[1], a[2], a[3], b[8 + 4 * kk], b[9 + 4 * kk]);
      mma16(sc[2], a[0], a[1], a[2], a[3], b[10 + 4 * kk], b[11 + 4 * kk]);
    }
    if (half) {
#pragma unroll
      for (int kk = 0; kk < 4; kk++) {
        const uint32_t* a = &q[16 * u + 4 * kk];
        mma16(sc[3], a[0], a[1], a[2], a[3], b[24 + 4 * kk], b[25 + 4 * kk]);
        mma16(sc[4], a[0], a[1], a[2], a[3], b[26 + 4 * kk], b[27 + 4 * kk]);
      }
    }
    SCHED();
  }
  load(4);
  SCHED();
  if (2 * c > g) { sc[1][0] = NEG; sc[2][2] = NEG; }
  if (2 * c + 1 > g) { sc[1][1] = NEG; sc[2][3] = NEG; }
  sc[2][0] = sc[2][1] = NEG;
  uint32_t pp[5][2]; float inv[2];
#pragma unroll
  for (int hh = 0; hh < 2; hh++) {
    float m = NEG, l = 0.f;
#pragma unroll
    for (int n = 0; n < 5; n++) m = fmaxf(m, fmaxf(sc[n][2 * hh], sc[n][2 * hh + 1]));
    m = fmaxf(m, __shfl_xor_sync(~0u, m, 1)); m = fmaxf(m, __shfl_xor_sync(~0u, m, 2));
#pragma unroll
    for (int n = 0; n < 5; n++) { const float x = ex2((sc[n][2 * hh] - m) * k2), y = ex2((sc[n][2 * hh + 1] - m) * k2); l += x + y; pp[n][hh] = pack2(x, y); }
    l += __shfl_xor_sync(~0u, l, 1); l += __shfl_xor_sync(~0u, l, 2);
    inv[hh] = rcp(l);
  }
#pragma unroll
  for (int u = 0; u < 3; u++) {
    float o[8][4] = {};
    const uint32_t* b = f[~u & 1];
#pragma unroll
    for (int n = 0; n < 8; n++) mma8(o[n], pp[0][0], pp[0][1], b[n]);
#pragma unroll
    for (int n = 0; n < 8; n++) mma16(o[n], pp[1][0], pp[1][1], pp[2][0], pp[2][1], b[8 + 2 * n], b[9 + 2 * n]);
    if (half) {
#pragma unroll
      for (int n = 0; n < 8; n++) mma16(o[n], pp[3][0], pp[3][1], pp[4][0], pp[4][1], b[24 + 2 * n], b[25 + 2 * n]);
    }
    SCHED();
    if (u != 1) r.release(r.seq - 2 + u / 2);
    if (u == 0) { load(5); SCHED(); }
#pragma unroll
    for (int i = 0; i < 16; i++) q[16 * u + i] = pack2(o[i & 7][i >> 2 & 2] * inv[i >> 3], o[i & 7][(i >> 2 & 2) + 1] * inv[i >> 3]);
    if (now) {
#pragma unroll
      for (int i = 0; i < 4; i++) pend.store(4 * u + i);
    }
  }
}

__device__ __forceinline__ void ln_groups(Ring& ring, uint32_t scratch, int planes, int rg, bool two) {
  constexpr int G = 2;
  const int warp = fresh_tid() >> 5, lane = fresh_tid() & 31;
  const uint32_t id = (lane >> 3) == (lane & 3) ? ((lane & 4) ? 0x3f800000u : 0x00003f80u) : 0u;
  const uint32_t at = (warp * 160 + lane) * 8, at1 = planes > 1 ? at : (lane >> 2) * 1280 + warp * 160 + (lane & 3) * 4;
  const uint32_t step = planes > 1 ? 256 : 32, half = planes > 1 ? 4 : 16;
  float v[G][5][4] = {};
#pragma unroll
  for (int r = 0; r < G; r++) {
#pragma unroll 1
    for (int k = r && !two ? 0 : planes; k > 0; k -= 4) {
      const uint32_t a = ring.wait(min(k, 4) + 1);
      if (k == 1) {
#pragma unroll
        for (int i = 0; i < 5; i++) mma8(v[r][i], lds32(a + at1 + i * step), lds32(a + at1 + i * step + half), id);
      } else {
#pragma unroll
        for (int i = 0; i < 10; i++) {
          if (i == 5 && k < 4) break;
          const uint2 x = lds64(a + at + i / 5 * 20480 + i % 5 * 256), y = lds64(a + at + i / 5 * 20480 + 10240 + i % 5 * 256);
          mma16(v[r][i % 5], x.x, x.y, y.x, y.y, id, id);
        }
      }
      ring.release(ring.seq - 1);
    }
  }
  uint2 xr[G][5];
  scratch += (lane >> 2) * 64;
#pragma unroll
  for (int r = 0; r < G; r++) {
    float m = 0.f, q = 0.f;
#pragma unroll
    for (int i = 0; i < 5; i++) {
      float* t = v[r][i];
      xr[r][i] = make_uint2(pack2(t[0], t[1]), pack2(t[2], t[3]));
      t[0] = bf_lo(xr[r][i].x); t[1] = bf_hi(xr[r][i].x); t[2] = bf_lo(xr[r][i].y); t[3] = bf_hi(xr[r][i].y);
      m += (t[0] + t[1]) + (t[2] + t[3]);
    }
    m += __shfl_xor_sync(~0u, m, 1); m += __shfl_xor_sync(~0u, m, 2);
    m *= 1.f / 80;
#pragma unroll
    for (int i = 0; i < 5; i++) { const float a = v[r][i][0] - m, b = v[r][i][1] - m, c = v[r][i][2] - m, d = v[r][i][3] - m; q += (a * a + b * b) + (c * c + d * d); }
    q += __shfl_xor_sync(~0u, q, 1); q += __shfl_xor_sync(~0u, q, 2);
    if ((lane & 3) == 0) sts64f(scratch + r * 512 + warp * 8, m, q);
  }
  bar_sync(1, 256);
#pragma unroll
  for (int r = 0; r < G; r++) {
    const float4 t = lds128f(scratch + r * 512 + (lane & 3) * 16);
    float mean = t.x + t.z;
    mean += __shfl_xor_sync(~0u, mean, 1); mean += __shfl_xor_sync(~0u, mean, 2);
    mean *= 0.125f;
    float var = (t.y + t.w) + 80.f * ((t.x - mean) * (t.x - mean) + (t.z - mean) * (t.z - mean));
    var += __shfl_xor_sync(~0u, var, 1); var += __shfl_xor_sync(~0u, var, 2);
    const float rs = rsqrtf(var * (1.f / DM) + 1e-5f);
#pragma unroll
    for (int i = 0; i < 20; i++) v[r][i >> 2][i & 3] = (v[r][i >> 2][i & 3] - mean) * rs;
  }
#pragma unroll
  for (int r = 0; r < G; r++) {
    if (r && !two) break;
    uint32_t* xn = g_xn + (rg + r) * 2560 + warp * 320 + lane;
#pragma unroll
    for (int i = 0; i < 10; i++) xn[i * 32] = pack2(v[r][i >> 1][2 * (i & 1)], v[r][i >> 1][2 * (i & 1) + 1]);
#pragma unroll
    for (int i = 0; i < 5; i++) g_x[(rg + r) * 17 * 1280 + warp * 160 + i * 32 + lane] = xr[r][i];
  }
}

__device__ __forceinline__ void store_partial(const float* d, int b, int split, int unit, int nu) {
  uint2* dst = g_x + (((b * 16 + (fresh_tid() >> 5) * 2) * 17 + 1 + split) * 40 + unit) * 32 + (fresh_tid() & 31);
#pragma unroll
  for (int u = 0; u < 20; u++) {
    if (u == 10 && nu == 10) break;
    dst[u * 32] = make_uint2(pack2(d[8 * u], d[8 * u + 1]), pack2(d[8 * u + 4], d[8 * u + 5]));
    dst[(680 + u) * 32] = make_uint2(pack2(d[8 * u + 2], d[8 * u + 3]), pack2(d[8 * u + 6], d[8 * u + 7]));
  }
}

__device__ __forceinline__ void store_bqkv(const float* d, int b, int idx, int nh) {
  const int lane = fresh_tid() & 31, c = lane & 3, rg = b * 16 + (fresh_tid() >> 5) * 2, h0 = idx * nh;
  const float sc = h0 < 32 ? 0.22360679775f * 1.44269504089f : 1.f;
  const bool lo = c < 2;
  uint32_t* da = g_bqkv + (h0 * 256 + rg) * 96 + lane;
  uint32_t* db = da + 256 * 96 + (lo ? 2 : -2);
  uint32_t pad[2];
#pragma unroll
  for (int r = 0; r < 2; r++) pad[r] = !(c & 1) && (h0 >= 64 || (h0 >= 32 && (lane & 4) && poly_group(rg + r))) ? 0x00003f80u : 0u;
#pragma unroll
  for (int q = 0; q < 8; q++) {
    if ((q == 2 || q == 4) && nh == 2 * q) break;
#pragma unroll
    for (int r = 0; r < 2; r++) {
      uint32_t w[5];
#pragma unroll
      for (int i = 0; i < 5; i++) w[i] = pack2(d[20 * q + 4 * i + 2 * r] * sc, d[20 * q + 4 * i + 2 * r + 1] * sc);
      const int o = q * 2 * 256 * 96 + r * 96;
      da[o] = w[0]; da[o + 32] = w[1]; da[o + 64] = lo ? w[2] : pad[r];
      db[o] = lo ? w[3] : w[2]; db[o + 32] = lo ? w[4] : w[3]; db[o + 64] = lo ? pad[r] : w[4];
    }
  }
}

__device__ __forceinline__ void work_loader(const WorkParams& p, const uint32_t sb, const bool weights) {
  const uint32_t bars = sb + WK_BAR, bIF = bars + 128, bIE = bars + 160, bGo = bars + 224, slots = bars + 272;
  int pos = 0, seq = 0, tail = 0, used = 0;
  uint32_t lens = 0;
  const bool one = elect();
  if (p.kind == WK_CHAIN) {
    seq = 1; used = lens = 8;
    if (one) mbar_arrive(bars);
  }
  for (int n = 0;; n++) {
    mbar_wait_uniform(bIF + 8 * (n & 3), (n >> 2) & 1);
    const int code = __shfl_sync(~0u, (int)lds32(slots + 4 * (n & 3)), 0);
    if (code < 0) break;
    const int type = (code >> 16) & 15, b = (code >> 8) & 255, idx = code & 255;
    if (one) mbar_arrive(bIE + 8 * (n & 3));
    const bool qa = type == IT_ATT && b < p.qa_end, ln = type == IT_FIN || type == IT_LN || type == IT_LN0;
    const int parts = ln ? item_groups(type, b) : type == IT_ATT ? 2 : 1;
#pragma unroll 1
    for (int part = 0; part < parts; part++) {
      int bytes = 163840, chunk = 40960, nb = 0, flag = b * 8 + 4 + type, need = item_need(type & 3, b), c0 = 0, c3 = idx, c4 = 0, step = 64;
      const uint8_t* src = g_kv + (b * 32 + idx) * 6 * KV_PART;
      const CUtensorMap* m = nullptr;
      if (ln) {
        const int rg = b * 16 + idx * parts + part;
        bytes = (type == IT_FIN ? op_split(b) + 1 : type == IT_LN ? 2 : 1) * 10240;
        src = type == IT_LN0 ? reinterpret_cast<const uint8_t*>(p.x) + rg * 10240 : reinterpret_cast<const uint8_t*>(g_x) + rg * 174080;
        if (type == IT_LN) { flag = SY_P + b * 4; need = 2; }
        if (type == IT_LN0 || part) need = 0;
      } else if (part) {
        bytes = 6 * KV_PART;
      } else if (type == IT_ATT && !qa) {
        bytes = chunk = 49152;
        src = reinterpret_cast<const uint8_t*>(g_q) + (b * 32 + idx) * 49152;
        flag = SY_P + b * 4 + 3; need = 32;
      } else {
        const int cols = item_cols(type, b);
        chunk = 16384; nb = (cols + 63) >> 6;
        src = reinterpret_cast<const uint8_t*>(g_of) + b * 163840;
        if (type == IT_OP) {
          const int nkb = 96 / op_split(b), kb0 = (idx >> op_tiles(b) / 2) * nkb;
          bytes = nkb * 16384;
          src = reinterpret_cast<const uint8_t*>(g_o) + (b * 96 + kb0) * 16384;
          if (weights) m = &p.wo;
          c0 = (idx & (op_tiles(b) - 1)) * cols; c3 = 0; c4 = kb0 * 2; step = 2;
        } else if (type == IT_BQ) {
          m = weights ? &p.wb[cols / 160] : &p.xn;
        } else if (type == IT_BO || type == IT_OUT) {
          if (weights) m = &p.wc[cols / 320];
          flag = SY_OB; need = type == IT_BO && b < 2 ? 32 : -1;
        } else {
          m = weights ? &p.wq : &p.xp;
          flag = SY_P + b * 4 + 1; need = ln_items(p.ch.layer, b);
        }
      }
      if (!weights) {
        c3 = b * 4;
        if (need < 0) pdl_wait(); else if (need) wait_count_uniform(p.sync + flag, need);
        if ((ln ? !part : part && (!qa || (code & C_EARLY))) && one) mbar_arrive(bGo);
      }
      const int boxes = weights ? nb : m != nullptr;
#pragma unroll 1
      for (; bytes > 0; bytes -= chunk) {
        const int now = min(bytes, chunk), len = ((now + 8191) >> 13) + nb, skip = pos + len > WK_SLOTS ? WK_SLOTS - pos : 0, sh = 4 * (seq & 7);
        used += len + skip;
        while (used > WK_SLOTS || seq - tail >= 8) {
          mbar_wait_uniform(bars + 64 + 8 * (tail & 7), (tail >> 3) & 1);
          used -= (lens >> 4 * (tail & 7)) & 15;
          tail++;
        }
        lens = (lens & ~(15u << sh)) | (len + skip) << sh;
        if (pos + len > WK_SLOTS) pos = 0;
        const uint32_t bar = bars + 2 * sh, dst = sb + pos * 8192 + weights * 16384;
        if (one) mbar_expect(bar, weights ? nb * 8192 : now);
#pragma unroll 1
        for (int i = 0; i < boxes; i++)
          if (one)
            asm volatile("cp.async.bulk.tensor.5d.shared::cluster.global.mbarrier::complete_tx::bytes [%0], [%1, {%3, %6, %6, %4, %5}], [%2];"
                         :: "r"(dst + i * 8192), "l"(m), "r"(bar), "r"(c0 + i * 64), "r"(c3), "r"(c4), "r"(0) : "memory");
        if (!weights && !m && one) bulk_load_last(dst, src, now, bar);
        if (weights) c4 += step; else c0 += 128;
        src += chunk; pos += len; seq++;
      }
    }
  }
}

__global__ void __launch_bounds__(384, 1) work_kernel(const __grid_constant__ WorkParams p) {
  extern __shared__ __align__(1024) uint8_t smem_raw[];
  const uint32_t sb = s2u(smem_raw), bars = sb + WK_BAR;
  const uint32_t bIF = bars + 128, bIE = bars + 160, done = bars + 192, bGo = bars + 224, slots = bars + 272, scratch = bars + 384;
  const int warp = __shfl_sync(~0u, threadIdx.x >> 5, 0);
  uint32_t* const sync = p.sync;
  TRACE(0);
  pdl_launch();
  if (p.kind == WK_LEAD && !helper_sm() && __syncthreads_or(threadIdx.x == 0 && ldg_strong32(sync + SY_PRE + 1) >= LEAD1)) { pdl_wait(); return; }
  if (p.kind == WK_CHAIN) {
    chain_start(p.ch, sb);
  } else {
    if (warp == 0) work_init(sb);
    __syncthreads();
    if (p.kind == WK_FIRST) {
      if (!(warp & 13)) probe_slots(bars + 320);
      if (!helper_sm()) return;
    }
  }
  if (warp >= 8) {
    if (p.kind == WK_CHAIN) {
      asm volatile("setmaxnreg.dec.sync.aligned.u32 40;");
      chain_comm(p.ch, sb, &p.wo);
    } else {
      asm volatile("setmaxnreg.dec.sync.aligned.u32 56;");
    }
    const int warp = __shfl_sync(~0u, fresh_tid() >> 5, 0), lane = fresh_tid() & 31;
    if (warp == 9) {
      const bool keep = p.kind > WK_LEAD || helper_sm();
      int n = 0;
      if (p.kind == WK_CHAIN && reserved_item(blockIdx.x) >= 0) {
        if (lane == 0) { sts32(slots, reserved_item(blockIdx.x)); mbar_arrive(bIF); }
        n = 1;
      }
      const int b = lane & 15, layer = p.kind == WK_LAST ? 2 : sync != g_sync;
      bool first = layer == 1, lead = p.kind != WK_CHAIN;
      for (;; n++) {
        if (n > 0) mbar_wait_uniform(bGo, (n - 1) & 1);
        mbar_wait_uniform(bIE + 8 * (n & 3), ((n >> 2) & 1) ^ 1);
        int code = -1;
        if (lead) {
          int i = blockIdx.x + n * 256;
          if (first) { if (lane == 0) i = atomicAdd(sync + SY_PRE + 1, 1); i = __shfl_sync(~0u, i, 0); first = i < LEAD1; }
          if (layer < 2 && !first) {
            if (lane == 0) i = keep ? atomicAdd(sync + SY_PRE, 1) + layer * LEAD1 : 1 << 20;
            i = __shfl_sync(~0u, i, 0);
            if (!keep) pdl_wait();
          }
          code = lead_item(layer, p.qa_end, i);
          lead = code >= 0 || layer == 2 || !keep;
          if (!lead && p.kind <= WK_LEAD) {
            const uint32_t t0 = gtime();
            while (!lead && ldg_strong32(sync + SY_UP) < 96) lead = gtime() - t0 > 20000;
          }
        }
        if (!lead) {
          int spin = 0, ticket = 0;
          if (lane == 0) ticket = atomicAdd(sync + SY_T, 1);
          for (;;) {
            const uint4 hd = ldg_strong128(sync + b * 8), pr = ldg_strong128(sync + b * 8 + 4);
            const uint32_t hv[4] = {hd.x, hd.y, hd.z, hd.w}, pv[4] = {pr.x, pr.y, pr.z, pr.w};
            const uint32_t chain_done = __ballot_sync(~0u, (pr.x & 0xffff) >= 96);
            int left[4], avail[4], rdy = 0, claimed = 0, upstream = 0;
#pragma unroll
            for (int t = 0; t < 4; t++) {
              const int cnt = lane < 16 && !reserved(t, b) ? item_count(t, b) : 0;
              left[t] = max(cnt - (int)hv[t], 0);
              claimed += cnt - left[t];
              const bool ready = (pv[t] & 0xffff) >= item_need(t, b);
              rdy |= ready << t;
              bool ok = ready || (t != IT_ATT && (chain_done >> 15 & 1) && !left[t - 1] && (t < 2 || !left[t - 2]));
              if (t == IT_BQ && (chain_done >> 12 & 9) == 1) ok = false;
              avail[t] = ok ? left[t] : 0;
              upstream |= __any_sync(~0u, left[t] > 0);
            }
            if (!upstream) { code = -1; break; }
            int rank = max(__shfl_sync(~0u, ticket, 0) - __reduce_add_sync(~0u, claimed), 0), type = -1, mine = 0;
#pragma unroll
            for (int c = 0; c < 7; c++) {
              const int t = c == 0 || c == 4 ? IT_FIN : c == 1 || c == 6 ? IT_ATT : c == 2 ? IT_OP : IT_BQ;
              int a = c == 1 || c == 2 || ((rdy >> t & 1) == (c < 4)) ? avail[t] : 0;
              if (c == 6) a = b < p.qa_end && !(rdy & 1) && ((chain_done << 1 | 1) >> b & 1) ? left[t] : 0;
              const int tot = __reduce_add_sync(~0u, a);
              if (type < 0) { if (rank < tot) { type = t; mine = a; } else rank -= tot; }
            }
            if (type >= 0) {
#pragma unroll
              for (int o = 1; o < 16; o <<= 1) { const int y = __shfl_up_sync(~0u, mine, o); if (lane >= o) mine += y; }
              const int blk = __ffs(__ballot_sync(~0u, mine > rank)) - 1;
              const int early = !(__shfl_sync(~0u, rdy, blk) >> type & 1);
              uint32_t idx = 0;
              if (lane == 0) idx = atomicAdd(sync + blk * 8 + type, 1);
              idx = __shfl_sync(~0u, idx, 0);
              if (idx < item_count(type, blk)) { code = (chain_done >> 14 & 1) << 22 | early << 20 | type << 16 | blk << 8 | idx; break; }
            } else {
              __nanosleep(50);
            }
            spin_guard(spin);
          }
        }
        if (lane == 0) {
          sts32(slots + 4 * (n & 3), code);
          mbar_arrive(bIF + 8 * (n & 3));
        }
        __syncwarp();
        if (code < 0) break;
      }
    } else if (warp >= 10) {
      work_loader(p, sb, warp == 10);
    } else {
      for (int n = 0;; n++) {
        mbar_wait_uniform(bIF + 8 * (n & 3), (n >> 2) & 1);
        const int code = __shfl_sync(~0u, (int)lds32(slots + 4 * (n & 3)), 0);
        if (code < 0) break;
        const int type = (code >> 16) & 15, b = (code >> 8) & 255;
        mbar_wait_uniform(done + 8 * (n & 3), (n >> 2) & 1);
        if (elect()) {
          if (type != IT_OUT) red_release(sync + (type < IT_BQ ? b * 8 + 5 + type : SY_P + b * 4 + ((0x13102 >> 4 * (type - IT_BQ)) & 3)), 1);
          mbar_arrive(bIE + 8 * (n & 3));
        }
        __syncwarp();
      }
    }
  } else {
    if (p.kind == WK_CHAIN) {
      asm volatile("setmaxnreg.inc.sync.aligned.u32 232;");
      if (warp < 4) chain_compute<0>(p.ch, sb); else chain_compute<1>(p.ch, sb);
    } else {
      asm volatile("setmaxnreg.inc.sync.aligned.u32 224;");
    }
    const int warp = __shfl_sync(~0u, fresh_tid() >> 5, 0), lane = fresh_tid() & 31;
    Ring r{sb, 0, p.kind == WK_CHAIN};
    Pending pend;
    pend.done = 0;
    int nln = 0;
    auto projects = [&](int n) {
      uint32_t here;
      asm volatile("{.reg .pred p; mbarrier.test_wait.parity.shared::cta.b64 p, [%1], %2; vote.sync.all.pred p, p, 0xffffffff; selp.u32 %0, 1, 0, p;}" : "=r"(here) : "r"(bIF + 8 * (n & 3)), "r"((n >> 2) & 1) : "memory");
      if (!here) return false;
      const int code = __shfl_sync(~0u, (int)lds32(slots + 4 * (n & 3)), 0);
      return code >= 0 && (((code >> 16) & 15) == IT_Q || (((code >> 16) & 15) == IT_ATT && ((code >> 8) & 255) < p.qa_end));
    };
#pragma unroll 1
    for (int n = 0;; n++) {
      if (pend.done && !projects(n)) pend.flush();
      mbar_wait_uniform(bIF + 8 * (n & 3), (n >> 2) & 1);
      const int code = __shfl_sync(~0u, (int)lds32(slots + 4 * (n & 3)), 0);
      if (code < 0) { TRACE(2); break; }
      const int type = (code >> 16) & 15, b = (code >> 8) & 255, idx = code & 255;
      const uint32_t go = (code & C_LATE) || (type == IT_ATT && (code & C_EARLY)) ? 0 : bGo;
      ITEM(code & 0xfffff, 0);
      if (type == IT_ATT || type == IT_Q) {
        if (type == IT_Q || b < p.qa_end) {
          float d[96] = {};
          reg_fence<96>(d);
          ITEM(9 << 16 | (code & 0xffff), 0);
          gemm_item<192>(d, r, 10, go, 4, pend);
          ITEM(9 << 16 | (code & 0xffff), 1);
#pragma unroll
          for (int i = 0; i < 48; i++) pend.w[i] = pack2(d[2 * i], d[2 * i + 1]);
        } else {
          const uint32_t base = r.wait(6) + warp * 2048 + lane * 16;
#pragma unroll
          for (int i = 0; i < 12; i++) {
            const uint4 t = lds128(base + (i >> 2) * 16384 + (i & 3) * 512);
            pend.w[4 * i] = t.x; pend.w[4 * i + 1] = t.y; pend.w[4 * i + 2] = t.z; pend.w[4 * i + 3] = t.w;
          }
          __syncwarp();
          r.release(r.seq - 1);
        }
        const bool now = type == IT_ATT && !projects(n + 1);
        if (type == IT_Q) {
          pend.dst = g_q + (b * 32 + idx) * 3072 + warp * 128 + lane;
        } else {
          pend.dst = g_o + (b * 32 + idx) * 3072 + (warp & 3) * 256 + (warp >> 2) * 128 + (lane & 3) * 8 + (lane >> 2);
          attn_a_warp(r, pend, now, warp);
        }
        pend.done = done + 8 * (n & 3);
        if (now) pend.finish();
      } else {
        if (type == IT_FIN || type == IT_LN || type == IT_LN0) {
          const int ng = item_groups(type, b);
          const int planes = type == IT_FIN ? op_split(b) + 1 : type == IT_LN ? 2 : 1;
#pragma unroll 1
          for (int i = 0; i < ng; i += 2) ln_groups(r, scratch + (nln++ & 1) * 1024, planes, b * 16 + idx * ng + i, ng > 1);
        } else {
          const int cols = item_cols(type, b), nkb = type == IT_OP ? 96 / op_split(b) : 10;
          float d[160] = {};
          if (type == IT_OUT) {
            const uint2* x = g_x + ((b * 16 + warp * 2) * 680 + idx * 5) * 32 + lane;
#pragma unroll
            for (int i = 0; i < 10; i++) { const uint2 y = __ldcg(x + (i / 5 * 680 + i % 5) * 32); d[40 + 2 * i] = __uint_as_float(y.x); d[41 + 2 * i] = __uint_as_float(y.y); }
          }
          reg_fence<160>(d);
          if (type != IT_OUT) ITEM((type == IT_BQ ? 10 : 11) << 16 | (code & 0xffff), 0);
          const int ask = max(nkb - (code & C_TAIL ? GO_TAIL : GO_320) * 320 / cols, 0);
          if (cols == 320) gemm_item<320>(d, r, nkb, go, ask, pend);
          else if (cols == 160) gemm_item<160>(d, r, nkb, go, ask, pend);
          else gemm_item<80>(d, r, nkb, go, ask, pend);
          if (type != IT_OUT) ITEM((type == IT_BQ ? 10 : 11) << 16 | (code & 0xffff), 1);
          reg_fence<160>(d);
          if (type == IT_OUT) {
            bar_sync(1, 256);
            const uint32_t dst = sb + (warp * 16 + (lane & 15)) * 160 + (lane >> 4) * 16;
#pragma unroll
            for (int u = 0; u < 5; u++) {
              uint32_t w[4];
#pragma unroll
              for (int i = 0; i < 4; i++) { const uint32_t y = __float_as_uint(d[40 + (i & 1) * 10 + 2 * u + (i >> 1)]); w[i] = pack2(bf_lo(y) + d[8 * u + 2 * i], bf_hi(y) + d[8 * u + 2 * i + 1]); }
              stsm4(dst + u * 32, w[0], w[1], w[2], w[3]);
            }
            fence_async();
            __syncwarp();
            if (elect()) { tma_store(&p.out, sb + warp * 2560, idx * 80, b * 128 + warp * 16); bulk_commit(); bulk_wait<0>(); }
          } else {
            if (warp >= 4) bar_sync(7, 256);
            if (type == IT_BQ) store_bqkv(d, b, idx, cols / 20);
            else store_partial(d, b, cols == 320 ? idx >> 1 : idx >> 2, cols == 320 ? (idx & 1) * 20 : (idx & 3) * 10, cols >> 4);
            if (warp < 4) bar_arrive(7, 256);
          }
        }
        __syncwarp();
        if (elect()) mbar_arrive(done + 8 * (n & 3));
#pragma unroll
        for (int i = 0; i < 48; i++) pend.w[i] = 0;
      }
      if ((code & C_LATE) && warp == 4 && elect()) mbar_arrive(bGo);
      ITEM(code & 0xfffff, 1);
    }
  }
}

constexpr int AB_SMEM = 1024 + 2 * 98304 + 256;
#define AB_N 32
#define AB_WG 4
constexpr int AB_T = AB_WG * 128, AB_PASS = 8 / AB_WG;
__device__ __forceinline__ float ex2_poly(float t) {
  const uint32_t r = __float_as_uint(t) & 0xffff8000u;
  const float f = t - __uint_as_float(r);
  const float p = fmaf(fmaf(fmaf(-5.869912678e-38f, f, -1.700740250e-37f), f, -5.234869734e-37f), f, -7.522601252e-37f);
  uint32_t y;
  asm("mad.lo.u32 %0, %1, 256, %2;" : "=r"(y) : "r"(r), "r"(__float_as_uint(p)));
  return __uint_as_float(y);
}
__device__ __forceinline__ uint32_t hsq(uint32_t w, uint32_t c) { uint32_t r; asm("fma.rn.bf16x2 %0, %1, %1, %2;" : "=r"(r) : "r"(w), "r"(c)); return r; }
__device__ __forceinline__ float sq2(uint32_t w) { const float a = bf_lo(w), b = bf_hi(w); return fmaf(a, a, b * b); }

__device__ __forceinline__ void attn_b_store(const float* o, int h, int row0, int lane) {
  const int g = lane >> 2, c = lane & 3;
  const float i0 = 1.f / __shfl_sync(~0u, o[8], (lane & ~3) | 2), i1 = 1.f / __shfl_sync(~0u, o[10], (lane & ~3) | 2);
#pragma unroll
  for (int jj = 0; jj < 3; jj++) {
    if (jj < 2 || c < 2) {
      const int col = h * 20 + 8 * jj + 2 * c;
      g_of[core_word(row0 + g, col)] = pack2(o[4 * jj] * i0, o[4 * jj + 1] * i0);
      g_of[core_word(row0 + g + 8, col)] = pack2(o[4 * jj + 2] * i1, o[4 * jj + 3] * i1);
    }
  }
}

__device__ __forceinline__ void attn_b_qk(float* s, uint32_t q0, uint32_t q1, uint32_t q2, uint32_t q3, uint32_t q4, uint32_t q5, uint32_t z0, uint32_t z1,
                                          uint64_t dk, uint64_t dk2) {
  wg_rs32_00(s, q0, q1, q2, q3, dk, 0);
  wg_rs32_00(s, q4, q5, z0, z1, dk2, 1);
}

struct AttnParams { const uint8_t* pf[4]; uint32_t *sync, *next; };
__global__ void __launch_bounds__(AB_T + 128, 1) attn_b_kernel(const __grid_constant__ AttnParams p) {
  extern __shared__ uint8_t smem_raw[];
  const uint32_t sb = (s2u(smem_raw) + 1023) & ~1023u, sK = sb, sV = sb + 98304, bars = sb + 2 * 98304;
  const int warp = __shfl_sync(~0u, threadIdx.x >> 5, 0), lane = threadIdx.x & 31;
  const int h = blockIdx.x & 31, quarter = blockIdx.x >> 5;
  BT(0);
  TRACE(0);
  if (threadIdx.x == 0) {
    for (int i = 0; i < 8; i++) mbar_init(bars + 8 * i, 1);
    mbar_init(bars + 128, AB_T / 32);
    mbar_init(bars + 136, 2);
    asm volatile("fence.mbarrier_init.release.cluster;" ::: "memory");
  }
  __syncthreads();
  if (warp >= AB_T / 32) {
    asm volatile("setmaxnreg.dec.sync.aligned.u32 32;");
    if (warp == AB_T / 32 + 1) return;
    if (warp > AB_T / 32) {
      uint32_t kmax = 0;
#pragma unroll 1
      for (int i = 0; i < 32; i++) {
        if (!(i & 3)) mbar_wait_uniform(bars + 2 * i, 0);
        const uint32_t a = sK + i * 3072 + ((threadIdx.x >> 3) & 7) * 384 + (lane & 7) * 16;
        const uint4 x = lds128(a), y = lds128(a + 128);
        const uint2 z = lds64(a + 256);
        const uint32_t n = hadd2(hsq(x.x, hsq(x.y, hsq(x.z, hsq(x.w, hsq(z.x, 0))))), hsq(y.x, hsq(y.y, hsq(y.z, hsq(y.w, hsq(z.y, 0))))));
        kmax = max(kmax, __float_as_uint(bf_lo(n) + bf_hi(n)) & 0x7fffffffu);
      }
      const uint32_t kbits = __reduce_max_sync(~0u, kmax);
      if (lane == 0) { sts32(bars + 64 + (warp & 1) * 4, kbits); mbar_arrive(bars + 136); }
      return;
    }
    const uint8_t* gk = reinterpret_cast<const uint8_t*>(g_bqkv + (32 + h) * 256 * 96);
    const uint8_t* gv = reinterpret_cast<const uint8_t*>(g_bqkv + (64 + h) * 256 * 96);
    uint32_t todo = 255;
    for (int spin = 0; todo;) {
      const uint32_t up = __ballot_sync(~0u, ld_acquire(p.sync + SY_P + (lane & 15) * 4 + 2) >= bq_items(lane & 15));
      fence_async_global();
      for (int i = 0; i < 8; i++) {
        if (!(todo >> i & 1) || (up >> 2 * i & 3) != 3) continue;
        todo &= ~(1u << i);
        if (elect()) {
          mbar_expect(bars + 8 * i, 24576);
          bulk_load(sK + i * 12288, gk + i * 12288, 12288, bars + 8 * i);
          bulk_load(sV + i * 12288, gv + i * 12288, 12288, bars + 8 * i);
        }
      }
      spin_guard(spin);
    }
    pdl_launch();
    TRACE(1);
    if (blockIdx.x < NSLOT) for (int i = lane; i < 512; i += 32) reinterpret_cast<uint4*>(pool_at(blockIdx.x * 8192))[i] = make_uint4(0, 0, 0, 0);
    if (!p.next && blockIdx.x == 127) for (int i = lane; i < 256; i += 32) { g_smpart[i] = 0; if (i < NSLOT) g_orient[i] = 0; }
    if (p.next) {
      mbar_wait_uniform(bars + 128, 0);
      if (quarter == 0 && lane == 0) red_release(p.next + SY_OB, 1);
      for (int i = 0; i < 32; i++) {
        if (elect()) prefetch_l2(p.pf[i >> 3] + blockIdx.x * 61440 + (i & 7) * 7680, 7680);
        __nanosleep(300);
      }
    }
    return;
  }
  asm volatile("setmaxnreg.inc.sync.aligned.u32 112;");
  constexpr int NT = SEQ / AB_N, PER = 256 / AB_N;
  uint32_t qn[8];
  auto load_q = [&](int pass) {
    const uint32_t* gq = g_bqkv + (h * 256 + pass * 128 + quarter * 32 + warp * 2) * 96 + lane;
#pragma unroll
    for (int i = 0; i < 8; i++) qn[i] = __ldcg(gq + (i & 1) * 96 + min(i >> 1, 2) * 32 + (i < 6 ? 0 : 3 - (lane & 3)));
  };
  mbar_wait_uniform(bars + 8 * quarter, 0);
  load_q(0);
#pragma unroll 1
  for (int pass = 0; pass < AB_PASS; pass++) {
    const int row0 = pass * 1024 + quarter * 256 + warp * 16;
    const uint32_t q0 = qn[0], q1 = qn[1], q2 = qn[2], q3 = qn[3], z0 = qn[6], z1 = qn[7];
    uint32_t q4 = qn[4], q5 = qn[5];
    if ((lane & 3) == 2) { q4 = 0x43BCu; q5 = 0x43BCu; }
    float o[12];
    uint64_t dk = mkdesc(sK, 128, 384, 0), dk2 = mkdesc(sK + 256, 0, 384, 0), dv = mkdesc(sV, 384, 128, 0);
    float sa[AB_N / 2], sb2[AB_N / 2];
    uint32_t pa[AB_N / 4], pb[AB_N / 4];
    if (pass == 0) mbar_wait_uniform(bars, 0);
    BT(1 + 2 * pass);
    wg_fence();
    attn_b_qk(sa, q0, q1, q2, q3, q4, q5, z0, z1, dk, dk2);
    wg_commit();
    attn_b_qk(sb2, q0, q1, q2, q3, q4, q5, z0, z1, dk + AB_N * 3, dk2 + AB_N * 3);
    wg_commit();
#pragma unroll 1
    for (int kt = 0; kt < NT; kt += 2) {
      const int nx = kt + 2 < NT ? kt + 2 : 0;
      if (pass == 0 && (nx & (PER - 1)) == 0) mbar_wait_uniform(bars + 8 * (nx / PER), 0);
      const uint64_t nk = dk + nx * (AB_N * 3), nk2 = dk2 + nx * (AB_N * 3);
      wg_wait<1>();
      reg_fence<AB_N / 2>(sa);
#pragma unroll
      for (int i = 0; i < AB_N / 4; i++) pa[i] = pack2(ex2(sa[2 * i]), poly_group(i >> 1) ? ex2_poly(sa[2 * i + 1]) : ex2(sa[2 * i + 1]));
      wg_fence();
#pragma unroll
      for (int kk = 0; kk < AB_N / 16; kk++) wg_rs24_01(o, pa[4 * kk], pa[4 * kk + 1], pa[4 * kk + 2], pa[4 * kk + 3], dv + kk * 48, kk | kt);
      attn_b_qk(sa, q0, q1, q2, q3, q4, q5, z0, z1, nk, nk2);
      wg_commit();
      wg_wait<1>();
      reg_fence<AB_N / 2>(sb2);
#pragma unroll
      for (int i = 0; i < AB_N / 4; i++) pb[i] = pack2(ex2(sb2[2 * i]), poly_group((i >> 1) + AB_N / 8) ? ex2_poly(sb2[2 * i + 1]) : ex2(sb2[2 * i + 1]));
      wg_fence();
#pragma unroll
      for (int kk = 0; kk < AB_N / 16; kk++) wg_rs24_01(o, pb[4 * kk], pb[4 * kk + 1], pb[4 * kk + 2], pb[4 * kk + 3], dv + AB_N * 3 + kk * 48, 1);
      attn_b_qk(sb2, q0, q1, q2, q3, q4, q5, z0, z1, nk + AB_N * 3, nk2 + AB_N * 3);
      wg_commit();
      dv += AB_N * 6;
    }
    wg_wait<0>();
    reg_fence<12>(o); reg_fence<AB_N / 2>(sa); reg_fence<AB_N / 2>(sb2);
    BT(2 + 2 * pass);
    if (pass + 1 < AB_PASS) load_q(pass + 1);
    mbar_wait_uniform(bars + 136, 0);
    const uint2 kb = lds64(bars + 64);
    const float kmax = __uint_as_float(max(kb.x, kb.y));
    if ((lane & 3) == 2) q4 = q5 = 0;
    float n0 = sq2(q0) + sq2(q2) + sq2(q4), n1 = sq2(q1) + sq2(q3) + sq2(q5);
    n0 += __shfl_xor_sync(~0u, n0, 1); n1 += __shfl_xor_sync(~0u, n1, 1);
    n0 += __shfl_xor_sync(~0u, n0, 2); n1 += __shfl_xor_sync(~0u, n1, 2);
    uint32_t redo;
    asm volatile("{.reg .pred p, q; setp.ne.u32 p, %1, 0; bar.red.or.pred q, %2, 128, p; selp.u32 %0, 1, 0, q;}"
                 : "=r"(redo) : "r"((uint32_t)!(n0 * kmax <= 9500.f && n1 * kmax <= 9500.f)), "r"(2 + (warp >> 2)) : "memory");
    if (redo) {
#pragma unroll
      for (int i = 0; i < 12; i++) o[i] = 0.f;
      float m0 = -INFINITY, m1 = -INFINITY;
#pragma unroll 1
      for (int kt = 0; kt < 64; kt++) {
        float s[16];
        wg_fence();
        wg_rs32_00(s, q0, q1, q2, q3, dk + kt * 96, 0);
        wg_rs32_00(s, q4, q5, z0, z1, dk2 + kt * 96, 1);
        wg_commit();
        wg_wait<0>();
        reg_fence<16>(s); reg_fence<12>(o);
        float n0 = m0, n1 = m1;
#pragma unroll
        for (int jj = 0; jj < 4; jj++) { n0 = fmaxf(n0, fmaxf(s[4 * jj], s[4 * jj + 1])); n1 = fmaxf(n1, fmaxf(s[4 * jj + 2], s[4 * jj + 3])); }
        n0 = fmaxf(n0, __shfl_xor_sync(~0u, n0, 1)); n0 = fmaxf(n0, __shfl_xor_sync(~0u, n0, 2));
        n1 = fmaxf(n1, __shfl_xor_sync(~0u, n1, 1)); n1 = fmaxf(n1, __shfl_xor_sync(~0u, n1, 2));
        const float r0 = ex2(m0 - n0), r1 = ex2(m1 - n1);
        m0 = n0; m1 = n1;
#pragma unroll
        for (int jj = 0; jj < 3; jj++) { o[4 * jj] *= r0; o[4 * jj + 1] *= r0; o[4 * jj + 2] *= r1; o[4 * jj + 3] *= r1; }
        uint32_t pp[8];
#pragma unroll
        for (int jj = 0; jj < 4; jj++) {
          pp[2 * jj] = pack2(ex2(s[4 * jj] - m0), ex2(s[4 * jj + 1] - m0));
          pp[2 * jj + 1] = pack2(ex2(s[4 * jj + 2] - m1), ex2(s[4 * jj + 3] - m1));
        }
        reg_fence<12>(o);
        wg_fence();
#pragma unroll
        for (int kk = 0; kk < 2; kk++) wg_rs24_01(o, pp[4 * kk], pp[4 * kk + 1], pp[4 * kk + 2], pp[4 * kk + 3], mkdesc(sV, 384, 128, 0) + kt * 96 + kk * 48, 1);
        wg_commit();
      }
      wg_wait<0>();
      reg_fence<12>(o);
    }
    attn_b_store(o, h, row0, lane);
    __syncwarp();
    if (pass == 0 && lane == 0) mbar_arrive(bars + 128);
  }
  BT(5);
  TRACE(2);
}

typedef CUresult (*EncodeFn)(CUtensorMap*, CUtensorMapDataType, cuuint32_t, void*, const cuuint64_t*, const cuuint64_t*,
                             const cuuint32_t*, const cuuint32_t*, CUtensorMapInterleave, CUtensorMapSwizzle,
                             CUtensorMapL2promotion, CUtensorMapFloatOOBfill);

void make_map(EncodeFn enc, CUtensorMap* m, const void* ptr, int cols, int rows, int box_rows, int box_cols = 64) {
  const cuuint64_t dims[2] = {(cuuint64_t)cols, (cuuint64_t)rows};
  const cuuint64_t strides[1] = {(cuuint64_t)cols * 2};
  const cuuint32_t box[2] = {(cuuint32_t)box_cols, (cuuint32_t)box_rows}, es[2] = {1, 1};
  enc(m, CU_TENSOR_MAP_DATA_TYPE_BFLOAT16, 2, const_cast<void*>(ptr), dims, strides, box, es, CU_TENSOR_MAP_INTERLEAVE_NONE,
      box_cols == 64 ? CU_TENSOR_MAP_SWIZZLE_128B : box_cols == 32 ? CU_TENSOR_MAP_SWIZZLE_64B : CU_TENSOR_MAP_SWIZZLE_NONE, CU_TENSOR_MAP_L2_PROMOTION_L2_256B, CU_TENSOR_MAP_FLOAT_OOB_FILL_NONE);
}
void make_map5(EncodeFn enc, CUtensorMap* m, const void* ptr, bool words, const cuuint64_t (&dims)[5], const cuuint64_t (&strides)[4], const cuuint32_t (&box)[5]) {
  const cuuint32_t es[5] = {1, 1, 1, 1, 1};
  enc(m, words ? CU_TENSOR_MAP_DATA_TYPE_UINT64 : CU_TENSOR_MAP_DATA_TYPE_BFLOAT16, 5, const_cast<void*>(ptr), dims, strides, box, es, CU_TENSOR_MAP_INTERLEAVE_NONE,
      words ? CU_TENSOR_MAP_SWIZZLE_NONE : CU_TENSOR_MAP_SWIZZLE_128B, dims[0] % 64 ? CU_TENSOR_MAP_L2_PROMOTION_L2_128B : CU_TENSOR_MAP_L2_PROMOTION_L2_256B,
      CU_TENSOR_MAP_FLOAT_OOB_FILL_NONE);
}
void make_tiles(EncodeFn enc, CUtensorMap* m, const void* ptr, cuuint64_t cols, cuuint64_t tile) {
  make_map5(enc, m, ptr, false, {tile, 1, 1, cols / tile, DM}, {tile * 2, tile * 2, tile * 2, cols * 2}, {64, 1, 1, 1, 64});
}
template <class... KA, class... A>
void launch(void (*kern)(KA...), int grid, int block, int smem, int cluster, bool pdl, A... args) {
  cudaFuncSetAttribute(kern, cudaFuncAttributeMaxDynamicSharedMemorySize, smem);
  cudaLaunchConfig_t cfg = {};
  cfg.gridDim = dim3(grid); cfg.blockDim = dim3(block); cfg.dynamicSmemBytes = smem; cfg.stream = cudaStreamPerThread;
  cudaLaunchAttribute at[2];
  int n = 0;
  if (cluster > 1) { at[n].id = cudaLaunchAttributeClusterDimension; at[n].val.clusterDim.x = cluster; at[n].val.clusterDim.y = 1; at[n].val.clusterDim.z = 1; n++; }
  if (pdl) { at[n].id = cudaLaunchAttributeProgrammaticStreamSerialization; at[n].val.programmaticStreamSerializationAllowed = 1; n++; }
  cfg.attrs = at; cfg.numAttrs = n;
  cudaLaunchKernelEx(&cfg, kern, args...);
}
template <class T> void* sym(T& s) { void* p = nullptr; cudaGetSymbolAddress(&p, s); return p; }

}

#define MODE(b) 0
extern "C" void kernel_launch(void* const* d_in, const int* in_sizes, int n_in, void* d_out, int out_size) {
  const __nv_bfloat16* x = (const __nv_bfloat16*)d_in[0];
  void* fn = nullptr; cudaDriverEntryPointQueryResult qr;
  cudaGetDriverEntryPoint("cuTensorMapEncodeTiled", &fn, cudaEnableDefault, &qr);
  EncodeFn enc = (EncodeFn)fn;

  WorkParams wk = {};
  ChainParams& ch = wk.ch;
  AttnParams at = {};
  make_map(enc, &ch.wq, d_in[2], HD, DM, 128); make_map(enc, &ch.wk, d_in[3], HD, DM, 128); make_map(enc, &ch.wv, d_in[4], HD, DM, 128);
  make_map(enc, &ch.wo, d_in[5], DM, HD, 192, 32);
  ch.mem0 = (const __nv_bfloat16*)d_in[1];
  ch.wb = (const uint8_t*)d_in[8];
  ch.d1 = 300; ch.d2 = 300; ch.dn = 250; ch.dx = 900;
  make_tiles(enc, &wk.wq, d_in[2], HD, 192);
  for (int i = 0; i < 3; i++) make_tiles(enc, &wk.wb[i], d_in[8], 1920, 80 << i);
  for (int i = 0; i < 2; i++) make_tiles(enc, &wk.wc[i], d_in[9], DM, 80 << 2 * i);
  make_map(enc, &wk.out, d_out, DM, SEQ, 16, 80);
  make_map5(enc, &wk.wo, d_in[5], false, {DM, 2, 4, 4, HD / 32}, {DM * 2, DM * 16, DM * 4, DM * 64}, {64, 2, 4, 4, 2});
  make_map5(enc, &wk.xn, sym(g_xn), true, {1280, 2, 2, 64, 1}, {10240, 20480, 40960, 40960}, {128, 2, 2, 4, 1});
  make_map5(enc, &wk.xp, sym(g_xn), true, {1280, 2, 1, 64, 2}, {10240, 10240, 40960, 20480}, {128, 2, 1, 4, 2});
  wk.x = x;
  for (int i = 0; i < 4; i++) at.pf[i] = (const uint8_t*)d_in[i < 2 ? 3 + i : i == 2 ? 2 : 5];
  int qa_end[2] = {12, 12};
  for (int layer = 0; layer < 2; layer++) {
    ch.sync = wk.sync = at.sync = (uint32_t*)sym(g_sync) + layer * SY_N;
    ch.other = (uint32_t*)sym(g_sync) + (1 - layer) * SY_N;
    ch.layer = layer;
    at.next = layer ? nullptr : ch.other;
    wk.qa_end = qa_end[layer];
    wk.kind = layer ? WK_LEAD : WK_FIRST;
    launch(work_kernel, 132, 384, CH_SMEM, 1, layer != 0, wk);
    wk.kind = WK_CHAIN;
    launch(work_kernel, 96, 384, CH_SMEM, 3, true, wk);
    launch(attn_b_kernel, 128, AB_T + 128, AB_SMEM, 1, true, at);
  }
  wk.kind = WK_LAST;
  launch(work_kernel, 128, 384, CH_SMEM, 1, true, wk);
}
```

```cpp
#include <cuda_runtime.h>
#include <cuda_bf16.h>
#include <cuda.h>
#include <stdint.h>
#include <stdlib.h>

namespace {

constexpr int SEQ = 2048, DM = 640, HD = 6144, NSEG = 64;
constexpr int SPIN_LIMIT = 1 << 20;

__device__ __align__(128) uint2 g_x[256 * 17 * 1280];
__device__ __align__(128) uint32_t g_xn[SEQ * DM / 2];
__device__ __align__(128) uint32_t g_of[SEQ * DM / 2];
__device__ __align__(128) uint4 g_o[SEQ * HD / 8];
__device__ __align__(128) uint4 g_q[SEQ * HD / 8];
constexpr int KV_M = 16384, KV_PART = 20480, KV_V = 3 * KV_PART;
__device__ __align__(128) uint8_t g_kv[16 * 32 * 6 * KV_PART];
#define OP_B8 11
#define OP_B16 14
#define OP_N4 15
#define BQ_12 12
#define BQ_24 14
#define FIN_16 12
__host__ __device__ constexpr int op_split(int b) { return b < OP_B8 ? 4 : b < OP_B16 ? 8 : 16; }
__host__ __device__ constexpr int op_tiles(int b) { return b < OP_N4 ? 2 : 4; }
__host__ __device__ constexpr int fin_items(int b) { return b < OP_B8 ? 4 : b < FIN_16 ? 8 : 16; }
__host__ __device__ constexpr int bq_items(int b) { return b < BQ_12 ? 6 : b < BQ_24 ? 12 : 24; }
__host__ __device__ constexpr int ln_items(int layer, int b) { return layer == 0 && b < 2 ? 16 : 4; }
constexpr int SY_P = 128, SY_T = 192, SY_UP = 224, SY_OB = 225, SY_PRE = 256, SY_PART = 288, SY_TIME = 384, SY_N = 448;
__device__ __align__(128) uint32_t g_sync[2 * SY_N];
constexpr int NSLOT = 92;
__device__ uint32_t g_pool[(NSLOT + 2) * 2048];
__device__ uint32_t g_smpart[256], g_orient[NSLOT];
__device__ __align__(128) uint32_t g_bqkv[3 * 32 * 256 * 96];

#define BT(i)
#define MISS(k, n)
#define PRO(i)
#define TRACE(w)
#define ITEM(code, w)
#define STAT(k)
#define TMV(i, v)
#define TM(i)
#define TMD(i, dep)

__device__ __forceinline__ uint32_t gtime() { uint32_t c; asm volatile("mov.u32 %0, %%globaltimer_lo;" : "=r"(c) :: "memory"); return c; }
__device__ __forceinline__ uint32_t clk32() { uint32_t c; asm volatile("mov.u32 %0, %%clock;" : "=r"(c) :: "memory"); return c; }
__device__ __forceinline__ uint32_t fresh_tid() { uint32_t t; asm volatile("mov.u32 %0, %%tid.x;" : "=r"(t)); return t; }
__device__ __forceinline__ uint32_t s2u(const void* p) { return (uint32_t)__cvta_generic_to_shared(p); }
__device__ __forceinline__ uint32_t pack2(float a, float b) {
  uint32_t r; asm("cvt.rn.bf16x2.f32 %0, %1, %2;" : "=r"(r) : "f"(b), "f"(a)); return r; }
__device__ __forceinline__ float bf_lo(uint32_t w) { return __uint_as_float(w << 16); }
__device__ __forceinline__ float bf_hi(uint32_t w) { return __uint_as_float(w & 0xffff0000u); }
__device__ __forceinline__ float ex2(float x) { float y; asm("ex2.approx.ftz.f32 %0, %1;" : "=f"(y) : "f"(x)); return y; }

__device__ __forceinline__ void mbar_init(uint32_t bar, uint32_t n) {
  asm volatile("mbarrier.init.shared::cta.b64 [%0], %1;" :: "r"(bar), "r"(n) : "memory"); }
__device__ __forceinline__ void mbar_expect(uint32_t bar, uint32_t bytes) {
  asm volatile("mbarrier.arrive.expect_tx.shared::cta.b64 _, [%0], %1;" :: "r"(bar), "r"(bytes) : "memory"); }
__device__ __forceinline__ void mbar_arrive(uint32_t bar) {
  asm volatile("mbarrier.arrive.shared::cta.b64 _, [%0];" :: "r"(bar) : "memory"); }
__device__ __forceinline__ void mbar_arrive_remote(uint32_t bar) {
  asm volatile("mbarrier.arrive.shared::cluster.b64 _, [%0];" :: "r"(bar) : "memory"); }
__device__ __forceinline__ void mbar_wait_slow(uint32_t bar, uint32_t ph) {
  asm volatile("{.reg .pred p; .reg .u32 n; mov.u32 n, 0;\n"
               "W: mbarrier.try_wait.parity.shared::cta.b64 p, [%0], %1; @p bra D;\n"
               "add.u32 n, n, 1; setp.gt.u32 p, n, %2; @p trap; bra W;\n"
               "D: }" :: "r"(bar), "r"(ph), "n"(SPIN_LIMIT) : "memory");
}
__device__ __forceinline__ void mbar_wait(uint32_t bar, uint32_t ph) {
  uint32_t ok;
  asm volatile("{.reg .pred p; mbarrier.try_wait.parity.shared::cta.b64 p, [%1], %2; selp.u32 %0, 1, 0, p;}" : "=r"(ok) : "r"(bar), "r"(ph) : "memory");
  if (__builtin_expect(!ok, 0)) mbar_wait_slow(bar, ph);
}
__device__ __forceinline__ void mbar_wait_uniform(uint32_t bar, uint32_t ph) {
  asm volatile("{.reg .pred p; .reg .u32 n; mov.u32 n, 0;\n"
               "W: mbarrier.try_wait.parity.shared::cta.b64 p, [%0], %1; vote.sync.all.pred p, p, 0xffffffff; @p bra.uni D;\n"
               "add.u32 n, n, 1; setp.gt.u32 p, n, %2; @p trap; bra.uni W;\n"
               "D: }" :: "r"(bar), "r"(ph), "n"(SPIN_LIMIT) : "memory");
}
__device__ __forceinline__ bool elect() {
  uint32_t p; asm volatile("{.reg .pred q; elect.sync _|q, 0xffffffff; selp.u32 %0, 1, 0, q;}" : "=r"(p)); return p; }
__device__ __forceinline__ void mbar_wait_cluster(uint32_t bar, uint32_t ph) {
  asm volatile("{.reg .pred p; .reg .u32 n; mov.u32 n, 0;\n"
               "W: mbarrier.try_wait.parity.acquire.cluster.shared::cta.b64 p, [%0], %1; @p bra D;\n"
               "add.u32 n, n, 1; setp.gt.u32 p, n, %2; @p trap; bra W;\n"
               "D: }" :: "r"(bar), "r"(ph), "n"(SPIN_LIMIT) : "memory");
}
__device__ __forceinline__ void spin_guard(int& n) {
  asm volatile("{.reg .pred p; add.s32 %0, %0, 1; setp.gt.s32 p, %0, %1; @p trap;}" : "+r"(n) : "n"(SPIN_LIMIT));
}
__device__ __forceinline__ void pdl_wait() { asm volatile("griddepcontrol.wait;" ::: "memory"); TRACE(1); }
__device__ __forceinline__ void pdl_launch() { asm volatile("griddepcontrol.launch_dependents;" ::: "memory"); }
__device__ __forceinline__ uint32_t ld_acquire(const uint32_t* p) { uint32_t v; asm volatile("ld.acquire.gpu.global.u32 %0, [%1];" : "=r"(v) : "l"(p) : "memory"); return v; }
__device__ __forceinline__ void red_release(uint32_t* p, uint32_t v) { asm volatile("red.release.gpu.global.add.u32 [%0], %1;" :: "l"(p), "r"(v) : "memory"); }
__device__ __forceinline__ void fence_async_global() { asm volatile("fence.proxy.async.global;" ::: "memory"); }
__device__ __forceinline__ void fence_async() { asm volatile("fence.proxy.async.shared::cta;" ::: "memory"); }
__device__ __forceinline__ void bar_sync(int id, int n) { asm volatile("bar.sync %0, %1;" :: "r"(id), "r"(n) : "memory"); }
__device__ __forceinline__ void bar_arrive(int id, int n) { asm volatile("bar.arrive %0, %1;" :: "r"(id), "r"(n) : "memory"); }
__device__ __forceinline__ void tma_load(uint32_t dst, const CUtensorMap* m, int c0, int c1, uint32_t bar) {
  asm volatile("cp.async.bulk.tensor.2d.shared::cluster.global.mbarrier::complete_tx::bytes [%0], [%1, {%3, %4}], [%2];"
               :: "r"(dst), "l"(m), "r"(bar), "r"(c0), "r"(c1) : "memory"); }
__device__ __forceinline__ void tma_store(const CUtensorMap* m, uint32_t src, int c0, int c1) {
  asm volatile("cp.async.bulk.tensor.2d.global.shared::cta.bulk_group [%0, {%2, %3}], [%1];"
               :: "l"(m), "r"(src), "r"(c0), "r"(c1) : "memory"); }
__device__ __forceinline__ uint64_t evict_first() { uint64_t p; asm("createpolicy.fractional.L2::evict_first.b64 %0, 1.0;" : "=l"(p)); return p; }
__device__ __forceinline__ void bulk_load_last(uint32_t dst, const void* src, uint32_t bytes, uint32_t bar) {
  asm volatile("cp.async.bulk.shared::cluster.global.mbarrier::complete_tx::bytes.L2::cache_hint [%0], [%1], %2, [%3], %4;"
               :: "r"(dst), "l"(src), "r"(bytes), "r"(bar), "l"(evict_first()) : "memory"); }
__device__ __forceinline__ void bulk_store_stream(void* dst, uint32_t src, uint32_t bytes) {
  asm volatile("cp.async.bulk.global.shared::cta.bulk_group.L2::cache_hint [%0], [%1], %2, %3;" :: "l"(dst), "r"(src), "r"(bytes), "l"(evict_first()) : "memory"); }
__device__ __forceinline__ void bulk_load(uint32_t dst, const void* src, uint32_t bytes, uint32_t bar) {
  asm volatile("cp.async.bulk.shared::cluster.global.mbarrier::complete_tx::bytes [%0], [%1], %2, [%3];"
               :: "r"(dst), "l"(src), "r"(bytes), "r"(bar) : "memory"); }
__device__ __forceinline__ void bulk_push(uint32_t dst, uint32_t src, uint32_t bytes, uint32_t bar) {
  asm volatile("cp.async.bulk.shared::cluster.shared::cta.mbarrier::complete_tx::bytes [%0], [%1], %2, [%3];"
               :: "r"(dst), "r"(src), "r"(bytes), "r"(bar) : "memory"); }
__device__ __forceinline__ void bulk_store(void* dst, uint32_t src, uint32_t bytes) {
  asm volatile("cp.async.bulk.global.shared::cta.bulk_group [%0], [%1], %2;" :: "l"(dst), "r"(src), "r"(bytes) : "memory"); }
__device__ __forceinline__ void bulk_commit() { asm volatile("cp.async.bulk.commit_group;" ::: "memory"); }
template <int N> __device__ __forceinline__ void bulk_wait_read() { asm volatile("cp.async.bulk.wait_group.read %0;" :: "n"(N) : "memory"); }
template <int N> __device__ __forceinline__ void bulk_wait() { asm volatile("cp.async.bulk.wait_group %0;" :: "n"(N) : "memory"); }

__device__ __forceinline__ uint64_t mkdesc(uint32_t addr, uint32_t lbo, uint32_t sbo, uint32_t sw) {
  return (uint64_t)((addr & 0x3FFFF) >> 4) | ((uint64_t)(lbo >> 4) << 16) | ((uint64_t)(sbo >> 4) << 32) | ((uint64_t)sw << 62); }
__device__ __forceinline__ void wg_fence() { asm volatile("wgmma.fence.sync.aligned;" ::: "memory"); }
__device__ __forceinline__ void wg_commit() { asm volatile("wgmma.commit_group.sync.aligned;" ::: "memory"); }
template <int N> __device__ __forceinline__ void wg_wait() { asm volatile("wgmma.wait_group.sync.aligned %0;" :: "n"(N) : "memory"); }
template <int N> __device__ __forceinline__ void reg_fence(float* d) {
#pragma unroll
  for (int i = 0; i < N; i++) asm volatile("" : "+f"(d[i]) :: "memory");
}

__device__ __forceinline__ void mma16(float* d, uint32_t a0, uint32_t a1, uint32_t a2, uint32_t a3, uint32_t b0, uint32_t b1) {
  asm volatile("mma.sync.aligned.m16n8k16.row.col.f32.bf16.bf16.f32 {%0,%1,%2,%3},{%4,%5,%6,%7},{%8,%9},{%0,%1,%2,%3};"
               : "+f"(d[0]), "+f"(d[1]), "+f"(d[2]), "+f"(d[3]) : "r"(a0), "r"(a1), "r"(a2), "r"(a3), "r"(b0), "r"(b1)); }
__device__ __forceinline__ void mma8(float* d, uint32_t a0, uint32_t a1, uint32_t b0) {
  asm volatile("mma.sync.aligned.m16n8k8.row.col.f32.bf16.bf16.f32 {%0,%1,%2,%3},{%4,%5},{%6},{%0,%1,%2,%3};"
               : "+f"(d[0]), "+f"(d[1]), "+f"(d[2]), "+f"(d[3]) : "r"(a0), "r"(a1), "r"(b0)); }
__device__ __forceinline__ void ldsm4(uint32_t* r, uint32_t a) {
  asm volatile("ldmatrix.sync.aligned.m8n8.x4.shared.b16 {%0,%1,%2,%3},[%4];" : "=r"(r[0]), "=r"(r[1]), "=r"(r[2]), "=r"(r[3]) : "r"(a) : "memory"); }
__device__ __forceinline__ uint4 ldsm4v(uint32_t a) { uint32_t r[4]; ldsm4(r, a); return make_uint4(r[0], r[1], r[2], r[3]); }
__device__ __forceinline__ void ldsm4t(uint32_t* r, uint32_t a) {
  asm volatile("ldmatrix.sync.aligned.m8n8.x4.trans.shared.b16 {%0,%1,%2,%3},[%4];" : "=r"(r[0]), "=r"(r[1]), "=r"(r[2]), "=r"(r[3]) : "r"(a) : "memory"); }
__device__ __forceinline__ void ldsm2t(uint32_t* r, uint32_t a) {
  asm volatile("ldmatrix.sync.aligned.m8n8.x2.trans.shared.b16 {%0,%1},[%2];" : "=r"(r[0]), "=r"(r[1]) : "r"(a) : "memory"); }
__device__ __forceinline__ void stsm4(uint32_t a, uint32_t r0, uint32_t r1, uint32_t r2, uint32_t r3) {
  asm volatile("stmatrix.sync.aligned.m8n8.x4.shared.b16 [%0], {%1,%2,%3,%4};" :: "r"(a), "r"(r0), "r"(r1), "r"(r2), "r"(r3) : "memory"); }
__device__ __forceinline__ void stsm4t(uint32_t a, uint32_t r0, uint32_t r1, uint32_t r2, uint32_t r3) {
  asm volatile("stmatrix.sync.aligned.m8n8.x4.trans.shared.b16 [%0], {%1,%2,%3,%4};" :: "r"(a), "r"(r0), "r"(r1), "r"(r2), "r"(r3) : "memory"); }
__device__ __forceinline__ void stsm2(uint32_t a, uint32_t r0, uint32_t r1) {
  asm volatile("stmatrix.sync.aligned.m8n8.x2.shared.b16 [%0], {%1,%2};" :: "r"(a), "r"(r0), "r"(r1) : "memory"); }
__device__ __forceinline__ void stsm2t(uint32_t a, uint32_t r0, uint32_t r1) {
  asm volatile("stmatrix.sync.aligned.m8n8.x2.trans.shared.b16 [%0], {%1,%2};" :: "r"(a), "r"(r0), "r"(r1) : "memory"); }
__device__ __forceinline__ void sts32(uint32_t a, uint32_t v) { asm volatile("st.shared.b32 [%0], %1;" :: "r"(a), "r"(v) : "memory"); }
__device__ __forceinline__ void sts64f(uint32_t a, float x, float y) { asm volatile("st.shared.v2.f32 [%0], {%1,%2};" :: "r"(a), "f"(x), "f"(y) : "memory"); }
__device__ __forceinline__ void sts128(uint32_t a, uint4 v) {
  asm volatile("st.shared.v4.b32 [%0], {%1,%2,%3,%4};" :: "r"(a), "r"(v.x), "r"(v.y), "r"(v.z), "r"(v.w) : "memory"); }
__device__ __forceinline__ void sts128f(uint32_t a, float x, float y, float z, float w) {
  asm volatile("st.shared.v4.f32 [%0], {%1,%2,%3,%4};" :: "r"(a), "f"(x), "f"(y), "f"(z), "f"(w) : "memory"); }
__device__ __forceinline__ float lds32f(uint32_t a) { float v; asm volatile("ld.shared.f32 %0, [%1];" : "=f"(v) : "r"(a) : "memory"); return v; }
__device__ __forceinline__ float2 lds64f(uint32_t a) { float2 v; asm volatile("ld.shared.v2.f32 {%0,%1}, [%2];" : "=f"(v.x), "=f"(v.y) : "r"(a) : "memory"); return v; }
__device__ __forceinline__ float4 lds128f(uint32_t a) {
  float4 v; asm volatile("ld.shared.v4.f32 {%0,%1,%2,%3}, [%4];" : "=f"(v.x), "=f"(v.y), "=f"(v.z), "=f"(v.w) : "r"(a) : "memory"); return v; }
__device__ __forceinline__ uint4 lds128(uint32_t a) {
  uint4 v; asm volatile("ld.shared.v4.b32 {%0,%1,%2,%3}, [%4];" : "=r"(v.x), "=r"(v.y), "=r"(v.z), "=r"(v.w) : "r"(a) : "memory"); return v; }
__device__ __forceinline__ uint4 ldg_strong128(const void* p) {
  uint4 v; asm volatile("ld.relaxed.gpu.global.v4.u32 {%0,%1,%2,%3}, [%4];" : "=r"(v.x), "=r"(v.y), "=r"(v.z), "=r"(v.w) : "l"(p) : "memory"); return v; }
__device__ __forceinline__ uint2 ldg_strong64(const void* p) {
  uint2 v; asm volatile("ld.relaxed.gpu.global.v2.u32 {%0,%1}, [%2];" : "=r"(v.x), "=r"(v.y) : "l"(p) : "memory"); return v; }
__device__ __forceinline__ void stg_strong32(void* p, uint32_t v) { asm volatile("st.relaxed.gpu.global.u32 [%0], %1;" :: "l"(p), "r"(v) : "memory"); }
__device__ __forceinline__ void stg_strong128(void* p, uint4 v) {
  asm volatile("st.relaxed.gpu.global.v4.u32 [%0], {%1,%2,%3,%4};" :: "l"(p), "r"(v.x), "r"(v.y), "r"(v.z), "r"(v.w) : "memory"); }
__device__ __forceinline__ uint32_t mapa(uint32_t a, uint32_t r) {
  uint32_t o; asm("mapa.shared::cluster.u32 %0, %1, %2;" : "=r"(o) : "r"(a), "r"(r)); return o; }
__device__ __forceinline__ void st_async2f(uint32_t a, float x, float y, uint32_t bar) {
  asm volatile("st.async.shared::cluster.mbarrier::complete_tx::bytes.v2.f32 [%0], {%1,%2}, [%3];" :: "r"(a), "f"(x), "f"(y), "r"(bar) : "memory"); }
__device__ __forceinline__ void st_async32(uint32_t a, uint32_t x, uint32_t bar) {
  asm volatile("st.async.shared::cluster.mbarrier::complete_tx::bytes.b32 [%0], %1, [%2];" :: "r"(a), "r"(x), "r"(bar) : "memory"); }
__device__ __forceinline__ uint32_t lds32(uint32_t a) { uint32_t v; asm volatile("ld.shared.b32 %0, [%1];" : "=r"(v) : "r"(a) : "memory"); return v; }
__device__ __forceinline__ void st_async64(uint32_t a, uint32_t x, uint32_t y, uint32_t bar) {
  asm volatile("st.async.shared::cluster.mbarrier::complete_tx::bytes.v2.b32 [%0], {%1,%2}, [%3];" :: "r"(a), "r"(x), "r"(y), "r"(bar) : "memory"); }
__device__ __forceinline__ void st_async128(uint32_t a, uint4 v, uint32_t bar) {
  asm volatile("st.async.shared::cluster.mbarrier::complete_tx::bytes.v4.b32 [%0], {%1,%2,%3,%4}, [%5];" :: "r"(a), "r"(v.x), "r"(v.y), "r"(v.z), "r"(v.w), "r"(bar) : "memory"); }
__device__ __forceinline__ uint2 lds64(uint32_t a) { uint2 v; asm volatile("ld.shared.v2.b32 {%0,%1}, [%2];" : "=r"(v.x), "=r"(v.y) : "r"(a) : "memory"); return v; }
__device__ __forceinline__ void sts64(uint32_t a, uint32_t x, uint32_t y) { asm volatile("st.shared.v2.b32 [%0], {%1,%2};" :: "r"(a), "r"(x), "r"(y) : "memory"); }
__device__ __forceinline__ uint32_t ldg_strong32(const void* p) { uint32_t v; asm volatile("ld.relaxed.gpu.global.u32 %0, [%1];" : "=r"(v) : "l"(p) : "memory"); return v; }
__device__ __forceinline__ uint32_t transpose8(uint32_t x) { uint32_t r; asm volatile("movmatrix.sync.aligned.m8n8.trans.b16 %0, %1;" : "=r"(r) : "r"(x)); return r; }
__device__ __forceinline__ uint32_t hadd2(uint32_t a, uint32_t b) { uint32_t r; asm("add.rn.bf16x2 %0, %1, %2;" : "=r"(r) : "r"(a), "r"(b)); return r; }
__device__ __forceinline__ uint32_t min4(uint4 v) { return min(__vimin3_u32(v.x, v.y, v.z), v.w); }

__device__ __forceinline__ void wg_ss192_01(float* d, uint64_t da, uint64_t db, int sd) {
  asm volatile("{.reg .pred p; setp.ne.b32 p, %98, 0;\n"
    "wgmma.mma_async.sync.aligned.m64n192k16.f32.bf16.bf16 {%0,%1,%2,%3,%4,%5,%6,%7,%8,%9,%10,%11,%12,%13,%14,%15,%16,%17,%18,%19,%20,%21,%22,%23,%24,%25,%26,%27,%28,%29,%30,%31,%32,%33,%34,%35,%36,%37,%38,%39,%40,%41,%42,%43,%44,%45,%46,%47,%48,%49,%50,%51,%52,%53,%54,%55,%56,%57,%58,%59,%60,%61,%62,%63,%64,%65,%66,%67,%68,%69,%70,%71,%72,%73,%74,%75,%76,%77,%78,%79,%80,%81,%82,%83,%84,%85,%86,%87,%88,%89,%90,%91,%92,%93,%94,%95}, %96, %97, p, 1, 1, 0, 1;}"
    : "+f"(d[0]),"+f"(d[1]),"+f"(d[2]),"+f"(d[3]),"+f"(d[4]),"+f"(d[5]),"+f"(d[6]),"+f"(d[7]),"+f"(d[8]),"+f"(d[9]),"+f"(d[10]),"+f"(d[11]),"+f"(d[12]),"+f"(d[13]),"+f"(d[14]),"+f"(d[15]),"+f"(d[16]),"+f"(d[17]),"+f"(d[18]),"+f"(d[19]),"+f"(d[20]),"+f"(d[21]),"+f"(d[22]),"+f"(d[23]),"+f"(d[24]),"+f"(d[25]),"+f"(d[26]),"+f"(d[27]),"+f"(d[28]),"+f"(d[29]),"+f"(d[30]),"+f"(d[31]),"+f"(d[32]),"+f"(d[33]),"+f"(d[34]),"+f"(d[35]),"+f"(d[36]),"+f"(d[37]),"+f"(d[38]),"+f"(d[39]),"+f"(d[40]),"+f"(d[41]),"+f"(d[42]),"+f"(d[43]),"+f"(d[44]),"+f"(d[45]),"+f"(d[46]),"+f"(d[47]),"+f"(d[48]),"+f"(d[49]),"+f"(d[50]),"+f"(d[51]),"+f"(d[52]),"+f"(d[53]),"+f"(d[54]),"+f"(d[55]),"+f"(d[56]),"+f"(d[57]),"+f"(d[58]),"+f"(d[59]),"+f"(d[60]),"+f"(d[61]),"+f"(d[62]),"+f"(d[63]),"+f"(d[64]),"+f"(d[65]),"+f"(d[66]),"+f"(d[67]),"+f"(d[68]),"+f"(d[69]),"+f"(d[70]),"+f"(d[71]),"+f"(d[72]),"+f"(d[73]),"+f"(d[74]),"+f"(d[75]),"+f"(d[76]),"+f"(d[77]),"+f"(d[78]),"+f"(d[79]),"+f"(d[80]),"+f"(d[81]),"+f"(d[82]),"+f"(d[83]),"+f"(d[84]),"+f"(d[85]),"+f"(d[86]),"+f"(d[87]),"+f"(d[88]),"+f"(d[89]),"+f"(d[90]),"+f"(d[91]),"+f"(d[92]),"+f"(d[93]),"+f"(d[94]),"+f"(d[95])
    : "l"(da), "l"(db), "r"(sd));
}
__device__ __forceinline__ void wg_ss128_01(float* d, uint64_t da, uint64_t db, int sd) {
  asm volatile("{.reg .pred p; setp.ne.b32 p, %66, 0;\n"
    "wgmma.mma_async.sync.aligned.m64n128k16.f32.bf16.bf16 {%0,%1,%2,%3,%4,%5,%6,%7,%8,%9,%10,%11,%12,%13,%14,%15,%16,%17,%18,%19,%20,%21,%22,%23,%24,%25,%26,%27,%28,%29,%30,%31,%32,%33,%34,%35,%36,%37,%38,%39,%40,%41,%42,%43,%44,%45,%46,%47,%48,%49,%50,%51,%52,%53,%54,%55,%56,%57,%58,%59,%60,%61,%62,%63}, %64, %65, p, 1, 1, 0, 1;}"
    : "+f"(d[0]),"+f"(d[1]),"+f"(d[2]),"+f"(d[3]),"+f"(d[4]),"+f"(d[5]),"+f"(d[6]),"+f"(d[7]),"+f"(d[8]),"+f"(d[9]),"+f"(d[10]),"+f"(d[11]),"+f"(d[12]),"+f"(d[13]),"+f"(d[14]),"+f"(d[15]),"+f"(d[16]),"+f"(d[17]),"+f"(d[18]),"+f"(d[19]),"+f"(d[20]),"+f"(d[21]),"+f"(d[22]),"+f"(d[23]),"+f"(d[24]),"+f"(d[25]),"+f"(d[26]),"+f"(d[27]),"+f"(d[28]),"+f"(d[29]),"+f"(d[30]),"+f"(d[31]),"+f"(d[32]),"+f"(d[33]),"+f"(d[34]),"+f"(d[35]),"+f"(d[36]),"+f"(d[37]),"+f"(d[38]),"+f"(d[39]),"+f"(d[40]),"+f"(d[41]),"+f"(d[42]),"+f"(d[43]),"+f"(d[44]),"+f"(d[45]),"+f"(d[46]),"+f"(d[47]),"+f"(d[48]),"+f"(d[49]),"+f"(d[50]),"+f"(d[51]),"+f"(d[52]),"+f"(d[53]),"+f"(d[54]),"+f"(d[55]),"+f"(d[56]),"+f"(d[57]),"+f"(d[58]),"+f"(d[59]),"+f"(d[60]),"+f"(d[61]),"+f"(d[62]),"+f"(d[63])
    : "l"(da), "l"(db), "r"(sd));
}
__device__ __forceinline__ void wg_ss160_01(float* d, uint64_t da, uint64_t db, int sd) {
  asm volatile("{.reg .pred p; setp.ne.b32 p, %82, 0;\n"
    "wgmma.mma_async.sync.aligned.m64n160k16.f32.bf16.bf16 {%0,%1,%2,%3,%4,%5,%6,%7,%8,%9,%10,%11,%12,%13,%14,%15,%16,%17,%18,%19,%20,%21,%22,%23,%24,%25,%26,%27,%28,%29,%30,%31,%32,%33,%34,%35,%36,%37,%38,%39,%40,%41,%42,%43,%44,%45,%46,%47,%48,%49,%50,%51,%52,%53,%54,%55,%56,%57,%58,%59,%60,%61,%62,%63,%64,%65,%66,%67,%68,%69,%70,%71,%72,%73,%74,%75,%76,%77,%78,%79}, %80, %81, p, 1, 1, 0, 1;}"
    : "+f"(d[0]),"+f"(d[1]),"+f"(d[2]),"+f"(d[3]),"+f"(d[4]),"+f"(d[5]),"+f"(d[6]),"+f"(d[7]),"+f"(d[8]),"+f"(d[9]),"+f"(d[10]),"+f"(d[11]),"+f"(d[12]),"+f"(d[13]),"+f"(d[14]),"+f"(d[15]),"+f"(d[16]),"+f"(d[17]),"+f"(d[18]),"+f"(d[19]),"+f"(d[20]),"+f"(d[21]),"+f"(d[22]),"+f"(d[23]),"+f"(d[24]),"+f"(d[25]),"+f"(d[26]),"+f"(d[27]),"+f"(d[28]),"+f"(d[29]),"+f"(d[30]),"+f"(d[31]),"+f"(d[32]),"+f"(d[33]),"+f"(d[34]),"+f"(d[35]),"+f"(d[36]),"+f"(d[37]),"+f"(d[38]),"+f"(d[39]),"+f"(d[40]),"+f"(d[41]),"+f"(d[42]),"+f"(d[43]),"+f"(d[44]),"+f"(d[45]),"+f"(d[46]),"+f"(d[47]),"+f"(d[48]),"+f"(d[49]),"+f"(d[50]),"+f"(d[51]),"+f"(d[52]),"+f"(d[53]),"+f"(d[54]),"+f"(d[55]),"+f"(d[56]),"+f"(d[57]),"+f"(d[58]),"+f"(d[59]),"+f"(d[60]),"+f"(d[61]),"+f"(d[62]),"+f"(d[63]),"+f"(d[64]),"+f"(d[65]),"+f"(d[66]),"+f"(d[67]),"+f"(d[68]),"+f"(d[69]),"+f"(d[70]),"+f"(d[71]),"+f"(d[72]),"+f"(d[73]),"+f"(d[74]),"+f"(d[75]),"+f"(d[76]),"+f"(d[77]),"+f"(d[78]),"+f"(d[79])
    : "l"(da), "l"(db), "r"(sd));
}
__device__ __forceinline__ void wg_ss80_01(float* d, uint64_t da, uint64_t db, int sd) {
  asm volatile("{.reg .pred p; setp.ne.b32 p, %42, 0;\n"
    "wgmma.mma_async.sync.aligned.m64n80k16.f32.bf16.bf16 {%0,%1,%2,%3,%4,%5,%6,%7,%8,%9,%10,%11,%12,%13,%14,%15,%16,%17,%18,%19,%20,%21,%22,%23,%24,%25,%26,%27,%28,%29,%30,%31,%32,%33,%34,%35,%36,%37,%38,%39}, %40, %41, p, 1, 1, 0, 1;}"
    : "+f"(d[0]),"+f"(d[1]),"+f"(d[2]),"+f"(d[3]),"+f"(d[4]),"+f"(d[5]),"+f"(d[6]),"+f"(d[7]),"+f"(d[8]),"+f"(d[9]),"+f"(d[10]),"+f"(d[11]),"+f"(d[12]),"+f"(d[13]),"+f"(d[14]),"+f"(d[15]),"+f"(d[16]),"+f"(d[17]),"+f"(d[18]),"+f"(d[19]),"+f"(d[20]),"+f"(d[21]),"+f"(d[22]),"+f"(d[23]),"+f"(d[24]),"+f"(d[25]),"+f"(d[26]),"+f"(d[27]),"+f"(d[28]),"+f"(d[29]),"+f"(d[30]),"+f"(d[31]),"+f"(d[32]),"+f"(d[33]),"+f"(d[34]),"+f"(d[35]),"+f"(d[36]),"+f"(d[37]),"+f"(d[38]),"+f"(d[39])
    : "l"(da), "l"(db), "r"(sd));
}
__device__ __forceinline__ void wg_rs32_00(float* d, uint32_t a0, uint32_t a1, uint32_t a2, uint32_t a3, uint64_t db, int sd) {
  asm volatile("{.reg .pred p; setp.ne.b32 p, %21, 0;\n"
    "wgmma.mma_async.sync.aligned.m64n32k16.f32.bf16.bf16 {%0,%1,%2,%3,%4,%5,%6,%7,%8,%9,%10,%11,%12,%13,%14,%15}, {%16,%17,%18,%19}, %20, p, 1, 1, 0;}"
    : "+f"(d[0]),"+f"(d[1]),"+f"(d[2]),"+f"(d[3]),"+f"(d[4]),"+f"(d[5]),"+f"(d[6]),"+f"(d[7]),"+f"(d[8]),"+f"(d[9]),"+f"(d[10]),"+f"(d[11]),"+f"(d[12]),"+f"(d[13]),"+f"(d[14]),"+f"(d[15])
    : "r"(a0), "r"(a1), "r"(a2), "r"(a3), "l"(db), "r"(sd));
}
__device__ __forceinline__ void wg_rs64_00(float* d, uint32_t a0, uint32_t a1, uint32_t a2, uint32_t a3, uint64_t db, int sd) {
  asm volatile("{.reg .pred p; setp.ne.b32 p, %37, 0;\n"
    "wgmma.mma_async.sync.aligned.m64n64k16.f32.bf16.bf16 {%0,%1,%2,%3,%4,%5,%6,%7,%8,%9,%10,%11,%12,%13,%14,%15,%16,%17,%18,%19,%20,%21,%22,%23,%24,%25,%26,%27,%28,%29,%30,%31}, {%32,%33,%34,%35}, %36, p, 1, 1, 0;}"
    : "+f"(d[0]),"+f"(d[1]),"+f"(d[2]),"+f"(d[3]),"+f"(d[4]),"+f"(d[5]),"+f"(d[6]),"+f"(d[7]),"+f"(d[8]),"+f"(d[9]),"+f"(d[10]),"+f"(d[11]),"+f"(d[12]),"+f"(d[13]),"+f"(d[14]),"+f"(d[15]),"+f"(d[16]),"+f"(d[17]),"+f"(d[18]),"+f"(d[19]),"+f"(d[20]),"+f"(d[21]),"+f"(d[22]),"+f"(d[23]),"+f"(d[24]),"+f"(d[25]),"+f"(d[26]),"+f"(d[27]),"+f"(d[28]),"+f"(d[29]),"+f"(d[30]),"+f"(d[31])
    : "r"(a0), "r"(a1), "r"(a2), "r"(a3), "l"(db), "r"(sd));
}
__device__ __forceinline__ void wg_rs24_01(float* d, uint32_t a0, uint32_t a1, uint32_t a2, uint32_t a3, uint64_t db, int sd) {
  asm volatile("{.reg .pred p; setp.ne.b32 p, %17, 0;\n"
    "wgmma.mma_async.sync.aligned.m64n24k16.f32.bf16.bf16 {%0,%1,%2,%3,%4,%5,%6,%7,%8,%9,%10,%11}, {%12,%13,%14,%15}, %16, p, 1, 1, 1;}"
    : "+f"(d[0]),"+f"(d[1]),"+f"(d[2]),"+f"(d[3]),"+f"(d[4]),"+f"(d[5]),"+f"(d[6]),"+f"(d[7]),"+f"(d[8]),"+f"(d[9]),"+f"(d[10]),"+f"(d[11])
    : "r"(a0), "r"(a1), "r"(a2), "r"(a3), "l"(db), "r"(sd));
}

#define AB_POLY 0x77
__device__ __forceinline__ constexpr bool poly_group(int group) { return (AB_POLY >> (group & 7)) & 1; }

template <int V> struct Int { static constexpr int value = V; };

__device__ __forceinline__ int core_word(int row, int col) {
  return ((((row >> 7) * 10 + (col >> 6)) * 16 + ((row >> 3) & 15)) * 8 + ((col >> 3) & 7)) * 32 + (row & 7) * 4 + ((col & 7) >> 1);
}
__device__ __forceinline__ void wait_count(const uint32_t* c, uint32_t n) {
  int spin = 0;
  while ((ld_acquire(c) & 0xffff) < n) { __nanosleep(32); spin_guard(spin); }
}
__device__ __forceinline__ void wait_count_uniform(const uint32_t* c, uint32_t n) {
  for (int spin = 0; !__all_sync(~0u, (ld_acquire(c) & 0xffff) >= n);) { __nanosleep(32); spin_guard(spin); }
  fence_async_global();
}
__device__ __forceinline__ void prefetch_l2(const void* p, uint32_t bytes) {
  asm volatile("cp.async.bulk.prefetch.L2.global [%0], %1;" :: "l"(p), "r"(bytes) : "memory"); }

#define PLACE 4
__device__ __forceinline__ bool helper_sm() {
  uint32_t m; asm volatile("mov.u32 %0, %%smid;" : "=r"(m));
  return m < 2 || m >= 120 || (m >= 92 && m < 102) || (m >= 106 && m < 117) || m == 118;
}

__device__ __forceinline__ uint8_t* pool_at(uint32_t off) {
  return reinterpret_cast<uint8_t*>((reinterpret_cast<uintptr_t>(g_pool) + 8191) & ~(uintptr_t)8191) + off; }
__device__ __forceinline__ uint32_t page_latency(uint32_t* w) {
  uint32_t best = ~0u;
  stg_strong32(w, 0u);
#pragma unroll 1
  for (int r = 0; r < 4; r++) {
    uint32_t t0, t1, v;
    asm volatile("mov.u32 %0, %%clock;" : "=r"(t0) :: "memory");
    asm volatile("atom.relaxed.gpu.global.exch.b32 %0, [%1], 0;" : "=r"(v) : "l"(w) : "memory");
    asm volatile("{.reg .u32 t; add.u32 t, %1, 1; mov.u32 %0, %%clock; sub.u32 %0, %0, %1;}" : "=r"(t1) : "r"(__shfl_sync(1u, v, 0)) : "memory");
    best = min(best, t1 - t0);
  }
  return best;
}
__device__ __forceinline__ void probe_slots(uint32_t scratch) {
  const int w = (threadIdx.x >> 6) & 1, slot = w == 0 ? NSLOT : blockIdx.x;
  if ((threadIdx.x & 31) == 0 && (w == 0 || slot < NSLOT)) {
    uint32_t* q = reinterpret_cast<uint32_t*>(pool_at(slot * 8192)) + (w == 0 ? (blockIdx.x & 31) * 32 + (blockIdx.x >> 5) : 0);
    sts32(scratch + w * 4, page_latency(q) < page_latency(q + 1024));
  }
  bar_sync(2, 64);
  if ((threadIdx.x & 31) == 0) {
    const int part = lds32(scratch) ? 1 : 2;
    if (w == 0) { uint32_t smid; asm("mov.u32 %0, %%smid;" : "=r"(smid)); stg_strong32(g_smpart + (smid & 255), part); }
    else if (slot < NSLOT) stg_strong32(g_orient + slot, lds32(scratch + 4) ? part : 3 - part);
  }
  __syncwarp();
}

constexpr int WK_SLOTS = 28, WK_BAR = WK_SLOTS * 8192;
__device__ __forceinline__ void work_init(uint32_t sb) {
  const int i = fresh_tid() & 31;
  mbar_init(sb + WK_BAR + 8 * i, i < 8 ? 2 : i < 16 ? 8 : i < 20 ? 1 : i < 24 ? 3 : i < 28 ? 8 : 1);
  asm volatile("fence.mbarrier_init.release.cluster;" ::: "memory");
}

struct ChainParams {
  CUtensorMap wq, wk, wv, wo;
  const __nv_bfloat16* mem0;
  const uint8_t* wb;
  uint32_t *sync, *other;
  int layer;
  int d1, d2, dn, dx, mode, zero;
};
constexpr int CH_WQ = 0, CH_WO = 81920, CH_X = CH_WO + 86016, CH_M = CH_X, CH_Q = CH_X + 34816, CH_KM = CH_Q + 2048, CH_VP = CH_KM + 2048,
              CH_K = CH_X + 40960, CH_O = CH_K, CH_KS = CH_K + 3072, CH_V = CH_K + 4096, CH_VX = CH_V + 12288, CH_R2 = CH_VX,
              CH_SX = CH_VX + 3072, CH_SO = CH_SX + 2048, CH_ID = CH_SO + 1024, CH_L = CH_ID + 256, CH_TAB = CH_L + 64, CH_BAR = CH_TAB + 384;
constexpr int CH_SMEM = CH_BAR + 144;
constexpr int MB_WO = CH_BAR, MB_WQ = CH_BAR + 8, MB_X = CH_BAR + 16, MB_V = CH_BAR + 24, MB_T = CH_BAR + 32, MB_F = CH_BAR + 40, MB_G = CH_BAR + 48, MB_W = CH_BAR + 56;
enum { NB_PROJ = 1, NB_O = 2, NB_W1 = 3, NB_PRE = 4, NB_ST = 5, NB_MEM = 6, NB_XFREE = 7, NB_H1 = 8, NB_PUB = 9, NB_W2 = 10, NB_PROJ2 = 11, NB_PRE2 = 12, NB_H2 = 13, NB_W1V = 14 };
#define CH_NQ 9
#define CH_XPF 1
#define CH_TPF 1
#define CH_NQ0 4
#define CH_PA 6
#define CH_PB 10
#define CH_PC 12
#define CH_PL 3
#define CH_DBL 0x2108
#define CH_PD 2
#define SCHED() asm volatile("griddepcontrol.launch_dependents;" ::: "memory")
__device__ __forceinline__ uint32_t opaque(uint32_t x) { return __shfl_sync(~0u, x, threadIdx.x & 31); }
__device__ __forceinline__ uint32_t uniform(uint32_t x) { return __shfl_sync(~0u, x, 0); }
__device__ __forceinline__ uint32_t nz(uint32_t x) { uint32_t r; asm("max.u32 %0, %1, 1;" : "=r"(r) : "r"(x)); return r; }
__device__ __forceinline__ uint32_t set_tag(uint32_t w, uint32_t tag) { uint32_t r; asm("lop3.b32 %0, %1, %2, 1, 0xD8;" : "=r"(r) : "r"(w), "r"(tag)); return r; }
__device__ __forceinline__ uint32_t pack_tag(float lo, float hi, uint32_t tag) { return set_tag(__byte_perm(__float_as_uint(lo) + tag, pack2(hi, hi), 0x7632), tag); }
__device__ __forceinline__ uint32_t differ(uint32_t a, uint32_t b, uint32_t t) { uint32_t r; asm("lop3.b32 %0, %1, %2, %3, 0x7E;" : "=r"(r) : "r"(a), "r"(b), "r"(t)); return r; }
__device__ __forceinline__ uint32_t clk64() { uint64_t c; asm volatile("mov.u64 %0, %%clock64;" : "=l"(c) :: "memory"); return (uint32_t)c; }
__device__ __forceinline__ void until(uint32_t t) { while ((int)(clk64() - t) < 0) {} }
__device__ __forceinline__ float rcp(float x) { float y; asm("rcp.approx.ftz.f32 %0, %1;" : "=f"(y) : "f"(x)); return y; }

__device__ __forceinline__ void chain_compute(const ChainParams& p, const uint32_t sb) {
  const int tid = threadIdx.x & 127, WG = __shfl_sync(~0u, threadIdx.x >> 7, 0), t4 = __shfl_sync(~0u, tid >> 5, 0), lane = tid & 31;
  const int cta = blockIdx.x, h = cta / 3, j = cta - 3 * h;
  uint32_t a0[80], a1[80], tw[4 * CH_NQ];
  const uint32_t wq = opaque(sb + CH_WQ + (WG * 320 + (lane & 7) + (lane >> 4) * 8) * 128 + (((2 * t4 + ((lane >> 3) & 1)) ^ (lane & 7)) << 4));
#pragma unroll
  for (int k = 0; k < 40; k++) {
    if (k % 10 == 0) mbar_wait_uniform(sb + MB_W + WG * 16 + k / 20 * 32 + k / 10 % 2 * 8, 0);
    if (k < 20) ldsm4t(&a0[4 * k], wq + k * 2048); else ldsm4t(&a1[4 * k - 80], wq + CH_WO + (k - 20) * 2048);
    if (k % 20 == 19) bar_arrive(k < 20 ? NB_PROJ2 : NB_PRE2, 384);
  }
  const int r1 = j == 2 ? 0 : j + 1, r2 = j == 0 ? 2 : j - 1;
  const uint32_t l16 = opaque(sb + lane * 16), l8 = opaque(sb + lane * 8), l4 = opaque(sb + lane * 4);
  const uint32_t t16 = l16 + t4 * 512, t8 = l8 + t4 * 256;
  uint32_t wo = opaque(sb + CH_WO + (WG == 0 ? (t4 >> 1) * 36864 : 73728 + t4 * 1024) + ((lane & 7) + (lane >> 4) * 8) * 64 +
                       (((((lane >> 3) & 1) + (WG == 0 ? (t4 & 1) * 2 : 0)) ^ ((lane >> 1) & 3)) << 4));
  const uint32_t ko0 = uniform((tid >> 6) * 3072 + (tid & 32) * 8), ko1 = uniform((tid >> 6) * 1024 + 1024 + (tid & 32) * 8), o768 = uniform((tid >> 5) * 768);
  const uint32_t give = uniform(t4 * 512 + (WG == 0 ? CH_K : CH_V + j * 4096)), own = uniform(t4 * 512 + (WG == 0 ? CH_V + j * 4096 : CH_K)), mem = uniform(CH_M + WG * 5120);
  const uint32_t vxo = uniform(t4 * 256 + CH_VX + j * 1024);
  uint32_t tag = 1, xd = uniform((1024 + CH_X + WG * 20480) >> 4 | 8 << 16);
  asm volatile("barrier.cluster.wait.aligned;" ::: "memory");
  mbar_wait_uniform(sb + MB_WQ, 0);
  bar_sync(NB_ST, 384);
  uint8_t* pdst[6];
#pragma unroll
  for (int i = 0; i < 6; i++) {
    const int line = WG == 0 ? 24 * j + 12 * (t4 >> 1) + 2 * (t4 & 1) + 4 * (i >> 1) + (i & 1) : j == 0 ? 72 + t4 : 74 + 2 * j + (t4 & 1);
    pdst[i] = pool_at(uniform(lds32(sb + CH_TAB + line * 4)) + h * 128);
  }
  auto batch = [&](float* d, const uint32_t (&a)[80], int acc, int n0, int n1) {
    const uint32_t d0 = xd ^ (tag & (2 << acc));
    wg_fence();
#pragma unroll
    for (int k = 0; k < 20; k++) {
      if (!(k & 3) && n0 + k / 4 < n1) {
        __syncwarp();
        ldsm4t(&tw[4 * n0 + k], wq + (n0 + k / 4) * 2048);
        __syncwarp();
      }
      uint64_t db;
      asm("mov.b64 %0, {%1, %2};" : "=l"(db) : "r"(d0 + k * 16), "r"(320));
      wg_rs32_00(d, a[4 * k], a[4 * k + 1], a[4 * k + 2], a[4 * k + 3], db, acc | k);
    }
    wg_commit();
    wg_wait<0>();
    reg_fence<16>(d);
  };
  int s = 0;
#pragma unroll 1
  do {
    {
      float d[16];
      mbar_wait(sb + MB_T, s & 1);
      batch(d, a0, 0, 0, CH_NQ0);
      s--; TM(10); s++;
      mbar_wait(sb + MB_F, ~s & 1);
#pragma unroll
      for (int i = 0; i < 2; i++)
        sts128(l16 + give + i * 2048, make_uint4(pack2(d[8 * i], d[8 * i + 1]), pack2(d[8 * i + 2], d[8 * i + 3]), pack2(d[8 * i + 4], d[8 * i + 5]), pack2(d[8 * i + 6], d[8 * i + 7])));
      bar_sync(NB_PUB, 384);
#pragma unroll
      for (int i = 0; i < 2; i++) {
        const uint4 t = lds128(l16 + own + i * 2048);
        d[8 * i] = bf_lo(t.x); d[8 * i + 1] = bf_hi(t.x); d[8 * i + 2] = bf_lo(t.y); d[8 * i + 3] = bf_hi(t.y);
        d[8 * i + 4] = bf_lo(t.z); d[8 * i + 5] = bf_hi(t.z); d[8 * i + 6] = bf_lo(t.w); d[8 * i + 7] = bf_hi(t.w);
      }
      reg_fence<16>(d);
      batch(d, a1, 1, CH_NQ0, CH_NQ);
      s--; TM(11); s++;
      if (WG == 0) bar_arrive(NB_XFREE, 256);
#pragma unroll
      for (int i = 0; i < 2; i++)
        stsm4(l16 + own + i * 2048, pack2(d[8 * i], d[8 * i + 1]), pack2(d[8 * i + 2], d[8 * i + 3]), pack2(d[8 * i + 4], d[8 * i + 5]), pack2(d[8 * i + 6], d[8 * i + 7]));
      s--; TM(9); s++;
    }
    float dq[4] = {}, d0[4] = {}, d1[4] = {};
    uint32_t b[40], wf[80];
#pragma unroll
    for (int i = 0; i < 4 * CH_NQ; i++) wf[i] = tw[i];
    auto step = [&](int k) {
      mma16(dq, wf[4 * k], wf[4 * k + 1], wf[4 * k + 2], wf[4 * k + 3], b[2 * k], b[2 * k + 1]);
      mma16(d0, a0[4 * k], a0[4 * k + 1], a0[4 * k + 2], a0[4 * k + 3], b[2 * k], b[2 * k + 1]);
      mma16(d1, a1[4 * k], a1[4 * k + 1], a1[4 * k + 2], a1[4 * k + 3], b[2 * k], b[2 * k + 1]);
    };
    auto finish = [&](int wg, const float* dk) {
#pragma unroll
      for (int k = 18; k < 20; k++) step(k);
      const float k2 = 0.07216878364870322f * 1.44269504089f;
      sts32(l4 + t4 * 512 + CH_Q + wg * 128, pack2(dq[0] * k2, dq[1] * k2));
      sts32(l4 + t4 * 512 + CH_Q + wg * 128 + 256, pack2(dq[2] * k2, dq[3] * k2));
      stsm2t(t16 + CH_KM + wg * 256, pack2(dk[0], dk[1]), pack2(dk[2], dk[3]));
    };
    bar_sync(NB_MEM, 384);
    ldsm4t(&b[0], l16 + mem);
    ldsm4t(&b[4], l16 + mem + 512);
    TMD(0, b[0]);
    {
      int nw = CH_NQ, nb = 2;
#pragma unroll
      for (int k = 0; k < 16; k++) {
        SCHED();
        step(k);
#pragma unroll
        for (int i = 0; i < (CH_DBL >> k & 1) + 1; i++) {
          if (nb < 10 && 2 * nb <= nw) { ldsm4t(&b[4 * nb], l16 + mem + nb * 512); nb++; }
          else if (nw < 20) { ldsm4t(&wf[4 * nw], wq + nw * 2048); nw++; }
        }
      }
      SCHED();
    }
    if (WG == 0) {
      step(16); step(17);
      finish(0, d0);
      TM(1);
      bar_sync(NB_PROJ, 256);
      const float4 pv = lds128f(t16 + CH_VP);
      const uint32_t v0 = pack2(d1[0] + pv.x, d1[1] + pv.y), v1 = pack2(d1[2] + pv.z, d1[3] + pv.w);
      const uint32_t xo = l8 + (vxo ^ (tag & 2));
      if (s == NSEG - 1) { sts64(xo, v0, v1); continue; }
      st_async64(mapa(xo, r1), v0, v1, mapa(sb + MB_X, r1));
      st_async64(mapa(xo, r2), v0, v1, mapa(sb + MB_X, r2));
      sts64(xo, v0, v1);
      __syncwarp();
      if (elect()) mbar_arrive(sb + MB_X);
      bar_arrive(NB_PROJ2, 256);
      TM(3);
      uint32_t w[144];
      auto tile_of = [](int n) { return n < 27 ? n % 3 : (0x26484 >> 2 * (n - 27)) & 3; };
      auto step_of = [](int n) { return n < 27 ? n / 3 : 9 + ((0x29610 >> 2 * (n - 27)) & 3); };
      auto wload = [&](int n) { ldsm4t(&w[4 * n], wo + tile_of(n) * 12288 + (step_of(n) % 3) * 4096 + (step_of(n) / 3) * 1024); };
#pragma unroll
      for (int n = 0; n < CH_PA; n++) wload(n);
      bar_sync(NB_PRE, 256);
#pragma unroll
      for (int n = CH_PA; n < CH_PB; n++) wload(n);
      bar_arrive(NB_PRE2, 256);
      if (CH_PC > CH_PB) {
        mbar_wait(sb + MB_X, s & 1);
        for (int i = 0; i < CH_PD; i++) wo = __shfl_xor_sync(~0u, wo, p.zero);
#pragma unroll
        for (int n = CH_PB; n < CH_PC; n++) wload(n);
      }
      TM(4);
      bar_sync(NB_O, 256);
      {
        float x[3][4] = {};
        uint32_t ob[24];
        float4 l;
        ldsm4t(&ob[0], l16 + CH_O);
        ldsm4t(&ob[4], l16 + CH_O + 512);
        TMD(7, ob[0]);
        int nw = CH_PC, no = 2;
        float i0, i1;
        uint8_t* dst[6];
        uint32_t lo[6], hi[6];
        auto pre = [&](int i) { lo[i] = __float_as_uint(x[i >> 1][2 * (i & 1)] * i0) + tag; hi[i] = pack2(0.f, x[i >> 1][2 * (i & 1) + 1] * i1); };
        auto emit = [&](int i) { stg_strong32(dst[i], set_tag(__byte_perm(lo[i], hi[i], 0x7632), tag)); };
#pragma unroll
        for (int n = 0; n < 36; n++) {
          SCHED();
          mma16(x[tile_of(n)], w[4 * n], w[4 * n + 1], w[4 * n + 2], w[4 * n + 3], ob[step_of(n) * 2], ob[step_of(n) * 2 + 1]);
          if (n >= CH_PL) {
            if (no < 6 && no * 2 <= step_of(min(nw, 35))) { ldsm4t(&ob[4 * no], l16 + CH_O + no * 512); no++; }
            else if (nw < 36) { wload(nw); nw++; }
          }
          if (n == 18) l = lds128f(sb + CH_L + ((l16 ^ tag) & 0x30));
          if (n == 26) { i0 = rcp(l.x + l.y); i1 = rcp(l.z + l.w); asm volatile("" : "+f"(i0), "+f"(i1)); }
          if (n >= 28 && n < 34) { dst[n - 28] = pdst[n - 28] + ((l4 ^ tag) & 0x7c); asm volatile("" : "+l"(dst[n - 28])); }
          if (n == 32) { for (int i = 0; i < 2; i++) { pre(i); asm volatile("" : "+r"(lo[i]), "+r"(hi[i])); } }
          if (n == 33) { emit(0); emit(1); }
        }
        for (int i = 2; i < 6; i++) pre(i);
        for (int i = 2; i < 6; i++) emit(i);
      }
      TM(8);
    } else {
      uint32_t kf[8];
      const uint32_t x = l16 ^ ((ko0 ^ tag) & 256);
      step(16);
      ldsm4t(kf, x + (x & 256) + ko0 + CH_K);
      SCHED();
      step(17);
      ldsm4t(kf + 4, x + (x & 256) + ko1 + CH_K);
      SCHED();
      finish(1, d1);
      sts128f(t16 + CH_VP, d0[0], d0[1], d0[2], d0[3]);
      TM(1);
      bar_sync(NB_PROJ, 256);
      if (s == NSEG - 1) continue;
      {
        float d0[4] = {}, d1[4] = {}, dm[4] = {};
        uint32_t q[16], km[4];
#pragma unroll
        for (int e = 0; e < 4; e++) {
          ldsm4t(&q[4 * e], l16 + (e ^ t4) * 512 + CH_Q);
          if (e == 1) ldsm4(km, t16 + CH_KM);
        }
        SCHED();
        mma16(d0, q[0], q[1], q[2], q[3], kf[0], kf[1]);
        mma16(d1, q[4], q[5], q[6], q[7], kf[2], kf[3]);
        mma16(dm, q[0], q[1], q[2], q[3], hadd2(km[0], km[2]), hadd2(km[1], km[3]));
        mma16(d0, q[8], q[9], q[10], q[11], kf[4], kf[5]);
        mma16(d1, q[12], q[13], q[14], q[15], kf[6], kf[7]);
        const uint32_t w0 = pack2((d0[0] + d0[2]) + (d1[0] + d1[2]), (d0[1] + d0[3]) + (d1[1] + d1[3])), w1 = pack2(dm[0] + dm[2], dm[1] + dm[3]);
        const uint32_t xo = l4 + ((t4 * 128) ^ (tag & 2)), x1 = mapa(xo, r1), x2 = mapa(xo, r2);
        st_async32(x1 + CH_SX + 512, w1, mapa(sb + MB_X, r1));
        st_async32(x2 + CH_SX + 1536, w1, mapa(sb + MB_X, r2));
        st_async32(x1 + CH_SX, w0, mapa(sb + MB_X, r1));
        st_async32(x2 + CH_SX + 1024, w0, mapa(sb + MB_X, r2));
        sts32(xo + CH_SO, w0);
        sts32(xo + CH_SO + 512, w1);
      }
      TM(3);
      float sc[3][4] = {};
      uint32_t wd[12];
      uint32_t redo;
      auto attend = [&](auto first) {
        uint4 vb[6];
        uint2 vm[3];
        float e[10];
        uint32_t ow[6];
        if (first.value) {
          const uint2 id = lds64(l8 + CH_ID);
          bar_sync(NB_W1V, 160);
          uint32_t r[8];
          ldsm4(r, l16 + CH_SO); ldsm4(r + 4, l16 + CH_SO + 512);
#pragma unroll
          for (int u = 0; u < 6; u++) vb[u] = ldsm4v(t16 + CH_V + u * 2048);
          bar_arrive(NB_PRE, 256);
          uint32_t sxa = l16 + ((l16 ^ tag) & 256) * 3;
          asm volatile("" : "+r"(sxa));
          sxa += CH_SX;
          SCHED();
          mma8(sc[0], r[0], r[1], id.x);
          mma8(sc[1], r[2], r[3], id.x);
          mma16(sc[2], r[4], r[5], r[6], r[7], id.x, id.y);
          TM(7);
          mbar_wait(sb + MB_X, s & 1);
          TM(4);
          uint32_t t[16];
          ldsm4(t, sxa); ldsm4(t + 4, sxa + 256); ldsm4(t + 8, sxa + 512);
          SCHED();
          mma16(sc[0], t[0], t[1], t[2], t[3], id.x, id.y);
          ldsm4(t + 12, sxa + 768);
          SCHED();
          mma16(sc[1], t[4], t[5], t[6], t[7], id.x, id.y);
#pragma unroll
          for (int u = 0; u < 2; u++) vm[u] = lds64(t8 + CH_VX + u * 1024);
          SCHED();
          e[0] = ex2(sc[0][0]);
          mma16(sc[2], t[8], t[9], t[10], t[11], id.x, id.y);
          vm[2] = lds64(t8 + CH_VX + 2048);
          SCHED();
          e[1] = ex2(sc[0][1]);
          ldsm4t(&wd[0], wo);
          SCHED();
          e[2] = ex2(sc[0][2]);
          SCHED();
          e[3] = ex2(sc[0][3]);
          mma16(sc[2], t[12], t[13], t[14], t[15], id.x, id.y);
          SCHED();
          e[4] = ex2(sc[1][0]);
          ldsm4t(&wd[4], wo + 4096);
          SCHED();
          e[5] = ex2(sc[1][1]);
        } else {
#pragma unroll
          for (int u = 0; u < 6; u++) vb[u] = ldsm4v(t16 + CH_V + u * 2048);
#pragma unroll
          for (int u = 0; u < 3; u++) vm[u] = lds64(t8 + CH_VX + u * 1024);
        }
        float o[3][4] = {};
        if (!first.value) {
#pragma unroll
          for (int i = 0; i < 6; i++) e[i] = ex2(sc[i >> 2][i & 3]);
        }
        const uint32_t p1 = pack2(e[0], e[1]), p2 = pack2(e[2], e[3]);
        float l = (e[0] + e[1]) + (e[2] + e[3]);
        asm volatile("" : "+f"(l));
        SCHED();
        e[6] = ex2(sc[1][2]);
        mma16(o[0], vb[0].x, vb[0].y, vb[0].z, vb[0].w, p1, p2);
        if (first.value) { sc[2][0] += sc[2][2]; sc[2][1] += sc[2][3]; }
        SCHED();
        e[7] = ex2(sc[1][3]);
        mma16(o[1], vb[2].x, vb[2].y, vb[2].z, vb[2].w, p1, p2);
        SCHED();
        e[8] = ex2(sc[2][0]);
        mma16(o[2], vb[4].x, vb[4].y, vb[4].z, vb[4].w, p1, p2);
        SCHED();
        e[9] = ex2(sc[2][1]);
        SCHED();
        const uint32_t p3 = pack2(e[4], e[5]), p4 = pack2(e[6], e[7]);
        l += (e[4] + e[5]) + (e[6] + e[7]);
#pragma unroll
        for (int u = 0; u < 3; u++) mma16(o[u], vb[2 * u + 1].x, vb[2 * u + 1].y, vb[2 * u + 1].z, vb[2 * u + 1].w, p3, p4);
        SCHED();
        const uint32_t p0 = pack2(e[8], e[9]);
        l += e[8] + e[9];
        const float l2 = __shfl_xor_sync(~0u, l, 1);
        if (first.value) ldsm4t(&wd[8], wo + 8192);
#pragma unroll
        for (int u = 0; u < 3; u++) mma8(o[u], vm[u].x, vm[u].y, p0);
        redo = __any_sync(~0u, !(l > 1e-9f && l < 1e9f));
        uint32_t la = sb + CH_L + (((l4 ^ tag) >> 1) & 0x3c);
        asm volatile("" : "+r"(la));
        SCHED();
#pragma unroll
        for (int u = 0; u < 3; u++) { ow[2 * u] = pack2(o[u][0], o[u][1]); ow[2 * u + 1] = pack2(o[u][2], o[u][3]); }
        stsm4(l16 + o768 + CH_O, ow[0], ow[1], ow[2], ow[3]);
        stsm2(l16 + o768 + CH_O + 512, ow[4], ow[5]);
        if (t4 == 0) sts32(la, __float_as_uint(l + l2));
      };
      attend(Int<1>());
      TM(6);
      asm volatile("{.reg .pred p; setp.eq.u32 p, %0, 0; @p bar.arrive 2, 256;}" :: "r"(redo) : "memory");
      if (redo) {
        float mx = fmaxf(sc[2][0], sc[2][1]);
#pragma unroll
        for (int i = 0; i < 4; i++) mx = fmaxf(mx, fmaxf(sc[0][i], sc[1][i]));
        mx = fmaxf(mx, __shfl_xor_sync(~0u, mx, 1));
        mx = fmaxf(mx, __shfl_xor_sync(~0u, mx, 2));
#pragma unroll
        for (int i = 0; i < 4; i++) { sc[0][i] -= mx; sc[1][i] -= mx; }
        sc[2][0] -= mx; sc[2][1] -= mx;
        attend(Int<0>());
        bar_arrive(NB_O, 256);
      }
      {
        float z[4] = {};
        const uint32_t scr = l8 + ((CH_V + r1 * 4096) ^ (tag & 2));
        uint32_t ow[6], we[12];
        __syncwarp();
        ldsm4t(ow, l16 + o768 + CH_O);
        ldsm2t(ow + 4, l16 + o768 + CH_O + 512);
        if (j == 0) {
          float y[4] = {};
#pragma unroll
          for (int u = 0; u < 3; u++) ldsm4t(&we[4 * u], (wo ^ 32) + u * 4096);
          SCHED();
#pragma unroll
          for (int u = 0; u < 3; u++) {
            mma16(z, wd[4 * u], wd[4 * u + 1], wd[4 * u + 2], wd[4 * u + 3], ow[2 * u], ow[2 * u + 1]);
            mma16(y, we[4 * u], we[4 * u + 1], we[4 * u + 2], we[4 * u + 3], ow[2 * u], ow[2 * u + 1]);
          }
          sts64f(scr + t4 * 512 + 2048, y[0], y[1]); sts64f(scr + t4 * 512 + 2304, y[2], y[3]);
        } else {
#pragma unroll
          for (int u = 0; u < 3; u++) mma16(z, wd[4 * u], wd[4 * u + 1], wd[4 * u + 2], wd[4 * u + 3], ow[2 * u], ow[2 * u + 1]);
        }
        sts64f(scr + t4 * 512, z[0], z[1]); sts64f(scr + t4 * 512 + 256, z[2], z[3]);
        bar_sync(NB_W1, 128);
        if (j == 0 || t4 < 2) {
          float2 q[4];
          const float4 l = lds128f(sb + CH_L + ((l16 ^ tag) & 0x30));
#pragma unroll
          for (int i = 0; i < 4; i++) q[i] = lds64f(scr + (t4 >> 1) * 2048 + (t4 & 1) * 256 + i * 512);
          SCHED();
          stg_strong32(pdst[0] + ((l4 ^ tag) & 0x7c), pack_tag(((q[0].x + q[1].x) + (q[2].x + q[3].x)) * rcp(l.x + l.y), ((q[0].y + q[1].y) + (q[2].y + q[3].y)) * rcp(l.z + l.w), tag));
        }
      }
      TM(2);
    }
    bar_sync(NB_ST, 384);
    tag ^= 0x10001;
  } while (++s < NSEG);
  if (WG == 1) {
    const uint2 a = lds64(t8 + t4 * 256 + CH_KM), b = lds64(t8 + t4 * 256 + CH_KM + 256);
    sts64(t8 + CH_Q, hadd2(a.x, b.x), hadd2(a.y, b.y));
  }
  bar_arrive(NB_PRE2, 288);
}

__device__ __forceinline__ void chain_comm(const ChainParams& p, const uint32_t sb, const CUtensorMap* maps) {
  [[maybe_unused]] constexpr int WG = 2;
  const int tid = threadIdx.x & 127, t4 = __shfl_sync(~0u, tid >> 5, 0), lane = tid & 31;
  const int cta = blockIdx.x, h = cta / 3, j = cta - 3 * h, colbase = cta * 64;
  const uint8_t* const xs = reinterpret_cast<const uint8_t*>(g_xn);
  auto xload = [&](int seg, int i, int off, int bytes) { bulk_load(sb + CH_X + i * 5120 + off, xs + (seg * 4 + (i & 3)) * 10240 + (i >> 2) * 5120 + off, bytes, sb + MB_T); };
  if (cta == 0) for (int i = tid; i < SY_N; i += 128) p.other[i] = 0;
  uint32_t smid; asm("mov.u32 %0, %%smid;" : "=r"(smid));
  const uint32_t part = max(ldg_strong32(g_smpart + (smid & 255)), 1u);
  if (tid == 64) stg_strong32(p.sync + SY_PART + cta, part);
  PRO(0);
  if (t4 == 3) {
    bar_arrive(NB_PROJ2, 384);
    bar_arrive(NB_PRE2, 384);
    if (elect()) {
      wait_count(p.sync + SY_P + 1, ln_items(p.layer, 0));
      fence_async_global();
      mbar_expect(sb + MB_T, 40960);
      #pragma unroll 1
      for (int i = 0; i < 8; i++) xload(0, i, 0, 5120);
    }
    __syncwarp();
  } else {
  bar_sync(NB_PROJ2, 384);
  __syncwarp();
  PRO(1);
  if (t4 == 0 && elect()) {
    mbar_expect(sb + MB_WQ, 81920);
    #pragma unroll 1
    for (int i = 0; i < 4; i++) tma_load(sb + CH_WQ + i * 20480, &p.wq, colbase, i * 160, sb + MB_WQ);
  }
  bar_sync(NB_PRE2, 384);
  __syncwarp();
  PRO(2);
  if (t4 == 0 && elect()) {
    mbar_expect(sb + MB_WO, 86016);
#pragma unroll 1
    for (int i = 0; i < 7; i++) tma_load(sb + CH_WO + i * 12288, &p.wo, i < 6 ? j * 192 + i * 32 : j == 0 ? 576 : 592 + j * 16, h * 192, sb + MB_WO);
  }
  }
  if (tid < NSLOT) {
    const uint32_t* part_of = p.sync + SY_PART + (tid >= 80 ? cta : tid);
    uint32_t reader = 0, orient = 0;
    int n = 0;
    while (reader == 0 || orient == 0) { reader = ldg_strong32(part_of); orient = ldg_strong32(g_orient + tid); spin_guard(n); }
    sts32(sb + CH_TAB + tid * 4, tid * 8192 + (orient == reader ? 0 : 4096));
    if (t4 == 0) {
      const uint32_t near = __ballot_sync(~0u, reader == part) & 0xffffff;
      if (lane == 0) sts32(sb + CH_TAB + NSLOT * 4, cta < 80 ? cta : near ? __fns(near, 0, 1 + cta % __popc(near)) : 0);
    }
  }
  __syncwarp();
  asm volatile("barrier.cluster.wait.aligned;" ::: "memory");
  const uint32_t l8 = opaque(sb + t4 * 256 + lane * 8);
  bar_sync(NB_ST, 384);
  bar_arrive(NB_PUB, 384);
  {
    const uint32_t id = (lane >> 3) == (lane & 3) ? ((lane & 4) ? 0x3f800000u : 0x00003f80u) : 0u;
    if (t4 == 0) sts64(l8 + CH_ID, id, id);
    const uint32_t* m0 = reinterpret_cast<const uint32_t*>(p.mem0) + (lane >> 2) * (DM / 2) + t4 * 80 + (lane & 3);
    uint32_t g[20];
#pragma unroll
    for (int i = 0; i < 20; i++) g[i] = m0[i * 4];
    bar_sync(NB_XFREE, 256);
#pragma unroll
    for (int i = 0; i < 20; i += 4) stsm4t(sb + CH_M + (t4 * 20 + i) * 128 + lane * 16, g[i], g[i + 1], g[i + 2], g[i + 3]);
    mbar_wait_uniform(sb + MB_WO, 0);
  }
  uint8_t* const pool = pool_at(0);
  const uint8_t* const psrc = pool + opaque(lds32(sb + CH_TAB + lds32(sb + CH_TAB + NSLOT * 4) * 4) + t4 * 1024 + lane * 4);
  const uint32_t mdst = opaque((80 + cta / 20) * 8192 + (t4 & 1) * 4096 + (cta % 20) * 128 + lane * 4);
  int st = 0;
  uint32_t tag = opaque(1), span = ~0u;
  bar_sync(NB_MEM, 384);
  auto send_tokens = [&](int s) {
    uint8_t* dst = g_kv + ((s >> 2) * 192 + cta + 3 * h) * KV_PART + (s & 3) * 4096;
    bulk_store(dst, sb + CH_K, 4096);
    bulk_store(dst + KV_V, sb + CH_V + j * 4096, 4096);
    bulk_commit();
  };
  auto send_memory = [&](int s, uint32_t km) {
    fence_async();
    uint8_t* dst = g_kv + ((s >> 2) * 192 + cta + 3 * h) * KV_PART + KV_M + (s & 3) * 1024;
    bulk_store(dst, km, 1024);
    bulk_store(dst + KV_V, sb + CH_VX + j * 1024, 1024);
    bulk_commit();
    bulk_wait<0>();
    if ((s & 3) == 3) { fence_async_global(); atomicAdd(p.sync + (s >> 2) * 8 + 4, 1); }
  };
#pragma unroll 1
  for (int s = 0; s < NSEG - 1; s++) {
    TM(0);
    STAT(0);
    if (t4 == 0) {
      if (elect()) {
        fence_async();
#pragma unroll 1
        for (int r = j + 1; r < j + 3; r++) bulk_push(mapa(sb + CH_V + j * 4096, r % 3), sb + CH_V + j * 4096, 4096, mapa(sb + MB_V, r % 3));
        send_tokens(s);
        bulk_wait_read<0>();
      }
      __syncwarp();
    }
    uint32_t c0, g0;
    if (t4 == 1) {
      __syncwarp();
      c0 = clk32(); g0 = gtime();
      if (elect()) atomicMax(p.sync + SY_TIME + s, g0);
    }
    if (t4 == 3 && (s & 3) == 2 && s < NSEG - 2) wait_count_uniform(p.sync + SY_P + 5 + (s & ~3), ln_items(p.layer, (s >> 2) + 1));
    if (t4 == 2) { mbar_wait(sb + MB_V, s & 1); bar_arrive(NB_W1V, 160); }
    bar_sync(NB_PROJ2, 256);
    if (t4 == 0 && elect()) {
      mbar_expect(sb + MB_X, 4096);
      mbar_expect(sb + MB_T, 40960);
#pragma unroll 1
      for (int i = 0; i < 7; i++) xload(s + 1, i, 0, i < 6 ? 5120 : 4096);
    }
    __syncwarp();
    STAT(1);
    TM(1);
    {
      const uint2 a = lds64(l8 + t4 * 256 + CH_KM), b = lds64(l8 + t4 * 256 + CH_KM + 256);
      sts64(l8 + CH_KS, hadd2(a.x, b.x), hadd2(a.y, b.y));
    }
    TM(4);
    bar_sync(NB_PRE2, 256);
    if (t4 == 0 && elect()) {
      xload(s + 1, 6, 4096, 1024);
      xload(s + 1, 7, 0, 5120);
      if (CH_XPF && s < NSEG - 2) prefetch_l2(xs + (s + 2) * 40960 + cta % 20 * 2048, 2048);
      if (CH_TPF && s >= NSEG - 7) {
        const int i = s - (NSEG - 7);
        if (i < 2) prefetch_l2(p.wb + (cta * 2 + i) * 12800, 12800);
        else if (i < 4) prefetch_l2(xs + (cta * 2 + i - 2) * 8192, 8192);
        else prefetch_l2(g_q + 15 * 32 * 3072 + (cta * 2 + i - 4) * 512, 8192);
      }
      send_memory(s, sb + CH_KS);
    }
    __syncwarp();
    if (t4 == 1) {
      const uint32_t late = min(ldg_strong32(p.sync + SY_TIME + s) - g0, 640u);
      if (elect()) sts32(sb + CH_TAB + 380, c0 + span + (late * 115 >> 6) + (j ? 60 : 0) + p.d1);
    }
    bar_sync(NB_W2, 128);
    uint32_t due = lds32(sb + CH_TAB + 380);
    due = __shfl_sync(~0u, due, 0);
    const uint8_t* ms = pool + (lds32(sb + CH_TAB + (80 + st * 4 + t4) * 4) + (l8 & 255));
    uint8_t* md = pool + (mdst + (t4 < 2 ? st : st == 2 ? 0 : st + 1) * 32768);
    asm volatile("" : "+l"(ms), "+l"(md));
    TM(2);
    bar_sync(NB_ST, 384);
    __syncwarp();
    uint32_t tg = clk32();
    if (t4 == 3 && elect()) {
      if (s < NSEG - 2) mbar_expect(sb + MB_V, 8192);
      mbar_arrive_remote(mapa(sb + MB_F, j == 2 ? 0 : j + 1));
      mbar_arrive_remote(mapa(sb + MB_F, j == 0 ? 2 : j - 1));
    }
    if (t4 == 2 && s == NSEG - 2) {
      work_init(sb);
      if (elect()) for (int i = 0; i < 5; i++) asm volatile("prefetch.tensormap [%0];" :: "l"(maps + i) : "memory");
    }
    __syncwarp();
    STAT(2);
    {
      float2 q[4];
      TM(3);
      if (t4 == 1) span = min(span, tg - c0);
      until(s < 2 ? tg + 400 : (int)(due - tg) > p.dn ? due : tg + p.dn);
      for (int n = 0;;) {
        uint32_t v[8];
#pragma unroll
        for (int i = 0; i < 8; i++) v[i] = ldg_strong32(psrc + i * 128);
        sts64f(l8 + CH_R2, ((bf_lo(v[0]) + bf_lo(v[1])) + (bf_lo(v[2]) + bf_lo(v[3]))) + ((bf_lo(v[4]) + bf_lo(v[5])) + (bf_lo(v[6]) + bf_lo(v[7]))),
               ((bf_hi(v[0]) + bf_hi(v[1])) + (bf_hi(v[2]) + bf_hi(v[3]))) + ((bf_hi(v[4]) + bf_hi(v[5])) + (bf_hi(v[6]) + bf_hi(v[7]))));
        uint32_t bad;
        asm volatile("{.reg .pred p, q; .reg .b32 a; lop3.b32 a, %1, %2, %3, 0xFE; lop3.b32 a, a, %4, %6, 0xA8; setp.ne.u32 p, a, 0;\n"
                     "bar.red.or.pred q, %5, 128, p; selp.u32 %0, 1, 0, q;}"
                     : "=r"(bad) : "r"(differ(v[0], v[1], tag)), "r"(differ(v[2], v[3], tag)), "r"(differ(v[4], v[5], tag)), "r"(differ(v[6], v[7], tag)), "n"((int)NB_W2),
                       "r"((uint32_t)(cta < 80 || n < 3)) : "memory");
#pragma unroll
        for (int k = 0; k < 4; k++) asm volatile("ld.volatile.shared.v2.f32 {%0,%1}, [%2];" : "=f"(q[k].x), "=f"(q[k].y) : "r"(l8 - t4 * 256 + CH_R2 + k * 256) : "memory");
        TMV(12, n);
        if (!bad) break;
        spin_guard(n);
      }
      bar_arrive(NB_PUB, 384);
      SCHED();
      TM(9);
      if (cta < 80) stg_strong32(md, min(nz(pack2((q[0].x + q[1].x) + (q[2].x + q[3].x), (q[0].y + q[1].y) + (q[2].y + q[3].y))), t4 < 2 ? ~0u : 0u));
      tg = clk64() + p.d2;
      if (s >= 2 && (int)(due + p.dx - tg) > 0) tg = due + p.dx;
      TM(8);
    }
    STAT(3);
    until(tg);
    TM(10);
    for (int n = 0;;) {
      uint2 g[10];
#pragma unroll
      for (int i = 0; i < 10; i++) g[i] = ldg_strong64(ms + i * 256);
      if (n == 0) bar_sync(NB_XFREE, 256);
      spin_guard(n);
      uint32_t m = ~0u;
#pragma unroll
      for (int i = 0; i < 10; i++) { sts64(l8 + CH_M + t4 * 2304 + i * 256, g[i].x, g[i].y); m = __vimin3_u32(m, g[i].x, g[i].y); }
      TMV(13, n - 1);
      if (!__any_sync(~0u, m == 0)) break;
    }
    TM(11);
    if (t4 < 2 || s == NSEG - 2) bar_sync(NB_MEM, 384); else bar_arrive(NB_MEM, 384);
    if (++st == 3) st = 0;
    tag ^= 0x10001;
  }
  if (t4 == 0) {
    if (elect()) { fence_async(); send_tokens(NSEG - 1); }
    __syncwarp();
    bar_sync(NB_PRE2, 288);
    if (elect()) {
      send_memory(NSEG - 1, sb + CH_Q);
      asm volatile("mbarrier.arrive.shared::cta.b64 _, [%0], 8;" :: "r"(sb + WK_BAR + 64) : "memory");
    }
    __syncwarp();
  }
}

__device__ __forceinline__ void chain_start(const ChainParams& p, const uint32_t sb) {
  if (threadIdx.x < 32 && elect()) {
    mbar_init(sb + MB_WO, 1); mbar_init(sb + MB_WQ, 1); mbar_init(sb + MB_X, 5); mbar_init(sb + MB_V, 1); mbar_init(sb + MB_T, 1); mbar_init(sb + MB_F, 2);
    for (int i = 0; i < 8; i++) mbar_init(sb + MB_W + 8 * i, 1);
    asm volatile("fence.mbarrier_init.release.cluster;" ::: "memory");
    mbar_expect(sb + MB_V, 8192);
#pragma unroll 1
    for (int i = 0; i < 8; i++) {
      const int n = (i & 4) + (i & 1) * 2 + (i >> 1 & 1);
      mbar_expect(sb + MB_W + 8 * n, 20480);
      tma_load(sb + n * 20480, (i ^ i >> 2) & 1 ? &p.wv : &p.wk, blockIdx.x * 64, (n & 3) * 160, sb + MB_W + 8 * n);
    }
    atomicAdd(p.sync + SY_UP, 1);
    asm volatile("{.reg .pred p; setp.ne.u32 p, %0, 1024; @p trap;}" :: "r"(sb & 0xffffff));
  }
  __syncthreads();
  asm volatile("barrier.cluster.arrive.relaxed.aligned;" ::: "memory");
}

struct WorkParams {
  ChainParams ch;
  CUtensorMap wo, xn, wb[3], xp, wq, wc[2], out;
  const __nv_bfloat16* x;
  uint32_t* sync;
  int kind, qa_end, idle;
};
#define GO_320 4
#define GO_TAIL 1
enum { WK_FIRST = 0, WK_LEAD = 1, WK_CHAIN = 2, WK_LAST = 3 };
enum { IT_ATT = 0, IT_OP = 1, IT_FIN = 2, IT_BQ = 3, IT_BO = 4, IT_LN = 5, IT_Q = 6, IT_LN0 = 7, IT_OUT = 8 };
constexpr int C_EARLY = 1 << 20, C_LATE = 1 << 21, C_TAIL = 1 << 22;

__device__ __forceinline__ uint32_t item_count(int type, int b) { return type == IT_ATT ? 32 : type == IT_OP ? op_tiles(b) * op_split(b) : type == IT_FIN ? fin_items(b) : bq_items(b); }
__device__ __forceinline__ uint32_t item_need(int type, int b) { return type == IT_ATT ? 96 : item_count(type - 1, b); }
__device__ __forceinline__ int item_cols(int type, int b) {
  return type == IT_ATT || type == IT_Q ? 192 : type == IT_OUT ? 80 : type == IT_BQ ? (b < BQ_12 ? 320 : b < BQ_24 ? 160 : 80) : type == IT_OP && b >= OP_N4 ? 160 : 320; }
__device__ __forceinline__ int item_groups(int type, int b) { return 16 / (type == IT_FIN ? fin_items(b) : ln_items(type == IT_LN, b)); }
#define RES_OP 1
constexpr int RES_N = RES_OP ? op_tiles(14) * op_split(14) : 0, RES_BQ = (64 - RES_N) / 6;
__device__ __forceinline__ bool reserved(int type, int b) { return type == IT_ATT ? b == 15 : type == IT_OP ? RES_OP && b == 14 : type == IT_BQ && b < RES_BQ; }
__device__ __forceinline__ int reserved_item(int cta) {
  const int h = cta / 3, j = cta - 3 * h, i = h + (j - 1) * 32;
  if (j == 0) return C_EARLY | IT_ATT << 16 | 15 << 8 | h;
  return i < RES_N ? C_TAIL | IT_OP << 16 | 14 << 8 | i : i - RES_N < RES_BQ * 6 ? C_TAIL | IT_BQ << 16 | ((i - RES_N) / 6) << 8 | (i - RES_N) % 6 : -1;
}
constexpr int LEAD1 = 12;
__device__ __forceinline__ int lead_item(int layer, int qa_end, int i) {
  if (layer == 2) return i < 128 ? C_EARLY | C_LATE | IT_OUT << 16 | (i >> 3) << 8 | (i & 7) : -1;
  if (layer == 0) {
    if (i < 32) return IT_LN0 << 16 | (i >> 4) << 8 | (i & 15);
    if (i < 88) return IT_LN0 << 16 | ((i - 24) >> 2) << 8 | (i & 3);
    i -= 88;
  } else {
    if (i < 4) return C_EARLY | IT_BO << 16 | (i >> 1) << 8 | (i & 1);
    if (i < 12) return C_EARLY | IT_LN << 16 | ((i - 4) >> 2) << 8 | (i & 3);
    if (i < 40) return C_EARLY | IT_BO << 16 | ((i - 8) >> 1) << 8 | (i & 1);
    if (i < 96) return C_EARLY | IT_LN << 16 | ((i - 32) >> 2) << 8 | (i & 3);
    i -= 96;
  }
  return i < (16 - qa_end) * 32 ? C_EARLY | IT_Q << 16 | (qa_end + (i >> 5)) << 8 | (i & 31) : -1;
}

struct Ring {
  uint32_t sb;
  int pos, seq;
  __device__ __forceinline__ uint32_t full() const { return sb + WK_BAR + 8 * (seq & 7); }
  __device__ __forceinline__ uint32_t take(int len) { if (pos + len > WK_SLOTS) pos = 0; pos += len; seq++; return sb + (pos - len) * 8192; }
  __device__ __forceinline__ uint32_t wait(int len) { mbar_wait_uniform(full(), (seq >> 3) & 1); return take(len); }
  __device__ __forceinline__ void release(int sq) const { if (elect()) mbar_arrive(sb + WK_BAR + 64 + 8 * (sq & 7)); }
};

struct Pending {
  uint32_t w[48], done;
  uint4* dst;
  __device__ __forceinline__ void store(int i) const { dst[(i >> 2) * 1024 + (i & 3) * 32] = make_uint4(w[4 * i], w[4 * i + 1], w[4 * i + 2], w[4 * i + 3]); }
  __device__ __forceinline__ void finish() { __syncwarp(); if (elect()) mbar_arrive(done); done = 0; }
  __device__ __forceinline__ void flush() {
    if (done) {
#pragma unroll
      for (int i = 0; i < 12; i++) store(i);
      finish();
    }
  }
};

template <int N>
__device__ __forceinline__ void gemm_item(float* d, Ring& r, int nkb, uint32_t go, int ask, Pending& pend) {
  const int warp = __shfl_sync(~0u, fresh_tid() >> 5, 0), wg = warp >> 2;
#pragma unroll 1
  for (int kb = 0; kb < nkb; kb++) {
    const uint32_t base = r.wait(2 + (N + 63) / 64);
    const uint64_t da = mkdesc(base + wg * 8192, 128, 1024, 0), db = mkdesc(base + 16384, 8192, 1024, 1);
    wg_fence();
#pragma unroll
    for (int kk = 0; kk < 4; kk++) {
      if (N == 80) wg_ss80_01(d, da + kk * 16, db + kk * 128, (kb | kk) != 0);
      else if (N == 160) wg_ss160_01(d, da + kk * 16, db + kk * 128, (kb | kk) != 0);
      else wg_ss192_01(d, da + kk * 16, db + kk * 128, (kb | kk) != 0);
      if (N == 320) wg_ss128_01(d + 96, da + kk * 16, db + kk * 128 + 3 * 512, (kb | kk) != 0);
    }
    wg_commit();
    if (kb == ask && go && warp == 0 && elect()) mbar_arrive(go);
    if (N == 192 && pend.done) {
#pragma unroll
      for (int i = 0; i < 12; i++) if (kb == i / 2) pend.store(i);
      if (kb == 5) pend.finish();
    }
    if (kb > 0) { wg_wait<1>(); r.release(r.seq - 2); }
  }
  wg_wait<0>();
  reg_fence<N / 2>(d);
  r.release(r.seq - 1);
}

__device__ __forceinline__ void attn_a_warp(Ring& r, Pending& pend, bool now, const int warp) {
  uint32_t (&q)[48] = pend.w;
  const int lane = fresh_tid() & 31, g = lane >> 2, c = lane & 3, seg = warp & 3;
  const bool half = warp >= 4;
  const float k2 = 0.07216878364870322f * 1.44269504089f, NEG = -INFINITY;
  float sc[5][4] = {};
#pragma unroll
  for (int i = 0; i < 8; i++) sc[3 + (i >> 2)][i & 3] = half ? 0.f : NEG;
  uint32_t base, f[2][40] = {};
  const uint32_t ka = seg * 4096 + lane * 16, va = seg * 4096 + (lane & 8) * 32 + (lane & 16) * 8 + (lane & 7) * 16;
  auto load = [&](int n) {
    uint32_t* d = f[n & 1];
    base = n & 1 ? base + KV_PART : r.wait(5);
    const uint32_t a = base + (n < 3 ? ka : va), m = base + KV_M + seg * 1024;
#pragma unroll
    for (int i = 0; i < 4; i++) {
      if (n >= 3) { const uint2 vm = lds64(m + i * 256 + lane * 8); d[2 * i] = vm.x; d[2 * i + 1] = vm.y; }
      else if (!(i & 1)) ldsm4(&d[2 * i], m + i * 256 + lane * 16);
      (n < 3 ? ldsm4t : ldsm4)(&d[8 + 4 * i], a + half * 2048 + i * 512);
    }
    if (half) {
#pragma unroll
      for (int i = 0; i < 4; i++) (n < 3 ? ldsm4t : ldsm4)(&d[24 + 4 * i], a + i * 512);
    }
  };
  load(0);
#pragma unroll
  for (int u = 0; u < 3; u++) {
    if (u == 2) r.release(r.seq - 2);
    load(u + 1);
    SCHED();
    const uint32_t* b = f[u & 1];
#pragma unroll
    for (int kk = 0; kk < 4; kk++) {
      const uint32_t* a = &q[16 * u + 4 * kk];
      mma16(sc[0], a[0], a[1], a[2], a[3], b[2 * kk], b[2 * kk + 1]);
      mma16(sc[1], a[0], a[1], a[2], a[3], b[8 + 4 * kk], b[9 + 4 * kk]);
      mma16(sc[2], a[0], a[1], a[2], a[3], b[10 + 4 * kk], b[11 + 4 * kk]);
    }
    if (half) {
#pragma unroll
      for (int kk = 0; kk < 4; kk++) {
        const uint32_t* a = &q[16 * u + 4 * kk];
        mma16(sc[3], a[0], a[1], a[2], a[3], b[24 + 4 * kk], b[25 + 4 * kk]);
        mma16(sc[4], a[0], a[1], a[2], a[3], b[26 + 4 * kk], b[27 + 4 * kk]);
      }
    }
    SCHED();
  }
  load(4);
  SCHED();
  if (2 * c > g) { sc[1][0] = NEG; sc[2][2] = NEG; }
  if (2 * c + 1 > g) { sc[1][1] = NEG; sc[2][3] = NEG; }
  sc[2][0] = sc[2][1] = NEG;
  uint32_t pp[5][2]; float inv[2];
#pragma unroll
  for (int hh = 0; hh < 2; hh++) {
    float m = NEG, l = 0.f;
#pragma unroll
    for (int n = 0; n < 5; n++) m = fmaxf(m, fmaxf(sc[n][2 * hh], sc[n][2 * hh + 1]));
    m = fmaxf(m, __shfl_xor_sync(~0u, m, 1)); m = fmaxf(m, __shfl_xor_sync(~0u, m, 2));
#pragma unroll
    for (int n = 0; n < 5; n++) { const float x = ex2((sc[n][2 * hh] - m) * k2), y = ex2((sc[n][2 * hh + 1] - m) * k2); l += x + y; pp[n][hh] = pack2(x, y); }
    l += __shfl_xor_sync(~0u, l, 1); l += __shfl_xor_sync(~0u, l, 2);
    inv[hh] = rcp(l);
  }
#pragma unroll
  for (int u = 0; u < 3; u++) {
    float o[8][4] = {};
    const uint32_t* b = f[~u & 1];
#pragma unroll
    for (int n = 0; n < 8; n++) mma8(o[n], pp[0][0], pp[0][1], b[n]);
#pragma unroll
    for (int n = 0; n < 8; n++) mma16(o[n], pp[1][0], pp[1][1], pp[2][0], pp[2][1], b[8 + 2 * n], b[9 + 2 * n]);
    if (half) {
#pragma unroll
      for (int n = 0; n < 8; n++) mma16(o[n], pp[3][0], pp[3][1], pp[4][0], pp[4][1], b[24 + 2 * n], b[25 + 2 * n]);
    }
    SCHED();
    if (u != 1) r.release(r.seq - 2 + u / 2);
    if (u == 0) { load(5); SCHED(); }
#pragma unroll
    for (int i = 0; i < 16; i++) q[16 * u + i] = pack2(o[i & 7][i >> 2 & 2] * inv[i >> 3], o[i & 7][(i >> 2 & 2) + 1] * inv[i >> 3]);
    if (now) {
#pragma unroll
      for (int i = 0; i < 4; i++) pend.store(4 * u + i);
    }
  }
}

__device__ __forceinline__ void ln_groups(Ring& ring, uint32_t scratch, int planes, int rg, bool two) {
  constexpr int G = 2;
  const int warp = fresh_tid() >> 5, lane = fresh_tid() & 31;
  const uint32_t id = (lane >> 3) == (lane & 3) ? ((lane & 4) ? 0x3f800000u : 0x00003f80u) : 0u;
  const uint32_t at = (warp * 160 + lane) * 8, at1 = planes > 1 ? at : (lane >> 2) * 1280 + warp * 160 + (lane & 3) * 4;
  const uint32_t step = planes > 1 ? 256 : 32, half = planes > 1 ? 4 : 16;
  float v[G][5][4] = {};
#pragma unroll
  for (int r = 0; r < G; r++) {
#pragma unroll 1
    for (int k = r && !two ? 0 : planes; k > 0; k -= 4) {
      const uint32_t a = ring.wait(min(k, 4) + 1);
      if (k == 1) {
#pragma unroll
        for (int i = 0; i < 5; i++) mma8(v[r][i], lds32(a + at1 + i * step), lds32(a + at1 + i * step + half), id);
      } else {
#pragma unroll
        for (int i = 0; i < 10; i++) {
          if (i == 5 && k < 4) break;
          const uint2 x = lds64(a + at + i / 5 * 20480 + i % 5 * 256), y = lds64(a + at + i / 5 * 20480 + 10240 + i % 5 * 256);
          mma16(v[r][i % 5], x.x, x.y, y.x, y.y, id, id);
        }
      }
      ring.release(ring.seq - 1);
    }
  }
  uint2 xr[G][5];
  scratch += (lane >> 2) * 64;
#pragma unroll
  for (int r = 0; r < G; r++) {
    float m = 0.f, q = 0.f;
#pragma unroll
    for (int i = 0; i < 5; i++) {
      float* t = v[r][i];
      xr[r][i] = make_uint2(pack2(t[0], t[1]), pack2(t[2], t[3]));
      t[0] = bf_lo(xr[r][i].x); t[1] = bf_hi(xr[r][i].x); t[2] = bf_lo(xr[r][i].y); t[3] = bf_hi(xr[r][i].y);
      m += (t[0] + t[1]) + (t[2] + t[3]);
    }
    m += __shfl_xor_sync(~0u, m, 1); m += __shfl_xor_sync(~0u, m, 2);
    m *= 1.f / 80;
#pragma unroll
    for (int i = 0; i < 5; i++) { const float a = v[r][i][0] - m, b = v[r][i][1] - m, c = v[r][i][2] - m, d = v[r][i][3] - m; q += (a * a + b * b) + (c * c + d * d); }
    q += __shfl_xor_sync(~0u, q, 1); q += __shfl_xor_sync(~0u, q, 2);
    if ((lane & 3) == 0) sts64f(scratch + r * 512 + warp * 8, m, q);
  }
  bar_sync(1, 256);
#pragma unroll
  for (int r = 0; r < G; r++) {
    const float4 t = lds128f(scratch + r * 512 + (lane & 3) * 16);
    float mean = t.x + t.z;
    mean += __shfl_xor_sync(~0u, mean, 1); mean += __shfl_xor_sync(~0u, mean, 2);
    mean *= 0.125f;
    float var = (t.y + t.w) + 80.f * ((t.x - mean) * (t.x - mean) + (t.z - mean) * (t.z - mean));
    var += __shfl_xor_sync(~0u, var, 1); var += __shfl_xor_sync(~0u, var, 2);
    const float rs = rsqrtf(var * (1.f / DM) + 1e-5f);
#pragma unroll
    for (int i = 0; i < 20; i++) v[r][i >> 2][i & 3] = (v[r][i >> 2][i & 3] - mean) * rs;
  }
#pragma unroll
  for (int r = 0; r < G; r++) {
    if (r && !two) break;
    uint32_t* xn = g_xn + (rg + r) * 2560 + warp * 320 + lane;
#pragma unroll
    for (int i = 0; i < 10; i++) xn[i * 32] = pack2(v[r][i >> 1][2 * (i & 1)], v[r][i >> 1][2 * (i & 1) + 1]);
#pragma unroll
    for (int i = 0; i < 5; i++) g_x[(rg + r) * 17 * 1280 + warp * 160 + i * 32 + lane] = xr[r][i];
  }
}

__device__ __forceinline__ void store_partial(const float* d, int b, int split, int unit, int nu) {
  uint2* dst = g_x + (((b * 16 + (fresh_tid() >> 5) * 2) * 17 + 1 + split) * 40 + unit) * 32 + (fresh_tid() & 31);
#pragma unroll
  for (int u = 0; u < 20; u++) {
    if (u == 10 && nu == 10) break;
    dst[u * 32] = make_uint2(pack2(d[8 * u], d[8 * u + 1]), pack2(d[8 * u + 4], d[8 * u + 5]));
    dst[(680 + u) * 32] = make_uint2(pack2(d[8 * u + 2], d[8 * u + 3]), pack2(d[8 * u + 6], d[8 * u + 7]));
  }
}

__device__ __forceinline__ void store_bqkv(const float* d, int b, int idx, int nh) {
  const int lane = fresh_tid() & 31, c = lane & 3, rg = b * 16 + (fresh_tid() >> 5) * 2, h0 = idx * nh;
  const float sc = h0 < 32 ? 0.22360679775f * 1.44269504089f : 1.f;
  const bool lo = c < 2;
  uint32_t* da = g_bqkv + (h0 * 256 + rg) * 96 + lane;
  uint32_t* db = da + 256 * 96 + (lo ? 2 : -2);
  uint32_t pad[2];
#pragma unroll
  for (int r = 0; r < 2; r++) pad[r] = !(c & 1) && (h0 >= 64 || (h0 >= 32 && (lane & 4) && poly_group(rg + r))) ? 0x00003f80u : 0u;
#pragma unroll
  for (int q = 0; q < 8; q++) {
    if ((q == 2 || q == 4) && nh == 2 * q) break;
#pragma unroll
    for (int r = 0; r < 2; r++) {
      uint32_t w[5];
#pragma unroll
      for (int i = 0; i < 5; i++) w[i] = pack2(d[20 * q + 4 * i + 2 * r] * sc, d[20 * q + 4 * i + 2 * r + 1] * sc);
      const int o = q * 2 * 256 * 96 + r * 96;
      da[o] = w[0]; da[o + 32] = w[1]; da[o + 64] = lo ? w[2] : pad[r];
      db[o] = lo ? w[3] : w[2]; db[o + 32] = lo ? w[4] : w[3]; db[o + 64] = lo ? pad[r] : w[4];
    }
  }
}

__device__ __forceinline__ void work_loader(const WorkParams& p, const uint32_t sb, const bool weights) {
  const uint32_t bars = sb + WK_BAR, bIF = bars + 128, bIE = bars + 160, bGo = bars + 224, slots = bars + 272;
  int pos = 0, seq = 0, tail = 0, used = 0;
  uint32_t lens = 0;
  const bool one = elect();
  if (p.kind == WK_CHAIN) {
    seq = 1; used = lens = 8;
    if (one) mbar_arrive(bars);
  }
  for (int n = 0;; n++) {
    mbar_wait_uniform(bIF + 8 * (n & 3), (n >> 2) & 1);
    const int code = __shfl_sync(~0u, (int)lds32(slots + 4 * (n & 3)), 0);
    if (code < 0) break;
    const int type = (code >> 16) & 15, b = (code >> 8) & 255, idx = code & 255;
    if (one) mbar_arrive(bIE + 8 * (n & 3));
    const bool qa = type == IT_ATT && b < p.qa_end, ln = type == IT_FIN || type == IT_LN || type == IT_LN0;
    const int parts = ln ? item_groups(type, b) : type == IT_ATT ? 2 : 1;
#pragma unroll 1
    for (int part = 0; part < parts; part++) {
      int bytes = 163840, chunk = 40960, nb = 0, flag = b * 8 + 4 + type, need = item_need(type & 3, b), c0 = 0, c3 = idx, c4 = 0, step = 64;
      const uint8_t* src = g_kv + (b * 32 + idx) * 6 * KV_PART;
      const CUtensorMap* m = nullptr;
      if (ln) {
        const int rg = b * 16 + idx * parts + part;
        bytes = (type == IT_FIN ? op_split(b) + 1 : type == IT_LN ? 2 : 1) * 10240;
        src = type == IT_LN0 ? reinterpret_cast<const uint8_t*>(p.x) + rg * 10240 : reinterpret_cast<const uint8_t*>(g_x) + rg * 174080;
        if (type == IT_LN) { flag = SY_P + b * 4; need = 2; }
        if (type == IT_LN0 || part) need = 0;
      } else if (part) {
        bytes = 6 * KV_PART;
      } else if (type == IT_ATT && !qa) {
        bytes = chunk = 49152;
        src = reinterpret_cast<const uint8_t*>(g_q) + (b * 32 + idx) * 49152;
        flag = SY_P + b * 4 + 3; need = 32;
      } else {
        const int cols = item_cols(type, b);
        chunk = 16384; nb = (cols + 63) >> 6;
        src = reinterpret_cast<const uint8_t*>(g_of) + b * 163840;
        if (type == IT_OP) {
          const int nkb = 96 / op_split(b), kb0 = (idx >> op_tiles(b) / 2) * nkb;
          bytes = nkb * 16384;
          src = reinterpret_cast<const uint8_t*>(g_o) + (b * 96 + kb0) * 16384;
          if (weights) m = &p.wo;
          c0 = (idx & (op_tiles(b) - 1)) * cols; c3 = 0; c4 = kb0 * 2; step = 2;
        } else if (type == IT_BQ) {
          m = weights ? &p.wb[cols / 160] : &p.xn;
        } else if (type == IT_BO || type == IT_OUT) {
          if (weights) m = &p.wc[cols / 320];
          flag = SY_OB; need = type == IT_BO && b < 2 ? 32 : -1;
        } else {
          m = weights ? &p.wq : &p.xp;
          flag = SY_P + b * 4 + 1; need = ln_items(p.ch.layer, b);
        }
      }
      if (!weights) {
        c3 = b * 4;
        if (need < 0) pdl_wait(); else if (need) wait_count_uniform(p.sync + flag, need);
        if ((ln ? !part : part && (!qa || (code & C_EARLY))) && one) mbar_arrive(bGo);
      }
      const int boxes = weights ? nb : m != nullptr;
#pragma unroll 1
      for (; bytes > 0; bytes -= chunk) {
        const int now = min(bytes, chunk), len = ((now + 8191) >> 13) + nb, skip = pos + len > WK_SLOTS ? WK_SLOTS - pos : 0, sh = 4 * (seq & 7);
        used += len + skip;
        while (used > WK_SLOTS || seq - tail >= 8) {
          mbar_wait_uniform(bars + 64 + 8 * (tail & 7), (tail >> 3) & 1);
          used -= (lens >> 4 * (tail & 7)) & 15;
          tail++;
        }
        lens = (lens & ~(15u << sh)) | (len + skip) << sh;
        if (pos + len > WK_SLOTS) pos = 0;
        const uint32_t bar = bars + 2 * sh, dst = sb + pos * 8192 + weights * 16384;
        if (one) mbar_expect(bar, weights ? nb * 8192 : now);
#pragma unroll 1
        for (int i = 0; i < boxes; i++)
          if (one)
            asm volatile("cp.async.bulk.tensor.5d.shared::cluster.global.mbarrier::complete_tx::bytes [%0], [%1, {%3, %6, %6, %4, %5}], [%2];"
                         :: "r"(dst + i * 8192), "l"(m), "r"(bar), "r"(c0 + i * 64), "r"(c3), "r"(c4), "r"(0) : "memory");
        if (!weights && !m && one) bulk_load_last(dst, src, now, bar);
        if (weights) c4 += step; else c0 += 128;
        src += chunk; pos += len; seq++;
      }
    }
  }
}

__global__ void __launch_bounds__(384, 1) work_kernel(const __grid_constant__ WorkParams p) {
  extern __shared__ __align__(1024) uint8_t smem_raw[];
  const uint32_t sb = s2u(smem_raw), bars = sb + WK_BAR;
  const uint32_t bIF = bars + 128, bIE = bars + 160, done = bars + 192, bGo = bars + 224, slots = bars + 272, scratch = bars + 384;
  const int warp = __shfl_sync(~0u, threadIdx.x >> 5, 0);
  uint32_t* const sync = p.sync;
  TRACE(0);
  pdl_launch();
  if (p.kind == WK_LEAD && !helper_sm() && __syncthreads_or(threadIdx.x == 0 && ldg_strong32(sync + SY_PRE + 1) >= LEAD1)) { pdl_wait(); return; }
  if (p.kind == WK_CHAIN) {
    chain_start(p.ch, sb);
  } else {
    if (warp == 0) work_init(sb);
    __syncthreads();
    if (p.kind == WK_FIRST) {
      if (!(warp & 13)) probe_slots(bars + 320);
      if (!helper_sm()) return;
    }
  }
  if (warp >= 8) {
    asm volatile("setmaxnreg.dec.sync.aligned.u32 40;");
    if (p.kind == WK_CHAIN) chain_comm(p.ch, sb, &p.wo);
    const int warp = __shfl_sync(~0u, fresh_tid() >> 5, 0), lane = fresh_tid() & 31;
    if (warp == 9) {
      const bool keep = p.kind > WK_LEAD || helper_sm();
      int n = 0;
      if (p.kind == WK_CHAIN && reserved_item(blockIdx.x) >= 0) {
        if (lane == 0) { sts32(slots, reserved_item(blockIdx.x)); mbar_arrive(bIF); }
        n = 1;
      }
      const int b = lane & 15, layer = p.kind == WK_LAST ? 2 : sync != g_sync;
      bool first = layer == 1, lead = p.kind != WK_CHAIN;
      for (;; n++) {
        if (n > 0) mbar_wait_uniform(bGo, (n - 1) & 1);
        mbar_wait_uniform(bIE + 8 * (n & 3), ((n >> 2) & 1) ^ 1);
        int code = -1;
        if (lead) {
          int i = blockIdx.x + n * 256;
          if (first) { if (lane == 0) i = atomicAdd(sync + SY_PRE + 1, 1); i = __shfl_sync(~0u, i, 0); first = i < LEAD1; }
          if (layer < 2 && !first) {
            if (lane == 0) i = keep ? atomicAdd(sync + SY_PRE, 1) + layer * LEAD1 : 1 << 20;
            i = __shfl_sync(~0u, i, 0);
            if (!keep) pdl_wait();
          }
          code = lead_item(layer, p.qa_end, i);
          lead = code >= 0 || layer == 2 || !keep;
          if (!lead && p.kind <= WK_LEAD) {
            const uint32_t t0 = gtime();
            while (!lead && ldg_strong32(sync + SY_UP) < 96) lead = gtime() - t0 > 20000;
          }
        }
        if (!lead) {
          int spin = 0, ticket = 0;
          if (lane == 0) ticket = atomicAdd(sync + SY_T, 1);
          for (;;) {
            const uint4 hd = ldg_strong128(sync + b * 8), pr = ldg_strong128(sync + b * 8 + 4);
            const uint32_t hv[4] = {hd.x, hd.y, hd.z, hd.w}, pv[4] = {pr.x, pr.y, pr.z, pr.w};
            const uint32_t chain_done = __ballot_sync(~0u, (pr.x & 0xffff) >= 96);
            int left[4], avail[4], rdy = 0, claimed = 0, upstream = 0;
#pragma unroll
            for (int t = 0; t < 4; t++) {
              const int cnt = lane < 16 && !reserved(t, b) ? item_count(t, b) : 0;
              left[t] = max(cnt - (int)hv[t], 0);
              claimed += cnt - left[t];
              const bool ready = (pv[t] & 0xffff) >= item_need(t, b);
              rdy |= ready << t;
              bool ok = ready || (t != IT_ATT && (chain_done >> 15 & 1) && !left[t - 1] && (t < 2 || !left[t - 2]));
              if (t == IT_BQ && (chain_done >> 12 & 9) == 1) ok = false;
              avail[t] = ok ? left[t] : 0;
              upstream |= __any_sync(~0u, left[t] > 0);
            }
            if (!upstream) { code = -1; break; }
            int rank = max(__shfl_sync(~0u, ticket, 0) - __reduce_add_sync(~0u, claimed), 0), type = -1, mine = 0;
#pragma unroll
            for (int c = 0; c < 7; c++) {
              const int t = c == 0 || c == 4 ? IT_FIN : c == 1 || c == 6 ? IT_ATT : c == 2 ? IT_OP : IT_BQ;
              int a = c == 1 || c == 2 || ((rdy >> t & 1) == (c < 4)) ? avail[t] : 0;
              if (c == 6) a = b < p.qa_end && !(rdy & 1) && ((chain_done << 1 | 1) >> b & 1) ? left[t] : 0;
              const int tot = __reduce_add_sync(~0u, a);
              if (type < 0) { if (rank < tot) { type = t; mine = a; } else rank -= tot; }
            }
            if (type >= 0) {
#pragma unroll
              for (int o = 1; o < 16; o <<= 1) { const int y = __shfl_up_sync(~0u, mine, o); if (lane >= o) mine += y; }
              const int blk = __ffs(__ballot_sync(~0u, mine > rank)) - 1;
              const int early = !(__shfl_sync(~0u, rdy, blk) >> type & 1);
              uint32_t idx = 0;
              if (lane == 0) idx = atomicAdd(sync + blk * 8 + type, 1);
              idx = __shfl_sync(~0u, idx, 0);
              if (idx < item_count(type, blk)) { code = (chain_done >> 14 & 1) << 22 | early << 20 | type << 16 | blk << 8 | idx; break; }
            } else {
              __nanosleep(50);
            }
            spin_guard(spin);
          }
        }
        if (lane == 0) {
          sts32(slots + 4 * (n & 3), code);
          mbar_arrive(bIF + 8 * (n & 3));
        }
        __syncwarp();
        if (code < 0) break;
      }
    } else if (warp >= 10) {
      work_loader(p, sb, warp == 10);
    } else {
      for (int n = 0;; n++) {
        mbar_wait_uniform(bIF + 8 * (n & 3), (n >> 2) & 1);
        const int code = __shfl_sync(~0u, (int)lds32(slots + 4 * (n & 3)), 0);
        if (code < 0) break;
        const int type = (code >> 16) & 15, b = (code >> 8) & 255;
        mbar_wait_uniform(done + 8 * (n & 3), (n >> 2) & 1);
        if (elect()) {
          if (type != IT_OUT) red_release(sync + (type < IT_BQ ? b * 8 + 5 + type : SY_P + b * 4 + ((0x13102 >> 4 * (type - IT_BQ)) & 3)), 1);
          mbar_arrive(bIE + 8 * (n & 3));
        }
        __syncwarp();
      }
    }
  } else {
    asm volatile("setmaxnreg.inc.sync.aligned.u32 232;");
    if (p.kind == WK_CHAIN) chain_compute(p.ch, sb);
    const int warp = __shfl_sync(~0u, fresh_tid() >> 5, 0), lane = fresh_tid() & 31;
    Ring r{sb, 0, p.kind == WK_CHAIN};
    Pending pend;
    pend.done = 0;
    int nln = 0;
    auto projects = [&](int n) {
      uint32_t here;
      asm volatile("{.reg .pred p; mbarrier.test_wait.parity.shared::cta.b64 p, [%1], %2; vote.sync.all.pred p, p, 0xffffffff; selp.u32 %0, 1, 0, p;}" : "=r"(here) : "r"(bIF + 8 * (n & 3)), "r"((n >> 2) & 1) : "memory");
      if (!here) return false;
      const int code = __shfl_sync(~0u, (int)lds32(slots + 4 * (n & 3)), 0);
      return code >= 0 && (((code >> 16) & 15) == IT_Q || (((code >> 16) & 15) == IT_ATT && ((code >> 8) & 255) < p.qa_end));
    };
#pragma unroll 1
    for (int n = 0;; n++) {
      if (pend.done && !projects(n)) pend.flush();
      mbar_wait_uniform(bIF + 8 * (n & 3), (n >> 2) & 1);
      const int code = __shfl_sync(~0u, (int)lds32(slots + 4 * (n & 3)), 0);
      if (code < 0) { TRACE(2); break; }
      const int type = (code >> 16) & 15, b = (code >> 8) & 255, idx = code & 255;
      const uint32_t go = (code & C_LATE) || (type == IT_ATT && (code & C_EARLY)) ? 0 : bGo;
      ITEM(code & 0xfffff, 0);
      if (type == IT_ATT || type == IT_Q) {
        if (type == IT_Q || b < p.qa_end) {
          float d[96] = {};
          reg_fence<96>(d);
          ITEM(9 << 16 | (code & 0xffff), 0);
          gemm_item<192>(d, r, 10, go, 4, pend);
          ITEM(9 << 16 | (code & 0xffff), 1);
#pragma unroll
          for (int i = 0; i < 48; i++) pend.w[i] = pack2(d[2 * i], d[2 * i + 1]);
        } else {
          const uint32_t base = r.wait(6) + warp * 2048 + lane * 16;
#pragma unroll
          for (int i = 0; i < 12; i++) {
            const uint4 t = lds128(base + (i >> 2) * 16384 + (i & 3) * 512);
            pend.w[4 * i] = t.x; pend.w[4 * i + 1] = t.y; pend.w[4 * i + 2] = t.z; pend.w[4 * i + 3] = t.w;
          }
          __syncwarp();
          r.release(r.seq - 1);
        }
        const bool now = type == IT_ATT && !projects(n + 1);
        if (type == IT_Q) {
          pend.dst = g_q + (b * 32 + idx) * 3072 + warp * 128 + lane;
        } else {
          pend.dst = g_o + (b * 32 + idx) * 3072 + (warp & 3) * 256 + (warp >> 2) * 128 + (lane & 3) * 8 + (lane >> 2);
          attn_a_warp(r, pend, now, warp);
        }
        pend.done = done + 8 * (n & 3);
        if (now) pend.finish();
      } else {
        if (type == IT_FIN || type == IT_LN || type == IT_LN0) {
          const int ng = item_groups(type, b);
          const int planes = type == IT_FIN ? op_split(b) + 1 : type == IT_LN ? 2 : 1;
#pragma unroll 1
          for (int i = 0; i < ng; i += 2) ln_groups(r, scratch + (nln++ & 1) * 1024, planes, b * 16 + idx * ng + i, ng > 1);
        } else {
          const int cols = item_cols(type, b), nkb = type == IT_OP ? 96 / op_split(b) : 10;
          float d[160] = {};
          if (type == IT_OUT) {
            const uint2* x = g_x + ((b * 16 + warp * 2) * 680 + idx * 5) * 32 + lane;
#pragma unroll
            for (int i = 0; i < 10; i++) { const uint2 y = __ldcg(x + (i / 5 * 680 + i % 5) * 32); d[40 + 2 * i] = __uint_as_float(y.x); d[41 + 2 * i] = __uint_as_float(y.y); }
          }
          reg_fence<160>(d);
          if (type != IT_OUT) ITEM((type == IT_BQ ? 10 : 11) << 16 | (code & 0xffff), 0);
          const int ask = max(nkb - (code & C_TAIL ? GO_TAIL : GO_320) * 320 / cols, 0);
          if (cols == 320) gemm_item<320>(d, r, nkb, go, ask, pend);
          else if (cols == 160) gemm_item<160>(d, r, nkb, go, ask, pend);
          else gemm_item<80>(d, r, nkb, go, ask, pend);
          if (type != IT_OUT) ITEM((type == IT_BQ ? 10 : 11) << 16 | (code & 0xffff), 1);
          reg_fence<160>(d);
          if (type == IT_OUT) {
            bar_sync(1, 256);
            const uint32_t dst = sb + (warp * 16 + (lane & 15)) * 160 + (lane >> 4) * 16;
#pragma unroll
            for (int u = 0; u < 5; u++) {
              uint32_t w[4];
#pragma unroll
              for (int i = 0; i < 4; i++) { const uint32_t y = __float_as_uint(d[40 + (i & 1) * 10 + 2 * u + (i >> 1)]); w[i] = pack2(bf_lo(y) + d[8 * u + 2 * i], bf_hi(y) + d[8 * u + 2 * i + 1]); }
              stsm4(dst + u * 32, w[0], w[1], w[2], w[3]);
            }
            fence_async();
            __syncwarp();
            if (elect()) { tma_store(&p.out, sb + warp * 2560, idx * 80, b * 128 + warp * 16); bulk_commit(); bulk_wait<0>(); }
          } else {
            if (warp >= 4) bar_sync(7, 256);
            if (type == IT_BQ) store_bqkv(d, b, idx, cols / 20);
            else store_partial(d, b, cols == 320 ? idx >> 1 : idx >> 2, cols == 320 ? (idx & 1) * 20 : (idx & 3) * 10, cols >> 4);
            if (warp < 4) bar_arrive(7, 256);
          }
        }
        __syncwarp();
        if (elect()) mbar_arrive(done + 8 * (n & 3));
#pragma unroll
        for (int i = 0; i < 48; i++) pend.w[i] = 0;
      }
      if ((code & C_LATE) && warp == 4 && elect()) mbar_arrive(bGo);
      ITEM(code & 0xfffff, 1);
    }
  }
}

constexpr int AB_SMEM = 1024 + 2 * 98304 + 256;
#define AB_N 32
#define AB_WG 4
constexpr int AB_T = AB_WG * 128, AB_PASS = 8 / AB_WG;
__device__ __forceinline__ float ex2_poly(float t) {
  const uint32_t r = __float_as_uint(t) & 0xffff8000u;
  const float f = t - __uint_as_float(r);
  const float p = fmaf(fmaf(fmaf(-5.869912678e-38f, f, -1.700740250e-37f), f, -5.234869734e-37f), f, -7.522601252e-37f);
  uint32_t y;
  asm("mad.lo.u32 %0, %1, 256, %2;" : "=r"(y) : "r"(r), "r"(__float_as_uint(p)));
  return __uint_as_float(y);
}
__device__ __forceinline__ uint32_t hsq(uint32_t w, uint32_t c) { uint32_t r; asm("fma.rn.bf16x2 %0, %1, %1, %2;" : "=r"(r) : "r"(w), "r"(c)); return r; }
__device__ __forceinline__ float sq2(uint32_t w) { const float a = bf_lo(w), b = bf_hi(w); return fmaf(a, a, b * b); }

__device__ __forceinline__ void attn_b_store(const float* o, int h, int row0, int lane) {
  const int g = lane >> 2, c = lane & 3;
  const float i0 = 1.f / __shfl_sync(~0u, o[8], (lane & ~3) | 2), i1 = 1.f / __shfl_sync(~0u, o[10], (lane & ~3) | 2);
#pragma unroll
  for (int jj = 0; jj < 3; jj++) {
    if (jj < 2 || c < 2) {
      const int col = h * 20 + 8 * jj + 2 * c;
      g_of[core_word(row0 + g, col)] = pack2(o[4 * jj] * i0, o[4 * jj + 1] * i0);
      g_of[core_word(row0 + g + 8, col)] = pack2(o[4 * jj + 2] * i1, o[4 * jj + 3] * i1);
    }
  }
}

__device__ __forceinline__ void attn_b_qk(float* s, uint32_t q0, uint32_t q1, uint32_t q2, uint32_t q3, uint32_t q4, uint32_t q5, uint32_t z0, uint32_t z1,
                                          uint64_t dk, uint64_t dk2) {
  wg_rs32_00(s, q0, q1, q2, q3, dk, 0);
  wg_rs32_00(s, q4, q5, z0, z1, dk2, 1);
}

struct AttnParams { const uint8_t* pf[4]; uint32_t *sync, *next; };
__global__ void __launch_bounds__(AB_T + 128, 1) attn_b_kernel(const __grid_constant__ AttnParams p) {
  extern __shared__ uint8_t smem_raw[];
  const uint32_t sb = (s2u(smem_raw) + 1023) & ~1023u, sK = sb, sV = sb + 98304, bars = sb + 2 * 98304;
  const int warp = __shfl_sync(~0u, threadIdx.x >> 5, 0), lane = threadIdx.x & 31;
  const int h = blockIdx.x & 31, quarter = blockIdx.x >> 5;
  BT(0);
  TRACE(0);
  if (threadIdx.x == 0) {
    for (int i = 0; i < 8; i++) mbar_init(bars + 8 * i, 1);
    mbar_init(bars + 128, AB_T / 32);
    mbar_init(bars + 136, 2);
    asm volatile("fence.mbarrier_init.release.cluster;" ::: "memory");
  }
  __syncthreads();
  if (warp >= AB_T / 32) {
    asm volatile("setmaxnreg.dec.sync.aligned.u32 32;");
    if (warp == AB_T / 32 + 1) return;
    if (warp > AB_T / 32) {
      uint32_t kmax = 0;
#pragma unroll 1
      for (int i = 0; i < 32; i++) {
        if (!(i & 3)) mbar_wait_uniform(bars + 2 * i, 0);
        const uint32_t a = sK + i * 3072 + ((threadIdx.x >> 3) & 7) * 384 + (lane & 7) * 16;
        const uint4 x = lds128(a), y = lds128(a + 128);
        const uint2 z = lds64(a + 256);
        const uint32_t n = hadd2(hsq(x.x, hsq(x.y, hsq(x.z, hsq(x.w, hsq(z.x, 0))))), hsq(y.x, hsq(y.y, hsq(y.z, hsq(y.w, hsq(z.y, 0))))));
        kmax = max(kmax, __float_as_uint(bf_lo(n) + bf_hi(n)) & 0x7fffffffu);
      }
      const uint32_t kbits = __reduce_max_sync(~0u, kmax);
      if (lane == 0) { sts32(bars + 64 + (warp & 1) * 4, kbits); mbar_arrive(bars + 136); }
      return;
    }
    const uint8_t* gk = reinterpret_cast<const uint8_t*>(g_bqkv + (32 + h) * 256 * 96);
    const uint8_t* gv = reinterpret_cast<const uint8_t*>(g_bqkv + (64 + h) * 256 * 96);
    uint32_t todo = 255;
    for (int spin = 0; todo;) {
      const uint32_t up = __ballot_sync(~0u, ld_acquire(p.sync + SY_P + (lane & 15) * 4 + 2) >= bq_items(lane & 15));
      fence_async_global();
      for (int i = 0; i < 8; i++) {
        if (!(todo >> i & 1) || (up >> 2 * i & 3) != 3) continue;
        todo &= ~(1u << i);
        if (elect()) {
          mbar_expect(bars + 8 * i, 24576);
          bulk_load(sK + i * 12288, gk + i * 12288, 12288, bars + 8 * i);
          bulk_load(sV + i * 12288, gv + i * 12288, 12288, bars + 8 * i);
        }
      }
      spin_guard(spin);
    }
    pdl_launch();
    TRACE(1);
    if (blockIdx.x < NSLOT) for (int i = lane; i < 512; i += 32) reinterpret_cast<uint4*>(pool_at(blockIdx.x * 8192))[i] = make_uint4(0, 0, 0, 0);
    if (!p.next && blockIdx.x == 127) for (int i = lane; i < 256; i += 32) { g_smpart[i] = 0; if (i < NSLOT) g_orient[i] = 0; }
    if (p.next) {
      mbar_wait_uniform(bars + 128, 0);
      if (quarter == 0 && lane == 0) red_release(p.next + SY_OB, 1);
      for (int i = 0; i < 32; i++) {
        if (elect()) prefetch_l2(p.pf[i >> 3] + blockIdx.x * 61440 + (i & 7) * 7680, 7680);
        __nanosleep(300);
      }
    }
    return;
  }
  asm volatile("setmaxnreg.inc.sync.aligned.u32 112;");
  constexpr int NT = SEQ / AB_N, PER = 256 / AB_N;
  uint32_t qn[8];
  auto load_q = [&](int pass) {
    const uint32_t* gq = g_bqkv + (h * 256 + pass * 128 + quarter * 32 + warp * 2) * 96 + lane;
#pragma unroll
    for (int i = 0; i < 8; i++) qn[i] = __ldcg(gq + (i & 1) * 96 + min(i >> 1, 2) * 32 + (i < 6 ? 0 : 3 - (lane & 3)));
  };
  mbar_wait_uniform(bars + 8 * quarter, 0);
  load_q(0);
#pragma unroll 1
  for (int pass = 0; pass < AB_PASS; pass++) {
    const int row0 = pass * 1024 + quarter * 256 + warp * 16;
    const uint32_t q0 = qn[0], q1 = qn[1], q2 = qn[2], q3 = qn[3], z0 = qn[6], z1 = qn[7];
    uint32_t q4 = qn[4], q5 = qn[5];
    if ((lane & 3) == 2) { q4 = 0x43BCu; q5 = 0x43BCu; }
    float o[12];
    uint64_t dk = mkdesc(sK, 128, 384, 0), dk2 = mkdesc(sK + 256, 0, 384, 0), dv = mkdesc(sV, 384, 128, 0);
    float sa[AB_N / 2], sb2[AB_N / 2];
    uint32_t pa[AB_N / 4], pb[AB_N / 4];
    if (pass == 0) mbar_wait_uniform(bars, 0);
    BT(1 + 2 * pass);
    wg_fence();
    attn_b_qk(sa, q0, q1, q2, q3, q4, q5, z0, z1, dk, dk2);
    wg_commit();
    attn_b_qk(sb2, q0, q1, q2, q3, q4, q5, z0, z1, dk + AB_N * 3, dk2 + AB_N * 3);
    wg_commit();
#pragma unroll 1
    for (int kt = 0; kt < NT; kt += 2) {
      const int nx = kt + 2 < NT ? kt + 2 : 0;
      if (pass == 0 && (nx & (PER - 1)) == 0) mbar_wait_uniform(bars + 8 * (nx / PER), 0);
      const uint64_t nk = dk + nx * (AB_N * 3), nk2 = dk2 + nx * (AB_N * 3);
      wg_wait<1>();
      reg_fence<AB_N / 2>(sa);
#pragma unroll
      for (int i = 0; i < AB_N / 4; i++) pa[i] = pack2(ex2(sa[2 * i]), poly_group(i >> 1) ? ex2_poly(sa[2 * i + 1]) : ex2(sa[2 * i + 1]));
      wg_fence();
#pragma unroll
      for (int kk = 0; kk < AB_N / 16; kk++) wg_rs24_01(o, pa[4 * kk], pa[4 * kk + 1], pa[4 * kk + 2], pa[4 * kk + 3], dv + kk * 48, kk | kt);
      attn_b_qk(sa, q0, q1, q2, q3, q4, q5, z0, z1, nk, nk2);
      wg_commit();
      wg_wait<1>();
      reg_fence<AB_N / 2>(sb2);
#pragma unroll
      for (int i = 0; i < AB_N / 4; i++) pb[i] = pack2(ex2(sb2[2 * i]), poly_group((i >> 1) + AB_N / 8) ? ex2_poly(sb2[2 * i + 1]) : ex2(sb2[2 * i + 1]));
      wg_fence();
#pragma unroll
      for (int kk = 0; kk < AB_N / 16; kk++) wg_rs24_01(o, pb[4 * kk], pb[4 * kk + 1], pb[4 * kk + 2], pb[4 * kk + 3], dv + AB_N * 3 + kk * 48, 1);
      attn_b_qk(sb2, q0, q1, q2, q3, q4, q5, z0, z1, nk + AB_N * 3, nk2 + AB_N * 3);
      wg_commit();
      dv += AB_N * 6;
    }
    wg_wait<0>();
    reg_fence<12>(o); reg_fence<AB_N / 2>(sa); reg_fence<AB_N / 2>(sb2);
    BT(2 + 2 * pass);
    if (pass + 1 < AB_PASS) load_q(pass + 1);
    mbar_wait_uniform(bars + 136, 0);
    const uint2 kb = lds64(bars + 64);
    const float kmax = __uint_as_float(max(kb.x, kb.y));
    if ((lane & 3) == 2) q4 = q5 = 0;
    float n0 = sq2(q0) + sq2(q2) + sq2(q4), n1 = sq2(q1) + sq2(q3) + sq2(q5);
    n0 += __shfl_xor_sync(~0u, n0, 1); n1 += __shfl_xor_sync(~0u, n1, 1);
    n0 += __shfl_xor_sync(~0u, n0, 2); n1 += __shfl_xor_sync(~0u, n1, 2);
    uint32_t redo;
    asm volatile("{.reg .pred p, q; setp.ne.u32 p, %1, 0; bar.red.or.pred q, %2, 128, p; selp.u32 %0, 1, 0, q;}"
                 : "=r"(redo) : "r"((uint32_t)!(n0 * kmax <= 9500.f && n1 * kmax <= 9500.f)), "r"(2 + (warp >> 2)) : "memory");
    if (redo) {
#pragma unroll
      for (int i = 0; i < 12; i++) o[i] = 0.f;
      float m0 = -INFINITY, m1 = -INFINITY;
#pragma unroll 1
      for (int kt = 0; kt < 64; kt++) {
        float s[16];
        wg_fence();
        wg_rs32_00(s, q0, q1, q2, q3, dk + kt * 96, 0);
        wg_rs32_00(s, q4, q5, z0, z1, dk2 + kt * 96, 1);
        wg_commit();
        wg_wait<0>();
        reg_fence<16>(s); reg_fence<12>(o);
        float n0 = m0, n1 = m1;
#pragma unroll
        for (int jj = 0; jj < 4; jj++) { n0 = fmaxf(n0, fmaxf(s[4 * jj], s[4 * jj + 1])); n1 = fmaxf(n1, fmaxf(s[4 * jj + 2], s[4 * jj + 3])); }
        n0 = fmaxf(n0, __shfl_xor_sync(~0u, n0, 1)); n0 = fmaxf(n0, __shfl_xor_sync(~0u, n0, 2));
        n1 = fmaxf(n1, __shfl_xor_sync(~0u, n1, 1)); n1 = fmaxf(n1, __shfl_xor_sync(~0u, n1, 2));
        const float r0 = ex2(m0 - n0), r1 = ex2(m1 - n1);
        m0 = n0; m1 = n1;
#pragma unroll
        for (int jj = 0; jj < 3; jj++) { o[4 * jj] *= r0; o[4 * jj + 1] *= r0; o[4 * jj + 2] *= r1; o[4 * jj + 3] *= r1; }
        uint32_t pp[8];
#pragma unroll
        for (int jj = 0; jj < 4; jj++) {
          pp[2 * jj] = pack2(ex2(s[4 * jj] - m0), ex2(s[4 * jj + 1] - m0));
          pp[2 * jj + 1] = pack2(ex2(s[4 * jj + 2] - m1), ex2(s[4 * jj + 3] - m1));
        }
        reg_fence<12>(o);
        wg_fence();
#pragma unroll
        for (int kk = 0; kk < 2; kk++) wg_rs24_01(o, pp[4 * kk], pp[4 * kk + 1], pp[4 * kk + 2], pp[4 * kk + 3], mkdesc(sV, 384, 128, 0) + kt * 96 + kk * 48, 1);
        wg_commit();
      }
      wg_wait<0>();
      reg_fence<12>(o);
    }
    attn_b_store(o, h, row0, lane);
    __syncwarp();
    if (pass == 0 && lane == 0) mbar_arrive(bars + 128);
  }
  BT(5);
  TRACE(2);
}

typedef CUresult (*EncodeFn)(CUtensorMap*, CUtensorMapDataType, cuuint32_t, void*, const cuuint64_t*, const cuuint64_t*,
                             const cuuint32_t*, const cuuint32_t*, CUtensorMapInterleave, CUtensorMapSwizzle,
                             CUtensorMapL2promotion, CUtensorMapFloatOOBfill);

void make_map(EncodeFn enc, CUtensorMap* m, const void* ptr, int cols, int rows, int box_rows, int box_cols = 64) {
  const cuuint64_t dims[2] = {(cuuint64_t)cols, (cuuint64_t)rows};
  const cuuint64_t strides[1] = {(cuuint64_t)cols * 2};
  const cuuint32_t box[2] = {(cuuint32_t)box_cols, (cuuint32_t)box_rows}, es[2] = {1, 1};
  enc(m, CU_TENSOR_MAP_DATA_TYPE_BFLOAT16, 2, const_cast<void*>(ptr), dims, strides, box, es, CU_TENSOR_MAP_INTERLEAVE_NONE,
      box_cols == 64 ? CU_TENSOR_MAP_SWIZZLE_128B : box_cols == 32 ? CU_TENSOR_MAP_SWIZZLE_64B : CU_TENSOR_MAP_SWIZZLE_NONE, CU_TENSOR_MAP_L2_PROMOTION_L2_256B, CU_TENSOR_MAP_FLOAT_OOB_FILL_NONE);
}
void make_map5(EncodeFn enc, CUtensorMap* m, const void* ptr, bool words, const cuuint64_t (&dims)[5], const cuuint64_t (&strides)[4], const cuuint32_t (&box)[5]) {
  const cuuint32_t es[5] = {1, 1, 1, 1, 1};
  enc(m, words ? CU_TENSOR_MAP_DATA_TYPE_UINT64 : CU_TENSOR_MAP_DATA_TYPE_BFLOAT16, 5, const_cast<void*>(ptr), dims, strides, box, es, CU_TENSOR_MAP_INTERLEAVE_NONE,
      words ? CU_TENSOR_MAP_SWIZZLE_NONE : CU_TENSOR_MAP_SWIZZLE_128B, dims[0] % 64 ? CU_TENSOR_MAP_L2_PROMOTION_L2_128B : CU_TENSOR_MAP_L2_PROMOTION_L2_256B,
      CU_TENSOR_MAP_FLOAT_OOB_FILL_NONE);
}
void make_tiles(EncodeFn enc, CUtensorMap* m, const void* ptr, cuuint64_t cols, cuuint64_t tile) {
  make_map5(enc, m, ptr, false, {tile, 1, 1, cols / tile, DM}, {tile * 2, tile * 2, tile * 2, cols * 2}, {64, 1, 1, 1, 64});
}
template <class... KA, class... A>
void launch(void (*kern)(KA...), int grid, int block, int smem, int cluster, bool pdl, A... args) {
  cudaFuncSetAttribute(kern, cudaFuncAttributeMaxDynamicSharedMemorySize, smem);
  cudaLaunchConfig_t cfg = {};
  cfg.gridDim = dim3(grid); cfg.blockDim = dim3(block); cfg.dynamicSmemBytes = smem; cfg.stream = cudaStreamPerThread;
  cudaLaunchAttribute at[2];
  int n = 0;
  if (cluster > 1) { at[n].id = cudaLaunchAttributeClusterDimension; at[n].val.clusterDim.x = cluster; at[n].val.clusterDim.y = 1; at[n].val.clusterDim.z = 1; n++; }
  if (pdl) { at[n].id = cudaLaunchAttributeProgrammaticStreamSerialization; at[n].val.programmaticStreamSerializationAllowed = 1; n++; }
  cfg.attrs = at; cfg.numAttrs = n;
  cudaLaunchKernelEx(&cfg, kern, args...);
}
template <class T> void* sym(T& s) { void* p = nullptr; cudaGetSymbolAddress(&p, s); return p; }

}

#define MODE(b) 0
extern "C" void kernel_launch(void* const* d_in, const int* in_sizes, int n_in, void* d_out, int out_size) {
  const __nv_bfloat16* x = (const __nv_bfloat16*)d_in[0];
  void* fn = nullptr; cudaDriverEntryPointQueryResult qr;
  cudaGetDriverEntryPoint("cuTensorMapEncodeTiled", &fn, cudaEnableDefault, &qr);
  EncodeFn enc = (EncodeFn)fn;

  WorkParams wk = {};
  ChainParams& ch = wk.ch;
  AttnParams at = {};
  make_map(enc, &ch.wq, d_in[2], HD, DM, 160); make_map(enc, &ch.wk, d_in[3], HD, DM, 160); make_map(enc, &ch.wv, d_in[4], HD, DM, 160);
  make_map(enc, &ch.wo, d_in[5], DM, HD, 192, 32);
  ch.mem0 = (const __nv_bfloat16*)d_in[1];
  ch.wb = (const uint8_t*)d_in[8];
  ch.d1 = 300; ch.d2 = 300; ch.dn = 250; ch.dx = 900;
  make_tiles(enc, &wk.wq, d_in[2], HD, 192);
  for (int i = 0; i < 3; i++) make_tiles(enc, &wk.wb[i], d_in[8], 1920, 80 << i);
  for (int i = 0; i < 2; i++) make_tiles(enc, &wk.wc[i], d_in[9], DM, 80 << 2 * i);
  make_map(enc, &wk.out, d_out, DM, SEQ, 16, 80);
  make_map5(enc, &wk.wo, d_in[5], false, {DM, 2, 4, 4, HD / 32}, {DM * 2, DM * 16, DM * 4, DM * 64}, {64, 2, 4, 4, 2});
  make_map5(enc, &wk.xn, sym(g_xn), true, {1280, 2, 2, 64, 1}, {10240, 20480, 40960, 40960}, {128, 2, 2, 4, 1});
  make_map5(enc, &wk.xp, sym(g_xn), true, {1280, 2, 1, 64, 2}, {10240, 10240, 40960, 20480}, {128, 2, 1, 4, 2});
  wk.x = x;
  for (int i = 0; i < 4; i++) at.pf[i] = (const uint8_t*)d_in[i < 2 ? 3 + i : i == 2 ? 2 : 5];
  int qa_end[2] = {12, 12};
  for (int layer = 0; layer < 2; layer++) {
    ch.sync = wk.sync = at.sync = (uint32_t*)sym(g_sync) + layer * SY_N;
    ch.other = (uint32_t*)sym(g_sync) + (1 - layer) * SY_N;
    ch.layer = layer;
    at.next = layer ? nullptr : ch.other;
    wk.qa_end = qa_end[layer];
    wk.kind = layer ? WK_LEAD : WK_FIRST;
    launch(work_kernel, 132, 384, CH_SMEM, 1, layer != 0, wk);
    wk.kind = WK_CHAIN;
    launch(work_kernel, 96, 384, CH_SMEM, 3, true, wk);
    launch(attn_b_kernel, 128, AB_T + 128, AB_SMEM, 1, true, at);
  }
  wk.kind = WK_LAST;
  launch(work_kernel, 128, 384, CH_SMEM, 1, true, wk);
}
```

```cpp
#include <cuda_runtime.h>
#include <cuda_bf16.h>
#include <cuda.h>
#include <stdint.h>
#include <stdlib.h>

namespace {

constexpr int SEQ = 2048, DM = 640, HD = 6144, NSEG = 64;
constexpr int SPIN_LIMIT = 1 << 20;

__device__ __align__(128) uint2 g_x[256 * 17 * 1280];
__device__ __align__(128) uint32_t g_xn[SEQ * DM / 2];
__device__ __align__(128) uint32_t g_of[SEQ * DM / 2];
__device__ __align__(128) uint4 g_o[SEQ * HD / 8];
__device__ __align__(128) uint4 g_q[SEQ * HD / 8];
constexpr int KV_M = 16384, KV_PART = 20480, KV_V = 3 * KV_PART;
__device__ __align__(128) uint8_t g_kv[16 * 32 * 6 * KV_PART];
#define OP_B8 11
#define OP_B16 14
#define OP_N4 15
#define BQ_12 12
#define BQ_24 14
#define FIN_16 12
__host__ __device__ constexpr int op_split(int b) { return b < OP_B8 ? 4 : b < OP_B16 ? 8 : 16; }
__host__ __device__ constexpr int op_tiles(int b) { return b < OP_N4 ? 2 : 4; }
__host__ __device__ constexpr int fin_items(int b) { return b < OP_B8 ? 4 : b < FIN_16 ? 8 : 16; }
__host__ __device__ constexpr int bq_items(int b) { return b < BQ_12 ? 6 : b < BQ_24 ? 12 : 24; }
__host__ __device__ constexpr int ln_items(int layer, int b) { return layer == 0 && b < 2 ? 16 : 4; }
constexpr int SY_P = 128, SY_T = 192, SY_UP = 224, SY_OB = 225, SY_PRE = 256, SY_PART = 288, SY_TIME = 384, SY_N = 448;
__device__ __align__(128) uint32_t g_sync[2 * SY_N];
constexpr int NSLOT = 92;
__device__ uint32_t g_pool[(NSLOT + 2) * 2048];
__device__ uint32_t g_smpart[256], g_orient[NSLOT];
__device__ __align__(128) uint32_t g_bqkv[3 * 32 * 256 * 96];

#define BT(i)
#define MISS(k, n)
#define PRO(i)
#define TRACE(w)
#define ITEM(code, w)
#define STAT(k)
#define TMV(i, v)
#define TM(i)
#define TMD(i, dep)

__device__ __forceinline__ uint32_t gtime() { uint32_t c; asm volatile("mov.u32 %0, %%globaltimer_lo;" : "=r"(c) :: "memory"); return c; }
__device__ __forceinline__ uint32_t clk32() { uint32_t c; asm volatile("mov.u32 %0, %%clock;" : "=r"(c) :: "memory"); return c; }
__device__ __forceinline__ uint32_t fresh_tid() { uint32_t t; asm volatile("mov.u32 %0, %%tid.x;" : "=r"(t)); return t; }
__device__ __forceinline__ uint32_t s2u(const void* p) { return (uint32_t)__cvta_generic_to_shared(p); }
__device__ __forceinline__ uint32_t pack2(float a, float b) {
  uint32_t r; asm("cvt.rn.bf16x2.f32 %0, %1, %2;" : "=r"(r) : "f"(b), "f"(a)); return r; }
__device__ __forceinline__ float bf_lo(uint32_t w) { return __uint_as_float(w << 16); }
__device__ __forceinline__ float bf_hi(uint32_t w) { return __uint_as_float(w & 0xffff0000u); }
__device__ __forceinline__ float ex2(float x) { float y; asm("ex2.approx.ftz.f32 %0, %1;" : "=f"(y) : "f"(x)); return y; }

__device__ __forceinline__ void mbar_init(uint32_t bar, uint32_t n) {
  asm volatile("mbarrier.init.shared::cta.b64 [%0], %1;" :: "r"(bar), "r"(n) : "memory"); }
__device__ __forceinline__ void mbar_expect(uint32_t bar, uint32_t bytes) {
  asm volatile("mbarrier.arrive.expect_tx.shared::cta.b64 _, [%0], %1;" :: "r"(bar), "r"(bytes) : "memory"); }
__device__ __forceinline__ void mbar_arrive(uint32_t bar) {
  asm volatile("mbarrier.arrive.shared::cta.b64 _, [%0];" :: "r"(bar) : "memory"); }
__device__ __forceinline__ void mbar_arrive_remote(uint32_t bar) {
  asm volatile("mbarrier.arrive.shared::cluster.b64 _, [%0];" :: "r"(bar) : "memory"); }
__device__ __forceinline__ void mbar_wait_slow(uint32_t bar, uint32_t ph) {
  asm volatile("{.reg .pred p; .reg .u32 n; mov.u32 n, 0;\n"
               "W: mbarrier.try_wait.parity.shared::cta.b64 p, [%0], %1; @p bra D;\n"
               "add.u32 n, n, 1; setp.gt.u32 p, n, %2; @p trap; bra W;\n"
               "D: }" :: "r"(bar), "r"(ph), "n"(SPIN_LIMIT) : "memory");
}
__device__ __forceinline__ void mbar_wait(uint32_t bar, uint32_t ph) {
  uint32_t ok;
  asm volatile("{.reg .pred p; mbarrier.try_wait.parity.shared::cta.b64 p, [%1], %2; selp.u32 %0, 1, 0, p;}" : "=r"(ok) : "r"(bar), "r"(ph) : "memory");
  if (__builtin_expect(!ok, 0)) mbar_wait_slow(bar, ph);
}
__device__ __forceinline__ void mbar_wait_uniform(uint32_t bar, uint32_t ph) {
  asm volatile("{.reg .pred p; .reg .u32 n; mov.u32 n, 0;\n"
               "W: mbarrier.try_wait.parity.shared::cta.b64 p, [%0], %1; vote.sync.all.pred p, p, 0xffffffff; @p bra.uni D;\n"
               "add.u32 n, n, 1; setp.gt.u32 p, n, %2; @p trap; bra.uni W;\n"
               "D: }" :: "r"(bar), "r"(ph), "n"(SPIN_LIMIT) : "memory");
}
__device__ __forceinline__ bool elect() {
  uint32_t p; asm volatile("{.reg .pred q; elect.sync _|q, 0xffffffff; selp.u32 %0, 1, 0, q;}" : "=r"(p)); return p; }
__device__ __forceinline__ void mbar_wait_cluster(uint32_t bar, uint32_t ph) {
  asm volatile("{.reg .pred p; .reg .u32 n; mov.u32 n, 0;\n"
               "W: mbarrier.try_wait.parity.acquire.cluster.shared::cta.b64 p, [%0], %1; @p bra D;\n"
               "add.u32 n, n, 1; setp.gt.u32 p, n, %2; @p trap; bra W;\n"
               "D: }" :: "r"(bar), "r"(ph), "n"(SPIN_LIMIT) : "memory");
}
__device__ __forceinline__ void spin_guard(int& n) {
  asm volatile("{.reg .pred p; add.s32 %0, %0, 1; setp.gt.s32 p, %0, %1; @p trap;}" : "+r"(n) : "n"(SPIN_LIMIT));
}
__device__ __forceinline__ void pdl_wait() { asm volatile("griddepcontrol.wait;" ::: "memory"); TRACE(1); }
__device__ __forceinline__ void pdl_launch() { asm volatile("griddepcontrol.launch_dependents;" ::: "memory"); }
__device__ __forceinline__ uint32_t ld_acquire(const uint32_t* p) { uint32_t v; asm volatile("ld.acquire.gpu.global.u32 %0, [%1];" : "=r"(v) : "l"(p) : "memory"); return v; }
__device__ __forceinline__ void red_release(uint32_t* p, uint32_t v) { asm volatile("red.release.gpu.global.add.u32 [%0], %1;" :: "l"(p), "r"(v) : "memory"); }
__device__ __forceinline__ void fence_async_global() { asm volatile("fence.proxy.async.global;" ::: "memory"); }
__device__ __forceinline__ void fence_async() { asm volatile("fence.proxy.async.shared::cta;" ::: "memory"); }
__device__ __forceinline__ void bar_sync(int id, int n) { asm volatile("bar.sync %0, %1;" :: "r"(id), "r"(n) : "memory"); }
__device__ __forceinline__ void bar_arrive(int id, int n) { asm volatile("bar.arrive %0, %1;" :: "r"(id), "r"(n) : "memory"); }
__device__ __forceinline__ void tma_load(uint32_t dst, const CUtensorMap* m, int c0, int c1, uint32_t bar) {
  asm volatile("cp.async.bulk.tensor.2d.shared::cluster.global.mbarrier::complete_tx::bytes [%0], [%1, {%3, %4}], [%2];"
               :: "r"(dst), "l"(m), "r"(bar), "r"(c0), "r"(c1) : "memory"); }
__device__ __forceinline__ void tma_load5(uint32_t dst, const CUtensorMap* m, int c0, int c3, int c4, uint32_t bar) {
  asm volatile("cp.async.bulk.tensor.5d.shared::cluster.global.mbarrier::complete_tx::bytes [%0], [%1, {%3, %6, %6, %4, %5}], [%2];"
               :: "r"(dst), "l"(m), "r"(bar), "r"(c0), "r"(c3), "r"(c4), "r"(0) : "memory"); }
__device__ __forceinline__ void tma_store(const CUtensorMap* m, uint32_t src, int c0, int c1) {
  asm volatile("cp.async.bulk.tensor.2d.global.shared::cta.bulk_group [%0, {%2, %3}], [%1];"
               :: "l"(m), "r"(src), "r"(c0), "r"(c1) : "memory"); }
__device__ __forceinline__ uint64_t evict_first() { uint64_t p; asm("createpolicy.fractional.L2::evict_first.b64 %0, 1.0;" : "=l"(p)); return p; }
__device__ __forceinline__ void bulk_load_last(uint32_t dst, const void* src, uint32_t bytes, uint32_t bar) {
  asm volatile("cp.async.bulk.shared::cluster.global.mbarrier::complete_tx::bytes.L2::cache_hint [%0], [%1], %2, [%3], %4;"
               :: "r"(dst), "l"(src), "r"(bytes), "r"(bar), "l"(evict_first()) : "memory"); }
__device__ __forceinline__ void bulk_store_stream(void* dst, uint32_t src, uint32_t bytes) {
  asm volatile("cp.async.bulk.global.shared::cta.bulk_group.L2::cache_hint [%0], [%1], %2, %3;" :: "l"(dst), "r"(src), "r"(bytes), "l"(evict_first()) : "memory"); }
__device__ __forceinline__ void bulk_load(uint32_t dst, const void* src, uint32_t bytes, uint32_t bar) {
  asm volatile("cp.async.bulk.shared::cluster.global.mbarrier::complete_tx::bytes [%0], [%1], %2, [%3];"
               :: "r"(dst), "l"(src), "r"(bytes), "r"(bar) : "memory"); }
__device__ __forceinline__ void bulk_push(uint32_t dst, uint32_t src, uint32_t bytes, uint32_t bar) {
  asm volatile("cp.async.bulk.shared::cluster.shared::cta.mbarrier::complete_tx::bytes [%0], [%1], %2, [%3];"
               :: "r"(dst), "r"(src), "r"(bytes), "r"(bar) : "memory"); }
__device__ __forceinline__ void bulk_store(void* dst, uint32_t src, uint32_t bytes) {
  asm volatile("cp.async.bulk.global.shared::cta.bulk_group [%0], [%1], %2;" :: "l"(dst), "r"(src), "r"(bytes) : "memory"); }
__device__ __forceinline__ void bulk_commit() { asm volatile("cp.async.bulk.commit_group;" ::: "memory"); }
template <int N> __device__ __forceinline__ void bulk_wait_read() { asm volatile("cp.async.bulk.wait_group.read %0;" :: "n"(N) : "memory"); }
template <int N> __device__ __forceinline__ void bulk_wait() { asm volatile("cp.async.bulk.wait_group %0;" :: "n"(N) : "memory"); }

__device__ __forceinline__ uint64_t mkdesc(uint32_t addr, uint32_t lbo, uint32_t sbo, uint32_t sw) {
  return (uint64_t)((addr & 0x3FFFF) >> 4) | ((uint64_t)(lbo >> 4) << 16) | ((uint64_t)(sbo >> 4) << 32) | ((uint64_t)sw << 62); }
__device__ __forceinline__ void wg_fence() { asm volatile("wgmma.fence.sync.aligned;" ::: "memory"); }
__device__ __forceinline__ void wg_commit() { asm volatile("wgmma.commit_group.sync.aligned;" ::: "memory"); }
template <int N> __device__ __forceinline__ void wg_wait() { asm volatile("wgmma.wait_group.sync.aligned %0;" :: "n"(N) : "memory"); }
template <int N> __device__ __forceinline__ void reg_fence(float* d) {
#pragma unroll
  for (int i = 0; i < N; i++) asm volatile("" : "+f"(d[i]) :: "memory");
}

__device__ __forceinline__ void mma16(float* d, uint32_t a0, uint32_t a1, uint32_t a2, uint32_t a3, uint32_t b0, uint32_t b1) {
  asm volatile("mma.sync.aligned.m16n8k16.row.col.f32.bf16.bf16.f32 {%0,%1,%2,%3},{%4,%5,%6,%7},{%8,%9},{%0,%1,%2,%3};"
               : "+f"(d[0]), "+f"(d[1]), "+f"(d[2]), "+f"(d[3]) : "r"(a0), "r"(a1), "r"(a2), "r"(a3), "r"(b0), "r"(b1)); }
__device__ __forceinline__ void mma8(float* d, uint32_t a0, uint32_t a1, uint32_t b0) {
  asm volatile("mma.sync.aligned.m16n8k8.row.col.f32.bf16.bf16.f32 {%0,%1,%2,%3},{%4,%5},{%6},{%0,%1,%2,%3};"
               : "+f"(d[0]), "+f"(d[1]), "+f"(d[2]), "+f"(d[3]) : "r"(a0), "r"(a1), "r"(b0)); }
__device__ __forceinline__ void ldsm4(uint32_t* r, uint32_t a) {
  asm volatile("ldmatrix.sync.aligned.m8n8.x4.shared.b16 {%0,%1,%2,%3},[%4];" : "=r"(r[0]), "=r"(r[1]), "=r"(r[2]), "=r"(r[3]) : "r"(a) : "memory"); }
__device__ __forceinline__ uint4 ldsm4v(uint32_t a) { uint32_t r[4]; ldsm4(r, a); return make_uint4(r[0], r[1], r[2], r[3]); }
__device__ __forceinline__ void ldsm4t(uint32_t* r, uint32_t a) {
  asm volatile("ldmatrix.sync.aligned.m8n8.x4.trans.shared.b16 {%0,%1,%2,%3},[%4];" : "=r"(r[0]), "=r"(r[1]), "=r"(r[2]), "=r"(r[3]) : "r"(a) : "memory"); }
__device__ __forceinline__ void ldsm2t(uint32_t* r, uint32_t a) {
  asm volatile("ldmatrix.sync.aligned.m8n8.x2.trans.shared.b16 {%0,%1},[%2];" : "=r"(r[0]), "=r"(r[1]) : "r"(a) : "memory"); }
__device__ __forceinline__ void stsm4(uint32_t a, uint32_t r0, uint32_t r1, uint32_t r2, uint32_t r3) {
  asm volatile("stmatrix.sync.aligned.m8n8.x4.shared.b16 [%0], {%1,%2,%3,%4};" :: "r"(a), "r"(r0), "r"(r1), "r"(r2), "r"(r3) : "memory"); }
__device__ __forceinline__ void stsm4t(uint32_t a, uint32_t r0, uint32_t r1, uint32_t r2, uint32_t r3) {
  asm volatile("stmatrix.sync.aligned.m8n8.x4.trans.shared.b16 [%0], {%1,%2,%3,%4};" :: "r"(a), "r"(r0), "r"(r1), "r"(r2), "r"(r3) : "memory"); }
__device__ __forceinline__ void stsm2(uint32_t a, uint32_t r0, uint32_t r1) {
  asm volatile("stmatrix.sync.aligned.m8n8.x2.shared.b16 [%0], {%1,%2};" :: "r"(a), "r"(r0), "r"(r1) : "memory"); }
__device__ __forceinline__ void stsm2t(uint32_t a, uint32_t r0, uint32_t r1) {
  asm volatile("stmatrix.sync.aligned.m8n8.x2.trans.shared.b16 [%0], {%1,%2};" :: "r"(a), "r"(r0), "r"(r1) : "memory"); }
__device__ __forceinline__ void sts32(uint32_t a, uint32_t v) { asm volatile("st.shared.b32 [%0], %1;" :: "r"(a), "r"(v) : "memory"); }
__device__ __forceinline__ void sts64f(uint32_t a, float x, float y) { asm volatile("st.shared.v2.f32 [%0], {%1,%2};" :: "r"(a), "f"(x), "f"(y) : "memory"); }
__device__ __forceinline__ void sts128(uint32_t a, uint4 v) {
  asm volatile("st.shared.v4.b32 [%0], {%1,%2,%3,%4};" :: "r"(a), "r"(v.x), "r"(v.y), "r"(v.z), "r"(v.w) : "memory"); }
__device__ __forceinline__ void sts128f(uint32_t a, float x, float y, float z, float w) {
  asm volatile("st.shared.v4.f32 [%0], {%1,%2,%3,%4};" :: "r"(a), "f"(x), "f"(y), "f"(z), "f"(w) : "memory"); }
__device__ __forceinline__ float lds32f(uint32_t a) { float v; asm volatile("ld.shared.f32 %0, [%1];" : "=f"(v) : "r"(a) : "memory"); return v; }
__device__ __forceinline__ float2 lds64f(uint32_t a) { float2 v; asm volatile("ld.shared.v2.f32 {%0,%1}, [%2];" : "=f"(v.x), "=f"(v.y) : "r"(a) : "memory"); return v; }
__device__ __forceinline__ float4 lds128f(uint32_t a) {
  float4 v; asm volatile("ld.shared.v4.f32 {%0,%1,%2,%3}, [%4];" : "=f"(v.x), "=f"(v.y), "=f"(v.z), "=f"(v.w) : "r"(a) : "memory"); return v; }
__device__ __forceinline__ uint4 lds128(uint32_t a) {
  uint4 v; asm volatile("ld.shared.v4.b32 {%0,%1,%2,%3}, [%4];" : "=r"(v.x), "=r"(v.y), "=r"(v.z), "=r"(v.w) : "r"(a) : "memory"); return v; }
__device__ __forceinline__ uint4 ldg_strong128(const void* p) {
  uint4 v; asm volatile("ld.relaxed.gpu.global.v4.u32 {%0,%1,%2,%3}, [%4];" : "=r"(v.x), "=r"(v.y), "=r"(v.z), "=r"(v.w) : "l"(p) : "memory"); return v; }
__device__ __forceinline__ uint2 ldg_strong64(const void* p) {
  uint2 v; asm volatile("ld.relaxed.gpu.global.v2.u32 {%0,%1}, [%2];" : "=r"(v.x), "=r"(v.y) : "l"(p) : "memory"); return v; }
__device__ __forceinline__ void stg_strong32(void* p, uint32_t v) { asm volatile("st.relaxed.gpu.global.u32 [%0], %1;" :: "l"(p), "r"(v) : "memory"); }
__device__ __forceinline__ void stg_strong128(void* p, uint4 v) {
  asm volatile("st.relaxed.gpu.global.v4.u32 [%0], {%1,%2,%3,%4};" :: "l"(p), "r"(v.x), "r"(v.y), "r"(v.z), "r"(v.w) : "memory"); }
__device__ __forceinline__ uint32_t mapa(uint32_t a, uint32_t r) {
  uint32_t o; asm("mapa.shared::cluster.u32 %0, %1, %2;" : "=r"(o) : "r"(a), "r"(r)); return o; }
__device__ __forceinline__ void st_async2f(uint32_t a, float x, float y, uint32_t bar) {
  asm volatile("st.async.shared::cluster.mbarrier::complete_tx::bytes.v2.f32 [%0], {%1,%2}, [%3];" :: "r"(a), "f"(x), "f"(y), "r"(bar) : "memory"); }
__device__ __forceinline__ void st_async32(uint32_t a, uint32_t x, uint32_t bar) {
  asm volatile("st.async.shared::cluster.mbarrier::complete_tx::bytes.b32 [%0], %1, [%2];" :: "r"(a), "r"(x), "r"(bar) : "memory"); }
__device__ __forceinline__ uint32_t lds32(uint32_t a) { uint32_t v; asm volatile("ld.shared.b32 %0, [%1];" : "=r"(v) : "r"(a) : "memory"); return v; }
__device__ __forceinline__ void st_async64(uint32_t a, uint32_t x, uint32_t y, uint32_t bar, uint32_t on) {
  asm volatile("{.reg .pred p; setp.ne.u32 p, %4, 0; @p st.async.shared::cluster.mbarrier::complete_tx::bytes.v2.b32 [%0], {%1,%2}, [%3];}" :: "r"(a), "r"(x), "r"(y), "r"(bar), "r"(on) : "memory"); }
__device__ __forceinline__ void st_async128(uint32_t a, uint4 v, uint32_t bar) {
  asm volatile("st.async.shared::cluster.mbarrier::complete_tx::bytes.v4.b32 [%0], {%1,%2,%3,%4}, [%5];" :: "r"(a), "r"(v.x), "r"(v.y), "r"(v.z), "r"(v.w), "r"(bar) : "memory"); }
__device__ __forceinline__ uint2 lds64(uint32_t a) { uint2 v; asm volatile("ld.shared.v2.b32 {%0,%1}, [%2];" : "=r"(v.x), "=r"(v.y) : "r"(a) : "memory"); return v; }
__device__ __forceinline__ void sts64(uint32_t a, uint32_t x, uint32_t y) { asm volatile("st.shared.v2.b32 [%0], {%1,%2};" :: "r"(a), "r"(x), "r"(y) : "memory"); }
__device__ __forceinline__ uint32_t ldg_strong32(const void* p) { uint32_t v; asm volatile("ld.relaxed.gpu.global.u32 %0, [%1];" : "=r"(v) : "l"(p) : "memory"); return v; }
__device__ __forceinline__ uint32_t transpose8(uint32_t x) { uint32_t r; asm volatile("movmatrix.sync.aligned.m8n8.trans.b16 %0, %1;" : "=r"(r) : "r"(x)); return r; }
__device__ __forceinline__ uint32_t hadd2(uint32_t a, uint32_t b) { uint32_t r; asm("add.rn.bf16x2 %0, %1, %2;" : "=r"(r) : "r"(a), "r"(b)); return r; }
__device__ __forceinline__ uint32_t min4(uint4 v) { return min(__vimin3_u32(v.x, v.y, v.z), v.w); }

__device__ __forceinline__ void wg_ss192_01(float* d, uint64_t da, uint64_t db, int sd) {
  asm volatile("{.reg .pred p; setp.ne.b32 p, %98, 0;\n"
    "wgmma.mma_async.sync.aligned.m64n192k16.f32.bf16.bf16 {%0,%1,%2,%3,%4,%5,%6,%7,%8,%9,%10,%11,%12,%13,%14,%15,%16,%17,%18,%19,%20,%21,%22,%23,%24,%25,%26,%27,%28,%29,%30,%31,%32,%33,%34,%35,%36,%37,%38,%39,%40,%41,%42,%43,%44,%45,%46,%47,%48,%49,%50,%51,%52,%53,%54,%55,%56,%57,%58,%59,%60,%61,%62,%63,%64,%65,%66,%67,%68,%69,%70,%71,%72,%73,%74,%75,%76,%77,%78,%79,%80,%81,%82,%83,%84,%85,%86,%87,%88,%89,%90,%91,%92,%93,%94,%95}, %96, %97, p, 1, 1, 0, 1;}"
    : "+f"(d[0]),"+f"(d[1]),"+f"(d[2]),"+f"(d[3]),"+f"(d[4]),"+f"(d[5]),"+f"(d[6]),"+f"(d[7]),"+f"(d[8]),"+f"(d[9]),"+f"(d[10]),"+f"(d[11]),"+f"(d[12]),"+f"(d[13]),"+f"(d[14]),"+f"(d[15]),"+f"(d[16]),"+f"(d[17]),"+f"(d[18]),"+f"(d[19]),"+f"(d[20]),"+f"(d[21]),"+f"(d[22]),"+f"(d[23]),"+f"(d[24]),"+f"(d[25]),"+f"(d[26]),"+f"(d[27]),"+f"(d[28]),"+f"(d[29]),"+f"(d[30]),"+f"(d[31]),"+f"(d[32]),"+f"(d[33]),"+f"(d[34]),"+f"(d[35]),"+f"(d[36]),"+f"(d[37]),"+f"(d[38]),"+f"(d[39]),"+f"(d[40]),"+f"(d[41]),"+f"(d[42]),"+f"(d[43]),"+f"(d[44]),"+f"(d[45]),"+f"(d[46]),"+f"(d[47]),"+f"(d[48]),"+f"(d[49]),"+f"(d[50]),"+f"(d[51]),"+f"(d[52]),"+f"(d[53]),"+f"(d[54]),"+f"(d[55]),"+f"(d[56]),"+f"(d[57]),"+f"(d[58]),"+f"(d[59]),"+f"(d[60]),"+f"(d[61]),"+f"(d[62]),"+f"(d[63]),"+f"(d[64]),"+f"(d[65]),"+f"(d[66]),"+f"(d[67]),"+f"(d[68]),"+f"(d[69]),"+f"(d[70]),"+f"(d[71]),"+f"(d[72]),"+f"(d[73]),"+f"(d[74]),"+f"(d[75]),"+f"(d[76]),"+f"(d[77]),"+f"(d[78]),"+f"(d[79]),"+f"(d[80]),"+f"(d[81]),"+f"(d[82]),"+f"(d[83]),"+f"(d[84]),"+f"(d[85]),"+f"(d[86]),"+f"(d[87]),"+f"(d[88]),"+f"(d[89]),"+f"(d[90]),"+f"(d[91]),"+f"(d[92]),"+f"(d[93]),"+f"(d[94]),"+f"(d[95])
    : "l"(da), "l"(db), "r"(sd));
}
__device__ __forceinline__ void wg_ss128_01(float* d, uint64_t da, uint64_t db, int sd) {
  asm volatile("{.reg .pred p; setp.ne.b32 p, %66, 0;\n"
    "wgmma.mma_async.sync.aligned.m64n128k16.f32.bf16.bf16 {%0,%1,%2,%3,%4,%5,%6,%7,%8,%9,%10,%11,%12,%13,%14,%15,%16,%17,%18,%19,%20,%21,%22,%23,%24,%25,%26,%27,%28,%29,%30,%31,%32,%33,%34,%35,%36,%37,%38,%39,%40,%41,%42,%43,%44,%45,%46,%47,%48,%49,%50,%51,%52,%53,%54,%55,%56,%57,%58,%59,%60,%61,%62,%63}, %64, %65, p, 1, 1, 0, 1;}"
    : "+f"(d[0]),"+f"(d[1]),"+f"(d[2]),"+f"(d[3]),"+f"(d[4]),"+f"(d[5]),"+f"(d[6]),"+f"(d[7]),"+f"(d[8]),"+f"(d[9]),"+f"(d[10]),"+f"(d[11]),"+f"(d[12]),"+f"(d[13]),"+f"(d[14]),"+f"(d[15]),"+f"(d[16]),"+f"(d[17]),"+f"(d[18]),"+f"(d[19]),"+f"(d[20]),"+f"(d[21]),"+f"(d[22]),"+f"(d[23]),"+f"(d[24]),"+f"(d[25]),"+f"(d[26]),"+f"(d[27]),"+f"(d[28]),"+f"(d[29]),"+f"(d[30]),"+f"(d[31]),"+f"(d[32]),"+f"(d[33]),"+f"(d[34]),"+f"(d[35]),"+f"(d[36]),"+f"(d[37]),"+f"(d[38]),"+f"(d[39]),"+f"(d[40]),"+f"(d[41]),"+f"(d[42]),"+f"(d[43]),"+f"(d[44]),"+f"(d[45]),"+f"(d[46]),"+f"(d[47]),"+f"(d[48]),"+f"(d[49]),"+f"(d[50]),"+f"(d[51]),"+f"(d[52]),"+f"(d[53]),"+f"(d[54]),"+f"(d[55]),"+f"(d[56]),"+f"(d[57]),"+f"(d[58]),"+f"(d[59]),"+f"(d[60]),"+f"(d[61]),"+f"(d[62]),"+f"(d[63])
    : "l"(da), "l"(db), "r"(sd));
}
__device__ __forceinline__ void wg_ss160_01(float* d, uint64_t da, uint64_t db, int sd) {
  asm volatile("{.reg .pred p; setp.ne.b32 p, %82, 0;\n"
    "wgmma.mma_async.sync.aligned.m64n160k16.f32.bf16.bf16 {%0,%1,%2,%3,%4,%5,%6,%7,%8,%9,%10,%11,%12,%13,%14,%15,%16,%17,%18,%19,%20,%21,%22,%23,%24,%25,%26,%27,%28,%29,%30,%31,%32,%33,%34,%35,%36,%37,%38,%39,%40,%41,%42,%43,%44,%45,%46,%47,%48,%49,%50,%51,%52,%53,%54,%55,%56,%57,%58,%59,%60,%61,%62,%63,%64,%65,%66,%67,%68,%69,%70,%71,%72,%73,%74,%75,%76,%77,%78,%79}, %80, %81, p, 1, 1, 0, 1;}"
    : "+f"(d[0]),"+f"(d[1]),"+f"(d[2]),"+f"(d[3]),"+f"(d[4]),"+f"(d[5]),"+f"(d[6]),"+f"(d[7]),"+f"(d[8]),"+f"(d[9]),"+f"(d[10]),"+f"(d[11]),"+f"(d[12]),"+f"(d[13]),"+f"(d[14]),"+f"(d[15]),"+f"(d[16]),"+f"(d[17]),"+f"(d[18]),"+f"(d[19]),"+f"(d[20]),"+f"(d[21]),"+f"(d[22]),"+f"(d[23]),"+f"(d[24]),"+f"(d[25]),"+f"(d[26]),"+f"(d[27]),"+f"(d[28]),"+f"(d[29]),"+f"(d[30]),"+f"(d[31]),"+f"(d[32]),"+f"(d[33]),"+f"(d[34]),"+f"(d[35]),"+f"(d[36]),"+f"(d[37]),"+f"(d[38]),"+f"(d[39]),"+f"(d[40]),"+f"(d[41]),"+f"(d[42]),"+f"(d[43]),"+f"(d[44]),"+f"(d[45]),"+f"(d[46]),"+f"(d[47]),"+f"(d[48]),"+f"(d[49]),"+f"(d[50]),"+f"(d[51]),"+f"(d[52]),"+f"(d[53]),"+f"(d[54]),"+f"(d[55]),"+f"(d[56]),"+f"(d[57]),"+f"(d[58]),"+f"(d[59]),"+f"(d[60]),"+f"(d[61]),"+f"(d[62]),"+f"(d[63]),"+f"(d[64]),"+f"(d[65]),"+f"(d[66]),"+f"(d[67]),"+f"(d[68]),"+f"(d[69]),"+f"(d[70]),"+f"(d[71]),"+f"(d[72]),"+f"(d[73]),"+f"(d[74]),"+f"(d[75]),"+f"(d[76]),"+f"(d[77]),"+f"(d[78]),"+f"(d[79])
    : "l"(da), "l"(db), "r"(sd));
}
__device__ __forceinline__ void wg_ss80_01(float* d, uint64_t da, uint64_t db, int sd) {
  asm volatile("{.reg .pred p; setp.ne.b32 p, %42, 0;\n"
    "wgmma.mma_async.sync.aligned.m64n80k16.f32.bf16.bf16 {%0,%1,%2,%3,%4,%5,%6,%7,%8,%9,%10,%11,%12,%13,%14,%15,%16,%17,%18,%19,%20,%21,%22,%23,%24,%25,%26,%27,%28,%29,%30,%31,%32,%33,%34,%35,%36,%37,%38,%39}, %40, %41, p, 1, 1, 0, 1;}"
    : "+f"(d[0]),"+f"(d[1]),"+f"(d[2]),"+f"(d[3]),"+f"(d[4]),"+f"(d[5]),"+f"(d[6]),"+f"(d[7]),"+f"(d[8]),"+f"(d[9]),"+f"(d[10]),"+f"(d[11]),"+f"(d[12]),"+f"(d[13]),"+f"(d[14]),"+f"(d[15]),"+f"(d[16]),"+f"(d[17]),"+f"(d[18]),"+f"(d[19]),"+f"(d[20]),"+f"(d[21]),"+f"(d[22]),"+f"(d[23]),"+f"(d[24]),"+f"(d[25]),"+f"(d[26]),"+f"(d[27]),"+f"(d[28]),"+f"(d[29]),"+f"(d[30]),"+f"(d[31]),"+f"(d[32]),"+f"(d[33]),"+f"(d[34]),"+f"(d[35]),"+f"(d[36]),"+f"(d[37]),"+f"(d[38]),"+f"(d[39])
    : "l"(da), "l"(db), "r"(sd));
}
__device__ __forceinline__ void wg_rs32_00(float* d, uint32_t a0, uint32_t a1, uint32_t a2, uint32_t a3, uint64_t db, int sd) {
  asm volatile("{.reg .pred p; setp.ne.b32 p, %21, 0;\n"
    "wgmma.mma_async.sync.aligned.m64n32k16.f32.bf16.bf16 {%0,%1,%2,%3,%4,%5,%6,%7,%8,%9,%10,%11,%12,%13,%14,%15}, {%16,%17,%18,%19}, %20, p, 1, 1, 0;}"
    : "+f"(d[0]),"+f"(d[1]),"+f"(d[2]),"+f"(d[3]),"+f"(d[4]),"+f"(d[5]),"+f"(d[6]),"+f"(d[7]),"+f"(d[8]),"+f"(d[9]),"+f"(d[10]),"+f"(d[11]),"+f"(d[12]),"+f"(d[13]),"+f"(d[14]),"+f"(d[15])
    : "r"(a0), "r"(a1), "r"(a2), "r"(a3), "l"(db), "r"(sd));
}
__device__ __forceinline__ void wg_rs64_00(float* d, uint32_t a0, uint32_t a1, uint32_t a2, uint32_t a3, uint64_t db, int sd) {
  asm volatile("{.reg .pred p; setp.ne.b32 p, %37, 0;\n"
    "wgmma.mma_async.sync.aligned.m64n64k16.f32.bf16.bf16 {%0,%1,%2,%3,%4,%5,%6,%7,%8,%9,%10,%11,%12,%13,%14,%15,%16,%17,%18,%19,%20,%21,%22,%23,%24,%25,%26,%27,%28,%29,%30,%31}, {%32,%33,%34,%35}, %36, p, 1, 1, 0;}"
    : "+f"(d[0]),"+f"(d[1]),"+f"(d[2]),"+f"(d[3]),"+f"(d[4]),"+f"(d[5]),"+f"(d[6]),"+f"(d[7]),"+f"(d[8]),"+f"(d[9]),"+f"(d[10]),"+f"(d[11]),"+f"(d[12]),"+f"(d[13]),"+f"(d[14]),"+f"(d[15]),"+f"(d[16]),"+f"(d[17]),"+f"(d[18]),"+f"(d[19]),"+f"(d[20]),"+f"(d[21]),"+f"(d[22]),"+f"(d[23]),"+f"(d[24]),"+f"(d[25]),"+f"(d[26]),"+f"(d[27]),"+f"(d[28]),"+f"(d[29]),"+f"(d[30]),"+f"(d[31])
    : "r"(a0), "r"(a1), "r"(a2), "r"(a3), "l"(db), "r"(sd));
}
__device__ __forceinline__ void wg_rs24_01(float* d, uint32_t a0, uint32_t a1, uint32_t a2, uint32_t a3, uint64_t db, int sd) {
  asm volatile("{.reg .pred p; setp.ne.b32 p, %17, 0;\n"
    "wgmma.mma_async.sync.aligned.m64n24k16.f32.bf16.bf16 {%0,%1,%2,%3,%4,%5,%6,%7,%8,%9,%10,%11}, {%12,%13,%14,%15}, %16, p, 1, 1, 1;}"
    : "+f"(d[0]),"+f"(d[1]),"+f"(d[2]),"+f"(d[3]),"+f"(d[4]),"+f"(d[5]),"+f"(d[6]),"+f"(d[7]),"+f"(d[8]),"+f"(d[9]),"+f"(d[10]),"+f"(d[11])
    : "r"(a0), "r"(a1), "r"(a2), "r"(a3), "l"(db), "r"(sd));
}

#define AB_POLY 0x77
__device__ __forceinline__ constexpr bool poly_group(int group) { return (AB_POLY >> (group & 7)) & 1; }

template <int V> struct Int { static constexpr int value = V; };

__device__ __forceinline__ int core_word(int row, int col) {
  return ((((row >> 7) * 10 + (col >> 6)) * 16 + ((row >> 3) & 15)) * 8 + ((col >> 3) & 7)) * 32 + (row & 7) * 4 + ((col & 7) >> 1);
}
__device__ __forceinline__ void wait_count(const uint32_t* c, uint32_t n) {
  int spin = 0;
  while ((ld_acquire(c) & 0xffff) < n) { __nanosleep(32); spin_guard(spin); }
}
__device__ __forceinline__ void wait_count_uniform(const uint32_t* c, uint32_t n) {
  for (int spin = 0; !__all_sync(~0u, (ld_acquire(c) & 0xffff) >= n);) { __nanosleep(32); spin_guard(spin); }
  fence_async_global();
}
__device__ __forceinline__ void prefetch_l2(const void* p, uint32_t bytes) {
  asm volatile("cp.async.bulk.prefetch.L2.global [%0], %1;" :: "l"(p), "r"(bytes) : "memory"); }

#define PLACE 4
__device__ __forceinline__ bool helper_sm() {
  uint32_t m; asm volatile("mov.u32 %0, %%smid;" : "=r"(m));
  return m < 2 || m >= 120 || (m >= 92 && m < 102) || (m >= 106 && m < 117) || m == 118;
}

__device__ __forceinline__ uint8_t* pool_at(uint32_t off) {
  return reinterpret_cast<uint8_t*>((reinterpret_cast<uintptr_t>(g_pool) + 8191) & ~(uintptr_t)8191) + off; }
__device__ __forceinline__ uint32_t page_latency(uint32_t* w) {
  uint32_t best = ~0u;
  stg_strong32(w, 0u);
#pragma unroll 1
  for (int r = 0; r < 4; r++) {
    uint32_t t0, t1, v;
    asm volatile("mov.u32 %0, %%clock;" : "=r"(t0) :: "memory");
    asm volatile("atom.relaxed.gpu.global.exch.b32 %0, [%1], 0;" : "=r"(v) : "l"(w) : "memory");
    asm volatile("{.reg .u32 t; add.u32 t, %1, 1; mov.u32 %0, %%clock; sub.u32 %0, %0, %1;}" : "=r"(t1) : "r"(__shfl_sync(1u, v, 0)) : "memory");
    best = min(best, t1 - t0);
  }
  return best;
}
__device__ __forceinline__ void probe_slots(uint32_t scratch) {
  const int w = (threadIdx.x >> 6) & 1, slot = w == 0 ? NSLOT : blockIdx.x;
  if ((threadIdx.x & 31) == 0 && (w == 0 || slot < NSLOT)) {
    uint32_t* q = reinterpret_cast<uint32_t*>(pool_at(slot * 8192)) + (w == 0 ? (blockIdx.x & 31) * 32 + (blockIdx.x >> 5) : 0);
    sts32(scratch + w * 4, page_latency(q) < page_latency(q + 1024));
  }
  bar_sync(2, 64);
  if ((threadIdx.x & 31) == 0) {
    const int part = lds32(scratch) ? 1 : 2;
    if (w == 0) { uint32_t smid; asm("mov.u32 %0, %%smid;" : "=r"(smid)); stg_strong32(g_smpart + (smid & 255), part); }
    else if (slot < NSLOT) stg_strong32(g_orient + slot, lds32(scratch + 4) ? part : 3 - part);
  }
  __syncwarp();
}

constexpr int WK_SLOTS = 28, WK_BAR = WK_SLOTS * 8192;
__device__ __forceinline__ void work_init(uint32_t sb) {
  const int i = fresh_tid() & 31;
  mbar_init(sb + WK_BAR + 8 * i, i < 8 ? 2 : i < 16 ? 8 : i < 20 ? 1 : i < 24 ? 3 : i < 28 ? 8 : 1);
  asm volatile("fence.mbarrier_init.release.cluster;" ::: "memory");
}

struct ChainParams {
  CUtensorMap wq, wk, wv, wo, xc;
  const __nv_bfloat16* mem0;
  const uint8_t* wb;
  uint32_t *sync, *other;
  int layer;
  int d1, d2, dn, dx, mode, zero;
};
constexpr int CH_WQ = 0, CH_WO = 81920, CH_X = CH_WO + 86016, CH_M = CH_X, CH_Q = CH_X + 34816, CH_KM = CH_Q + 2048, CH_VP = CH_KM + 2048,
              CH_K = CH_X + 40960, CH_O = CH_K, CH_KS = CH_K + 3072, CH_V = CH_K + 4096, CH_VX = CH_V + 12288, CH_R2 = CH_VX,
              CH_SX = CH_VX + 3072, CH_SO = CH_SX + 2048, CH_ID = CH_SO + 1024, CH_L = CH_ID + 256, CH_TAB = CH_L + 64, CH_BAR = CH_TAB + 384;
constexpr int CH_SMEM = CH_BAR + 144;
constexpr int MB_WO = CH_BAR, MB_WQ = CH_BAR + 8, MB_X = CH_BAR + 16, MB_V = CH_BAR + 24, MB_T = CH_BAR + 32, MB_F = CH_BAR + 40, MB_G = CH_BAR + 48, MB_W = CH_BAR + 56;
enum { NB_PROJ = 1, NB_O = 2, NB_W1 = 3, NB_PRE = 4, NB_ST = 5, NB_MEM = 6, NB_XFREE = 7, NB_H1 = 8, NB_PUB = 9, NB_W2 = 10, NB_PROJ2 = 11, NB_PRE2 = 12, NB_H2 = 13, NB_W1V = 14 };
#define CH_NQ 9
#define CH_XPF 1
#define CH_TPF 1
#define CH_NQ0 4
#define CH_PA 6
#define CH_PB 10
#define CH_PC 12
#define CH_PL 3
#define CH_DBL 0x0888
#define CH_PD 1
#define SCHED() asm volatile("griddepcontrol.launch_dependents;" ::: "memory")
__device__ __forceinline__ uint32_t opaque(uint32_t x) { return __shfl_sync(~0u, x, threadIdx.x & 31); }
__device__ __forceinline__ uint32_t uniform(uint32_t x) { return __shfl_sync(~0u, x, 0); }
__device__ __forceinline__ uint32_t nz(uint32_t x) { uint32_t r; asm("max.u32 %0, %1, 1;" : "=r"(r) : "r"(x)); return r; }
__device__ __forceinline__ uint32_t set_tag(uint32_t w, uint32_t tag) { uint32_t r; asm("lop3.b32 %0, %1, %2, 1, 0xD8;" : "=r"(r) : "r"(w), "r"(tag)); return r; }
__device__ __forceinline__ uint32_t pack_tag(float lo, float hi, uint32_t tag) { return set_tag(__byte_perm(__float_as_uint(lo) + tag, pack2(hi, hi), 0x7632), tag); }
__device__ __forceinline__ uint32_t differ(uint32_t a, uint32_t b, uint32_t t) { uint32_t r; asm("lop3.b32 %0, %1, %2, %3, 0x7E;" : "=r"(r) : "r"(a), "r"(b), "r"(t)); return r; }
__device__ __forceinline__ uint32_t clk64() { uint64_t c; asm volatile("mov.u64 %0, %%clock64;" : "=l"(c) :: "memory"); return (uint32_t)c; }
__device__ __forceinline__ void until(uint32_t t) { while ((int)(clk64() - t) < 0) {} }
__device__ __forceinline__ float rcp(float x) { float y; asm("rcp.approx.ftz.f32 %0, %1;" : "=f"(y) : "f"(x)); return y; }

__device__ __forceinline__ void chain_compute(const ChainParams& p, const uint32_t sb) {
  const int tid = threadIdx.x & 127, WG = __shfl_sync(~0u, threadIdx.x >> 7, 0), t4 = __shfl_sync(~0u, tid >> 5, 0), lane = tid & 31;
  const int cta = blockIdx.x, h = cta / 3, j = cta - 3 * h;
  uint32_t a0[80], a1[80], tw[4 * CH_NQ];
  const uint32_t wq = opaque(sb + CH_WQ + (WG * 320 + (lane & 7) + (lane >> 4) * 8) * 128 + (((2 * t4 + ((lane >> 3) & 1)) ^ (lane & 7)) << 4));
#pragma unroll
  for (int k = 0; k < 40; k++) {
    if (k % 10 == 0) mbar_wait_uniform(sb + MB_W + WG * 16 + k / 20 * 32 + k / 10 % 2 * 8, 0);
    if (k < 20) ldsm4t(&a0[4 * k], wq + k * 2048); else ldsm4t(&a1[4 * k - 80], wq + CH_WO + (k - 20) * 2048);
    if (k % 20 == 19) bar_arrive(k < 20 ? NB_PROJ2 : NB_PRE2, 384);
  }
  const int r1 = j == 2 ? 0 : j + 1, r2 = j == 0 ? 2 : j - 1;
  const uint32_t l16 = opaque(sb + lane * 16), l8 = opaque(sb + lane * 8), l4 = opaque(sb + lane * 4);
  const uint32_t t16 = l16 + t4 * 512, t8 = l8 + t4 * 256;
  uint32_t wo = opaque(sb + CH_WO + (WG == 0 ? (t4 >> 1) * 36864 : 73728 + t4 * 1024) + ((lane & 7) + (lane >> 4) * 8) * 64 +
                       (((((lane >> 3) & 1) + (WG == 0 ? (t4 & 1) * 2 : 0)) ^ ((lane >> 1) & 3)) << 4));
  const uint32_t ko0 = uniform(CH_K + (tid >> 6) * 3072 + (tid & 32) * 8), ko1 = uniform(CH_K + (tid >> 6) * 1024 + 1024 + (tid & 32) * 8),
                 o768 = uniform((tid >> 5) * 768);
  const uint32_t give = uniform(t4 * 512 + (WG == 0 ? CH_K : CH_V + j * 4096)), own = uniform(t4 * 512 + (WG == 0 ? CH_V + j * 4096 : CH_K)), mem = uniform(CH_M + WG * 5120);
  const uint32_t vxo = uniform(t4 * 256 + CH_VX + j * 1024);
  uint32_t tag = 1, xd = uniform((1024 + CH_X + WG * 20480) >> 4 | 8 << 16);
  asm volatile("barrier.cluster.wait.aligned;" ::: "memory");
  mbar_wait_uniform(sb + MB_WQ, 0);
  bar_sync(NB_ST, 384);
  uint8_t* pdst[6];
#pragma unroll
  for (int i = 0; i < 6; i++) {
    const int line = WG == 0 ? 24 * j + 12 * (t4 >> 1) + 2 * (t4 & 1) + 4 * (i >> 1) + (i & 1) : j == 0 ? 72 + t4 : 74 + 2 * j + (t4 & 1);
    pdst[i] = pool_at(uniform(lds32(sb + CH_TAB + line * 4)) + h * 128);
  }
  auto batch = [&](float* d, const uint32_t (&a)[80], int acc, int n0, int n1) {
    const uint32_t d0 = xd ^ (tag & (2 << acc));
    wg_fence();
#pragma unroll
    for (int k = 0; k < 20; k++) {
      if (!(k & 3) && n0 + k / 4 < n1) {
        __syncwarp();
        ldsm4t(&tw[4 * n0 + k], wq + (n0 + k / 4) * 2048);
        __syncwarp();
      }
      uint64_t db;
      asm("mov.b64 %0, {%1, %2};" : "=l"(db) : "r"(d0 + k / 5 * 320 + k % 5 * 16), "r"(80));
      wg_rs32_00(d, a[4 * k], a[4 * k + 1], a[4 * k + 2], a[4 * k + 3], db, acc | k);
    }
    wg_commit();
    wg_wait<0>();
    reg_fence<16>(d);
  };
  int s = 0;
#pragma unroll 1
  do {
    {
      float d[16];
      mbar_wait(sb + MB_T, s & 1);
      batch(d, a0, 0, 0, CH_NQ0);
      s--; TM(10); s++;
      mbar_wait(sb + MB_F, ~s & 1);
#pragma unroll
      for (int i = 0; i < 2; i++)
        sts128(l16 + give + i * 2048, make_uint4(pack2(d[8 * i], d[8 * i + 1]), pack2(d[8 * i + 2], d[8 * i + 3]), pack2(d[8 * i + 4], d[8 * i + 5]), pack2(d[8 * i + 6], d[8 * i + 7])));
      bar_sync(NB_PUB, 384);
#pragma unroll
      for (int i = 0; i < 2; i++) {
        const uint4 t = lds128(l16 + own + i * 2048);
        d[8 * i] = bf_lo(t.x); d[8 * i + 1] = bf_hi(t.x); d[8 * i + 2] = bf_lo(t.y); d[8 * i + 3] = bf_hi(t.y);
        d[8 * i + 4] = bf_lo(t.z); d[8 * i + 5] = bf_hi(t.z); d[8 * i + 6] = bf_lo(t.w); d[8 * i + 7] = bf_hi(t.w);
      }
      reg_fence<16>(d);
      batch(d, a1, 1, CH_NQ0, CH_NQ);
      s--; TM(11); s++;
      if (WG == 0) bar_arrive(NB_XFREE, 256);
#pragma unroll
      for (int i = 0; i < 2; i++)
        stsm4(l16 + own + i * 2048, pack2(d[8 * i], d[8 * i + 1]), pack2(d[8 * i + 2], d[8 * i + 3]), pack2(d[8 * i + 4], d[8 * i + 5]), pack2(d[8 * i + 6], d[8 * i + 7]));
      s--; TM(9); s++;
    }
    float dq[4] = {}, d0[4] = {}, d1[4] = {};
    uint32_t b[40], wf[80];
    const uint32_t* kf = &wf[52];
#pragma unroll
    for (int i = 0; i < 4 * CH_NQ; i++) wf[i] = tw[i];
    auto step = [&](int k) {
      mma16(dq, wf[4 * k], wf[4 * k + 1], wf[4 * k + 2], wf[4 * k + 3], b[2 * k], b[2 * k + 1]);
      mma16(d0, a0[4 * k], a0[4 * k + 1], a0[4 * k + 2], a0[4 * k + 3], b[2 * k], b[2 * k + 1]);
      mma16(d1, a1[4 * k], a1[4 * k + 1], a1[4 * k + 2], a1[4 * k + 3], b[2 * k], b[2 * k + 1]);
    };
    auto finish = [&](int wg, const float* dk) {
      const float k2 = 0.07216878364870322f * 1.44269504089f;
      sts32(l4 + t4 * 512 + CH_Q + wg * 128, pack2(dq[0] * k2, dq[1] * k2));
      sts32(l4 + t4 * 512 + CH_Q + wg * 128 + 256, pack2(dq[2] * k2, dq[3] * k2));
      stsm2t(t16 + CH_KM + wg * 256, pack2(dk[0], dk[1]), pack2(dk[2], dk[3]));
    };
    const bool more = s < NSEG - 1;
    bar_sync(NB_MEM, 384);
    ldsm4t(&b[0], l16 + mem);
    ldsm4t(&b[4], l16 + mem + 512);
    TMD(0, b[0]);
    {
      int nw = CH_NQ, nb = 2;
#pragma unroll
      for (int k = 0; k < 20; k++) {
        SCHED();
        step(k);
#pragma unroll
        for (int i = 0; i < (CH_DBL >> k & 1) + 1; i++) {
          if (nb < 10 && 2 * nb <= nw) { ldsm4t(&b[4 * nb], l16 + mem + nb * 512); nb++; }
          else if (nw < 20) { ldsm4t(&wf[4 * nw], wq + nw * 2048); nw++; }
          else if (nw < 22) {
            const uint32_t x = l16 ^ ((ko0 ^ tag) & 256);
            uint32_t* r = &wf[4 * nw - 28];
            asm volatile("{.reg .pred p; setp.ne.u32 p, %5, 0; @p ldmatrix.sync.aligned.m8n8.x4.trans.shared.b16 {%0,%1,%2,%3},[%4];}"
                         : "+r"(r[0]), "+r"(r[1]), "+r"(r[2]), "+r"(r[3]) : "r"(x + (x & 256) + (nw == 20 ? ko0 : ko1)), "r"(WG) : "memory");
            nw++;
          }
        }
      }
      SCHED();
    }
    if (WG == 0) {
      finish(0, d0);
      TM(1);
      bar_sync(NB_PROJ, 256);
      const float4 pv = lds128f(t16 + CH_VP);
      const uint32_t v0 = pack2(d1[0] + pv.x, d1[1] + pv.y), v1 = pack2(d1[2] + pv.z, d1[3] + pv.w);
      const uint32_t xo = l8 + (vxo ^ (tag & 2));
      st_async64(mapa(xo, r1), v0, v1, mapa(sb + MB_X, r1), more);
      st_async64(mapa(xo, r2), v0, v1, mapa(sb + MB_X, r2), more);
      sts64(xo, v0, v1);
      if (!more) continue;
      __syncwarp();
      if (elect()) mbar_arrive(sb + MB_X);
      bar_arrive(NB_PROJ2, 256);
      TM(3);
      uint32_t w[144];
      auto tile_of = [](int n) { return n < 27 ? n % 3 : (0x26484 >> 2 * (n - 27)) & 3; };
      auto step_of = [](int n) { return n < 27 ? n / 3 : 9 + ((0x29610 >> 2 * (n - 27)) & 3); };
      auto wload = [&](int n) { ldsm4t(&w[4 * n], wo + tile_of(n) * 12288 + (step_of(n) % 3) * 4096 + (step_of(n) / 3) * 1024); };
#pragma unroll
      for (int n = 0; n < CH_PA; n++) wload(n);
      bar_sync(NB_PRE, 256);
#pragma unroll
      for (int n = CH_PA; n < CH_PB; n++) wload(n);
      bar_arrive(NB_PRE2, 256);
      if (CH_PC > CH_PB) {
        mbar_wait(sb + MB_X, s & 1);
        for (int i = 0; i < CH_PD; i++) wo = __shfl_xor_sync(~0u, wo, p.zero);
#pragma unroll
        for (int n = CH_PB; n < CH_PC; n++) wload(n);
      }
      TM(4);
      bar_sync(NB_O, 256);
      {
        float x[3][4] = {};
        uint32_t ob[24];
        float4 l;
        ldsm4t(&ob[0], l16 + CH_O);
        ldsm4t(&ob[4], l16 + CH_O + 512);
        TMD(7, ob[0]);
        int nw = CH_PC, no = 2;
        float i0, i1;
        uint8_t* dst[6];
        uint32_t lo[6], hi[6];
        auto pre = [&](int i) { lo[i] = __float_as_uint(x[i >> 1][2 * (i & 1)] * i0) + tag; hi[i] = pack2(0.f, x[i >> 1][2 * (i & 1) + 1] * i1); };
        auto emit = [&](int i) { stg_strong32(dst[i], set_tag(__byte_perm(lo[i], hi[i], 0x7632), tag)); };
#pragma unroll
        for (int n = 0; n < 36; n++) {
          SCHED();
          mma16(x[tile_of(n)], w[4 * n], w[4 * n + 1], w[4 * n + 2], w[4 * n + 3], ob[step_of(n) * 2], ob[step_of(n) * 2 + 1]);
          if (n >= CH_PL) {
            if (no < 6 && no * 2 <= step_of(min(nw, 35))) { ldsm4t(&ob[4 * no], l16 + CH_O + no * 512); no++; }
            else if (nw < 36) { wload(nw); nw++; }
          }
          if (n == 18) l = lds128f(sb + CH_L + ((l16 ^ tag) & 0x30));
          if (n == 26) { i0 = rcp(l.x + l.y); i1 = rcp(l.z + l.w); asm volatile("" : "+f"(i0), "+f"(i1)); }
          if (n >= 28 && n < 34) { dst[n - 28] = pdst[n - 28] + ((l4 ^ tag) & 0x7c); asm volatile("" : "+l"(dst[n - 28])); }
          if (n == 32) { for (int i = 0; i < 2; i++) { pre(i); asm volatile("" : "+r"(lo[i]), "+r"(hi[i])); } }
          if (n == 33) { emit(0); emit(1); }
        }
        for (int i = 2; i < 6; i++) pre(i);
        for (int i = 2; i < 6; i++) emit(i);
      }
      TM(8);
    } else {
      finish(1, d1);
      sts128f(t16 + CH_VP, d0[0], d0[1], d0[2], d0[3]);
      TM(1);
      bar_sync(NB_PROJ, 256);
      {
        float d0[4] = {}, d1[4] = {}, dm[4] = {};
        uint32_t q[16], km[4];
#pragma unroll
        for (int e = 0; e < 4; e++) {
          ldsm4t(&q[4 * e], l16 + (e ^ t4) * 512 + CH_Q);
          SCHED();
          if (e == 1) { ldsm4(km, t16 + CH_KM); SCHED(); }
        }
        const uint32_t xo = l4 + ((t4 * 128) ^ (tag & 2));
        uint64_t x[4];
#pragma unroll
        for (int i = 0; i < 4; i++) {
          const int r = i & 1 ? r2 : r1;
          asm volatile("mov.b64 %0, {%1, %2};" : "=l"(x[i]) : "r"(mapa(xo, r) + CH_SX + (i & 1) * 1024 + (i & 2) * 256), "r"(mapa(sb + MB_X, r)));
        }
        SCHED();
        mma16(d0, q[0], q[1], q[2], q[3], kf[0], kf[1]);
        SCHED();
        mma16(d1, q[4], q[5], q[6], q[7], kf[2], kf[3]);
        SCHED();
        mma16(dm, q[0], q[1], q[2], q[3], hadd2(km[0], km[2]), hadd2(km[1], km[3]));
        mma16(d0, q[8], q[9], q[10], q[11], kf[4], kf[5]);
        SCHED();
        mma16(d1, q[12], q[13], q[14], q[15], kf[6], kf[7]);
        if (!more) continue;
        const uint32_t w1 = pack2(dm[0] + dm[2], dm[1] + dm[3]);
        st_async32((uint32_t)x[2], w1, x[2] >> 32);
        st_async32((uint32_t)x[3], w1, x[3] >> 32);
        SCHED();
        const uint32_t w0 = pack2((d0[0] + d0[2]) + (d1[0] + d1[2]), (d0[1] + d0[3]) + (d1[1] + d1[3]));
        st_async32((uint32_t)x[0], w0, x[0] >> 32);
        st_async32((uint32_t)x[1], w0, x[1] >> 32);
        sts32(xo + CH_SO, w0);
        sts32(xo + CH_SO + 512, w1);
      }
      TM(3);
      float sc[3][4] = {};
      uint32_t wd[12];
      uint32_t redo;
      auto attend = [&](auto first) {
        uint4 vb[6];
        uint2 vm[3];
        float e[10];
        uint32_t ow[6];
        if (first.value) {
          const uint2 id = lds64(l8 + CH_ID);
          bar_sync(NB_W1V, 160);
          uint32_t r[8];
          ldsm4(r, l16 + CH_SO); ldsm4(r + 4, l16 + CH_SO + 512);
#pragma unroll
          for (int u = 0; u < 6; u++) vb[u] = ldsm4v(t16 + CH_V + u * 2048);
          bar_arrive(NB_PRE, 256);
          SCHED();
          uint32_t sxa = l16 + ((l16 ^ tag) & 256) * 3;
          asm volatile("" : "+r"(sxa));
          sxa += CH_SX;
          SCHED();
          mma8(sc[0], r[0], r[1], id.x);
          mma8(sc[1], r[2], r[3], id.x);
          mma16(sc[2], r[4], r[5], r[6], r[7], id.x, id.y);
          TM(7);
          mbar_wait(sb + MB_X, s & 1);
          TM(4);
          uint32_t t[16];
          ldsm4(t, sxa); ldsm4(t + 4, sxa + 256); ldsm4(t + 8, sxa + 512);
          SCHED();
          mma16(sc[0], t[0], t[1], t[2], t[3], id.x, id.y);
          ldsm4(t + 12, sxa + 768);
          SCHED();
          mma16(sc[1], t[4], t[5], t[6], t[7], id.x, id.y);
#pragma unroll
          for (int u = 0; u < 2; u++) vm[u] = lds64(t8 + CH_VX + u * 1024);
          SCHED();
          e[0] = ex2(sc[0][0]);
          mma16(sc[2], t[8], t[9], t[10], t[11], id.x, id.y);
          vm[2] = lds64(t8 + CH_VX + 2048);
          SCHED();
          e[1] = ex2(sc[0][1]);
          ldsm4t(&wd[0], wo);
          SCHED();
          e[2] = ex2(sc[0][2]);
          SCHED();
          e[3] = ex2(sc[0][3]);
          mma16(sc[2], t[12], t[13], t[14], t[15], id.x, id.y);
          SCHED();
          e[4] = ex2(sc[1][0]);
          ldsm4t(&wd[4], wo + 4096);
          SCHED();
          e[5] = ex2(sc[1][1]);
        } else {
#pragma unroll
          for (int u = 0; u < 6; u++) vb[u] = ldsm4v(t16 + CH_V + u * 2048);
#pragma unroll
          for (int u = 0; u < 3; u++) vm[u] = lds64(t8 + CH_VX + u * 1024);
        }
        float o[3][4] = {};
        if (!first.value) {
#pragma unroll
          for (int i = 0; i < 6; i++) e[i] = ex2(sc[i >> 2][i & 3]);
        }
        const uint32_t p1 = pack2(e[0], e[1]), p2 = pack2(e[2], e[3]);
        float l = (e[0] + e[1]) + (e[2] + e[3]);
        asm volatile("" : "+f"(l));
        SCHED();
        e[6] = ex2(sc[1][2]);
        mma16(o[0], vb[0].x, vb[0].y, vb[0].z, vb[0].w, p1, p2);
        if (first.value) { sc[2][0] += sc[2][2]; sc[2][1] += sc[2][3]; }
        SCHED();
        e[7] = ex2(sc[1][3]);
        mma16(o[1], vb[2].x, vb[2].y, vb[2].z, vb[2].w, p1, p2);
        SCHED();
        e[8] = ex2(sc[2][0]);
        mma16(o[2], vb[4].x, vb[4].y, vb[4].z, vb[4].w, p1, p2);
        SCHED();
        e[9] = ex2(sc[2][1]);
        SCHED();
        const uint32_t p3 = pack2(e[4], e[5]), p4 = pack2(e[6], e[7]);
        l += (e[4] + e[5]) + (e[6] + e[7]);
#pragma unroll
        for (int u = 0; u < 3; u++) mma16(o[u], vb[2 * u + 1].x, vb[2 * u + 1].y, vb[2 * u + 1].z, vb[2 * u + 1].w, p3, p4);
        SCHED();
        const uint32_t p0 = pack2(e[8], e[9]);
        l += e[8] + e[9];
        const float l2 = __shfl_xor_sync(~0u, l, 1);
        if (first.value) ldsm4t(&wd[8], wo + 8192);
#pragma unroll
        for (int u = 0; u < 3; u++) mma8(o[u], vm[u].x, vm[u].y, p0);
        redo = __any_sync(~0u, !(l > 1e-9f && l < 1e9f));
        uint32_t la = sb + CH_L + (((l4 ^ tag) >> 1) & 0x3c);
        asm volatile("" : "+r"(la));
        SCHED();
#pragma unroll
        for (int u = 0; u < 3; u++) { ow[2 * u] = pack2(o[u][0], o[u][1]); ow[2 * u + 1] = pack2(o[u][2], o[u][3]); }
        stsm4(l16 + o768 + CH_O, ow[0], ow[1], ow[2], ow[3]);
        stsm2(l16 + o768 + CH_O + 512, ow[4], ow[5]);
        if (t4 == 0) sts32(la, __float_as_uint(l + l2));
      };
      attend(Int<1>());
      TM(6);
      asm volatile("{.reg .pred p; setp.eq.u32 p, %0, 0; @p bar.sync 2, 256;}" :: "r"(redo) : "memory");
      if (redo) {
        float mx = fmaxf(sc[2][0], sc[2][1]);
#pragma unroll
        for (int i = 0; i < 4; i++) mx = fmaxf(mx, fmaxf(sc[0][i], sc[1][i]));
        mx = fmaxf(mx, __shfl_xor_sync(~0u, mx, 1));
        mx = fmaxf(mx, __shfl_xor_sync(~0u, mx, 2));
#pragma unroll
        for (int i = 0; i < 4; i++) { sc[0][i] -= mx; sc[1][i] -= mx; }
        sc[2][0] -= mx; sc[2][1] -= mx;
        attend(Int<0>());
        bar_arrive(NB_O, 256);
      }
      {
        float z[4] = {};
        const uint32_t scr = l8 + ((CH_V + r1 * 4096) ^ (tag & 2));
        uint32_t ow[6], we[12];
        __syncwarp();
        ldsm4t(ow, l16 + o768 + CH_O);
        ldsm2t(ow + 4, l16 + o768 + CH_O + 512);
        if (j == 0) {
          float y[4] = {};
#pragma unroll
          for (int u = 0; u < 3; u++) ldsm4t(&we[4 * u], (wo ^ 32) + u * 4096);
          SCHED();
#pragma unroll
          for (int u = 0; u < 3; u++) {
            mma16(z, wd[4 * u], wd[4 * u + 1], wd[4 * u + 2], wd[4 * u + 3], ow[2 * u], ow[2 * u + 1]);
            mma16(y, we[4 * u], we[4 * u + 1], we[4 * u + 2], we[4 * u + 3], ow[2 * u], ow[2 * u + 1]);
          }
          sts64f(scr + t4 * 512 + 2048, y[0], y[1]); sts64f(scr + t4 * 512 + 2304, y[2], y[3]);
        } else {
#pragma unroll
          for (int u = 0; u < 3; u++) mma16(z, wd[4 * u], wd[4 * u + 1], wd[4 * u + 2], wd[4 * u + 3], ow[2 * u], ow[2 * u + 1]);
        }
        sts64f(scr + t4 * 512, z[0], z[1]); sts64f(scr + t4 * 512 + 256, z[2], z[3]);
        bar_sync(NB_W1, 128);
        if (j == 0 || t4 < 2) {
          float2 q[4];
          const float4 l = lds128f(sb + CH_L + ((l16 ^ tag) & 0x30));
#pragma unroll
          for (int i = 0; i < 4; i++) q[i] = lds64f(scr + (t4 >> 1) * 2048 + (t4 & 1) * 256 + i * 512);
          SCHED();
          stg_strong32(pdst[0] + ((l4 ^ tag) & 0x7c), pack_tag(((q[0].x + q[1].x) + (q[2].x + q[3].x)) * rcp(l.x + l.y), ((q[0].y + q[1].y) + (q[2].y + q[3].y)) * rcp(l.z + l.w), tag));
        }
      }
      TM(2);
    }
    bar_sync(NB_ST, 384);
    tag ^= 0x10001;
  } while (++s < NSEG);
  if (WG == 1) {
    const uint2 a = lds64(t8 + t4 * 256 + CH_KM), b = lds64(t8 + t4 * 256 + CH_KM + 256);
    sts64(t8 + CH_M, hadd2(a.x, b.x), hadd2(a.y, b.y));
  }
  bar_arrive(NB_PRE2, 288);
}

__device__ __forceinline__ void chain_comm(const ChainParams& p, const uint32_t sb, const CUtensorMap* maps) {
  [[maybe_unused]] constexpr int WG = 2;
  const int tid = threadIdx.x & 127, t4 = __shfl_sync(~0u, tid >> 5, 0), lane = tid & 31;
  const int cta = blockIdx.x, h = cta / 3, j = cta - 3 * h, colbase = cta * 64;
  const uint8_t* const xs = reinterpret_cast<const uint8_t*>(g_xn);
  auto xload = [&](int seg, int i) { tma_load5(sb + CH_X + i * 10240, &p.xc, 0, seg * 4, 2 * i, sb + MB_T); };
  if (cta == 0) for (int i = tid; i < SY_N; i += 128) p.other[i] = 0;
  uint32_t smid; asm("mov.u32 %0, %%smid;" : "=r"(smid));
  const uint32_t part = max(ldg_strong32(g_smpart + (smid & 255)), 1u);
  if (tid == 64) stg_strong32(p.sync + SY_PART + cta, part);
  PRO(0);
  if (t4 == 3) {
    bar_arrive(NB_PROJ2, 384);
    bar_arrive(NB_PRE2, 384);
    if (elect()) {
      wait_count(p.sync + SY_P + 1, ln_items(p.layer, 0));
      fence_async_global();
      mbar_expect(sb + MB_T, 40960);
      for (int i = 0; i < 4; i++) xload(0, i);
    }
    __syncwarp();
  } else {
  bar_sync(NB_PROJ2, 384);
  __syncwarp();
  PRO(1);
  if (t4 == 0 && elect()) {
    mbar_expect(sb + MB_WQ, 81920);
    #pragma unroll 1
    for (int i = 0; i < 4; i++) tma_load(sb + CH_WQ + i * 20480, &p.wq, colbase, i * 160, sb + MB_WQ);
  }
  bar_sync(NB_PRE2, 384);
  __syncwarp();
  PRO(2);
  if (t4 == 0 && elect()) {
    mbar_expect(sb + MB_WO, 86016);
#pragma unroll 1
    for (int i = 0; i < 7; i++) tma_load(sb + CH_WO + i * 12288, &p.wo, i < 6 ? j * 192 + i * 32 : j == 0 ? 576 : 592 + j * 16, h * 192, sb + MB_WO);
  }
  }
  if (tid < NSLOT) {
    const uint32_t* part_of = p.sync + SY_PART + (tid >= 80 ? cta : tid);
    uint32_t reader = 0, orient = 0;
    int n = 0;
    while (reader == 0 || orient == 0) { reader = ldg_strong32(part_of); orient = ldg_strong32(g_orient + tid); spin_guard(n); }
    sts32(sb + CH_TAB + tid * 4, tid * 8192 + (orient == reader ? 0 : 4096));
    if (t4 == 0) {
      const uint32_t near = __ballot_sync(~0u, reader == part) & 0xffffff;
      if (lane == 0) sts32(sb + CH_TAB + NSLOT * 4, cta < 80 ? cta : near ? __fns(near, 0, 1 + cta % __popc(near)) : 0);
    }
  }
  __syncwarp();
  asm volatile("barrier.cluster.wait.aligned;" ::: "memory");
  const uint32_t l8 = opaque(sb + t4 * 256 + lane * 8);
  bar_sync(NB_ST, 384);
  bar_arrive(NB_PUB, 384);
  {
    const uint32_t id = (lane >> 3) == (lane & 3) ? ((lane & 4) ? 0x3f800000u : 0x00003f80u) : 0u;
    if (t4 == 0) sts64(l8 + CH_ID, id, id);
    const uint32_t* m0 = reinterpret_cast<const uint32_t*>(p.mem0) + (lane >> 2) * (DM / 2) + t4 * 80 + (lane & 3);
    uint32_t g[20];
#pragma unroll
    for (int i = 0; i < 20; i++) g[i] = m0[i * 4];
    bar_sync(NB_XFREE, 256);
#pragma unroll
    for (int i = 0; i < 20; i += 4) stsm4t(sb + CH_M + (t4 * 20 + i) * 128 + lane * 16, g[i], g[i + 1], g[i + 2], g[i + 3]);
    mbar_wait_uniform(sb + MB_WO, 0);
  }
  uint8_t* const pool = pool_at(0);
  const uint8_t* const psrc = pool + opaque(lds32(sb + CH_TAB + lds32(sb + CH_TAB + NSLOT * 4) * 4) + t4 * 1024 + lane * 4);
  const uint32_t mdst = opaque((80 + cta / 20) * 8192 + (t4 & 1) * 4096 + (cta % 20) * 128 + lane * 4);
  int st = 0;
  uint32_t tag = opaque(1), span = ~0u;
  bar_sync(NB_MEM, 384);
  auto send_tokens = [&](int s) {
    uint8_t* dst = g_kv + ((s >> 2) * 192 + cta + 3 * h) * KV_PART + (s & 3) * 4096;
    bulk_store(dst, sb + CH_K, 4096);
    bulk_store(dst + KV_V, sb + CH_V + j * 4096, 4096);
    bulk_commit();
  };
  auto send_memory = [&](int s, uint32_t km) {
    fence_async();
    uint8_t* dst = g_kv + ((s >> 2) * 192 + cta + 3 * h) * KV_PART + KV_M + (s & 3) * 1024;
    bulk_store(dst, km, 1024);
    bulk_store(dst + KV_V, sb + CH_VX + j * 1024, 1024);
    bulk_commit();
    bulk_wait<0>();
    if ((s & 3) == 3) { fence_async_global(); atomicAdd(p.sync + (s >> 2) * 8 + 4, 1); }
  };
#pragma unroll 1
  for (int s = 0; s < NSEG - 1; s++) {
    TM(0);
    STAT(0);
    if (t4 == 0) {
      if (elect()) {
        fence_async();
#pragma unroll 1
        for (int r = j + 1; r < j + 3; r++) bulk_push(mapa(sb + CH_V + j * 4096, r % 3), sb + CH_V + j * 4096, 4096, mapa(sb + MB_V, r % 3));
        send_tokens(s);
        bulk_wait_read<0>();
      }
      __syncwarp();
    }
    uint32_t c0, g0;
    if (t4 == 1) {
      __syncwarp();
      c0 = clk32(); g0 = gtime();
      if (elect()) atomicMax(p.sync + SY_TIME + s, g0);
    }
    if (t4 == 3 && (s & 3) == 2 && s < NSEG - 2) wait_count_uniform(p.sync + SY_P + 5 + (s & ~3), ln_items(p.layer, (s >> 2) + 1));
    if (t4 == 2) { mbar_wait(sb + MB_V, s & 1); bar_arrive(NB_W1V, 160); }
    bar_sync(NB_PROJ2, 256);
    if (t4 == 0 && elect()) {
      mbar_expect(sb + MB_X, 4096);
      mbar_expect(sb + MB_T, 40960);
      for (int i = 0; i < 3; i++) xload(s + 1, i);
    }
    __syncwarp();
    STAT(1);
    TM(1);
    {
      const uint2 a = lds64(l8 + t4 * 256 + CH_KM), b = lds64(l8 + t4 * 256 + CH_KM + 256);
      sts64(l8 + CH_KS, hadd2(a.x, b.x), hadd2(a.y, b.y));
    }
    TM(4);
    bar_sync(NB_PRE2, 256);
    if (t4 == 0 && elect()) {
      xload(s + 1, 3);
      if (CH_XPF && s < NSEG - 2) prefetch_l2(xs + (s + 2) * 40960 + cta % 20 * 2048, 2048);
      if (CH_TPF && s >= NSEG - 7) {
        const int i = s - (NSEG - 7);
        if (i < 2) prefetch_l2(p.wb + (cta * 2 + i) * 12800, 12800);
        else if (i < 4) prefetch_l2(xs + (cta * 2 + i - 2) * 8192, 8192);
        else prefetch_l2(g_q + 15 * 32 * 3072 + (cta * 2 + i - 4) * 512, 8192);
      }
      send_memory(s, sb + CH_KS);
    }
    __syncwarp();
    if (t4 == 1) {
      const uint32_t late = min(ldg_strong32(p.sync + SY_TIME + s) - g0, 640u);
      if (elect()) sts32(sb + CH_TAB + 380, c0 + span + (late * 115 >> 6) + (j ? 60 : 0) + p.d1);
    }
    bar_sync(NB_W2, 128);
    uint32_t due = lds32(sb + CH_TAB + 380);
    due = __shfl_sync(~0u, due, 0);
    const uint8_t* ms = pool + (lds32(sb + CH_TAB + (80 + st * 4 + t4) * 4) + (l8 & 255));
    uint8_t* md = pool + (mdst + (t4 < 2 ? st : st == 2 ? 0 : st + 1) * 32768);
    asm volatile("" : "+l"(ms), "+l"(md));
    TM(2);
    bar_sync(NB_ST, 384);
    __syncwarp();
    uint32_t tg = clk32();
    if (t4 == 3 && elect()) {
      if (s < NSEG - 2) mbar_expect(sb + MB_V, 8192);
      mbar_arrive_remote(mapa(sb + MB_F, j == 2 ? 0 : j + 1));
      mbar_arrive_remote(mapa(sb + MB_F, j == 0 ? 2 : j - 1));
    }
    if (t4 == 2 && s == NSEG - 2) {
      work_init(sb);
      if (elect()) for (int i = 0; i < 5; i++) asm volatile("prefetch.tensormap [%0];" :: "l"(maps + i) : "memory");
    }
    __syncwarp();
    STAT(2);
    {
      float2 q[4];
      TM(3);
      if (t4 == 1) span = min(span, tg - c0);
      until(s < 2 ? tg + 400 : (int)(due - tg) > p.dn ? due : tg + p.dn);
      for (int n = 0;;) {
        uint32_t v[8];
#pragma unroll
        for (int i = 0; i < 8; i++) v[i] = ldg_strong32(psrc + i * 128);
        sts64f(l8 + CH_R2, ((bf_lo(v[0]) + bf_lo(v[1])) + (bf_lo(v[2]) + bf_lo(v[3]))) + ((bf_lo(v[4]) + bf_lo(v[5])) + (bf_lo(v[6]) + bf_lo(v[7]))),
               ((bf_hi(v[0]) + bf_hi(v[1])) + (bf_hi(v[2]) + bf_hi(v[3]))) + ((bf_hi(v[4]) + bf_hi(v[5])) + (bf_hi(v[6]) + bf_hi(v[7]))));
        uint32_t bad;
        asm volatile("{.reg .pred p, q; .reg .b32 a; lop3.b32 a, %1, %2, %3, 0xFE; lop3.b32 a, a, %4, %6, 0xA8; setp.ne.u32 p, a, 0;\n"
                     "bar.red.or.pred q, %5, 128, p; selp.u32 %0, 1, 0, q;}"
                     : "=r"(bad) : "r"(differ(v[0], v[1], tag)), "r"(differ(v[2], v[3], tag)), "r"(differ(v[4], v[5], tag)), "r"(differ(v[6], v[7], tag)), "n"((int)NB_W2),
                       "r"((uint32_t)(cta < 80 || n < 3)) : "memory");
#pragma unroll
        for (int k = 0; k < 4; k++) asm volatile("ld.volatile.shared.v2.f32 {%0,%1}, [%2];" : "=f"(q[k].x), "=f"(q[k].y) : "r"(l8 - t4 * 256 + CH_R2 + k * 256) : "memory");
        TMV(12, n);
        if (!bad) break;
        spin_guard(n);
      }
      bar_arrive(NB_PUB, 384);
      SCHED();
      TM(9);
      if (cta < 80) stg_strong32(md, min(nz(pack2((q[0].x + q[1].x) + (q[2].x + q[3].x), (q[0].y + q[1].y) + (q[2].y + q[3].y))), t4 < 2 ? ~0u : 0u));
      tg = clk64() + p.d2;
      if (s >= 2 && (int)(due + p.dx - tg) > 0) tg = due + p.dx;
      TM(8);
    }
    STAT(3);
    until(tg);
    TM(10);
    for (int n = 0;;) {
      uint2 g[10];
#pragma unroll
      for (int i = 0; i < 10; i++) g[i] = ldg_strong64(ms + i * 256);
      if (n == 0) bar_sync(NB_XFREE, 256);
      spin_guard(n);
      uint32_t m = ~0u;
#pragma unroll
      for (int i = 0; i < 10; i++) { sts64(l8 + CH_M + t4 * 2304 + i * 256, g[i].x, g[i].y); m = __vimin3_u32(m, g[i].x, g[i].y); }
      TMV(13, n - 1);
      if (!__any_sync(~0u, m == 0)) break;
    }
    TM(11);
    if (t4 < 2 || s == NSEG - 2) bar_sync(NB_MEM, 384); else bar_arrive(NB_MEM, 384);
    if (++st == 3) st = 0;
    tag ^= 0x10001;
  }
  if (t4 == 0) {
    if (elect()) { fence_async(); send_tokens(NSEG - 1); }
    __syncwarp();
    bar_sync(NB_PRE2, 288);
    if (elect()) {
      send_memory(NSEG - 1, sb + CH_M);
      asm volatile("mbarrier.arrive.shared::cta.b64 _, [%0], 8;" :: "r"(sb + WK_BAR + 64) : "memory");
    }
    __syncwarp();
  }
}

__device__ __forceinline__ void chain_start(const ChainParams& p, const uint32_t sb) {
  if (threadIdx.x < 32 && elect()) {
    mbar_init(sb + MB_WO, 1); mbar_init(sb + MB_WQ, 1); mbar_init(sb + MB_X, 5); mbar_init(sb + MB_V, 1); mbar_init(sb + MB_T, 1); mbar_init(sb + MB_F, 2);
    for (int i = 0; i < 8; i++) mbar_init(sb + MB_W + 8 * i, 1);
    asm volatile("fence.mbarrier_init.release.cluster;" ::: "memory");
    mbar_expect(sb + MB_V, 8192);
#pragma unroll 1
    for (int i = 0; i < 8; i++) {
      const int n = (i & 4) + (i & 1) * 2 + (i >> 1 & 1);
      mbar_expect(sb + MB_W + 8 * n, 20480);
      tma_load(sb + n * 20480, (i ^ i >> 2) & 1 ? &p.wv : &p.wk, blockIdx.x * 64, (n & 3) * 160, sb + MB_W + 8 * n);
    }
    atomicAdd(p.sync + SY_UP, 1);
    asm volatile("{.reg .pred p; setp.ne.u32 p, %0, 1024; @p trap;}" :: "r"(sb & 0xffffff));
  }
  __syncthreads();
  asm volatile("barrier.cluster.arrive.relaxed.aligned;" ::: "memory");
}

struct WorkParams {
  ChainParams ch;
  CUtensorMap wo, xn, wb[3], xp, wq, wc[2], out;
  const __nv_bfloat16* x;
  uint32_t* sync;
  int kind, qa_end, idle;
};
#define GO_320 4
#define GO_TAIL 1
enum { WK_FIRST = 0, WK_LEAD = 1, WK_CHAIN = 2, WK_LAST = 3 };
enum { IT_ATT = 0, IT_OP = 1, IT_FIN = 2, IT_BQ = 3, IT_BO = 4, IT_LN = 5, IT_Q = 6, IT_LN0 = 7, IT_OUT = 8 };
constexpr int C_EARLY = 1 << 20, C_LATE = 1 << 21, C_TAIL = 1 << 22;

__device__ __forceinline__ uint32_t item_count(int type, int b) { return type == IT_ATT ? 32 : type == IT_OP ? op_tiles(b) * op_split(b) : type == IT_FIN ? fin_items(b) : bq_items(b); }
__device__ __forceinline__ uint32_t item_need(int type, int b) { return type == IT_ATT ? 96 : item_count(type - 1, b); }
__device__ __forceinline__ int item_cols(int type, int b) {
  return type == IT_ATT || type == IT_Q ? 192 : type == IT_OUT ? 80 : type == IT_BQ ? (b < BQ_12 ? 320 : b < BQ_24 ? 160 : 80) : type == IT_OP && b >= OP_N4 ? 160 : 320; }
__device__ __forceinline__ int item_groups(int type, int b) { return 16 / (type == IT_FIN ? fin_items(b) : ln_items(type == IT_LN, b)); }
#define RES_OP 1
constexpr int RES_N = RES_OP ? op_tiles(14) * op_split(14) : 0, RES_BQ = (64 - RES_N) / 6;
__device__ __forceinline__ bool reserved(int type, int b) { return type == IT_ATT ? b == 15 : type == IT_OP ? RES_OP && b == 14 : type == IT_BQ && b < RES_BQ; }
__device__ __forceinline__ int reserved_item(int cta) {
  const int h = cta / 3, j = cta - 3 * h, i = h + (j - 1) * 32;
  if (j == 0) return C_EARLY | IT_ATT << 16 | 15 << 8 | h;
  return i < RES_N ? C_TAIL | IT_OP << 16 | 14 << 8 | i : i - RES_N < RES_BQ * 6 ? C_TAIL | IT_BQ << 16 | ((i - RES_N) / 6) << 8 | (i - RES_N) % 6 : -1;
}
constexpr int LEAD1 = 12;
__device__ __forceinline__ int lead_item(int layer, int qa_end, int i) {
  if (layer == 2) return i < 128 ? C_EARLY | C_LATE | IT_OUT << 16 | (i >> 3) << 8 | (i & 7) : -1;
  if (layer == 0) {
    if (i < 32) return IT_LN0 << 16 | (i >> 4) << 8 | (i & 15);
    if (i < 88) return IT_LN0 << 16 | ((i - 24) >> 2) << 8 | (i & 3);
    i -= 88;
  } else {
    if (i < 4) return C_EARLY | IT_BO << 16 | (i >> 1) << 8 | (i & 1);
    if (i < 12) return C_EARLY | IT_LN << 16 | ((i - 4) >> 2) << 8 | (i & 3);
    if (i < 40) return C_EARLY | IT_BO << 16 | ((i - 8) >> 1) << 8 | (i & 1);
    if (i < 96) return C_EARLY | IT_LN << 16 | ((i - 32) >> 2) << 8 | (i & 3);
    i -= 96;
  }
  return i < (16 - qa_end) * 32 ? C_EARLY | IT_Q << 16 | (qa_end + (i >> 5)) << 8 | (i & 31) : -1;
}

struct Ring {
  uint32_t sb;
  int pos, seq;
  __device__ __forceinline__ uint32_t full() const { return sb + WK_BAR + 8 * (seq & 7); }
  __device__ __forceinline__ uint32_t take(int len) { if (pos + len > WK_SLOTS) pos = 0; pos += len; seq++; return sb + (pos - len) * 8192; }
  __device__ __forceinline__ uint32_t wait(int len) { mbar_wait_uniform(full(), (seq >> 3) & 1); return take(len); }
  __device__ __forceinline__ void release(int sq) const { if (elect()) mbar_arrive(sb + WK_BAR + 64 + 8 * (sq & 7)); }
};

struct Pending {
  uint32_t w[48], done;
  uint4* dst;
  __device__ __forceinline__ void store(int i) const { dst[(i >> 2) * 1024 + (i & 3) * 32] = make_uint4(w[4 * i], w[4 * i + 1], w[4 * i + 2], w[4 * i + 3]); }
  __device__ __forceinline__ void finish() { __syncwarp(); if (elect()) mbar_arrive(done); done = 0; }
  __device__ __forceinline__ void flush() {
    if (done) {
#pragma unroll
      for (int i = 0; i < 12; i++) store(i);
      finish();
    }
  }
};

template <int N>
__device__ __forceinline__ void gemm_item(float* d, Ring& r, int nkb, uint32_t go, int ask, Pending& pend) {
  const int warp = __shfl_sync(~0u, fresh_tid() >> 5, 0), wg = warp >> 2;
#pragma unroll 1
  for (int kb = 0; kb < nkb; kb++) {
    const uint32_t base = r.wait(2 + (N + 63) / 64);
    const uint64_t da = mkdesc(base + wg * 8192, 128, 1024, 0), db = mkdesc(base + 16384, 8192, 1024, 1);
    wg_fence();
#pragma unroll
    for (int kk = 0; kk < 4; kk++) {
      if (N == 80) wg_ss80_01(d, da + kk * 16, db + kk * 128, (kb | kk) != 0);
      else if (N == 160) wg_ss160_01(d, da + kk * 16, db + kk * 128, (kb | kk) != 0);
      else wg_ss192_01(d, da + kk * 16, db + kk * 128, (kb | kk) != 0);
      if (N == 320) wg_ss128_01(d + 96, da + kk * 16, db + kk * 128 + 3 * 512, (kb | kk) != 0);
    }
    wg_commit();
    if (kb == ask && go && warp == 0 && elect()) mbar_arrive(go);
    if (N == 192 && pend.done) {
#pragma unroll
      for (int i = 0; i < 12; i++) if (kb == i / 2) pend.store(i);
      if (kb == 5) pend.finish();
    }
    if (kb > 0) { wg_wait<1>(); r.release(r.seq - 2); }
  }
  wg_wait<0>();
  reg_fence<N / 2>(d);
  r.release(r.seq - 1);
}

__device__ __forceinline__ void attn_a_warp(Ring& r, Pending& pend, bool now, const int warp) {
  uint32_t (&q)[48] = pend.w;
  const int lane = fresh_tid() & 31, g = lane >> 2, c = lane & 3, seg = warp & 3;
  const bool half = warp >= 4;
  const float k2 = 0.07216878364870322f * 1.44269504089f, NEG = -INFINITY;
  float sc[5][4] = {};
#pragma unroll
  for (int i = 0; i < 8; i++) sc[3 + (i >> 2)][i & 3] = half ? 0.f : NEG;
  uint32_t base, f[2][40] = {};
  const uint32_t ka = seg * 4096 + lane * 16, va = seg * 4096 + (lane & 8) * 32 + (lane & 16) * 8 + (lane & 7) * 16;
  auto load = [&](int n) {
    uint32_t* d = f[n & 1];
    base = n & 1 ? base + KV_PART : r.wait(5);
    const uint32_t a = base + (n < 3 ? ka : va), m = base + KV_M + seg * 1024;
#pragma unroll
    for (int i = 0; i < 4; i++) {
      if (n >= 3) { const uint2 vm = lds64(m + i * 256 + lane * 8); d[2 * i] = vm.x; d[2 * i + 1] = vm.y; }
      else if (!(i & 1)) ldsm4(&d[2 * i], m + i * 256 + lane * 16);
      (n < 3 ? ldsm4t : ldsm4)(&d[8 + 4 * i], a + half * 2048 + i * 512);
    }
    if (half) {
#pragma unroll
      for (int i = 0; i < 4; i++) (n < 3 ? ldsm4t : ldsm4)(&d[24 + 4 * i], a + i * 512);
    }
  };
  load(0);
#pragma unroll
  for (int u = 0; u < 3; u++) {
    if (u == 2) r.release(r.seq - 2);
    load(u + 1);
    SCHED();
    const uint32_t* b = f[u & 1];
#pragma unroll
    for (int kk = 0; kk < 4; kk++) {
      const uint32_t* a = &q[16 * u + 4 * kk];
      mma16(sc[0], a[0], a[1], a[2], a[3], b[2 * kk], b[2 * kk + 1]);
      mma16(sc[1], a[0], a[1], a[2], a[3], b[8 + 4 * kk], b[9 + 4 * kk]);
      mma16(sc[2], a[0], a[1], a[2], a[3], b[10 + 4 * kk], b[11 + 4 * kk]);
    }
    if (half) {
#pragma unroll
      for (int kk = 0; kk < 4; kk++) {
        const uint32_t* a = &q[16 * u + 4 * kk];
        mma16(sc[3], a[0], a[1], a[2], a[3], b[24 + 4 * kk], b[25 + 4 * kk]);
        mma16(sc[4], a[0], a[1], a[2], a[3], b[26 + 4 * kk], b[27 + 4 * kk]);
      }
    }
    SCHED();
  }
  load(4);
  SCHED();
  if (2 * c > g) { sc[1][0] = NEG; sc[2][2] = NEG; }
  if (2 * c + 1 > g) { sc[1][1] = NEG; sc[2][3] = NEG; }
  sc[2][0] = sc[2][1] = NEG;
  uint32_t pp[5][2]; float inv[2];
#pragma unroll
  for (int hh = 0; hh < 2; hh++) {
    float m = NEG, l = 0.f;
#pragma unroll
    for (int n = 0; n < 5; n++) m = fmaxf(m, fmaxf(sc[n][2 * hh], sc[n][2 * hh + 1]));
    m = fmaxf(m, __shfl_xor_sync(~0u, m, 1)); m = fmaxf(m, __shfl_xor_sync(~0u, m, 2));
#pragma unroll
    for (int n = 0; n < 5; n++) { const float x = ex2((sc[n][2 * hh] - m) * k2), y = ex2((sc[n][2 * hh + 1] - m) * k2); l += x + y; pp[n][hh] = pack2(x, y); }
    l += __shfl_xor_sync(~0u, l, 1); l += __shfl_xor_sync(~0u, l, 2);
    inv[hh] = rcp(l);
  }
#pragma unroll
  for (int u = 0; u < 3; u++) {
    float o[8][4] = {};
    const uint32_t* b = f[~u & 1];
#pragma unroll
    for (int n = 0; n < 8; n++) mma8(o[n], pp[0][0], pp[0][1], b[n]);
#pragma unroll
    for (int n = 0; n < 8; n++) mma16(o[n], pp[1][0], pp[1][1], pp[2][0], pp[2][1], b[8 + 2 * n], b[9 + 2 * n]);
    if (half) {
#pragma unroll
      for (int n = 0; n < 8; n++) mma16(o[n], pp[3][0], pp[3][1], pp[4][0], pp[4][1], b[24 + 2 * n], b[25 + 2 * n]);
    }
    SCHED();
    if (u != 1) r.release(r.seq - 2 + u / 2);
    if (u == 0) { load(5); SCHED(); }
#pragma unroll
    for (int i = 0; i < 16; i++) q[16 * u + i] = pack2(o[i & 7][i >> 2 & 2] * inv[i >> 3], o[i & 7][(i >> 2 & 2) + 1] * inv[i >> 3]);
    if (now) {
#pragma unroll
      for (int i = 0; i < 4; i++) pend.store(4 * u + i);
    }
  }
}

__device__ __forceinline__ void ln_groups(Ring& ring, uint32_t scratch, int planes, int rg, bool two) {
  constexpr int G = 2;
  const int warp = fresh_tid() >> 5, lane = fresh_tid() & 31;
  const uint32_t id = (lane >> 3) == (lane & 3) ? ((lane & 4) ? 0x3f800000u : 0x00003f80u) : 0u;
  const uint32_t at = (warp * 160 + lane) * 8, at1 = planes > 1 ? at : (lane >> 2) * 1280 + warp * 160 + (lane & 3) * 4;
  const uint32_t step = planes > 1 ? 256 : 32, half = planes > 1 ? 4 : 16;
  float v[G][5][4] = {};
#pragma unroll
  for (int r = 0; r < G; r++) {
#pragma unroll 1
    for (int k = r && !two ? 0 : planes; k > 0; k -= 4) {
      const uint32_t a = ring.wait(min(k, 4) + 1);
      if (k == 1) {
#pragma unroll
        for (int i = 0; i < 5; i++) mma8(v[r][i], lds32(a + at1 + i * step), lds32(a + at1 + i * step + half), id);
      } else {
#pragma unroll
        for (int i = 0; i < 10; i++) {
          if (i == 5 && k < 4) break;
          const uint2 x = lds64(a + at + i / 5 * 20480 + i % 5 * 256), y = lds64(a + at + i / 5 * 20480 + 10240 + i % 5 * 256);
          mma16(v[r][i % 5], x.x, x.y, y.x, y.y, id, id);
        }
      }
      ring.release(ring.seq - 1);
    }
  }
  uint2 xr[G][5];
  scratch += (lane >> 2) * 64;
#pragma unroll
  for (int r = 0; r < G; r++) {
    float m = 0.f, q = 0.f;
#pragma unroll
    for (int i = 0; i < 5; i++) {
      float* t = v[r][i];
      xr[r][i] = make_uint2(pack2(t[0], t[1]), pack2(t[2], t[3]));
      t[0] = bf_lo(xr[r][i].x); t[1] = bf_hi(xr[r][i].x); t[2] = bf_lo(xr[r][i].y); t[3] = bf_hi(xr[r][i].y);
      m += (t[0] + t[1]) + (t[2] + t[3]);
    }
    m += __shfl_xor_sync(~0u, m, 1); m += __shfl_xor_sync(~0u, m, 2);
    m *= 1.f / 80;
#pragma unroll
    for (int i = 0; i < 5; i++) { const float a = v[r][i][0] - m, b = v[r][i][1] - m, c = v[r][i][2] - m, d = v[r][i][3] - m; q += (a * a + b * b) + (c * c + d * d); }
    q += __shfl_xor_sync(~0u, q, 1); q += __shfl_xor_sync(~0u, q, 2);
    if ((lane & 3) == 0) sts64f(scratch + r * 512 + warp * 8, m, q);
  }
  bar_sync(1, 256);
#pragma unroll
  for (int r = 0; r < G; r++) {
    const float4 t = lds128f(scratch + r * 512 + (lane & 3) * 16);
    float mean = t.x + t.z;
    mean += __shfl_xor_sync(~0u, mean, 1); mean += __shfl_xor_sync(~0u, mean, 2);
    mean *= 0.125f;
    float var = (t.y + t.w) + 80.f * ((t.x - mean) * (t.x - mean) + (t.z - mean) * (t.z - mean));
    var += __shfl_xor_sync(~0u, var, 1); var += __shfl_xor_sync(~0u, var, 2);
    const float rs = rsqrtf(var * (1.f / DM) + 1e-5f);
#pragma unroll
    for (int i = 0; i < 20; i++) v[r][i >> 2][i & 3] = (v[r][i >> 2][i & 3] - mean) * rs;
  }
#pragma unroll
  for (int r = 0; r < G; r++) {
    if (r && !two) break;
    uint32_t* xn = g_xn + (rg + r) * 2560 + warp * 320 + lane;
#pragma unroll
    for (int i = 0; i < 10; i++) xn[i * 32] = pack2(v[r][i >> 1][2 * (i & 1)], v[r][i >> 1][2 * (i & 1) + 1]);
#pragma unroll
    for (int i = 0; i < 5; i++) g_x[(rg + r) * 17 * 1280 + warp * 160 + i * 32 + lane] = xr[r][i];
  }
}

__device__ __forceinline__ void store_partial(const float* d, int b, int split, int unit, int nu) {
  uint2* dst = g_x + (((b * 16 + (fresh_tid() >> 5) * 2) * 17 + 1 + split) * 40 + unit) * 32 + (fresh_tid() & 31);
#pragma unroll
  for (int u = 0; u < 20; u++) {
    if (u == 10 && nu == 10) break;
    dst[u * 32] = make_uint2(pack2(d[8 * u], d[8 * u + 1]), pack2(d[8 * u + 4], d[8 * u + 5]));
    dst[(680 + u) * 32] = make_uint2(pack2(d[8 * u + 2], d[8 * u + 3]), pack2(d[8 * u + 6], d[8 * u + 7]));
  }
}

__device__ __forceinline__ void store_bqkv(const float* d, int b, int idx, int nh) {
  const int lane = fresh_tid() & 31, c = lane & 3, rg = b * 16 + (fresh_tid() >> 5) * 2, h0 = idx * nh;
  const float sc = h0 < 32 ? 0.22360679775f * 1.44269504089f : 1.f;
  const bool lo = c < 2;
  uint32_t* da = g_bqkv + (h0 * 256 + rg) * 96 + lane;
  uint32_t* db = da + 256 * 96 + (lo ? 2 : -2);
  uint32_t pad[2];
#pragma unroll
  for (int r = 0; r < 2; r++) pad[r] = !(c & 1) && (h0 >= 64 || (h0 >= 32 && (lane & 4) && poly_group(rg + r))) ? 0x00003f80u : 0u;
#pragma unroll
  for (int q = 0; q < 8; q++) {
    if ((q == 2 || q == 4) && nh == 2 * q) break;
#pragma unroll
    for (int r = 0; r < 2; r++) {
      uint32_t w[5];
#pragma unroll
      for (int i = 0; i < 5; i++) w[i] = pack2(d[20 * q + 4 * i + 2 * r] * sc, d[20 * q + 4 * i + 2 * r + 1] * sc);
      const int o = q * 2 * 256 * 96 + r * 96;
      da[o] = w[0]; da[o + 32] = w[1]; da[o + 64] = lo ? w[2] : pad[r];
      db[o] = lo ? w[3] : w[2]; db[o + 32] = lo ? w[4] : w[3]; db[o + 64] = lo ? pad[r] : w[4];
    }
  }
}

__device__ __forceinline__ void work_loader(const WorkParams& p, const uint32_t sb, const bool weights) {
  const uint32_t bars = sb + WK_BAR, bIF = bars + 128, bIE = bars + 160, bGo = bars + 224, slots = bars + 272;
  int pos = 0, seq = 0, tail = 0, used = 0;
  uint32_t lens = 0;
  const bool one = elect();
  if (p.kind == WK_CHAIN) {
    seq = 1; used = lens = 8;
    if (one) mbar_arrive(bars);
  }
  for (int n = 0;; n++) {
    mbar_wait_uniform(bIF + 8 * (n & 3), (n >> 2) & 1);
    const int code = __shfl_sync(~0u, (int)lds32(slots + 4 * (n & 3)), 0);
    if (code < 0) break;
    const int type = (code >> 16) & 15, b = (code >> 8) & 255, idx = code & 255;
    if (one) mbar_arrive(bIE + 8 * (n & 3));
    const bool qa = type == IT_ATT && b < p.qa_end, ln = type == IT_FIN || type == IT_LN || type == IT_LN0;
    const int parts = ln ? item_groups(type, b) : type == IT_ATT ? 2 : 1;
#pragma unroll 1
    for (int part = 0; part < parts; part++) {
      int bytes = 163840, chunk = 40960, nb = 0, flag = b * 8 + 4 + type, need = item_need(type & 3, b), c0 = 0, c3 = idx, c4 = 0, step = 64;
      const uint8_t* src = g_kv + (b * 32 + idx) * 6 * KV_PART;
      const CUtensorMap* m = nullptr;
      if (ln) {
        const int rg = b * 16 + idx * parts + part;
        bytes = (type == IT_FIN ? op_split(b) + 1 : type == IT_LN ? 2 : 1) * 10240;
        src = type == IT_LN0 ? reinterpret_cast<const uint8_t*>(p.x) + rg * 10240 : reinterpret_cast<const uint8_t*>(g_x) + rg * 174080;
        if (type == IT_LN) { flag = SY_P + b * 4; need = 2; }
        if (type == IT_LN0 || part) need = 0;
      } else if (part) {
        bytes = 6 * KV_PART;
      } else if (type == IT_ATT && !qa) {
        bytes = chunk = 49152;
        src = reinterpret_cast<const uint8_t*>(g_q) + (b * 32 + idx) * 49152;
        flag = SY_P + b * 4 + 3; need = 32;
      } else {
        const int cols = item_cols(type, b);
        chunk = 16384; nb = (cols + 63) >> 6;
        src = reinterpret_cast<const uint8_t*>(g_of) + b * 163840;
        if (type == IT_OP) {
          const int nkb = 96 / op_split(b), kb0 = (idx >> op_tiles(b) / 2) * nkb;
          bytes = nkb * 16384;
          src = reinterpret_cast<const uint8_t*>(g_o) + (b * 96 + kb0) * 16384;
          if (weights) m = &p.wo;
          c0 = (idx & (op_tiles(b) - 1)) * cols; c3 = 0; c4 = kb0 * 2; step = 2;
        } else if (type == IT_BQ) {
          m = weights ? &p.wb[cols / 160] : &p.xn;
        } else if (type == IT_BO || type == IT_OUT) {
          if (weights) m = &p.wc[cols / 320];
          flag = SY_OB; need = type == IT_BO && b < 2 ? 32 : -1;
        } else {
          m = weights ? &p.wq : &p.xp;
          flag = SY_P + b * 4 + 1; need = ln_items(p.ch.layer, b);
        }
      }
      if (!weights) {
        c3 = b * 4;
        if (need < 0) pdl_wait(); else if (need) wait_count_uniform(p.sync + flag, need);
        if ((ln ? !part : part && (!qa || (code & C_EARLY))) && one) mbar_arrive(bGo);
      }
      const int boxes = weights ? nb : m != nullptr;
#pragma unroll 1
      for (; bytes > 0; bytes -= chunk) {
        const int now = min(bytes, chunk), len = ((now + 8191) >> 13) + nb, skip = pos + len > WK_SLOTS ? WK_SLOTS - pos : 0, sh = 4 * (seq & 7);
        used += len + skip;
        while (used > WK_SLOTS || seq - tail >= 8) {
          mbar_wait_uniform(bars + 64 + 8 * (tail & 7), (tail >> 3) & 1);
          used -= (lens >> 4 * (tail & 7)) & 15;
          tail++;
        }
        lens = (lens & ~(15u << sh)) | (len + skip) << sh;
        if (pos + len > WK_SLOTS) pos = 0;
        const uint32_t bar = bars + 2 * sh, dst = sb + pos * 8192 + weights * 16384;
        if (one) mbar_expect(bar, weights ? nb * 8192 : now);
#pragma unroll 1
        for (int i = 0; i < boxes; i++)
          if (one) tma_load5(dst + i * 8192, m, c0 + i * 64, c3, c4, bar);
        if (!weights && !m && one) bulk_load_last(dst, src, now, bar);
        if (weights) c4 += step; else c0 += 128;
        src += chunk; pos += len; seq++;
      }
    }
  }
}

__global__ void __launch_bounds__(384, 1) work_kernel(const __grid_constant__ WorkParams p) {
  extern __shared__ __align__(1024) uint8_t smem_raw[];
  const uint32_t sb = s2u(smem_raw), bars = sb + WK_BAR;
  const uint32_t bIF = bars + 128, bIE = bars + 160, done = bars + 192, bGo = bars + 224, slots = bars + 272, scratch = bars + 384;
  const int warp = __shfl_sync(~0u, threadIdx.x >> 5, 0);
  uint32_t* const sync = p.sync;
  TRACE(0);
  pdl_launch();
  if (p.kind == WK_LEAD && !helper_sm() && __syncthreads_or(threadIdx.x == 0 && ldg_strong32(sync + SY_PRE + 1) >= LEAD1)) { pdl_wait(); return; }
  if (p.kind == WK_CHAIN) {
    chain_start(p.ch, sb);
  } else {
    if (warp == 0) work_init(sb);
    __syncthreads();
    if (p.kind == WK_FIRST) {
      if (!(warp & 13)) probe_slots(bars + 320);
      if (!helper_sm()) return;
    }
  }
  if (warp >= 8) {
    asm volatile("setmaxnreg.dec.sync.aligned.u32 40;");
    if (p.kind == WK_CHAIN) chain_comm(p.ch, sb, &p.wo);
    const int warp = __shfl_sync(~0u, fresh_tid() >> 5, 0), lane = fresh_tid() & 31;
    if (warp == 9) {
      const bool keep = p.kind > WK_LEAD || helper_sm();
      int n = 0;
      if (p.kind == WK_CHAIN && reserved_item(blockIdx.x) >= 0) {
        if (lane == 0) { sts32(slots, reserved_item(blockIdx.x)); mbar_arrive(bIF); }
        n = 1;
      }
      const int b = lane & 15, layer = p.kind == WK_LAST ? 2 : sync != g_sync;
      bool first = layer == 1, lead = p.kind != WK_CHAIN;
      for (;; n++) {
        if (n > 0) mbar_wait_uniform(bGo, (n - 1) & 1);
        mbar_wait_uniform(bIE + 8 * (n & 3), ((n >> 2) & 1) ^ 1);
        int code = -1;
        if (lead) {
          int i = blockIdx.x + n * 256;
          if (first) { if (lane == 0) i = atomicAdd(sync + SY_PRE + 1, 1); i = __shfl_sync(~0u, i, 0); first = i < LEAD1; }
          if (layer < 2 && !first) {
            if (lane == 0) i = keep ? atomicAdd(sync + SY_PRE, 1) + layer * LEAD1 : 1 << 20;
            i = __shfl_sync(~0u, i, 0);
            if (!keep) pdl_wait();
          }
          code = lead_item(layer, p.qa_end, i);
          lead = code >= 0 || layer == 2 || !keep;
          if (!lead && p.kind <= WK_LEAD) {
            const uint32_t t0 = gtime();
            while (!lead && ldg_strong32(sync + SY_UP) < 96) lead = gtime() - t0 > 20000;
          }
        }
        if (!lead) {
          int spin = 0, ticket = 0;
          if (lane == 0) ticket = atomicAdd(sync + SY_T, 1);
          for (;;) {
            const uint4 hd = ldg_strong128(sync + b * 8), pr = ldg_strong128(sync + b * 8 + 4);
            const uint32_t hv[4] = {hd.x, hd.y, hd.z, hd.w}, pv[4] = {pr.x, pr.y, pr.z, pr.w};
            const uint32_t chain_done = __ballot_sync(~0u, (pr.x & 0xffff) >= 96);
            int left[4], avail[4], rdy = 0, claimed = 0, upstream = 0;
#pragma unroll
            for (int t = 0; t < 4; t++) {
              const int cnt = lane < 16 && !reserved(t, b) ? item_count(t, b) : 0;
              left[t] = max(cnt - (int)hv[t], 0);
              claimed += cnt - left[t];
              const bool ready = (pv[t] & 0xffff) >= item_need(t, b);
              rdy |= ready << t;
              bool ok = ready || (t != IT_ATT && (chain_done >> 15 & 1) && !left[t - 1] && (t < 2 || !left[t - 2]));
              if (t == IT_BQ && (chain_done >> 12 & 9) == 1) ok = false;
              avail[t] = ok ? left[t] : 0;
              upstream |= __any_sync(~0u, left[t] > 0);
            }
            if (!upstream) { code = -1; break; }
            int rank = max(__shfl_sync(~0u, ticket, 0) - __reduce_add_sync(~0u, claimed), 0), type = -1, mine = 0;
#pragma unroll
            for (int c = 0; c < 7; c++) {
              const int t = c == 0 || c == 4 ? IT_FIN : c == 1 || c == 6 ? IT_ATT : c == 2 ? IT_OP : IT_BQ;
              int a = c == 1 || c == 2 || ((rdy >> t & 1) == (c < 4)) ? avail[t] : 0;
              if (c == 6) a = b < p.qa_end && !(rdy & 1) && ((chain_done << 1 | 1) >> b & 1) ? left[t] : 0;
              const int tot = __reduce_add_sync(~0u, a);
              if (type < 0) { if (rank < tot) { type = t; mine = a; } else rank -= tot; }
            }
            if (type >= 0) {
#pragma unroll
              for (int o = 1; o < 16; o <<= 1) { const int y = __shfl_up_sync(~0u, mine, o); if (lane >= o) mine += y; }
              const int blk = __ffs(__ballot_sync(~0u, mine > rank)) - 1;
              const int early = !(__shfl_sync(~0u, rdy, blk) >> type & 1);
              uint32_t idx = 0;
              if (lane == 0) idx = atomicAdd(sync + blk * 8 + type, 1);
              idx = __shfl_sync(~0u, idx, 0);
              if (idx < item_count(type, blk)) { code = (chain_done >> 14 & 1) << 22 | early << 20 | type << 16 | blk << 8 | idx; break; }
            } else {
              __nanosleep(50);
            }
            spin_guard(spin);
          }
        }
        if (lane == 0) {
          sts32(slots + 4 * (n & 3), code);
          mbar_arrive(bIF + 8 * (n & 3));
        }
        __syncwarp();
        if (code < 0) break;
      }
    } else if (warp >= 10) {
      work_loader(p, sb, warp == 10);
    } else {
      for (int n = 0;; n++) {
        mbar_wait_uniform(bIF + 8 * (n & 3), (n >> 2) & 1);
        const int code = __shfl_sync(~0u, (int)lds32(slots + 4 * (n & 3)), 0);
        if (code < 0) break;
        const int type = (code >> 16) & 15, b = (code >> 8) & 255;
        mbar_wait_uniform(done + 8 * (n & 3), (n >> 2) & 1);
        if (elect()) {
          if (type != IT_OUT) red_release(sync + (type < IT_BQ ? b * 8 + 5 + type : SY_P + b * 4 + ((0x13102 >> 4 * (type - IT_BQ)) & 3)), 1);
          mbar_arrive(bIE + 8 * (n & 3));
        }
        __syncwarp();
      }
    }
  } else {
    asm volatile("setmaxnreg.inc.sync.aligned.u32 232;");
    if (p.kind == WK_CHAIN) chain_compute(p.ch, sb);
    const int warp = __shfl_sync(~0u, fresh_tid() >> 5, 0), lane = fresh_tid() & 31;
    Ring r{sb, 0, p.kind == WK_CHAIN};
    Pending pend;
    pend.done = 0;
    int nln = 0;
    auto projects = [&](int n) {
      uint32_t here;
      asm volatile("{.reg .pred p; mbarrier.test_wait.parity.shared::cta.b64 p, [%1], %2; vote.sync.all.pred p, p, 0xffffffff; selp.u32 %0, 1, 0, p;}" : "=r"(here) : "r"(bIF + 8 * (n & 3)), "r"((n >> 2) & 1) : "memory");
      if (!here) return false;
      const int code = __shfl_sync(~0u, (int)lds32(slots + 4 * (n & 3)), 0);
      return code >= 0 && (((code >> 16) & 15) == IT_Q || (((code >> 16) & 15) == IT_ATT && ((code >> 8) & 255) < p.qa_end));
    };
#pragma unroll 1
    for (int n = 0;; n++) {
      if (pend.done && !projects(n)) pend.flush();
      mbar_wait_uniform(bIF + 8 * (n & 3), (n >> 2) & 1);
      const int code = __shfl_sync(~0u, (int)lds32(slots + 4 * (n & 3)), 0);
      if (code < 0) { TRACE(2); break; }
      const int type = (code >> 16) & 15, b = (code >> 8) & 255, idx = code & 255;
      const uint32_t go = (code & C_LATE) || (type == IT_ATT && (code & C_EARLY)) ? 0 : bGo;
      ITEM(code & 0xfffff, 0);
      if (type == IT_ATT || type == IT_Q) {
        if (type == IT_Q || b < p.qa_end) {
          float d[96] = {};
          reg_fence<96>(d);
          ITEM(9 << 16 | (code & 0xffff), 0);
          gemm_item<192>(d, r, 10, go, 4, pend);
          ITEM(9 << 16 | (code & 0xffff), 1);
#pragma unroll
          for (int i = 0; i < 48; i++) pend.w[i] = pack2(d[2 * i], d[2 * i + 1]);
        } else {
          const uint32_t base = r.wait(6) + warp * 2048 + lane * 16;
#pragma unroll
          for (int i = 0; i < 12; i++) {
            const uint4 t = lds128(base + (i >> 2) * 16384 + (i & 3) * 512);
            pend.w[4 * i] = t.x; pend.w[4 * i + 1] = t.y; pend.w[4 * i + 2] = t.z; pend.w[4 * i + 3] = t.w;
          }
          __syncwarp();
          r.release(r.seq - 1);
        }
        const bool now = type == IT_ATT && !projects(n + 1);
        if (type == IT_Q) {
          pend.dst = g_q + (b * 32 + idx) * 3072 + warp * 128 + lane;
        } else {
          pend.dst = g_o + (b * 32 + idx) * 3072 + (warp & 3) * 256 + (warp >> 2) * 128 + (lane & 3) * 8 + (lane >> 2);
          attn_a_warp(r, pend, now, warp);
        }
        pend.done = done + 8 * (n & 3);
        if (now) pend.finish();
      } else {
        if (type == IT_FIN || type == IT_LN || type == IT_LN0) {
          const int ng = item_groups(type, b);
          const int planes = type == IT_FIN ? op_split(b) + 1 : type == IT_LN ? 2 : 1;
#pragma unroll 1
          for (int i = 0; i < ng; i += 2) ln_groups(r, scratch + (nln++ & 1) * 1024, planes, b * 16 + idx * ng + i, ng > 1);
        } else {
          const int cols = item_cols(type, b), nkb = type == IT_OP ? 96 / op_split(b) : 10;
          float d[160] = {};
          if (type == IT_OUT) {
            const uint2* x = g_x + ((b * 16 + warp * 2) * 680 + idx * 5) * 32 + lane;
#pragma unroll
            for (int i = 0; i < 10; i++) { const uint2 y = __ldcg(x + (i / 5 * 680 + i % 5) * 32); d[40 + 2 * i] = __uint_as_float(y.x); d[41 + 2 * i] = __uint_as_float(y.y); }
          }
          reg_fence<160>(d);
          if (type != IT_OUT) ITEM((type == IT_BQ ? 10 : 11) << 16 | (code & 0xffff), 0);
          const int ask = max(nkb - (code & C_TAIL ? GO_TAIL : GO_320) * 320 / cols, 0);
          if (cols == 320) gemm_item<320>(d, r, nkb, go, ask, pend);
          else if (cols == 160) gemm_item<160>(d, r, nkb, go, ask, pend);
          else gemm_item<80>(d, r, nkb, go, ask, pend);
          if (type != IT_OUT) ITEM((type == IT_BQ ? 10 : 11) << 16 | (code & 0xffff), 1);
          reg_fence<160>(d);
          if (type == IT_OUT) {
            bar_sync(1, 256);
            const uint32_t dst = sb + (warp * 16 + (lane & 15)) * 160 + (lane >> 4) * 16;
#pragma unroll
            for (int u = 0; u < 5; u++) {
              uint32_t w[4];
#pragma unroll
              for (int i = 0; i < 4; i++) { const uint32_t y = __float_as_uint(d[40 + (i & 1) * 10 + 2 * u + (i >> 1)]); w[i] = pack2(bf_lo(y) + d[8 * u + 2 * i], bf_hi(y) + d[8 * u + 2 * i + 1]); }
              stsm4(dst + u * 32, w[0], w[1], w[2], w[3]);
            }
            fence_async();
            __syncwarp();
            if (elect()) { tma_store(&p.out, sb + warp * 2560, idx * 80, b * 128 + warp * 16); bulk_commit(); bulk_wait<0>(); }
          } else {
            if (warp >= 4) bar_sync(7, 256);
            if (type == IT_BQ) store_bqkv(d, b, idx, cols / 20);
            else store_partial(d, b, cols == 320 ? idx >> 1 : idx >> 2, cols == 320 ? (idx & 1) * 20 : (idx & 3) * 10, cols >> 4);
            if (warp < 4) bar_arrive(7, 256);
          }
        }
        __syncwarp();
        if (elect()) mbar_arrive(done + 8 * (n & 3));
#pragma unroll
        for (int i = 0; i < 48; i++) pend.w[i] = 0;
      }
      if ((code & C_LATE) && warp == 4 && elect()) mbar_arrive(bGo);
      ITEM(code & 0xfffff, 1);
    }
  }
}

constexpr int AB_SMEM = 1024 + 2 * 98304 + 256;
#define AB_N 32
#define AB_WG 4
constexpr int AB_T = AB_WG * 128, AB_PASS = 8 / AB_WG;
__device__ __forceinline__ float ex2_poly(float t) {
  const uint32_t r = __float_as_uint(t) & 0xffff8000u;
  const float f = t - __uint_as_float(r);
  const float p = fmaf(fmaf(fmaf(-5.869912678e-38f, f, -1.700740250e-37f), f, -5.234869734e-37f), f, -7.522601252e-37f);
  uint32_t y;
  asm("mad.lo.u32 %0, %1, 256, %2;" : "=r"(y) : "r"(r), "r"(__float_as_uint(p)));
  return __uint_as_float(y);
}
__device__ __forceinline__ uint32_t hsq(uint32_t w, uint32_t c) { uint32_t r; asm("fma.rn.bf16x2 %0, %1, %1, %2;" : "=r"(r) : "r"(w), "r"(c)); return r; }
__device__ __forceinline__ float sq2(uint32_t w) { const float a = bf_lo(w), b = bf_hi(w); return fmaf(a, a, b * b); }

__device__ __forceinline__ void attn_b_store(const float* o, int h, int row0, int lane) {
  const int g = lane >> 2, c = lane & 3;
  const float i0 = 1.f / __shfl_sync(~0u, o[8], (lane & ~3) | 2), i1 = 1.f / __shfl_sync(~0u, o[10], (lane & ~3) | 2);
#pragma unroll
  for (int jj = 0; jj < 3; jj++) {
    if (jj < 2 || c < 2) {
      const int col = h * 20 + 8 * jj + 2 * c;
      g_of[core_word(row0 + g, col)] = pack2(o[4 * jj] * i0, o[4 * jj + 1] * i0);
      g_of[core_word(row0 + g + 8, col)] = pack2(o[4 * jj + 2] * i1, o[4 * jj + 3] * i1);
    }
  }
}

__device__ __forceinline__ void attn_b_qk(float* s, uint32_t q0, uint32_t q1, uint32_t q2, uint32_t q3, uint32_t q4, uint32_t q5, uint32_t z0, uint32_t z1,
                                          uint64_t dk, uint64_t dk2) {
  wg_rs32_00(s, q0, q1, q2, q3, dk, 0);
  wg_rs32_00(s, q4, q5, z0, z1, dk2, 1);
}

struct AttnParams { const uint8_t* pf[4]; uint32_t *sync, *next; };
__global__ void __launch_bounds__(AB_T + 128, 1) attn_b_kernel(const __grid_constant__ AttnParams p) {
  extern __shared__ uint8_t smem_raw[];
  const uint32_t sb = (s2u(smem_raw) + 1023) & ~1023u, sK = sb, sV = sb + 98304, bars = sb + 2 * 98304;
  const int warp = __shfl_sync(~0u, threadIdx.x >> 5, 0), lane = threadIdx.x & 31;
  const int h = blockIdx.x & 31, quarter = blockIdx.x >> 5;
  BT(0);
  TRACE(0);
  if (threadIdx.x == 0) {
    for (int i = 0; i < 8; i++) mbar_init(bars + 8 * i, 1);
    mbar_init(bars + 128, AB_T / 32);
    mbar_init(bars + 136, 2);
    asm volatile("fence.mbarrier_init.release.cluster;" ::: "memory");
  }
  __syncthreads();
  if (warp >= AB_T / 32) {
    asm volatile("setmaxnreg.dec.sync.aligned.u32 32;");
    if (warp == AB_T / 32 + 1) return;
    if (warp > AB_T / 32) {
      uint32_t kmax = 0;
#pragma unroll 1
      for (int i = 0; i < 32; i++) {
        if (!(i & 3)) mbar_wait_uniform(bars + 2 * i, 0);
        const uint32_t a = sK + i * 3072 + ((threadIdx.x >> 3) & 7) * 384 + (lane & 7) * 16;
        const uint4 x = lds128(a), y = lds128(a + 128);
        const uint2 z = lds64(a + 256);
        const uint32_t n = hadd2(hsq(x.x, hsq(x.y, hsq(x.z, hsq(x.w, hsq(z.x, 0))))), hsq(y.x, hsq(y.y, hsq(y.z, hsq(y.w, hsq(z.y, 0))))));
        kmax = max(kmax, __float_as_uint(bf_lo(n) + bf_hi(n)) & 0x7fffffffu);
      }
      const uint32_t kbits = __reduce_max_sync(~0u, kmax);
      if (lane == 0) { sts32(bars + 64 + (warp & 1) * 4, kbits); mbar_arrive(bars + 136); }
      return;
    }
    const uint8_t* gk = reinterpret_cast<const uint8_t*>(g_bqkv + (32 + h) * 256 * 96);
    const uint8_t* gv = reinterpret_cast<const uint8_t*>(g_bqkv + (64 + h) * 256 * 96);
    uint32_t todo = 255;
    for (int spin = 0; todo;) {
      const uint32_t up = __ballot_sync(~0u, ld_acquire(p.sync + SY_P + (lane & 15) * 4 + 2) >= bq_items(lane & 15));
      fence_async_global();
      for (int i = 0; i < 8; i++) {
        if (!(todo >> i & 1) || (up >> 2 * i & 3) != 3) continue;
        todo &= ~(1u << i);
        if (elect()) {
          mbar_expect(bars + 8 * i, 24576);
          bulk_load(sK + i * 12288, gk + i * 12288, 12288, bars + 8 * i);
          bulk_load(sV + i * 12288, gv + i * 12288, 12288, bars + 8 * i);
        }
      }
      spin_guard(spin);
    }
    pdl_launch();
    TRACE(1);
    if (blockIdx.x < NSLOT) for (int i = lane; i < 512; i += 32) reinterpret_cast<uint4*>(pool_at(blockIdx.x * 8192))[i] = make_uint4(0, 0, 0, 0);
    if (!p.next && blockIdx.x == 127) for (int i = lane; i < 256; i += 32) { g_smpart[i] = 0; if (i < NSLOT) g_orient[i] = 0; }
    if (p.next) {
      mbar_wait_uniform(bars + 128, 0);
      if (quarter == 0 && lane == 0) red_release(p.next + SY_OB, 1);
      for (int i = 0; i < 32; i++) {
        if (elect()) prefetch_l2(p.pf[i >> 3] + blockIdx.x * 61440 + (i & 7) * 7680, 7680);
        __nanosleep(300);
      }
    }
    return;
  }
  asm volatile("setmaxnreg.inc.sync.aligned.u32 112;");
  constexpr int NT = SEQ / AB_N, PER = 256 / AB_N;
  uint32_t qn[8];
  auto load_q = [&](int pass) {
    const uint32_t* gq = g_bqkv + (h * 256 + pass * 128 + quarter * 32 + warp * 2) * 96 + lane;
#pragma unroll
    for (int i = 0; i < 8; i++) qn[i] = __ldcg(gq + (i & 1) * 96 + min(i >> 1, 2) * 32 + (i < 6 ? 0 : 3 - (lane & 3)));
  };
  mbar_wait_uniform(bars + 8 * quarter, 0);
  load_q(0);
#pragma unroll 1
  for (int pass = 0; pass < AB_PASS; pass++) {
    const int row0 = pass * 1024 + quarter * 256 + warp * 16;
    const uint32_t q0 = qn[0], q1 = qn[1], q2 = qn[2], q3 = qn[3], z0 = qn[6], z1 = qn[7];
    uint32_t q4 = qn[4], q5 = qn[5];
    if ((lane & 3) == 2) { q4 = 0x43BCu; q5 = 0x43BCu; }
    float o[12];
    uint64_t dk = mkdesc(sK, 128, 384, 0), dk2 = mkdesc(sK + 256, 0, 384, 0), dv = mkdesc(sV, 384, 128, 0);
    float sa[AB_N / 2], sb2[AB_N / 2];
    uint32_t pa[AB_N / 4], pb[AB_N / 4];
    if (pass == 0) mbar_wait_uniform(bars, 0);
    BT(1 + 2 * pass);
    wg_fence();
    attn_b_qk(sa, q0, q1, q2, q3, q4, q5, z0, z1, dk, dk2);
    wg_commit();
    attn_b_qk(sb2, q0, q1, q2, q3, q4, q5, z0, z1, dk + AB_N * 3, dk2 + AB_N * 3);
    wg_commit();
#pragma unroll 1
    for (int kt = 0; kt < NT; kt += 2) {
      const int nx = kt + 2 < NT ? kt + 2 : 0;
      if (pass == 0 && (nx & (PER - 1)) == 0) mbar_wait_uniform(bars + 8 * (nx / PER), 0);
      const uint64_t nk = dk + nx * (AB_N * 3), nk2 = dk2 + nx * (AB_N * 3);
      wg_wait<1>();
      reg_fence<AB_N / 2>(sa);
#pragma unroll
      for (int i = 0; i < AB_N / 4; i++) pa[i] = pack2(ex2(sa[2 * i]), poly_group(i >> 1) ? ex2_poly(sa[2 * i + 1]) : ex2(sa[2 * i + 1]));
      wg_fence();
#pragma unroll
      for (int kk = 0; kk < AB_N / 16; kk++) wg_rs24_01(o, pa[4 * kk], pa[4 * kk + 1], pa[4 * kk + 2], pa[4 * kk + 3], dv + kk * 48, kk | kt);
      attn_b_qk(sa, q0, q1, q2, q3, q4, q5, z0, z1, nk, nk2);
      wg_commit();
      wg_wait<1>();
      reg_fence<AB_N / 2>(sb2);
#pragma unroll
      for (int i = 0; i < AB_N / 4; i++) pb[i] = pack2(ex2(sb2[2 * i]), poly_group((i >> 1) + AB_N / 8) ? ex2_poly(sb2[2 * i + 1]) : ex2(sb2[2 * i + 1]));
      wg_fence();
#pragma unroll
      for (int kk = 0; kk < AB_N / 16; kk++) wg_rs24_01(o, pb[4 * kk], pb[4 * kk + 1], pb[4 * kk + 2], pb[4 * kk + 3], dv + AB_N * 3 + kk * 48, 1);
      attn_b_qk(sb2, q0, q1, q2, q3, q4, q5, z0, z1, nk + AB_N * 3, nk2 + AB_N * 3);
      wg_commit();
      dv += AB_N * 6;
    }
    wg_wait<0>();
    reg_fence<12>(o); reg_fence<AB_N / 2>(sa); reg_fence<AB_N / 2>(sb2);
    BT(2 + 2 * pass);
    if (pass + 1 < AB_PASS) load_q(pass + 1);
    mbar_wait_uniform(bars + 136, 0);
    const uint2 kb = lds64(bars + 64);
    const float kmax = __uint_as_float(max(kb.x, kb.y));
    if ((lane & 3) == 2) q4 = q5 = 0;
    float n0 = sq2(q0) + sq2(q2) + sq2(q4), n1 = sq2(q1) + sq2(q3) + sq2(q5);
    n0 += __shfl_xor_sync(~0u, n0, 1); n1 += __shfl_xor_sync(~0u, n1, 1);
    n0 += __shfl_xor_sync(~0u, n0, 2); n1 += __shfl_xor_sync(~0u, n1, 2);
    uint32_t redo;
    asm volatile("{.reg .pred p, q; setp.ne.u32 p, %1, 0; bar.red.or.pred q, %2, 128, p; selp.u32 %0, 1, 0, q;}"
                 : "=r"(redo) : "r"((uint32_t)!(n0 * kmax <= 9500.f && n1 * kmax <= 9500.f)), "r"(2 + (warp >> 2)) : "memory");
    if (redo) {
#pragma unroll
      for (int i = 0; i < 12; i++) o[i] = 0.f;
      float m0 = -INFINITY, m1 = -INFINITY;
#pragma unroll 1
      for (int kt = 0; kt < 64; kt++) {
        float s[16];
        wg_fence();
        wg_rs32_00(s, q0, q1, q2, q3, dk + kt * 96, 0);
        wg_rs32_00(s, q4, q5, z0, z1, dk2 + kt * 96, 1);
        wg_commit();
        wg_wait<0>();
        reg_fence<16>(s); reg_fence<12>(o);
        float n0 = m0, n1 = m1;
#pragma unroll
        for (int jj = 0; jj < 4; jj++) { n0 = fmaxf(n0, fmaxf(s[4 * jj], s[4 * jj + 1])); n1 = fmaxf(n1, fmaxf(s[4 * jj + 2], s[4 * jj + 3])); }
        n0 = fmaxf(n0, __shfl_xor_sync(~0u, n0, 1)); n0 = fmaxf(n0, __shfl_xor_sync(~0u, n0, 2));
        n1 = fmaxf(n1, __shfl_xor_sync(~0u, n1, 1)); n1 = fmaxf(n1, __shfl_xor_sync(~0u, n1, 2));
        const float r0 = ex2(m0 - n0), r1 = ex2(m1 - n1);
        m0 = n0; m1 = n1;
#pragma unroll
        for (int jj = 0; jj < 3; jj++) { o[4 * jj] *= r0; o[4 * jj + 1] *= r0; o[4 * jj + 2] *= r1; o[4 * jj + 3] *= r1; }
        uint32_t pp[8];
#pragma unroll
        for (int jj = 0; jj < 4; jj++) {
          pp[2 * jj] = pack2(ex2(s[4 * jj] - m0), ex2(s[4 * jj + 1] - m0));
          pp[2 * jj + 1] = pack2(ex2(s[4 * jj + 2] - m1), ex2(s[4 * jj + 3] - m1));
        }
        reg_fence<12>(o);
        wg_fence();
#pragma unroll
        for (int kk = 0; kk < 2; kk++) wg_rs24_01(o, pp[4 * kk], pp[4 * kk + 1], pp[4 * kk + 2], pp[4 * kk + 3], mkdesc(sV, 384, 128, 0) + kt * 96 + kk * 48, 1);
        wg_commit();
      }
      wg_wait<0>();
      reg_fence<12>(o);
    }
    attn_b_store(o, h, row0, lane);
    __syncwarp();
    if (pass == 0 && lane == 0) mbar_arrive(bars + 128);
  }
  BT(5);
  TRACE(2);
}

typedef CUresult (*EncodeFn)(CUtensorMap*, CUtensorMapDataType, cuuint32_t, void*, const cuuint64_t*, const cuuint64_t*,
                             const cuuint32_t*, const cuuint32_t*, CUtensorMapInterleave, CUtensorMapSwizzle,
                             CUtensorMapL2promotion, CUtensorMapFloatOOBfill);

void make_map(EncodeFn enc, CUtensorMap* m, const void* ptr, int cols, int rows, int box_rows, int box_cols = 64) {
  const cuuint64_t dims[2] = {(cuuint64_t)cols, (cuuint64_t)rows};
  const cuuint64_t strides[1] = {(cuuint64_t)cols * 2};
  const cuuint32_t box[2] = {(cuuint32_t)box_cols, (cuuint32_t)box_rows}, es[2] = {1, 1};
  enc(m, CU_TENSOR_MAP_DATA_TYPE_BFLOAT16, 2, const_cast<void*>(ptr), dims, strides, box, es, CU_TENSOR_MAP_INTERLEAVE_NONE,
      box_cols == 64 ? CU_TENSOR_MAP_SWIZZLE_128B : box_cols == 32 ? CU_TENSOR_MAP_SWIZZLE_64B : CU_TENSOR_MAP_SWIZZLE_NONE, CU_TENSOR_MAP_L2_PROMOTION_L2_256B, CU_TENSOR_MAP_FLOAT_OOB_FILL_NONE);
}
void make_map5(EncodeFn enc, CUtensorMap* m, const void* ptr, bool words, const cuuint64_t (&dims)[5], const cuuint64_t (&strides)[4], const cuuint32_t (&box)[5]) {
  const cuuint32_t es[5] = {1, 1, 1, 1, 1};
  enc(m, words ? CU_TENSOR_MAP_DATA_TYPE_UINT64 : CU_TENSOR_MAP_DATA_TYPE_BFLOAT16, 5, const_cast<void*>(ptr), dims, strides, box, es, CU_TENSOR_MAP_INTERLEAVE_NONE,
      words ? CU_TENSOR_MAP_SWIZZLE_NONE : CU_TENSOR_MAP_SWIZZLE_128B, dims[0] % 64 ? CU_TENSOR_MAP_L2_PROMOTION_L2_128B : CU_TENSOR_MAP_L2_PROMOTION_L2_256B,
      CU_TENSOR_MAP_FLOAT_OOB_FILL_NONE);
}
void make_tiles(EncodeFn enc, CUtensorMap* m, const void* ptr, cuuint64_t cols, cuuint64_t tile) {
  make_map5(enc, m, ptr, false, {tile, 1, 1, cols / tile, DM}, {tile * 2, tile * 2, tile * 2, cols * 2}, {64, 1, 1, 1, 64});
}
template <class... KA, class... A>
void launch(void (*kern)(KA...), int grid, int block, int smem, int cluster, bool pdl, A... args) {
  cudaFuncSetAttribute(kern, cudaFuncAttributeMaxDynamicSharedMemorySize, smem);
  cudaLaunchConfig_t cfg = {};
  cfg.gridDim = dim3(grid); cfg.blockDim = dim3(block); cfg.dynamicSmemBytes = smem; cfg.stream = cudaStreamPerThread;
  cudaLaunchAttribute at[2];
  int n = 0;
  if (cluster > 1) { at[n].id = cudaLaunchAttributeClusterDimension; at[n].val.clusterDim.x = cluster; at[n].val.clusterDim.y = 1; at[n].val.clusterDim.z = 1; n++; }
  if (pdl) { at[n].id = cudaLaunchAttributeProgrammaticStreamSerialization; at[n].val.programmaticStreamSerializationAllowed = 1; n++; }
  cfg.attrs = at; cfg.numAttrs = n;
  cudaLaunchKernelEx(&cfg, kern, args...);
}
template <class T> void* sym(T& s) { void* p = nullptr; cudaGetSymbolAddress(&p, s); return p; }

}

#define MODE(b) 0
extern "C" void kernel_launch(void* const* d_in, const int* in_sizes, int n_in, void* d_out, int out_size) {
  const __nv_bfloat16* x = (const __nv_bfloat16*)d_in[0];
  void* fn = nullptr; cudaDriverEntryPointQueryResult qr;
  cudaGetDriverEntryPoint("cuTensorMapEncodeTiled", &fn, cudaEnableDefault, &qr);
  EncodeFn enc = (EncodeFn)fn;

  WorkParams wk = {};
  ChainParams& ch = wk.ch;
  AttnParams at = {};
  make_map(enc, &ch.wq, d_in[2], HD, DM, 160); make_map(enc, &ch.wk, d_in[3], HD, DM, 160); make_map(enc, &ch.wv, d_in[4], HD, DM, 160);
  make_map(enc, &ch.wo, d_in[5], DM, HD, 192, 32);
  ch.mem0 = (const __nv_bfloat16*)d_in[1];
  ch.wb = (const uint8_t*)d_in[8];
  ch.d1 = 300; ch.d2 = 200; ch.dn = 150; ch.dx = 950;
  make_tiles(enc, &wk.wq, d_in[2], HD, 192);
  for (int i = 0; i < 3; i++) make_tiles(enc, &wk.wb[i], d_in[8], 1920, 80 << i);
  for (int i = 0; i < 2; i++) make_tiles(enc, &wk.wc[i], d_in[9], DM, 80 << 2 * i);
  make_map(enc, &wk.out, d_out, DM, SEQ, 16, 80);
  make_map5(enc, &wk.wo, d_in[5], false, {DM, 2, 4, 4, HD / 32}, {DM * 2, DM * 16, DM * 4, DM * 64}, {64, 2, 4, 4, 2});
  make_map5(enc, &wk.xn, sym(g_xn), true, {1280, 2, 2, 64, 1}, {10240, 20480, 40960, 40960}, {128, 2, 2, 4, 1});
  make_map5(enc, &wk.xp, sym(g_xn), true, {1280, 2, 1, 64, 2}, {10240, 10240, 40960, 20480}, {128, 2, 1, 4, 2});
  make_map5(enc, &ch.xc, sym(g_xn), true, {160, 1, 1, 256, 8}, {1280, 1280, 10240, 1280}, {160, 1, 1, 4, 2});
  wk.x = x;
  for (int i = 0; i < 4; i++) at.pf[i] = (const uint8_t*)d_in[i < 2 ? 3 + i : i == 2 ? 2 : 5];
  int qa_end[2] = {12, 12};
  for (int layer = 0; layer < 2; layer++) {
    ch.sync = wk.sync = at.sync = (uint32_t*)sym(g_sync) + layer * SY_N;
    ch.other = (uint32_t*)sym(g_sync) + (1 - layer) * SY_N;
    ch.layer = layer;
    at.next = layer ? nullptr : ch.other;
    wk.qa_end = qa_end[layer];
    wk.kind = layer ? WK_LEAD : WK_FIRST;
    launch(work_kernel, 132, 384, CH_SMEM, 1, layer != 0, wk);
    wk.kind = WK_CHAIN;
    launch(work_kernel, 96, 384, CH_SMEM, 3, true, wk);
    launch(attn_b_kernel, 128, AB_T + 128, AB_SMEM, 1, true, at);
  }
  wk.kind = WK_LAST;
  launch(work_kernel, 128, 384, CH_SMEM, 1, true, wk);
}
```

```cpp
#include <cuda_runtime.h>
#include <cuda_bf16.h>
#include <cuda.h>
#include <stdint.h>
#include <stdlib.h>

namespace {

constexpr int SEQ = 2048, DM = 640, HD = 6144, NSEG = 64;
constexpr int SPIN_LIMIT = 1 << 20;

__device__ __align__(128) uint2 g_x[256 * 17 * 1280];
__device__ __align__(128) uint32_t g_xn[SEQ * DM / 2];
__device__ __align__(128) uint32_t g_of[SEQ * DM / 2];
__device__ __align__(128) uint4 g_o[SEQ * HD / 8];
__device__ __align__(128) uint4 g_q[SEQ * HD / 8];
constexpr int KV_M = 16384, KV_PART = 20480, KV_V = 3 * KV_PART;
__device__ __align__(128) uint8_t g_kv[16 * 32 * 6 * KV_PART];
#define OP_B8 11
#define OP_B16 14
#define OP_N4 15
#define BQ_12 12
#define BQ_24 14
#define FIN_16 12
__host__ __device__ constexpr int op_split(int b) { return b < OP_B8 ? 4 : b < OP_B16 ? 8 : 16; }
__host__ __device__ constexpr int op_steps(int b) { return b < OP_B8 ? 24 : b < OP_B16 ? 12 : 6; }
__host__ __device__ constexpr int op_tiles(int b) { return b < OP_N4 ? 2 : 4; }
__host__ __device__ constexpr int fin_items(int b) { return b < OP_B8 ? 4 : b < FIN_16 ? 8 : 16; }
__host__ __device__ constexpr int bq_items(int b) { return b < BQ_12 ? 6 : b < BQ_24 ? 12 : 24; }
__host__ __device__ constexpr int ln_items(int layer, int b) { return layer == 0 && b < 2 ? 16 : 4; }
constexpr int SY_P = 128, SY_T = 192, SY_UP = 224, SY_OB = 225, SY_PRE = 256, SY_PART = 288, SY_TIME = 384, SY_N = 448;
__device__ __align__(128) uint32_t g_sync[2 * SY_N];
constexpr int NSLOT = 92;
__device__ uint32_t g_pool[(NSLOT + 2) * 2048];
__device__ uint32_t g_smpart[256], g_orient[NSLOT];
__device__ __align__(128) uint32_t g_bqkv[3 * 32 * 256 * 96];

#define BT(i)
#define MISS(k, n)
#define PRO(i)
#define TRACE(w)
#define ITEM(code, w)
#define STAT(k)
#define TMV(i, v)
#define TM(i)
#define TMD(i, dep)

__device__ __forceinline__ uint32_t gtime() { uint32_t c; asm volatile("mov.u32 %0, %%globaltimer_lo;" : "=r"(c) :: "memory"); return c; }
__device__ __forceinline__ uint32_t clk32() { uint32_t c; asm volatile("mov.u32 %0, %%clock;" : "=r"(c) :: "memory"); return c; }
__device__ __forceinline__ uint32_t fresh_tid() { uint32_t t; asm volatile("mov.u32 %0, %%tid.x;" : "=r"(t)); return t; }
__device__ __forceinline__ uint32_t s2u(const void* p) { return (uint32_t)__cvta_generic_to_shared(p); }
__device__ __forceinline__ uint32_t pack2(float a, float b) {
  uint32_t r; asm("cvt.rn.bf16x2.f32 %0, %1, %2;" : "=r"(r) : "f"(b), "f"(a)); return r; }
__device__ __forceinline__ float bf_lo(uint32_t w) { return __uint_as_float(w << 16); }
__device__ __forceinline__ float bf_hi(uint32_t w) { return __uint_as_float(w & 0xffff0000u); }
__device__ __forceinline__ float ex2(float x) { float y; asm("ex2.approx.ftz.f32 %0, %1;" : "=f"(y) : "f"(x)); return y; }

__device__ __forceinline__ void mbar_init(uint32_t bar, uint32_t n) {
  asm volatile("mbarrier.init.shared::cta.b64 [%0], %1;" :: "r"(bar), "r"(n) : "memory"); }
__device__ __forceinline__ void mbar_expect(uint32_t bar, uint32_t bytes) {
  asm volatile("mbarrier.arrive.expect_tx.shared::cta.b64 _, [%0], %1;" :: "r"(bar), "r"(bytes) : "memory"); }
__device__ __forceinline__ void mbar_arrive(uint32_t bar) {
  asm volatile("mbarrier.arrive.shared::cta.b64 _, [%0];" :: "r"(bar) : "memory"); }
__device__ __forceinline__ void mbar_arrive_remote(uint32_t bar) {
  asm volatile("mbarrier.arrive.shared::cluster.b64 _, [%0];" :: "r"(bar) : "memory"); }
__device__ __forceinline__ void mbar_wait(uint32_t bar, uint32_t ph) {
  asm volatile("{.reg .pred p; .reg .u32 n; mov.u32 n, 0;\n"
               "W: mbarrier.try_wait.parity.shared::cta.b64 p, [%0], %1; @p bra.uni D;\n"
               "add.u32 n, n, 1; setp.gt.u32 p, n, %2; @p trap; bra.uni W;\n"
               "D: }" :: "r"(bar), "r"(ph), "n"(SPIN_LIMIT) : "memory");
}
__device__ __forceinline__ bool elect() {
  uint32_t p; asm volatile("{.reg .pred q; elect.sync _|q, 0xffffffff; selp.u32 %0, 1, 0, q;}" : "=r"(p)); return p; }
__device__ __forceinline__ void spin_guard(int& n) {
  asm volatile("{.reg .pred p; add.s32 %0, %0, 1; setp.gt.s32 p, %0, %1; @p trap;}" : "+r"(n) : "n"(SPIN_LIMIT));
}
__device__ __forceinline__ void pdl_wait() { asm volatile("griddepcontrol.wait;" ::: "memory"); TRACE(1); }
__device__ __forceinline__ void pdl_launch() { asm volatile("griddepcontrol.launch_dependents;" ::: "memory"); }
__device__ __forceinline__ uint32_t ld_acquire(const uint32_t* p) { uint32_t v; asm volatile("ld.acquire.gpu.global.u32 %0, [%1];" : "=r"(v) : "l"(p) : "memory"); return v; }
__device__ __forceinline__ void red_release(uint32_t* p, uint32_t v) { asm volatile("red.release.gpu.global.add.u32 [%0], %1;" :: "l"(p), "r"(v) : "memory"); }
__device__ __forceinline__ void fence_async_global() { asm volatile("fence.proxy.async.global;" ::: "memory"); }
__device__ __forceinline__ void fence_async() { asm volatile("fence.proxy.async.shared::cta;" ::: "memory"); }
__device__ __forceinline__ void bar_sync(int id, int n) { asm volatile("bar.sync %0, %1;" :: "r"(id), "r"(n) : "memory"); }
__device__ __forceinline__ void bar_arrive(int id, int n) { asm volatile("bar.arrive %0, %1;" :: "r"(id), "r"(n) : "memory"); }
__device__ __forceinline__ void tma_load(uint32_t dst, const CUtensorMap* m, int c0, int c1, uint32_t bar) {
  asm volatile("cp.async.bulk.tensor.2d.shared::cluster.global.mbarrier::complete_tx::bytes [%0], [%1, {%3, %4}], [%2];"
               :: "r"(dst), "l"(m), "r"(bar), "r"(c0), "r"(c1) : "memory"); }
__device__ __forceinline__ void tma_load5(uint32_t dst, const CUtensorMap* m, int c0, int c3, int c4, uint32_t bar) {
  asm volatile("cp.async.bulk.tensor.5d.shared::cluster.global.mbarrier::complete_tx::bytes [%0], [%1, {%3, %6, %6, %4, %5}], [%2];"
               :: "r"(dst), "l"(m), "r"(bar), "r"(c0), "r"(c3), "r"(c4), "r"(0) : "memory"); }
__device__ __forceinline__ void tma_store(const CUtensorMap* m, uint32_t src, int c0, int c1) {
  asm volatile("cp.async.bulk.tensor.2d.global.shared::cta.bulk_group [%0, {%2, %3}], [%1];"
               :: "l"(m), "r"(src), "r"(c0), "r"(c1) : "memory"); }
__device__ __forceinline__ uint64_t evict_first() { uint64_t p; asm("createpolicy.fractional.L2::evict_first.b64 %0, 1.0;" : "=l"(p)); return p; }
__device__ __forceinline__ void bulk_load_last(uint32_t dst, const void* src, uint32_t bytes, uint32_t bar) {
  asm volatile("cp.async.bulk.shared::cluster.global.mbarrier::complete_tx::bytes.L2::cache_hint [%0], [%1], %2, [%3], %4;"
               :: "r"(dst), "l"(src), "r"(bytes), "r"(bar), "l"(evict_first()) : "memory"); }
__device__ __forceinline__ void bulk_store_stream(void* dst, uint32_t src, uint32_t bytes) {
  asm volatile("cp.async.bulk.global.shared::cta.bulk_group.L2::cache_hint [%0], [%1], %2, %3;" :: "l"(dst), "r"(src), "r"(bytes), "l"(evict_first()) : "memory"); }
__device__ __forceinline__ void bulk_load(uint32_t dst, const void* src, uint32_t bytes, uint32_t bar) {
  asm volatile("cp.async.bulk.shared::cluster.global.mbarrier::complete_tx::bytes [%0], [%1], %2, [%3];"
               :: "r"(dst), "l"(src), "r"(bytes), "r"(bar) : "memory"); }
__device__ __forceinline__ void bulk_push(uint32_t dst, uint32_t src, uint32_t bytes, uint32_t bar) {
  asm volatile("cp.async.bulk.shared::cluster.shared::cta.mbarrier::complete_tx::bytes [%0], [%1], %2, [%3];"
               :: "r"(dst), "r"(src), "r"(bytes), "r"(bar) : "memory"); }
__device__ __forceinline__ void bulk_store(void* dst, uint32_t src, uint32_t bytes) {
  asm volatile("cp.async.bulk.global.shared::cta.bulk_group [%0], [%1], %2;" :: "l"(dst), "r"(src), "r"(bytes) : "memory"); }
__device__ __forceinline__ void bulk_commit() { asm volatile("cp.async.bulk.commit_group;" ::: "memory"); }
template <int N> __device__ __forceinline__ void bulk_wait_read() { asm volatile("cp.async.bulk.wait_group.read %0;" :: "n"(N) : "memory"); }
template <int N> __device__ __forceinline__ void bulk_wait() { asm volatile("cp.async.bulk.wait_group %0;" :: "n"(N) : "memory"); }

__device__ __forceinline__ uint64_t mkdesc(uint32_t addr, uint32_t lbo, uint32_t sbo, uint32_t sw) {
  return (uint64_t)((addr & 0x3FFFF) >> 4) | ((uint64_t)(lbo >> 4) << 16) | ((uint64_t)(sbo >> 4) << 32) | ((uint64_t)sw << 62); }
__device__ __forceinline__ void wg_fence() { asm volatile("wgmma.fence.sync.aligned;" ::: "memory"); }
__device__ __forceinline__ void wg_commit() { asm volatile("wgmma.commit_group.sync.aligned;" ::: "memory"); }
template <int N> __device__ __forceinline__ void wg_wait() { asm volatile("wgmma.wait_group.sync.aligned %0;" :: "n"(N) : "memory"); }
template <int N> __device__ __forceinline__ void reg_fence(float* d) {
#pragma unroll
  for (int i = 0; i < N; i++) asm volatile("" : "+f"(d[i]) :: "memory");
}

__device__ __forceinline__ void mma16(float* d, uint32_t a0, uint32_t a1, uint32_t a2, uint32_t a3, uint32_t b0, uint32_t b1) {
  asm volatile("mma.sync.aligned.m16n8k16.row.col.f32.bf16.bf16.f32 {%0,%1,%2,%3},{%4,%5,%6,%7},{%8,%9},{%0,%1,%2,%3};"
               : "+f"(d[0]), "+f"(d[1]), "+f"(d[2]), "+f"(d[3]) : "r"(a0), "r"(a1), "r"(a2), "r"(a3), "r"(b0), "r"(b1)); }
__device__ __forceinline__ void mma8(float* d, uint32_t a0, uint32_t a1, uint32_t b0) {
  asm volatile("mma.sync.aligned.m16n8k8.row.col.f32.bf16.bf16.f32 {%0,%1,%2,%3},{%4,%5},{%6},{%0,%1,%2,%3};"
               : "+f"(d[0]), "+f"(d[1]), "+f"(d[2]), "+f"(d[3]) : "r"(a0), "r"(a1), "r"(b0)); }
__device__ __forceinline__ void ldsm4(uint32_t* r, uint32_t a) {
  asm volatile("ldmatrix.sync.aligned.m8n8.x4.shared.b16 {%0,%1,%2,%3},[%4];" : "=r"(r[0]), "=r"(r[1]), "=r"(r[2]), "=r"(r[3]) : "r"(a) : "memory"); }
__device__ __forceinline__ uint4 ldsm4v(uint32_t a) { uint32_t r[4]; ldsm4(r, a); return make_uint4(r[0], r[1], r[2], r[3]); }
__device__ __forceinline__ void ldsm4t(uint32_t* r, uint32_t a) {
  asm volatile("ldmatrix.sync.aligned.m8n8.x4.trans.shared.b16 {%0,%1,%2,%3},[%4];" : "=r"(r[0]), "=r"(r[1]), "=r"(r[2]), "=r"(r[3]) : "r"(a) : "memory"); }
__device__ __forceinline__ void ldsm2t(uint32_t* r, uint32_t a) {
  asm volatile("ldmatrix.sync.aligned.m8n8.x2.trans.shared.b16 {%0,%1},[%2];" : "=r"(r[0]), "=r"(r[1]) : "r"(a) : "memory"); }
__device__ __forceinline__ void stsm4(uint32_t a, uint32_t r0, uint32_t r1, uint32_t r2, uint32_t r3) {
  asm volatile("stmatrix.sync.aligned.m8n8.x4.shared.b16 [%0], {%1,%2,%3,%4};" :: "r"(a), "r"(r0), "r"(r1), "r"(r2), "r"(r3) : "memory"); }
__device__ __forceinline__ void stsm4t(uint32_t a, uint32_t r0, uint32_t r1, uint32_t r2, uint32_t r3) {
  asm volatile("stmatrix.sync.aligned.m8n8.x4.trans.shared.b16 [%0], {%1,%2,%3,%4};" :: "r"(a), "r"(r0), "r"(r1), "r"(r2), "r"(r3) : "memory"); }
__device__ __forceinline__ void stsm2(uint32_t a, uint32_t r0, uint32_t r1) {
  asm volatile("stmatrix.sync.aligned.m8n8.x2.shared.b16 [%0], {%1,%2};" :: "r"(a), "r"(r0), "r"(r1) : "memory"); }
__device__ __forceinline__ void stsm2t(uint32_t a, uint32_t r0, uint32_t r1) {
  asm volatile("stmatrix.sync.aligned.m8n8.x2.trans.shared.b16 [%0], {%1,%2};" :: "r"(a), "r"(r0), "r"(r1) : "memory"); }
__device__ __forceinline__ void sts32(uint32_t a, uint32_t v) { asm volatile("st.shared.b32 [%0], %1;" :: "r"(a), "r"(v) : "memory"); }
__device__ __forceinline__ void sts64f(uint32_t a, float x, float y) { asm volatile("st.shared.v2.f32 [%0], {%1,%2};" :: "r"(a), "f"(x), "f"(y) : "memory"); }
__device__ __forceinline__ void sts128(uint32_t a, uint4 v) {
  asm volatile("st.shared.v4.b32 [%0], {%1,%2,%3,%4};" :: "r"(a), "r"(v.x), "r"(v.y), "r"(v.z), "r"(v.w) : "memory"); }
__device__ __forceinline__ void sts128f(uint32_t a, float x, float y, float z, float w) {
  asm volatile("st.shared.v4.f32 [%0], {%1,%2,%3,%4};" :: "r"(a), "f"(x), "f"(y), "f"(z), "f"(w) : "memory"); }
__device__ __forceinline__ float lds32f(uint32_t a) { float v; asm volatile("ld.shared.f32 %0, [%1];" : "=f"(v) : "r"(a) : "memory"); return v; }
__device__ __forceinline__ float2 lds64f(uint32_t a) { float2 v; asm volatile("ld.shared.v2.f32 {%0,%1}, [%2];" : "=f"(v.x), "=f"(v.y) : "r"(a) : "memory"); return v; }
__device__ __forceinline__ float4 lds128f(uint32_t a) {
  float4 v; asm volatile("ld.shared.v4.f32 {%0,%1,%2,%3}, [%4];" : "=f"(v.x), "=f"(v.y), "=f"(v.z), "=f"(v.w) : "r"(a) : "memory"); return v; }
__device__ __forceinline__ uint4 lds128(uint32_t a) {
  uint4 v; asm volatile("ld.shared.v4.b32 {%0,%1,%2,%3}, [%4];" : "=r"(v.x), "=r"(v.y), "=r"(v.z), "=r"(v.w) : "r"(a) : "memory"); return v; }
__device__ __forceinline__ uint4 ldg_strong128(const void* p) {
  uint4 v; asm volatile("ld.relaxed.gpu.global.v4.u32 {%0,%1,%2,%3}, [%4];" : "=r"(v.x), "=r"(v.y), "=r"(v.z), "=r"(v.w) : "l"(p) : "memory"); return v; }
__device__ __forceinline__ uint2 ldg_strong64(const void* p) {
  uint2 v; asm volatile("ld.relaxed.gpu.global.v2.u32 {%0,%1}, [%2];" : "=r"(v.x), "=r"(v.y) : "l"(p) : "memory"); return v; }
__device__ __forceinline__ void stg_strong32(void* p, uint32_t v) { asm volatile("st.relaxed.gpu.global.u32 [%0], %1;" :: "l"(p), "r"(v) : "memory"); }
__device__ __forceinline__ void stg_strong128(void* p, uint4 v) {
  asm volatile("st.relaxed.gpu.global.v4.u32 [%0], {%1,%2,%3,%4};" :: "l"(p), "r"(v.x), "r"(v.y), "r"(v.z), "r"(v.w) : "memory"); }
__device__ __forceinline__ uint32_t mapa(uint32_t a, uint32_t r) {
  uint32_t o; asm("mapa.shared::cluster.u32 %0, %1, %2;" : "=r"(o) : "r"(a), "r"(r)); return o; }
__device__ __forceinline__ void st_async2f(uint32_t a, float x, float y, uint32_t bar) {
  asm volatile("st.async.shared::cluster.mbarrier::complete_tx::bytes.v2.f32 [%0], {%1,%2}, [%3];" :: "r"(a), "f"(x), "f"(y), "r"(bar) : "memory"); }
__device__ __forceinline__ void st_async32(uint32_t a, uint32_t x, uint32_t bar) {
  asm volatile("st.async.shared::cluster.mbarrier::complete_tx::bytes.b32 [%0], %1, [%2];" :: "r"(a), "r"(x), "r"(bar) : "memory"); }
__device__ __forceinline__ uint32_t lds32(uint32_t a) { uint32_t v; asm volatile("ld.shared.b32 %0, [%1];" : "=r"(v) : "r"(a) : "memory"); return v; }
__device__ __forceinline__ void st_async64(uint32_t a, uint32_t x, uint32_t y, uint32_t bar, uint32_t on) {
  asm volatile("{.reg .pred p; setp.ne.u32 p, %4, 0; @p st.async.shared::cluster.mbarrier::complete_tx::bytes.v2.b32 [%0], {%1,%2}, [%3];}" :: "r"(a), "r"(x), "r"(y), "r"(bar), "r"(on) : "memory"); }
__device__ __forceinline__ void st_async128(uint32_t a, uint4 v, uint32_t bar) {
  asm volatile("st.async.shared::cluster.mbarrier::complete_tx::bytes.v4.b32 [%0], {%1,%2,%3,%4}, [%5];" :: "r"(a), "r"(v.x), "r"(v.y), "r"(v.z), "r"(v.w), "r"(bar) : "memory"); }
__device__ __forceinline__ uint2 lds64(uint32_t a) { uint2 v; asm volatile("ld.shared.v2.b32 {%0,%1}, [%2];" : "=r"(v.x), "=r"(v.y) : "r"(a) : "memory"); return v; }
__device__ __forceinline__ void sts64(uint32_t a, uint32_t x, uint32_t y) { asm volatile("st.shared.v2.b32 [%0], {%1,%2};" :: "r"(a), "r"(x), "r"(y) : "memory"); }
__device__ __forceinline__ uint32_t ldg_strong32(const void* p) { uint32_t v; asm volatile("ld.relaxed.gpu.global.u32 %0, [%1];" : "=r"(v) : "l"(p) : "memory"); return v; }
__device__ __forceinline__ uint32_t transpose8(uint32_t x) { uint32_t r; asm volatile("movmatrix.sync.aligned.m8n8.trans.b16 %0, %1;" : "=r"(r) : "r"(x)); return r; }
__device__ __forceinline__ uint32_t hadd2(uint32_t a, uint32_t b) { uint32_t r; asm("add.rn.bf16x2 %0, %1, %2;" : "=r"(r) : "r"(a), "r"(b)); return r; }
__device__ __forceinline__ uint32_t min4(uint4 v) { return min(__vimin3_u32(v.x, v.y, v.z), v.w); }

__device__ __forceinline__ void wg_ss192_01(float* d, uint64_t da, uint64_t db, int sd) {
  asm volatile("{.reg .pred p; setp.ne.b32 p, %98, 0;\n"
    "wgmma.mma_async.sync.aligned.m64n192k16.f32.bf16.bf16 {%0,%1,%2,%3,%4,%5,%6,%7,%8,%9,%10,%11,%12,%13,%14,%15,%16,%17,%18,%19,%20,%21,%22,%23,%24,%25,%26,%27,%28,%29,%30,%31,%32,%33,%34,%35,%36,%37,%38,%39,%40,%41,%42,%43,%44,%45,%46,%47,%48,%49,%50,%51,%52,%53,%54,%55,%56,%57,%58,%59,%60,%61,%62,%63,%64,%65,%66,%67,%68,%69,%70,%71,%72,%73,%74,%75,%76,%77,%78,%79,%80,%81,%82,%83,%84,%85,%86,%87,%88,%89,%90,%91,%92,%93,%94,%95}, %96, %97, p, 1, 1, 0, 1;}"
    : "+f"(d[0]),"+f"(d[1]),"+f"(d[2]),"+f"(d[3]),"+f"(d[4]),"+f"(d[5]),"+f"(d[6]),"+f"(d[7]),"+f"(d[8]),"+f"(d[9]),"+f"(d[10]),"+f"(d[11]),"+f"(d[12]),"+f"(d[13]),"+f"(d[14]),"+f"(d[15]),"+f"(d[16]),"+f"(d[17]),"+f"(d[18]),"+f"(d[19]),"+f"(d[20]),"+f"(d[21]),"+f"(d[22]),"+f"(d[23]),"+f"(d[24]),"+f"(d[25]),"+f"(d[26]),"+f"(d[27]),"+f"(d[28]),"+f"(d[29]),"+f"(d[30]),"+f"(d[31]),"+f"(d[32]),"+f"(d[33]),"+f"(d[34]),"+f"(d[35]),"+f"(d[36]),"+f"(d[37]),"+f"(d[38]),"+f"(d[39]),"+f"(d[40]),"+f"(d[41]),"+f"(d[42]),"+f"(d[43]),"+f"(d[44]),"+f"(d[45]),"+f"(d[46]),"+f"(d[47]),"+f"(d[48]),"+f"(d[49]),"+f"(d[50]),"+f"(d[51]),"+f"(d[52]),"+f"(d[53]),"+f"(d[54]),"+f"(d[55]),"+f"(d[56]),"+f"(d[57]),"+f"(d[58]),"+f"(d[59]),"+f"(d[60]),"+f"(d[61]),"+f"(d[62]),"+f"(d[63]),"+f"(d[64]),"+f"(d[65]),"+f"(d[66]),"+f"(d[67]),"+f"(d[68]),"+f"(d[69]),"+f"(d[70]),"+f"(d[71]),"+f"(d[72]),"+f"(d[73]),"+f"(d[74]),"+f"(d[75]),"+f"(d[76]),"+f"(d[77]),"+f"(d[78]),"+f"(d[79]),"+f"(d[80]),"+f"(d[81]),"+f"(d[82]),"+f"(d[83]),"+f"(d[84]),"+f"(d[85]),"+f"(d[86]),"+f"(d[87]),"+f"(d[88]),"+f"(d[89]),"+f"(d[90]),"+f"(d[91]),"+f"(d[92]),"+f"(d[93]),"+f"(d[94]),"+f"(d[95])
    : "l"(da), "l"(db), "r"(sd));
}
__device__ __forceinline__ void wg_ss128_01(float* d, uint64_t da, uint64_t db, int sd) {
  asm volatile("{.reg .pred p; setp.ne.b32 p, %66, 0;\n"
    "wgmma.mma_async.sync.aligned.m64n128k16.f32.bf16.bf16 {%0,%1,%2,%3,%4,%5,%6,%7,%8,%9,%10,%11,%12,%13,%14,%15,%16,%17,%18,%19,%20,%21,%22,%23,%24,%25,%26,%27,%28,%29,%30,%31,%32,%33,%34,%35,%36,%37,%38,%39,%40,%41,%42,%43,%44,%45,%46,%47,%48,%49,%50,%51,%52,%53,%54,%55,%56,%57,%58,%59,%60,%61,%62,%63}, %64, %65, p, 1, 1, 0, 1;}"
    : "+f"(d[0]),"+f"(d[1]),"+f"(d[2]),"+f"(d[3]),"+f"(d[4]),"+f"(d[5]),"+f"(d[6]),"+f"(d[7]),"+f"(d[8]),"+f"(d[9]),"+f"(d[10]),"+f"(d[11]),"+f"(d[12]),"+f"(d[13]),"+f"(d[14]),"+f"(d[15]),"+f"(d[16]),"+f"(d[17]),"+f"(d[18]),"+f"(d[19]),"+f"(d[20]),"+f"(d[21]),"+f"(d[22]),"+f"(d[23]),"+f"(d[24]),"+f"(d[25]),"+f"(d[26]),"+f"(d[27]),"+f"(d[28]),"+f"(d[29]),"+f"(d[30]),"+f"(d[31]),"+f"(d[32]),"+f"(d[33]),"+f"(d[34]),"+f"(d[35]),"+f"(d[36]),"+f"(d[37]),"+f"(d[38]),"+f"(d[39]),"+f"(d[40]),"+f"(d[41]),"+f"(d[42]),"+f"(d[43]),"+f"(d[44]),"+f"(d[45]),"+f"(d[46]),"+f"(d[47]),"+f"(d[48]),"+f"(d[49]),"+f"(d[50]),"+f"(d[51]),"+f"(d[52]),"+f"(d[53]),"+f"(d[54]),"+f"(d[55]),"+f"(d[56]),"+f"(d[57]),"+f"(d[58]),"+f"(d[59]),"+f"(d[60]),"+f"(d[61]),"+f"(d[62]),"+f"(d[63])
    : "l"(da), "l"(db), "r"(sd));
}
__device__ __forceinline__ void wg_ss160_01(float* d, uint64_t da, uint64_t db, int sd) {
  asm volatile("{.reg .pred p; setp.ne.b32 p, %82, 0;\n"
    "wgmma.mma_async.sync.aligned.m64n160k16.f32.bf16.bf16 {%0,%1,%2,%3,%4,%5,%6,%7,%8,%9,%10,%11,%12,%13,%14,%15,%16,%17,%18,%19,%20,%21,%22,%23,%24,%25,%26,%27,%28,%29,%30,%31,%32,%33,%34,%35,%36,%37,%38,%39,%40,%41,%42,%43,%44,%45,%46,%47,%48,%49,%50,%51,%52,%53,%54,%55,%56,%57,%58,%59,%60,%61,%62,%63,%64,%65,%66,%67,%68,%69,%70,%71,%72,%73,%74,%75,%76,%77,%78,%79}, %80, %81, p, 1, 1, 0, 1;}"
    : "+f"(d[0]),"+f"(d[1]),"+f"(d[2]),"+f"(d[3]),"+f"(d[4]),"+f"(d[5]),"+f"(d[6]),"+f"(d[7]),"+f"(d[8]),"+f"(d[9]),"+f"(d[10]),"+f"(d[11]),"+f"(d[12]),"+f"(d[13]),"+f"(d[14]),"+f"(d[15]),"+f"(d[16]),"+f"(d[17]),"+f"(d[18]),"+f"(d[19]),"+f"(d[20]),"+f"(d[21]),"+f"(d[22]),"+f"(d[23]),"+f"(d[24]),"+f"(d[25]),"+f"(d[26]),"+f"(d[27]),"+f"(d[28]),"+f"(d[29]),"+f"(d[30]),"+f"(d[31]),"+f"(d[32]),"+f"(d[33]),"+f"(d[34]),"+f"(d[35]),"+f"(d[36]),"+f"(d[37]),"+f"(d[38]),"+f"(d[39]),"+f"(d[40]),"+f"(d[41]),"+f"(d[42]),"+f"(d[43]),"+f"(d[44]),"+f"(d[45]),"+f"(d[46]),"+f"(d[47]),"+f"(d[48]),"+f"(d[49]),"+f"(d[50]),"+f"(d[51]),"+f"(d[52]),"+f"(d[53]),"+f"(d[54]),"+f"(d[55]),"+f"(d[56]),"+f"(d[57]),"+f"(d[58]),"+f"(d[59]),"+f"(d[60]),"+f"(d[61]),"+f"(d[62]),"+f"(d[63]),"+f"(d[64]),"+f"(d[65]),"+f"(d[66]),"+f"(d[67]),"+f"(d[68]),"+f"(d[69]),"+f"(d[70]),"+f"(d[71]),"+f"(d[72]),"+f"(d[73]),"+f"(d[74]),"+f"(d[75]),"+f"(d[76]),"+f"(d[77]),"+f"(d[78]),"+f"(d[79])
    : "l"(da), "l"(db), "r"(sd));
}
__device__ __forceinline__ void wg_ss80_01(float* d, uint64_t da, uint64_t db, int sd) {
  asm volatile("{.reg .pred p; setp.ne.b32 p, %42, 0;\n"
    "wgmma.mma_async.sync.aligned.m64n80k16.f32.bf16.bf16 {%0,%1,%2,%3,%4,%5,%6,%7,%8,%9,%10,%11,%12,%13,%14,%15,%16,%17,%18,%19,%20,%21,%22,%23,%24,%25,%26,%27,%28,%29,%30,%31,%32,%33,%34,%35,%36,%37,%38,%39}, %40, %41, p, 1, 1, 0, 1;}"
    : "+f"(d[0]),"+f"(d[1]),"+f"(d[2]),"+f"(d[3]),"+f"(d[4]),"+f"(d[5]),"+f"(d[6]),"+f"(d[7]),"+f"(d[8]),"+f"(d[9]),"+f"(d[10]),"+f"(d[11]),"+f"(d[12]),"+f"(d[13]),"+f"(d[14]),"+f"(d[15]),"+f"(d[16]),"+f"(d[17]),"+f"(d[18]),"+f"(d[19]),"+f"(d[20]),"+f"(d[21]),"+f"(d[22]),"+f"(d[23]),"+f"(d[24]),"+f"(d[25]),"+f"(d[26]),"+f"(d[27]),"+f"(d[28]),"+f"(d[29]),"+f"(d[30]),"+f"(d[31]),"+f"(d[32]),"+f"(d[33]),"+f"(d[34]),"+f"(d[35]),"+f"(d[36]),"+f"(d[37]),"+f"(d[38]),"+f"(d[39])
    : "l"(da), "l"(db), "r"(sd));
}
__device__ __forceinline__ void wg_rs32_00(float* d, uint32_t a0, uint32_t a1, uint32_t a2, uint32_t a3, uint64_t db, int sd) {
  asm volatile("{.reg .pred p; setp.ne.b32 p, %21, 0;\n"
    "wgmma.mma_async.sync.aligned.m64n32k16.f32.bf16.bf16 {%0,%1,%2,%3,%4,%5,%6,%7,%8,%9,%10,%11,%12,%13,%14,%15}, {%16,%17,%18,%19}, %20, p, 1, 1, 0;}"
    : "+f"(d[0]),"+f"(d[1]),"+f"(d[2]),"+f"(d[3]),"+f"(d[4]),"+f"(d[5]),"+f"(d[6]),"+f"(d[7]),"+f"(d[8]),"+f"(d[9]),"+f"(d[10]),"+f"(d[11]),"+f"(d[12]),"+f"(d[13]),"+f"(d[14]),"+f"(d[15])
    : "r"(a0), "r"(a1), "r"(a2), "r"(a3), "l"(db), "r"(sd));
}
__device__ __forceinline__ void wg_rs64_00(float* d, uint32_t a0, uint32_t a1, uint32_t a2, uint32_t a3, uint64_t db, int sd) {
  asm volatile("{.reg .pred p; setp.ne.b32 p, %37, 0;\n"
    "wgmma.mma_async.sync.aligned.m64n64k16.f32.bf16.bf16 {%0,%1,%2,%3,%4,%5,%6,%7,%8,%9,%10,%11,%12,%13,%14,%15,%16,%17,%18,%19,%20,%21,%22,%23,%24,%25,%26,%27,%28,%29,%30,%31}, {%32,%33,%34,%35}, %36, p, 1, 1, 0;}"
    : "+f"(d[0]),"+f"(d[1]),"+f"(d[2]),"+f"(d[3]),"+f"(d[4]),"+f"(d[5]),"+f"(d[6]),"+f"(d[7]),"+f"(d[8]),"+f"(d[9]),"+f"(d[10]),"+f"(d[11]),"+f"(d[12]),"+f"(d[13]),"+f"(d[14]),"+f"(d[15]),"+f"(d[16]),"+f"(d[17]),"+f"(d[18]),"+f"(d[19]),"+f"(d[20]),"+f"(d[21]),"+f"(d[22]),"+f"(d[23]),"+f"(d[24]),"+f"(d[25]),"+f"(d[26]),"+f"(d[27]),"+f"(d[28]),"+f"(d[29]),"+f"(d[30]),"+f"(d[31])
    : "r"(a0), "r"(a1), "r"(a2), "r"(a3), "l"(db), "r"(sd));
}
__device__ __forceinline__ void wg_rs24_01(float* d, uint32_t a0, uint32_t a1, uint32_t a2, uint32_t a3, uint64_t db, int sd) {
  asm volatile("{.reg .pred p; setp.ne.b32 p, %17, 0;\n"
    "wgmma.mma_async.sync.aligned.m64n24k16.f32.bf16.bf16 {%0,%1,%2,%3,%4,%5,%6,%7,%8,%9,%10,%11}, {%12,%13,%14,%15}, %16, p, 1, 1, 1;}"
    : "+f"(d[0]),"+f"(d[1]),"+f"(d[2]),"+f"(d[3]),"+f"(d[4]),"+f"(d[5]),"+f"(d[6]),"+f"(d[7]),"+f"(d[8]),"+f"(d[9]),"+f"(d[10]),"+f"(d[11])
    : "r"(a0), "r"(a1), "r"(a2), "r"(a3), "l"(db), "r"(sd));
}

#define AB_POLY 0x77
__device__ __forceinline__ constexpr bool poly_group(int group) { return (AB_POLY >> (group & 7)) & 1; }

template <int V> struct Int { static constexpr int value = V; };

__device__ __forceinline__ int core_word(int row, int col) {
  return ((((row >> 7) * 10 + (col >> 6)) * 16 + ((row >> 3) & 15)) * 8 + ((col >> 3) & 7)) * 32 + (row & 7) * 4 + ((col & 7) >> 1);
}
__device__ __forceinline__ void wait_count(const uint32_t* c, uint32_t n) {
  for (int spin = 0; !__all_sync(~0u, (ld_acquire(c) & 0xffff) >= n);) { __nanosleep(32); spin_guard(spin); }
  fence_async_global();
}
__device__ __forceinline__ void prefetch_l2(const void* p, uint32_t bytes) {
  asm volatile("cp.async.bulk.prefetch.L2.global [%0], %1;" :: "l"(p), "r"(bytes) : "memory"); }

#define PLACE 4
__device__ __forceinline__ bool helper_sm() {
  uint32_t m; asm volatile("mov.u32 %0, %%smid;" : "=r"(m));
  return m < 2 || m >= 120 || (m >= 92 && m < 102) || (m >= 106 && m < 117) || m == 118;
}

__device__ __forceinline__ uint8_t* pool_at(uint32_t off) {
  return reinterpret_cast<uint8_t*>((reinterpret_cast<uintptr_t>(g_pool) + 8191) & ~(uintptr_t)8191) + off; }
__device__ __forceinline__ void probe_slots(uint32_t scratch) {
  const int w = (threadIdx.x >> 6) & 1, slot = w == 0 ? NSLOT : blockIdx.x;
  if (w == 0 || slot < NSLOT) {
    uint32_t* q = reinterpret_cast<uint32_t*>(pool_at(slot * 8192)) + (w == 0 ? (blockIdx.x & 31) * 32 + (blockIdx.x >> 5) : 0);
    uint32_t best[2] = {~0u, ~0u};
    const bool one = elect();
    if (one) { stg_strong32(q, 0u); stg_strong32(q + 1024, 0u); }
#pragma unroll 1
    for (int r = 0; r < 8; r++) {
      uint32_t v = 0;
      const uint32_t t0 = clk32();
      if (one) asm volatile("atom.relaxed.gpu.global.exch.b32 %0, [%1], 0;" : "=r"(v) : "l"(q + (r & 1) * 1024) : "memory");
      if (__any_sync(~0u, v != 0)) break;
      const uint32_t t = min(clk32() - t0, best[0]);
      best[0] = best[1]; best[1] = t;
    }
    if (one) sts32(scratch + w * 4, best[0] < best[1]);
  }
  bar_sync(2, 64);
  if ((threadIdx.x & 31) == 0) {
    const int part = lds32(scratch) ? 1 : 2;
    if (w == 0) { uint32_t smid; asm("mov.u32 %0, %%smid;" : "=r"(smid)); stg_strong32(g_smpart + (smid & 255), part); }
    else if (slot < NSLOT) stg_strong32(g_orient + slot, lds32(scratch + 4) ? part : 3 - part);
  }
  __syncwarp();
}

constexpr int WK_SLOTS = 28, WK_BAR = WK_SLOTS * 8192;
__device__ __forceinline__ void work_init(uint32_t sb, int w) {
  if (elect()) {
#pragma unroll
    for (int i = 0; i < 8; i++) mbar_init(sb + WK_BAR + 64 * w + 8 * i, 0x18318822 >> (8 * w + (i & 4)) & 15);
  }
  asm volatile("fence.mbarrier_init.release.cluster;" ::: "memory");
}

struct ChainParams {
  CUtensorMap wq, wk, wv, wo, xc;
  const __nv_bfloat16* mem0;
  const uint8_t* wb;
  uint32_t *sync, *other;
  int layer;
  int d1, d2, dn, dx, mode, zero;
};
constexpr int CH_WQ = 0, CH_WO = 81920, CH_X = CH_WO + 86016, CH_M = CH_X, CH_Q = CH_X + 34816, CH_KM = CH_Q + 2048, CH_VP = CH_KM + 2048,
              CH_K = CH_X + 40960, CH_O = CH_K, CH_KS = CH_K + 3072, CH_V = CH_K + 4096, CH_VX = CH_V + 12288, CH_R2 = CH_VX,
              CH_SX = CH_VX + 3072, CH_SO = CH_SX + 2048, CH_ID = CH_SO + 1024, CH_L = CH_ID + 256, CH_TAB = CH_L + 64, CH_BAR = CH_TAB + 384;
constexpr int CH_SMEM = CH_BAR + 144;
constexpr int MB_WO = CH_BAR, MB_WQ = CH_BAR + 8, MB_X = CH_BAR + 16, MB_V = CH_BAR + 24, MB_T = CH_BAR + 32, MB_F = CH_BAR + 40, MB_G = CH_BAR + 48, MB_W = CH_BAR + 56;
enum { NB_PROJ = 1, NB_O = 2, NB_W1 = 3, NB_PRE = 4, NB_ST = 5, NB_MEM = 6, NB_XFREE = 7, NB_H1 = 8, NB_PUB = 9, NB_W2 = 10, NB_PROJ2 = 11, NB_PRE2 = 12, NB_H2 = 13, NB_W1V = 14 };
#define CH_NQ 9
#define CH_XPF 1
#define CH_TPF 1
#define CH_NQ0 4
#define CH_PA 6
#define CH_PB 10
#define CH_PC 12
#define CH_PL 3
#define CH_DBL 0x0888
#define CH_PD 1
#define SCHED() asm volatile("griddepcontrol.launch_dependents;" ::: "memory")
__device__ __forceinline__ uint32_t opaque(uint32_t x) { return __shfl_sync(~0u, x, threadIdx.x & 31); }
__device__ __forceinline__ uint32_t uniform(uint32_t x) { return __shfl_sync(~0u, x, 0); }
__device__ __forceinline__ uint32_t nz(uint32_t x) { uint32_t r; asm("max.u32 %0, %1, 1;" : "=r"(r) : "r"(x)); return r; }
__device__ __forceinline__ uint32_t set_tag(uint32_t w, uint32_t tag) { uint32_t r; asm("lop3.b32 %0, %1, %2, 1, 0xD8;" : "=r"(r) : "r"(w), "r"(tag)); return r; }
__device__ __forceinline__ uint32_t pack_tag(float lo, float hi, uint32_t tag) { return set_tag(__byte_perm(__float_as_uint(lo) + tag, pack2(hi, hi), 0x7632), tag); }
__device__ __forceinline__ uint32_t differ(uint32_t a, uint32_t b, uint32_t t) { uint32_t r; asm("lop3.b32 %0, %1, %2, %3, 0x7E;" : "=r"(r) : "r"(a), "r"(b), "r"(t)); return r; }
__device__ __forceinline__ uint32_t clk64() { uint64_t c; asm volatile("mov.u64 %0, %%clock64;" : "=l"(c) :: "memory"); return (uint32_t)c; }
__device__ __forceinline__ void until(uint32_t t) {
  asm volatile("{.reg .pred p; .reg .u64 c; .reg .s32 d;\nW: mov.u64 c, %%clock64; cvt.u32.u64 d, c; sub.s32 d, d, %0; setp.lt.s32 p, d, 0; @p bra.uni W;}" :: "r"(t) : "memory");
}
__device__ __forceinline__ float rcp(float x) { float y; asm("rcp.approx.ftz.f32 %0, %1;" : "=f"(y) : "f"(x)); return y; }

__device__ __forceinline__ void chain_compute(const ChainParams& p, const uint32_t sb) {
  const int tid = threadIdx.x & 127, WG = __shfl_sync(~0u, threadIdx.x >> 7, 0), t4 = __shfl_sync(~0u, tid >> 5, 0), lane = tid & 31;
  const int cta = blockIdx.x, h = cta / 3, j = cta - 3 * h;
  uint32_t a0[80], a1[80], tw[4 * CH_NQ];
  const uint32_t wq = opaque(sb + CH_WQ + (WG * 320 + (lane & 7) + (lane >> 4) * 8) * 128 + (((2 * t4 + ((lane >> 3) & 1)) ^ (lane & 7)) << 4));
#pragma unroll
  for (int k = 0; k < 40; k++) {
    if (k % 10 == 0) mbar_wait(sb + MB_W + WG * 16 + k / 20 * 32 + k / 10 % 2 * 8, 0);
    if (k < 20) ldsm4t(&a0[4 * k], wq + k * 2048); else ldsm4t(&a1[4 * k - 80], wq + CH_WO + (k - 20) * 2048);
    if (k % 20 == 19) bar_arrive(k < 20 ? NB_PROJ2 : NB_PRE2, 384);
  }
  const int r1 = j == 2 ? 0 : j + 1, r2 = j == 0 ? 2 : j - 1;
  const uint32_t l16 = opaque(sb + lane * 16), l8 = opaque(sb + lane * 8), l4 = opaque(sb + lane * 4);
  const uint32_t t16 = l16 + t4 * 512, t8 = l8 + t4 * 256;
  uint32_t wo = opaque(sb + CH_WO + (WG == 0 ? (t4 >> 1) * 36864 : 73728 + t4 * 1024) + ((lane & 7) + (lane >> 4) * 8) * 64 +
                       (((((lane >> 3) & 1) + (WG == 0 ? (t4 & 1) * 2 : 0)) ^ ((lane >> 1) & 3)) << 4));
  const uint32_t ko0 = uniform(CH_K + (tid >> 6) * 3072 + (tid & 32) * 8), ko1 = uniform(CH_K + (tid >> 6) * 1024 + 1024 + (tid & 32) * 8),
                 o768 = uniform((tid >> 5) * 768);
  const uint32_t give = uniform(t4 * 512 + (WG == 0 ? CH_K : CH_V + j * 4096)), own = uniform(t4 * 512 + (WG == 0 ? CH_V + j * 4096 : CH_K)), mem = uniform(CH_M + WG * 5120);
  const uint32_t vxo = uniform(t4 * 256 + CH_VX + j * 1024);
  uint32_t tag = 1, xd = uniform((1024 + CH_X + WG * 20480) >> 4 | 8 << 16);
  asm volatile("barrier.cluster.wait.aligned;" ::: "memory");
  mbar_wait(sb + MB_WQ, 0);
  bar_sync(NB_ST, 384);
  uint8_t* pdst[6];
#pragma unroll
  for (int i = 0; i < 6; i++) {
    const int line = WG == 0 ? 24 * j + 12 * (t4 >> 1) + 2 * (t4 & 1) + 4 * (i >> 1) + (i & 1) : j == 0 ? 72 + t4 : 74 + 2 * j + (t4 & 1);
    pdst[i] = pool_at(uniform(lds32(sb + CH_TAB + line * 4)) + h * 128);
  }
  auto batch = [&](float* d, const uint32_t (&a)[80], int acc, int n0, int n1) {
    const uint32_t d0 = xd ^ (tag & (2 << acc));
    wg_fence();
#pragma unroll
    for (int k = 0; k < 20; k++) {
      if (!(k & 3) && n0 + k / 4 < n1) {
        __syncwarp();
        ldsm4t(&tw[4 * n0 + k], wq + (n0 + k / 4) * 2048);
        __syncwarp();
      }
      uint64_t db;
      asm("mov.b64 %0, {%1, %2};" : "=l"(db) : "r"(d0 + k / 5 * 320 + k % 5 * 16), "r"(80));
      wg_rs32_00(d, a[4 * k], a[4 * k + 1], a[4 * k + 2], a[4 * k + 3], db, acc | k);
    }
    wg_commit();
    wg_wait<0>();
    reg_fence<16>(d);
  };
  int s = 0;
#pragma unroll 1
  do {
    {
      float d[16];
      mbar_wait(sb + MB_T, s & 1);
      batch(d, a0, 0, 0, CH_NQ0);
      s--; TM(10); s++;
      mbar_wait(sb + MB_F, ~s & 1);
#pragma unroll
      for (int i = 0; i < 2; i++)
        sts128(l16 + give + i * 2048, make_uint4(pack2(d[8 * i], d[8 * i + 1]), pack2(d[8 * i + 2], d[8 * i + 3]), pack2(d[8 * i + 4], d[8 * i + 5]), pack2(d[8 * i + 6], d[8 * i + 7])));
      bar_sync(NB_PUB, 384);
#pragma unroll
      for (int i = 0; i < 2; i++) {
        const uint4 t = lds128(l16 + own + i * 2048);
        d[8 * i] = bf_lo(t.x); d[8 * i + 1] = bf_hi(t.x); d[8 * i + 2] = bf_lo(t.y); d[8 * i + 3] = bf_hi(t.y);
        d[8 * i + 4] = bf_lo(t.z); d[8 * i + 5] = bf_hi(t.z); d[8 * i + 6] = bf_lo(t.w); d[8 * i + 7] = bf_hi(t.w);
      }
      reg_fence<16>(d);
      batch(d, a1, 1, CH_NQ0, CH_NQ);
      s--; TM(11); s++;
      if (WG == 0) bar_arrive(NB_XFREE, 256);
#pragma unroll
      for (int i = 0; i < 2; i++)
        stsm4(l16 + own + i * 2048, pack2(d[8 * i], d[8 * i + 1]), pack2(d[8 * i + 2], d[8 * i + 3]), pack2(d[8 * i + 4], d[8 * i + 5]), pack2(d[8 * i + 6], d[8 * i + 7]));
      s--; TM(9); s++;
    }
    float dq[4] = {}, d0[4] = {}, d1[4] = {};
    uint32_t b[40], wf[80];
    const uint32_t* kf = &wf[52];
#pragma unroll
    for (int i = 0; i < 4 * CH_NQ; i++) wf[i] = tw[i];
    auto step = [&](int k) {
      mma16(dq, wf[4 * k], wf[4 * k + 1], wf[4 * k + 2], wf[4 * k + 3], b[2 * k], b[2 * k + 1]);
      mma16(d0, a0[4 * k], a0[4 * k + 1], a0[4 * k + 2], a0[4 * k + 3], b[2 * k], b[2 * k + 1]);
      mma16(d1, a1[4 * k], a1[4 * k + 1], a1[4 * k + 2], a1[4 * k + 3], b[2 * k], b[2 * k + 1]);
    };
    auto finish = [&](int wg, const float* dk) {
      const float k2 = 0.07216878364870322f * 1.44269504089f;
      sts32(l4 + t4 * 512 + CH_Q + wg * 128, pack2(dq[0] * k2, dq[1] * k2));
      sts32(l4 + t4 * 512 + CH_Q + wg * 128 + 256, pack2(dq[2] * k2, dq[3] * k2));
      stsm2t(t16 + CH_KM + wg * 256, pack2(dk[0], dk[1]), pack2(dk[2], dk[3]));
    };
    const bool more = s < NSEG - 1;
    bar_sync(NB_MEM, 384);
    ldsm4t(&b[0], l16 + mem);
    ldsm4t(&b[4], l16 + mem + 512);
    TMD(0, b[0]);
    {
      int nw = CH_NQ, nb = 2;
#pragma unroll
      for (int k = 0; k < 20; k++) {
        SCHED();
        step(k);
#pragma unroll
        for (int i = 0; i < (CH_DBL >> k & 1) + 1; i++) {
          if (nb < 10 && 2 * nb <= nw) { ldsm4t(&b[4 * nb], l16 + mem + nb * 512); nb++; }
          else if (nw < 20) { ldsm4t(&wf[4 * nw], wq + nw * 2048); nw++; }
          else if (nw < 22) {
            const uint32_t x = l16 ^ ((ko0 ^ tag) & 256);
            uint32_t* r = &wf[4 * nw - 28];
            asm volatile("{.reg .pred p; setp.ne.u32 p, %5, 0; @p ldmatrix.sync.aligned.m8n8.x4.trans.shared.b16 {%0,%1,%2,%3},[%4];}"
                         : "+r"(r[0]), "+r"(r[1]), "+r"(r[2]), "+r"(r[3]) : "r"(x + (x & 256) + (nw == 20 ? ko0 : ko1)), "r"(WG) : "memory");
            nw++;
          }
        }
      }
      SCHED();
    }
    if (WG == 0) {
      finish(0, d0);
      TM(1);
      bar_sync(NB_PROJ, 256);
      const float4 pv = lds128f(t16 + CH_VP);
      const uint32_t v0 = pack2(d1[0] + pv.x, d1[1] + pv.y), v1 = pack2(d1[2] + pv.z, d1[3] + pv.w);
      const uint32_t xo = l8 + (vxo ^ (tag & 2));
      st_async64(mapa(xo, r1), v0, v1, mapa(sb + MB_X, r1), more);
      st_async64(mapa(xo, r2), v0, v1, mapa(sb + MB_X, r2), more);
      sts64(xo, v0, v1);
      if (!more) continue;
      __syncwarp();
      if (elect()) mbar_arrive(sb + MB_X);
      bar_arrive(NB_PROJ2, 256);
      TM(3);
      uint32_t w[144];
      auto tile_of = [](int n) { return n < 27 ? n % 3 : (0x26484 >> 2 * (n - 27)) & 3; };
      auto step_of = [](int n) { return n < 27 ? n / 3 : 9 + ((0x29610 >> 2 * (n - 27)) & 3); };
      auto wload = [&](int n) { ldsm4t(&w[4 * n], wo + tile_of(n) * 12288 + (step_of(n) % 3) * 4096 + (step_of(n) / 3) * 1024); };
#pragma unroll
      for (int n = 0; n < CH_PA; n++) wload(n);
      bar_sync(NB_PRE, 256);
#pragma unroll
      for (int n = CH_PA; n < CH_PB; n++) wload(n);
      bar_arrive(NB_PRE2, 256);
      if (CH_PC > CH_PB) {
        mbar_wait(sb + MB_X, s & 1);
        for (int i = 0; i < CH_PD; i++) wo = __shfl_xor_sync(~0u, wo, p.zero);
#pragma unroll
        for (int n = CH_PB; n < CH_PC; n++) wload(n);
      }
      TM(4);
      bar_sync(NB_O, 256);
      {
        float x[3][4] = {};
        uint32_t ob[24];
        float4 l;
        ldsm4t(&ob[0], l16 + CH_O);
        ldsm4t(&ob[4], l16 + CH_O + 512);
        TMD(7, ob[0]);
        int nw = CH_PC, no = 2;
        float i0, i1;
        uint8_t* dst[6];
        uint32_t lo[6], hi[6];
        auto pre = [&](int i) { lo[i] = __float_as_uint(x[i >> 1][2 * (i & 1)] * i0) + tag; hi[i] = pack2(0.f, x[i >> 1][2 * (i & 1) + 1] * i1); };
        auto emit = [&](int i) { stg_strong32(dst[i], set_tag(__byte_perm(lo[i], hi[i], 0x7632), tag)); };
#pragma unroll
        for (int n = 0; n < 36; n++) {
          SCHED();
          mma16(x[tile_of(n)], w[4 * n], w[4 * n + 1], w[4 * n + 2], w[4 * n + 3], ob[step_of(n) * 2], ob[step_of(n) * 2 + 1]);
          if (n >= CH_PL) {
            if (no < 6 && no * 2 <= step_of(min(nw, 35))) { ldsm4t(&ob[4 * no], l16 + CH_O + no * 512); no++; }
            else if (nw < 36) { wload(nw); nw++; }
          }
          if (n == 18) l = lds128f(sb + CH_L + ((l16 ^ tag) & 0x30));
          if (n == 26) { i0 = rcp(l.x + l.y); i1 = rcp(l.z + l.w); asm volatile("" : "+f"(i0), "+f"(i1)); }
          if (n >= 28 && n < 34) { dst[n - 28] = pdst[n - 28] + ((l4 ^ tag) & 0x7c); asm volatile("" : "+l"(dst[n - 28])); }
          if (n == 32) { for (int i = 0; i < 2; i++) { pre(i); asm volatile("" : "+r"(lo[i]), "+r"(hi[i])); } }
          if (n == 33) { emit(0); emit(1); }
        }
        for (int i = 2; i < 6; i++) pre(i);
        for (int i = 2; i < 6; i++) emit(i);
      }
      TM(8);
    } else {
      finish(1, d1);
      sts128f(t16 + CH_VP, d0[0], d0[1], d0[2], d0[3]);
      TM(1);
      bar_sync(NB_PROJ, 256);
      {
        float d0[4] = {}, d1[4] = {}, dm[4] = {};
        uint32_t q[16], km[4];
#pragma unroll
        for (int e = 0; e < 4; e++) {
          ldsm4t(&q[4 * e], l16 + (e ^ t4) * 512 + CH_Q);
          SCHED();
          if (e == 1) { ldsm4(km, t16 + CH_KM); SCHED(); }
        }
        const uint32_t xo = l4 + ((t4 * 128) ^ (tag & 2));
        uint64_t x[4];
#pragma unroll
        for (int i = 0; i < 4; i++) {
          const int r = i & 1 ? r2 : r1;
          asm volatile("mov.b64 %0, {%1, %2};" : "=l"(x[i]) : "r"(mapa(xo, r) + CH_SX + (i & 1) * 1024 + (i & 2) * 256), "r"(mapa(sb + MB_X, r)));
        }
        SCHED();
        mma16(d0, q[0], q[1], q[2], q[3], kf[0], kf[1]);
        SCHED();
        mma16(d1, q[4], q[5], q[6], q[7], kf[2], kf[3]);
        SCHED();
        mma16(dm, q[0], q[1], q[2], q[3], hadd2(km[0], km[2]), hadd2(km[1], km[3]));
        mma16(d0, q[8], q[9], q[10], q[11], kf[4], kf[5]);
        SCHED();
        mma16(d1, q[12], q[13], q[14], q[15], kf[6], kf[7]);
        if (!more) continue;
        const uint32_t w1 = pack2(dm[0] + dm[2], dm[1] + dm[3]);
        st_async32((uint32_t)x[2], w1, x[2] >> 32);
        st_async32((uint32_t)x[3], w1, x[3] >> 32);
        SCHED();
        const uint32_t w0 = pack2((d0[0] + d0[2]) + (d1[0] + d1[2]), (d0[1] + d0[3]) + (d1[1] + d1[3]));
        st_async32((uint32_t)x[0], w0, x[0] >> 32);
        st_async32((uint32_t)x[1], w0, x[1] >> 32);
        sts32(xo + CH_SO, w0);
        sts32(xo + CH_SO + 512, w1);
      }
      TM(3);
      float sc[3][4] = {};
      uint32_t wd[12];
      uint32_t redo;
      auto attend = [&](auto first) {
        uint4 vb[6];
        uint2 vm[3];
        float e[10];
        uint32_t ow[6];
        if (first.value) {
          const uint2 id = lds64(l8 + CH_ID);
          bar_sync(NB_W1V, 160);
          uint32_t r[8];
          ldsm4(r, l16 + CH_SO); ldsm4(r + 4, l16 + CH_SO + 512);
#pragma unroll
          for (int u = 0; u < 6; u++) vb[u] = ldsm4v(t16 + CH_V + u * 2048);
          bar_arrive(NB_PRE, 256);
          SCHED();
          uint32_t sxa = l16 + ((l16 ^ tag) & 256) * 3;
          asm volatile("" : "+r"(sxa));
          sxa += CH_SX;
          SCHED();
          mma8(sc[0], r[0], r[1], id.x);
          mma8(sc[1], r[2], r[3], id.x);
          mma16(sc[2], r[4], r[5], r[6], r[7], id.x, id.y);
          TM(7);
          mbar_wait(sb + MB_X, s & 1);
          TM(4);
          uint32_t t[16];
          ldsm4(t, sxa); ldsm4(t + 4, sxa + 256); ldsm4(t + 8, sxa + 512);
          SCHED();
          mma16(sc[0], t[0], t[1], t[2], t[3], id.x, id.y);
          ldsm4(t + 12, sxa + 768);
          SCHED();
          mma16(sc[1], t[4], t[5], t[6], t[7], id.x, id.y);
#pragma unroll
          for (int u = 0; u < 2; u++) vm[u] = lds64(t8 + CH_VX + u * 1024);
          SCHED();
          e[0] = ex2(sc[0][0]);
          mma16(sc[2], t[8], t[9], t[10], t[11], id.x, id.y);
          vm[2] = lds64(t8 + CH_VX + 2048);
          SCHED();
          e[1] = ex2(sc[0][1]);
          ldsm4t(&wd[0], wo);
          SCHED();
          e[2] = ex2(sc[0][2]);
          SCHED();
          e[3] = ex2(sc[0][3]);
          mma16(sc[2], t[12], t[13], t[14], t[15], id.x, id.y);
          SCHED();
          e[4] = ex2(sc[1][0]);
          ldsm4t(&wd[4], wo + 4096);
          SCHED();
          e[5] = ex2(sc[1][1]);
        } else {
#pragma unroll
          for (int u = 0; u < 6; u++) vb[u] = ldsm4v(t16 + CH_V + u * 2048);
#pragma unroll
          for (int u = 0; u < 3; u++) vm[u] = lds64(t8 + CH_VX + u * 1024);
        }
        float o[3][4] = {};
        if (!first.value) {
#pragma unroll
          for (int i = 0; i < 6; i++) e[i] = ex2(sc[i >> 2][i & 3]);
        }
        const uint32_t p1 = pack2(e[0], e[1]), p2 = pack2(e[2], e[3]);
        float l = (e[0] + e[1]) + (e[2] + e[3]);
        asm volatile("" : "+f"(l));
        SCHED();
        e[6] = ex2(sc[1][2]);
        mma16(o[0], vb[0].x, vb[0].y, vb[0].z, vb[0].w, p1, p2);
        if (first.value) { sc[2][0] += sc[2][2]; sc[2][1] += sc[2][3]; }
        SCHED();
        e[7] = ex2(sc[1][3]);
        mma16(o[1], vb[2].x, vb[2].y, vb[2].z, vb[2].w, p1, p2);
        SCHED();
        e[8] = ex2(sc[2][0]);
        mma16(o[2], vb[4].x, vb[4].y, vb[4].z, vb[4].w, p1, p2);
        SCHED();
        e[9] = ex2(sc[2][1]);
        SCHED();
        const uint32_t p3 = pack2(e[4], e[5]), p4 = pack2(e[6], e[7]);
        l += (e[4] + e[5]) + (e[6] + e[7]);
#pragma unroll
        for (int u = 0; u < 3; u++) mma16(o[u], vb[2 * u + 1].x, vb[2 * u + 1].y, vb[2 * u + 1].z, vb[2 * u + 1].w, p3, p4);
        SCHED();
        const uint32_t p0 = pack2(e[8], e[9]);
        l += e[8] + e[9];
        const float l2 = __shfl_xor_sync(~0u, l, 1);
        if (first.value) ldsm4t(&wd[8], wo + 8192);
#pragma unroll
        for (int u = 0; u < 3; u++) mma8(o[u], vm[u].x, vm[u].y, p0);
        redo = __any_sync(~0u, !(l > 1e-9f && l < 1e9f));
        uint32_t la = sb + CH_L + (((l4 ^ tag) >> 1) & 0x3c);
        asm volatile("" : "+r"(la));
        SCHED();
#pragma unroll
        for (int u = 0; u < 3; u++) { ow[2 * u] = pack2(o[u][0], o[u][1]); ow[2 * u + 1] = pack2(o[u][2], o[u][3]); }
        stsm4(l16 + o768 + CH_O, ow[0], ow[1], ow[2], ow[3]);
        stsm2(l16 + o768 + CH_O + 512, ow[4], ow[5]);
        if (t4 == 0) sts32(la, __float_as_uint(l + l2));
      };
      attend(Int<1>());
      TM(6);
      asm volatile("{.reg .pred p; setp.eq.u32 p, %0, 0; @p bar.sync 2, 256;}" :: "r"(redo) : "memory");
      if (redo) {
        float mx = fmaxf(sc[2][0], sc[2][1]);
#pragma unroll
        for (int i = 0; i < 4; i++) mx = fmaxf(mx, fmaxf(sc[0][i], sc[1][i]));
        mx = fmaxf(mx, __shfl_xor_sync(~0u, mx, 1));
        mx = fmaxf(mx, __shfl_xor_sync(~0u, mx, 2));
#pragma unroll
        for (int i = 0; i < 4; i++) { sc[0][i] -= mx; sc[1][i] -= mx; }
        sc[2][0] -= mx; sc[2][1] -= mx;
        attend(Int<0>());
        bar_arrive(NB_O, 256);
      }
      {
        float z[4] = {};
        const uint32_t scr = l8 + ((CH_V + r1 * 4096) ^ (tag & 2));
        uint32_t ow[6], we[12];
        __syncwarp();
        ldsm4t(ow, l16 + o768 + CH_O);
        ldsm2t(ow + 4, l16 + o768 + CH_O + 512);
        if (j == 0) {
          float y[4] = {};
#pragma unroll
          for (int u = 0; u < 3; u++) ldsm4t(&we[4 * u], (wo ^ 32) + u * 4096);
          SCHED();
#pragma unroll
          for (int u = 0; u < 3; u++) {
            mma16(z, wd[4 * u], wd[4 * u + 1], wd[4 * u + 2], wd[4 * u + 3], ow[2 * u], ow[2 * u + 1]);
            mma16(y, we[4 * u], we[4 * u + 1], we[4 * u + 2], we[4 * u + 3], ow[2 * u], ow[2 * u + 1]);
          }
          sts64f(scr + t4 * 512 + 2048, y[0], y[1]); sts64f(scr + t4 * 512 + 2304, y[2], y[3]);
        } else {
#pragma unroll
          for (int u = 0; u < 3; u++) mma16(z, wd[4 * u], wd[4 * u + 1], wd[4 * u + 2], wd[4 * u + 3], ow[2 * u], ow[2 * u + 1]);
        }
        sts64f(scr + t4 * 512, z[0], z[1]); sts64f(scr + t4 * 512 + 256, z[2], z[3]);
        bar_sync(NB_W1, 128);
        if (j == 0 || t4 < 2) {
          float2 q[4];
          const float4 l = lds128f(sb + CH_L + ((l16 ^ tag) & 0x30));
#pragma unroll
          for (int i = 0; i < 4; i++) q[i] = lds64f(scr + (t4 >> 1) * 2048 + (t4 & 1) * 256 + i * 512);
          SCHED();
          stg_strong32(pdst[0] + ((l4 ^ tag) & 0x7c), pack_tag(((q[0].x + q[1].x) + (q[2].x + q[3].x)) * rcp(l.x + l.y), ((q[0].y + q[1].y) + (q[2].y + q[3].y)) * rcp(l.z + l.w), tag));
        }
      }
      TM(2);
    }
    bar_sync(NB_ST, 384);
    tag ^= 0x10001;
  } while (++s < NSEG);
  if (WG == 1) {
    const uint2 a = lds64(t8 + t4 * 256 + CH_KM), b = lds64(t8 + t4 * 256 + CH_KM + 256);
    sts64(t8 + CH_M, hadd2(a.x, b.x), hadd2(a.y, b.y));
  }
  bar_arrive(NB_PRE2, 288);
}

__device__ __forceinline__ void chain_comm(const ChainParams& p, const uint32_t sb, const CUtensorMap* maps) {
  [[maybe_unused]] constexpr int WG = 2;
  const int tid = threadIdx.x & 127, t4 = __shfl_sync(~0u, tid >> 5, 0), lane = tid & 31;
  const int cta = blockIdx.x, h = cta / 3, j = cta - 3 * h, colbase = cta * 64;
  const uint8_t* const xs = reinterpret_cast<const uint8_t*>(g_xn);
  auto xload = [&](int seg, int i) { tma_load5(sb + CH_X + i * 10240, &p.xc, 0, seg * 4, 2 * i, sb + MB_T); };
  if (cta < 4 && cta * 128 + tid < SY_N) p.other[cta * 128 + tid] = 0;
  uint32_t smid; asm("mov.u32 %0, %%smid;" : "=r"(smid));
  const uint32_t part = max(ldg_strong32(g_smpart + (smid & 255)), 1u);
  if (tid == 64) stg_strong32(p.sync + SY_PART + cta, part);
  PRO(0);
  if (t4 == 3) {
    bar_arrive(NB_PROJ2, 384);
    bar_arrive(NB_PRE2, 384);
    wait_count(p.sync + SY_P + 1, ln_items(p.layer, 0));
    if (elect()) {
      mbar_expect(sb + MB_T, 40960);
      for (int i = 0; i < 4; i++) xload(0, i);
    }
    __syncwarp();
  } else {
  bar_sync(NB_PROJ2, 384);
  __syncwarp();
  PRO(1);
  if (t4 == 0 && elect()) {
    mbar_expect(sb + MB_WQ, 81920);
    #pragma unroll 1
    for (int i = 0; i < 4; i++) tma_load(sb + CH_WQ + i * 20480, &p.wq, colbase, i * 160, sb + MB_WQ);
  }
  bar_sync(NB_PRE2, 384);
  __syncwarp();
  PRO(2);
  if (t4 == 0 && elect()) {
    mbar_expect(sb + MB_WO, 86016);
#pragma unroll 1
    for (int i = 0; i < 7; i++) tma_load(sb + CH_WO + i * 12288, &p.wo, i < 6 ? j * 192 + i * 32 : j == 0 ? 576 : 592 + j * 16, h * 192, sb + MB_WO);
  }
  }
  if (t4 < 3) {
    uint32_t reader, orient;
    for (int n = 0;; spin_guard(n)) {
      reader = ldg_strong32(p.sync + SY_PART + (tid >= 80 ? cta : tid));
      orient = ldg_strong32(g_orient + min(tid, NSLOT - 1));
      if (__all_sync(~0u, reader && orient)) break;
    }
    const uint32_t near = __ballot_sync(~0u, reader == part) >> (cta & 7) & 0xffff;
    if (tid < NSLOT) sts32(sb + CH_TAB + tid * 4, tid * 8192 + (orient == reader ? 0 : 4096));
    if (tid == 0) sts32(sb + CH_TAB + NSLOT * 4, cta < 80 ? cta : (cta & 7) + max(__ffs(near) - 1, 0));
  }
  __syncwarp();
  asm volatile("barrier.cluster.wait.aligned;" ::: "memory");
  const uint32_t l8 = opaque(sb + t4 * 256 + lane * 8);
  bar_sync(NB_ST, 384);
  bar_arrive(NB_PUB, 384);
  {
    const uint32_t id = (lane >> 3) == (lane & 3) ? ((lane & 4) ? 0x3f800000u : 0x00003f80u) : 0u;
    if (t4 == 0) sts64(l8 + CH_ID, id, id);
    const uint32_t* m0 = reinterpret_cast<const uint32_t*>(p.mem0) + (lane >> 2) * (DM / 2) + t4 * 80 + (lane & 3);
    uint32_t g[20];
#pragma unroll
    for (int i = 0; i < 20; i++) g[i] = m0[i * 4];
    bar_sync(NB_XFREE, 256);
#pragma unroll
    for (int i = 0; i < 20; i += 4) stsm4t(sb + CH_M + (t4 * 20 + i) * 128 + lane * 16, g[i], g[i + 1], g[i + 2], g[i + 3]);
    mbar_wait(sb + MB_WO, 0);
  }
  uint8_t* const pool = pool_at(0);
  const uint8_t* const psrc = pool + opaque(lds32(sb + CH_TAB + lds32(sb + CH_TAB + NSLOT * 4) * 4) + t4 * 1024 + lane * 4);
  const uint32_t mdst = opaque((80 + cta / 20) * 8192 + (t4 & 1) * 4096 + (cta % 20) * 128 + lane * 4);
  int st = 0;
  uint32_t tag = opaque(1), span = ~0u;
  bar_sync(NB_MEM, 384);
  auto send_tokens = [&](int s) {
    uint8_t* dst = g_kv + ((s >> 2) * 192 + cta + 3 * h) * KV_PART + (s & 3) * 4096;
    bulk_store(dst, sb + CH_K, 4096);
    bulk_store(dst + KV_V, sb + CH_V + j * 4096, 4096);
    bulk_commit();
  };
  auto send_memory = [&](int s, uint32_t km) {
    fence_async();
    uint8_t* dst = g_kv + ((s >> 2) * 192 + cta + 3 * h) * KV_PART + KV_M + (s & 3) * 1024;
    bulk_store(dst, km, 1024);
    bulk_store(dst + KV_V, sb + CH_VX + j * 1024, 1024);
    bulk_commit();
    bulk_wait<0>();
    if ((s & 3) == 3) { fence_async_global(); atomicAdd(p.sync + (s >> 2) * 8 + 4, 1); }
  };
#pragma unroll 1
  for (int s = 0; s < NSEG - 1; s++) {
    TM(0);
    STAT(0);
    if (t4 == 0) {
      if (elect()) {
        fence_async();
#pragma unroll 1
        for (int r = j + 1; r < j + 3; r++) bulk_push(mapa(sb + CH_V + j * 4096, r % 3), sb + CH_V + j * 4096, 4096, mapa(sb + MB_V, r % 3));
        send_tokens(s);
        bulk_wait_read<0>();
      }
      __syncwarp();
    }
    uint32_t c0, g0;
    if (t4 == 1) {
      __syncwarp();
      c0 = clk32(); g0 = gtime();
      if (elect()) atomicMax(p.sync + SY_TIME + s, g0);
    }
    if (t4 == 3 && s >= NSEG - 6 && elect()) asm volatile("prefetch.tensormap [%0];" :: "l"(maps + (NSEG - 2 - s)) : "memory");
    if (t4 == 3 && (s & 3) == 2 && s < NSEG - 2) wait_count(p.sync + SY_P + 5 + (s & ~3), ln_items(p.layer, (s >> 2) + 1));
    if (t4 == 2) { mbar_wait(sb + MB_V, s & 1); bar_arrive(NB_W1V, 160); }
    bar_sync(NB_PROJ2, 256);
    if (t4 == 0 && elect()) {
      mbar_expect(sb + MB_X, 4096);
      mbar_expect(sb + MB_T, 40960);
      for (int i = 0; i < 3; i++) xload(s + 1, i);
    }
    __syncwarp();
    STAT(1);
    TM(1);
    {
      const uint2 a = lds64(l8 + t4 * 256 + CH_KM), b = lds64(l8 + t4 * 256 + CH_KM + 256);
      sts64(l8 + CH_KS, hadd2(a.x, b.x), hadd2(a.y, b.y));
    }
    TM(4);
    bar_sync(NB_PRE2, 256);
    if (t4 == 0 && elect()) {
      xload(s + 1, 3);
      if (CH_XPF && s < NSEG - 2) prefetch_l2(xs + (s + 2) * 40960 + cta % 20 * 2048, 2048);
      if (CH_TPF && s >= NSEG - 7) {
        const int i = s - (NSEG - 7);
        if (i < 2) prefetch_l2(p.wb + (cta * 2 + i) * 12800, 12800);
        else if (i < 4) prefetch_l2(xs + (cta * 2 + i - 2) * 8192, 8192);
        else prefetch_l2(g_q + 15 * 32 * 3072 + (cta * 2 + i - 4) * 512, 8192);
      }
      send_memory(s, sb + CH_KS);
    }
    __syncwarp();
    if (t4 == 1) {
      const uint32_t late = min(ldg_strong32(p.sync + SY_TIME + s) - g0, 640u);
      if (elect()) sts32(sb + CH_TAB + 380, c0 + span + (late * 115 >> 6) + (j ? 60 : 0) + p.d1);
    }
    bar_sync(NB_W2, 128);
    uint32_t due = lds32(sb + CH_TAB + 380);
    due = __shfl_sync(~0u, due, 0);
    const uint8_t* ms = pool + (lds32(sb + CH_TAB + (80 + st * 4 + t4) * 4) + (l8 & 255));
    uint8_t* md = pool + (mdst + (t4 < 2 ? st : st == 2 ? 0 : st + 1) * 32768);
    asm volatile("" : "+l"(ms), "+l"(md));
    TM(2);
    bar_sync(NB_ST, 384);
    __syncwarp();
    uint32_t tg = clk32();
    if (t4 == 3 && elect()) {
      if (s < NSEG - 2) mbar_expect(sb + MB_V, 8192);
      mbar_arrive_remote(mapa(sb + MB_F, j == 2 ? 0 : j + 1));
      mbar_arrive_remote(mapa(sb + MB_F, j == 0 ? 2 : j - 1));
    }
    if (s == NSEG - 2) work_init(sb, t4);
    __syncwarp();
    STAT(2);
    {
      float2 q[4];
      TM(3);
      if (t4 == 1) span = min(span, tg - c0);
      until(s < 2 ? tg + 400 : (int)(due - tg) > p.dn ? due : tg + p.dn);
      for (int n = 0;;) {
        uint32_t v[8];
#pragma unroll
        for (int i = 0; i < 8; i++) v[i] = ldg_strong32(psrc + i * 128);
        sts64f(l8 + CH_R2, ((bf_lo(v[0]) + bf_lo(v[1])) + (bf_lo(v[2]) + bf_lo(v[3]))) + ((bf_lo(v[4]) + bf_lo(v[5])) + (bf_lo(v[6]) + bf_lo(v[7]))),
               ((bf_hi(v[0]) + bf_hi(v[1])) + (bf_hi(v[2]) + bf_hi(v[3]))) + ((bf_hi(v[4]) + bf_hi(v[5])) + (bf_hi(v[6]) + bf_hi(v[7]))));
        uint32_t bad;
        asm volatile("{.reg .pred p, q; .reg .b32 a; lop3.b32 a, %1, %2, %3, 0xFE; lop3.b32 a, a, %4, %6, 0xA8; setp.ne.u32 p, a, 0;\n"
                     "bar.red.or.pred q, %5, 128, p; selp.u32 %0, 1, 0, q;}"
                     : "=r"(bad) : "r"(differ(v[0], v[1], tag)), "r"(differ(v[2], v[3], tag)), "r"(differ(v[4], v[5], tag)), "r"(differ(v[6], v[7], tag)), "n"((int)NB_W2),
                       "r"((uint32_t)(cta < 80 || n < 3)) : "memory");
#pragma unroll
        for (int k = 0; k < 4; k++) asm volatile("ld.volatile.shared.v2.f32 {%0,%1}, [%2];" : "=f"(q[k].x), "=f"(q[k].y) : "r"(l8 - t4 * 256 + CH_R2 + k * 256) : "memory");
        TMV(12, n);
        if (!bad) break;
        spin_guard(n);
      }
      bar_arrive(NB_PUB, 384);
      SCHED();
      TM(9);
      if (cta < 80) stg_strong32(md, min(nz(pack2((q[0].x + q[1].x) + (q[2].x + q[3].x), (q[0].y + q[1].y) + (q[2].y + q[3].y))), t4 < 2 ? ~0u : 0u));
      tg = clk64() + p.d2;
      if (s >= 2 && (int)(due + p.dx - tg) > 0) tg = due + p.dx;
      TM(8);
    }
    STAT(3);
    until(tg);
    TM(10);
    for (int n = 0;;) {
      uint2 g[10];
#pragma unroll
      for (int i = 0; i < 10; i++) g[i] = ldg_strong64(ms + i * 256);
      if (n == 0) bar_sync(NB_XFREE, 256);
      spin_guard(n);
      uint32_t m = ~0u;
#pragma unroll
      for (int i = 0; i < 10; i++) { sts64(l8 + CH_M + t4 * 2304 + i * 256, g[i].x, g[i].y); m = __vimin3_u32(m, g[i].x, g[i].y); }
      TMV(13, n - 1);
      if (!__any_sync(~0u, m == 0)) break;
    }
    TM(11);
    if (t4 < 2 || s == NSEG - 2) bar_sync(NB_MEM, 384); else bar_arrive(NB_MEM, 384);
    if (++st == 3) st = 0;
    tag ^= 0x10001;
  }
  if (t4 == 0) {
    if (elect()) { fence_async(); send_tokens(NSEG - 1); }
    __syncwarp();
    bar_sync(NB_PRE2, 288);
    if (elect()) {
      send_memory(NSEG - 1, sb + CH_M);
      asm volatile("mbarrier.arrive.shared::cta.b64 _, [%0], 8;" :: "r"(sb + WK_BAR + 64) : "memory");
    }
    __syncwarp();
  }
}

__device__ __forceinline__ void chain_start(const ChainParams& p, const uint32_t sb, const int warp) {
  if (warp == 1 && elect()) {
#pragma unroll
    for (int i = 0; i < 6; i++) mbar_init(sb + CH_BAR + 8 * i, i == 2 ? 5 : i == 5 ? 2 : 1);
    asm volatile("fence.mbarrier_init.release.cluster;" ::: "memory");
    mbar_expect(sb + MB_V, 8192);
    atomicAdd(p.sync + SY_UP, 1);
    asm volatile("{.reg .pred p; setp.ne.u32 p, %0, 1024; @p trap;}" :: "r"(sb & 0xffffff));
  }
  if (warp == 0 && elect()) {
#pragma unroll 1
    for (int i = 0; i < 8; i++) {
      const int n = (i & 4) + (i & 1) * 2 + (i >> 1 & 1);
      mbar_init(sb + MB_W + 8 * n, 1);
      asm volatile("fence.mbarrier_init.release.cluster;" ::: "memory");
      mbar_expect(sb + MB_W + 8 * n, 20480);
      tma_load(sb + n * 20480, (i ^ i >> 2) & 1 ? &p.wv : &p.wk, blockIdx.x * 64, (n & 3) * 160, sb + MB_W + 8 * n);
    }
  }
  __syncthreads();
  asm volatile("barrier.cluster.arrive.relaxed.aligned;" ::: "memory");
}

struct WorkParams {
  ChainParams ch;
  CUtensorMap wo, xn, wb[3], xp, wq, wc[2], out;
  const __nv_bfloat16* x;
  uint32_t* sync;
  int kind, qa_end, idle;
};
#define GO_320 4
#define GO_TAIL 1
enum { WK_FIRST = 0, WK_LEAD = 1, WK_CHAIN = 2, WK_LAST = 3 };
enum { IT_ATT = 0, IT_OP = 1, IT_FIN = 2, IT_BQ = 3, IT_BO = 4, IT_LN = 5, IT_Q = 6, IT_LN0 = 7, IT_OUT = 8 };
constexpr int C_EARLY = 1 << 20, C_LATE = 1 << 21, C_TAIL = 1 << 22;

__device__ __forceinline__ uint32_t item_count(int type, int b) { return type == IT_ATT ? 32 : type == IT_OP ? op_tiles(b) * op_split(b) : type == IT_FIN ? fin_items(b) : bq_items(b); }
__device__ __forceinline__ uint32_t item_need(int type, int b) { return type == IT_ATT ? 96 : item_count(type - 1, b); }
__device__ __forceinline__ int item_cols(int type, int b) {
  return type == IT_ATT || type == IT_Q ? 192 : type == IT_OUT ? 80 : type == IT_BQ ? (b < BQ_12 ? 320 : b < BQ_24 ? 160 : 80) : type == IT_OP && b >= OP_N4 ? 160 : 320; }
__device__ __forceinline__ int item_groups(int type, int b) { const int n = type == IT_FIN ? fin_items(b) : ln_items(type == IT_LN, b); return n == 4 ? 4 : n == 8 ? 2 : 1; }
#define RES_OP 1
constexpr int RES_N = RES_OP ? op_tiles(14) * op_split(14) : 0, RES_BQ = (64 - RES_N) / 6;
__device__ __forceinline__ bool reserved(int type, int b) { return type == IT_ATT ? b == 15 : type == IT_OP ? RES_OP && b == 14 : type == IT_BQ && b < RES_BQ; }
__device__ __forceinline__ int reserved_item(int cta) {
  const int h = cta / 3, j = cta - 3 * h, i = h + (j - 1) * 32;
  if (j == 0) return C_EARLY | IT_ATT << 16 | 15 << 8 | h;
  return i < RES_N ? C_TAIL | IT_OP << 16 | 14 << 8 | i : i - RES_N < RES_BQ * 6 ? C_TAIL | IT_BQ << 16 | ((i - RES_N) / 6) << 8 | (i - RES_N) % 6 : -1;
}
constexpr int LEAD1 = 12;
__device__ __forceinline__ int lead_item(int layer, int qa_end, int i) {
  if (layer == 2) return i < 128 ? C_EARLY | C_LATE | IT_OUT << 16 | (i >> 3) << 8 | (i & 7) : -1;
  if (layer == 0) {
    if (i < 32) return IT_LN0 << 16 | (i >> 4) << 8 | (i & 15);
    if (i < 88) return IT_LN0 << 16 | ((i - 24) >> 2) << 8 | (i & 3);
    i -= 88;
  } else {
    if (i < 4) return C_EARLY | IT_BO << 16 | (i >> 1) << 8 | (i & 1);
    if (i < 12) return C_EARLY | IT_LN << 16 | ((i - 4) >> 2) << 8 | (i & 3);
    if (i < 40) return C_EARLY | IT_BO << 16 | ((i - 8) >> 1) << 8 | (i & 1);
    if (i < 96) return C_EARLY | IT_LN << 16 | ((i - 32) >> 2) << 8 | (i & 3);
    i -= 96;
  }
  return i < (16 - qa_end) * 32 ? C_EARLY | IT_Q << 16 | (qa_end + (i >> 5)) << 8 | (i & 31) : -1;
}

struct Ring {
  uint32_t sb;
  int pos, seq;
  __device__ __forceinline__ uint32_t full() const { return sb + WK_BAR + 8 * (seq & 7); }
  __device__ __forceinline__ uint32_t take(int len) { if (pos + len > WK_SLOTS) pos = 0; pos += len; seq++; return sb + (pos - len) * 8192; }
  __device__ __forceinline__ uint32_t wait(int len) { mbar_wait(full(), (seq >> 3) & 1); return take(len); }
  __device__ __forceinline__ void release(int sq) const { if (elect()) mbar_arrive(sb + WK_BAR + 64 + 8 * (sq & 7)); }
};

struct Pending {
  uint32_t w[48], done;
  uint4* dst;
  __device__ __forceinline__ void store(int i) const { dst[(i >> 2) * 1024 + (i & 3) * 32] = make_uint4(w[4 * i], w[4 * i + 1], w[4 * i + 2], w[4 * i + 3]); }
  __device__ __forceinline__ void finish() { __syncwarp(); if (elect()) mbar_arrive(done); done = 0; }
  __device__ __forceinline__ void flush() {
    if (done) {
#pragma unroll
      for (int i = 0; i < 12; i++) store(i);
      finish();
    }
  }
};

template <int N>
__device__ __forceinline__ void gemm_item(float* d, Ring& r, int nkb, uint32_t go, int ask, Pending& pend) {
  const int warp = __shfl_sync(~0u, fresh_tid() >> 5, 0), wg = warp >> 2;
#pragma unroll 1
  for (int kb = 0; kb < nkb; kb++) {
    const uint32_t base = r.wait(2 + (N + 63) / 64);
    const uint64_t da = mkdesc(base + wg * 8192, 128, 1024, 0), db = mkdesc(base + 16384, 8192, 1024, 1);
    wg_fence();
#pragma unroll
    for (int kk = 0; kk < 4; kk++) {
      if (N == 80) wg_ss80_01(d, da + kk * 16, db + kk * 128, (kb | kk) != 0);
      else if (N == 160) wg_ss160_01(d, da + kk * 16, db + kk * 128, (kb | kk) != 0);
      else wg_ss192_01(d, da + kk * 16, db + kk * 128, (kb | kk) != 0);
      if (N == 320) wg_ss128_01(d + 96, da + kk * 16, db + kk * 128 + 3 * 512, (kb | kk) != 0);
    }
    wg_commit();
    if (kb == ask && go && warp == 0 && elect()) mbar_arrive(go);
    if (N == 192 && pend.done) {
#pragma unroll
      for (int i = 0; i < 12; i++) if (kb == i / 2) pend.store(i);
      if (kb == 5) pend.finish();
    }
    if (kb > 0) { wg_wait<1>(); r.release(r.seq - 2); }
  }
  wg_wait<0>();
  reg_fence<N / 2>(d);
  r.release(r.seq - 1);
}

__device__ __forceinline__ void attn_a_warp(Ring& r, Pending& pend, bool now, const int warp) {
  uint32_t (&q)[48] = pend.w;
  const int lane = fresh_tid() & 31, g = lane >> 2, c = lane & 3, seg = warp & 3;
  const bool half = warp >= 4;
  const float k2 = 0.07216878364870322f * 1.44269504089f, NEG = -INFINITY;
  float sc[5][4] = {};
#pragma unroll
  for (int i = 0; i < 8; i++) sc[3 + (i >> 2)][i & 3] = half ? 0.f : NEG;
  uint32_t base, f[2][40] = {};
  const uint32_t ka = seg * 4096 + lane * 16, va = seg * 4096 + (lane & 8) * 32 + (lane & 16) * 8 + (lane & 7) * 16;
  auto load = [&](int n) {
    uint32_t* d = f[n & 1];
    base = n & 1 ? base + KV_PART : r.wait(5);
    const uint32_t a = base + (n < 3 ? ka : va), m = base + KV_M + seg * 1024;
#pragma unroll
    for (int i = 0; i < 4; i++) {
      if (n >= 3) { const uint2 vm = lds64(m + i * 256 + lane * 8); d[2 * i] = vm.x; d[2 * i + 1] = vm.y; }
      else if (!(i & 1)) ldsm4(&d[2 * i], m + i * 256 + lane * 16);
      (n < 3 ? ldsm4t : ldsm4)(&d[8 + 4 * i], a + half * 2048 + i * 512);
    }
    if (half) {
#pragma unroll
      for (int i = 0; i < 4; i++) (n < 3 ? ldsm4t : ldsm4)(&d[24 + 4 * i], a + i * 512);
    }
  };
  load(0);
#pragma unroll
  for (int u = 0; u < 3; u++) {
    if (u == 2) r.release(r.seq - 2);
    load(u + 1);
    SCHED();
    const uint32_t* b = f[u & 1];
#pragma unroll
    for (int kk = 0; kk < 4; kk++) {
      const uint32_t* a = &q[16 * u + 4 * kk];
      mma16(sc[0], a[0], a[1], a[2], a[3], b[2 * kk], b[2 * kk + 1]);
      mma16(sc[1], a[0], a[1], a[2], a[3], b[8 + 4 * kk], b[9 + 4 * kk]);
      mma16(sc[2], a[0], a[1], a[2], a[3], b[10 + 4 * kk], b[11 + 4 * kk]);
    }
    if (half) {
#pragma unroll
      for (int kk = 0; kk < 4; kk++) {
        const uint32_t* a = &q[16 * u + 4 * kk];
        mma16(sc[3], a[0], a[1], a[2], a[3], b[24 + 4 * kk], b[25 + 4 * kk]);
        mma16(sc[4], a[0], a[1], a[2], a[3], b[26 + 4 * kk], b[27 + 4 * kk]);
      }
    }
    SCHED();
  }
  load(4);
  SCHED();
  if (2 * c > g) { sc[1][0] = NEG; sc[2][2] = NEG; }
  if (2 * c + 1 > g) { sc[1][1] = NEG; sc[2][3] = NEG; }
  sc[2][0] = sc[2][1] = NEG;
  uint32_t pp[5][2]; float inv[2];
#pragma unroll
  for (int hh = 0; hh < 2; hh++) {
    float m = NEG, l = 0.f;
#pragma unroll
    for (int n = 0; n < 5; n++) m = fmaxf(m, fmaxf(sc[n][2 * hh], sc[n][2 * hh + 1]));
    m = fmaxf(m, __shfl_xor_sync(~0u, m, 1)); m = fmaxf(m, __shfl_xor_sync(~0u, m, 2));
#pragma unroll
    for (int n = 0; n < 5; n++) { const float x = ex2((sc[n][2 * hh] - m) * k2), y = ex2((sc[n][2 * hh + 1] - m) * k2); l += x + y; pp[n][hh] = pack2(x, y); }
    l += __shfl_xor_sync(~0u, l, 1); l += __shfl_xor_sync(~0u, l, 2);
    inv[hh] = rcp(l);
  }
#pragma unroll
  for (int u = 0; u < 3; u++) {
    float o[8][4] = {};
    const uint32_t* b = f[~u & 1];
#pragma unroll
    for (int n = 0; n < 8; n++) mma8(o[n], pp[0][0], pp[0][1], b[n]);
#pragma unroll
    for (int n = 0; n < 8; n++) mma16(o[n], pp[1][0], pp[1][1], pp[2][0], pp[2][1], b[8 + 2 * n], b[9 + 2 * n]);
    if (half) {
#pragma unroll
      for (int n = 0; n < 8; n++) mma16(o[n], pp[3][0], pp[3][1], pp[4][0], pp[4][1], b[24 + 2 * n], b[25 + 2 * n]);
    }
    SCHED();
    if (u != 1) r.release(r.seq - 2 + u / 2);
    if (u == 0) { load(5); SCHED(); }
#pragma unroll
    for (int i = 0; i < 16; i++) q[16 * u + i] = pack2(o[i & 7][i >> 2 & 2] * inv[i >> 3], o[i & 7][(i >> 2 & 2) + 1] * inv[i >> 3]);
    if (now) {
#pragma unroll
      for (int i = 0; i < 4; i++) pend.store(4 * u + i);
    }
  }
}

__device__ __forceinline__ void ln_groups(Ring& ring, uint32_t scratch, int planes, int rg, bool two) {
  constexpr int G = 2;
  const int warp = fresh_tid() >> 5, lane = fresh_tid() & 31;
  const uint32_t id = (lane >> 3) == (lane & 3) ? ((lane & 4) ? 0x3f800000u : 0x00003f80u) : 0u;
  const uint32_t at = (warp * 160 + lane) * 8, at1 = planes > 1 ? at : (lane >> 2) * 1280 + warp * 160 + (lane & 3) * 4;
  const uint32_t step = planes > 1 ? 256 : 32, half = planes > 1 ? 4 : 16;
  float v[G][5][4] = {};
#pragma unroll
  for (int r = 0; r < G; r++) {
#pragma unroll 1
    for (int k = r && !two ? 0 : planes; k > 0; k -= 4) {
      const uint32_t a = ring.wait(min(k, 4) + 1);
      if (k == 1) {
#pragma unroll
        for (int i = 0; i < 5; i++) mma8(v[r][i], lds32(a + at1 + i * step), lds32(a + at1 + i * step + half), id);
      } else {
#pragma unroll
        for (int i = 0; i < 10; i++) {
          if (i == 5 && k < 4) break;
          const uint2 x = lds64(a + at + i / 5 * 20480 + i % 5 * 256), y = lds64(a + at + i / 5 * 20480 + 10240 + i % 5 * 256);
          mma16(v[r][i % 5], x.x, x.y, y.x, y.y, id, id);
        }
      }
      ring.release(ring.seq - 1);
    }
  }
  uint2 xr[G][5];
  float mw[G];
  scratch += (lane >> 2) * 64;
#pragma unroll
  for (int r = 0; r < G; r++) {
    float m = 0.f, q2[4] = {};
#pragma unroll
    for (int i = 0; i < 5; i++) {
      float* t = v[r][i];
      xr[r][i] = make_uint2(pack2(t[0], t[1]), pack2(t[2], t[3]));
      t[0] = bf_lo(xr[r][i].x); t[1] = bf_hi(xr[r][i].x); t[2] = bf_lo(xr[r][i].y); t[3] = bf_hi(xr[r][i].y);
      m += (t[0] + t[1]) + (t[2] + t[3]);
    }
    m += __shfl_xor_sync(~0u, m, 1); m += __shfl_xor_sync(~0u, m, 2);
    m *= 1.f / 80;
#pragma unroll
    for (int i = 0; i < 20; i++) { float& t = v[r][i >> 2][i & 3]; t -= m; q2[i & 3] = fmaf(t, t, q2[i & 3]); }
    float q = (q2[0] + q2[1]) + (q2[2] + q2[3]);
    mw[r] = m;
    q += __shfl_xor_sync(~0u, q, 1); q += __shfl_xor_sync(~0u, q, 2);
    if ((lane & 3) == 0) sts64f(scratch + r * 512 + warp * 8, m, q);
  }
  bar_sync(1, 256);
#pragma unroll
  for (int r = 0; r < G; r++) {
    const float4 t = lds128f(scratch + r * 512 + (lane & 3) * 16);
    float mean = t.x + t.z;
    mean += __shfl_xor_sync(~0u, mean, 1); mean += __shfl_xor_sync(~0u, mean, 2);
    mean *= 0.125f;
    float var = (t.y + t.w) + 80.f * ((t.x - mean) * (t.x - mean) + (t.z - mean) * (t.z - mean));
    var += __shfl_xor_sync(~0u, var, 1); var += __shfl_xor_sync(~0u, var, 2);
    float rs;
    asm("rsqrt.approx.ftz.f32 %0, %1;" : "=f"(rs) : "f"(var * (1.f / DM) + 1e-5f));
#pragma unroll
    for (int i = 0; i < 20; i++) v[r][i >> 2][i & 3] = fmaf(v[r][i >> 2][i & 3], rs, (mw[r] - mean) * rs);
  }
#pragma unroll
  for (int r = 0; r < G; r++) {
    if (r && !two) break;
    uint32_t* xn = g_xn + (rg + r) * 2560 + warp * 320 + lane;
#pragma unroll
    for (int i = 0; i < 10; i++) xn[i * 32] = pack2(v[r][i >> 1][2 * (i & 1)], v[r][i >> 1][2 * (i & 1) + 1]);
#pragma unroll
    for (int i = 0; i < 5; i++) g_x[(rg + r) * 17 * 1280 + warp * 160 + i * 32 + lane] = xr[r][i];
  }
}

__device__ __forceinline__ void store_partial(const float* d, int b, int split, int unit, int nu) {
  uint2* dst = g_x + (((b * 16 + (fresh_tid() >> 5) * 2) * 17 + 1 + split) * 40 + unit) * 32 + (fresh_tid() & 31);
#pragma unroll
  for (int u = 0; u < 20; u++) {
    if (u == 10 && nu == 10) break;
    dst[u * 32] = make_uint2(pack2(d[8 * u], d[8 * u + 1]), pack2(d[8 * u + 4], d[8 * u + 5]));
    dst[(680 + u) * 32] = make_uint2(pack2(d[8 * u + 2], d[8 * u + 3]), pack2(d[8 * u + 6], d[8 * u + 7]));
  }
}

__device__ __forceinline__ void store_bqkv(const float* d, int b, int idx, int nh) {
  const int lane = fresh_tid() & 31, c = lane & 3, rg = b * 16 + (fresh_tid() >> 5) * 2, h0 = idx * nh;
  const float sc = h0 < 32 ? 0.22360679775f * 1.44269504089f : 1.f;
  const bool lo = c < 2;
  uint32_t* da = g_bqkv + (h0 * 256 + rg) * 96 + lane;
  uint32_t* db = da + 256 * 96 + (lo ? 2 : -2);
  uint32_t pad[2];
#pragma unroll
  for (int r = 0; r < 2; r++) pad[r] = !(c & 1) && (h0 >= 64 || (h0 >= 32 && (lane & 4) && poly_group(rg + r))) ? 0x00003f80u : 0u;
#pragma unroll
  for (int q = 0; q < 8; q++) {
    if ((q == 2 || q == 4) && nh == 2 * q) break;
#pragma unroll
    for (int r = 0; r < 2; r++) {
      uint32_t w[5];
#pragma unroll
      for (int i = 0; i < 5; i++) w[i] = pack2(d[20 * q + 4 * i + 2 * r] * sc, d[20 * q + 4 * i + 2 * r + 1] * sc);
      const int o = q * 2 * 256 * 96 + r * 96;
      da[o] = w[0]; da[o + 32] = w[1]; da[o + 64] = lo ? w[2] : pad[r];
      db[o] = lo ? w[3] : w[2]; db[o + 32] = lo ? w[4] : w[3]; db[o + 64] = lo ? pad[r] : w[4];
    }
  }
}

__device__ __forceinline__ void work_loader(const WorkParams& p, const uint32_t sb, const bool weights) {
  const uint32_t bars = sb + WK_BAR, bIF = bars + 128, bIE = bars + 160, bGo = bars + 224, slots = bars + 272;
  int pos = 0, seq = 0, tail = 0, used = 0;
  uint32_t lens = 0;
  const bool one = elect();
  if (p.kind == WK_CHAIN) {
    seq = 1; used = lens = 8;
    if (one) mbar_arrive(bars);
  }
  for (int n = 0;; n++) {
    mbar_wait(bIF + 8 * (n & 3), (n >> 2) & 1);
    const int code = __shfl_sync(~0u, (int)lds32(slots + 4 * (n & 3)), 0);
    if (code < 0) break;
    const int type = (code >> 16) & 15, b = (code >> 8) & 255, idx = code & 255;
    if (one) mbar_arrive(bIE + 8 * (n & 3));
    const bool qa = type == IT_ATT && b < p.qa_end, ln = type == IT_FIN || type == IT_LN || type == IT_LN0;
    const int parts = ln ? item_groups(type, b) : type == IT_ATT ? 2 : 1;
#pragma unroll 1
    for (int part = 0; part < parts; part++) {
      int bytes = 163840, chunk = 40960, nb = 0, flag = b * 8 + 4 + type, need = item_need(type & 3, b), c0 = 0, c3 = idx, c4 = 0, step = 64;
      const uint8_t* src = g_kv + (b * 32 + idx) * 6 * KV_PART;
      const CUtensorMap* m = nullptr;
      if (ln) {
        const int rg = b * 16 + idx * parts + part;
        bytes = (type == IT_FIN ? op_split(b) + 1 : type == IT_LN ? 2 : 1) * 10240;
        src = type == IT_LN0 ? reinterpret_cast<const uint8_t*>(p.x) + rg * 10240 : reinterpret_cast<const uint8_t*>(g_x) + rg * 174080;
        if (type == IT_LN) { flag = SY_P + b * 4; need = 2; }
        if (type == IT_LN0 || part) need = 0;
      } else if (part) {
        bytes = 6 * KV_PART;
      } else if (type == IT_ATT && !qa) {
        bytes = chunk = 49152;
        src = reinterpret_cast<const uint8_t*>(g_q) + (b * 32 + idx) * 49152;
        flag = SY_P + b * 4 + 3; need = 32;
      } else {
        const int cols = item_cols(type, b);
        chunk = 16384; nb = (cols + 63) >> 6;
        src = reinterpret_cast<const uint8_t*>(g_of) + b * 163840;
        if (type == IT_OP) {
          const int nkb = op_steps(b), kb0 = (idx >> op_tiles(b) / 2) * nkb;
          bytes = nkb * 16384;
          src = reinterpret_cast<const uint8_t*>(g_o) + (b * 96 + kb0) * 16384;
          if (weights) m = &p.wo;
          c0 = (idx & (op_tiles(b) - 1)) * cols; c3 = 0; c4 = kb0 * 2; step = 2;
        } else if (type == IT_BQ) {
          m = weights ? &p.wb[cols >> 7] : &p.xn;
        } else if (type == IT_BO || type == IT_OUT) {
          if (weights) m = &p.wc[cols >> 8];
          flag = SY_OB; need = type == IT_BO && b < 2 ? 32 : -1;
        } else {
          m = weights ? &p.wq : &p.xp;
          flag = SY_P + b * 4 + 1; need = ln_items(p.ch.layer, b);
        }
      }
      if (!weights) {
        c3 = b * 4;
        if (need < 0) pdl_wait(); else if (need) wait_count(p.sync + flag, need);
        if ((ln ? !part : part && (!qa || (code & C_EARLY))) && one) mbar_arrive(bGo);
      }
      const int boxes = weights ? nb : m != nullptr;
#pragma unroll 1
      for (; bytes > 0; bytes -= chunk) {
        const int now = min(bytes, chunk), len = ((now + 8191) >> 13) + nb, skip = pos + len > WK_SLOTS ? WK_SLOTS - pos : 0, sh = 4 * (seq & 7);
        used += len + skip;
        while (used > WK_SLOTS || seq - tail >= 8) {
          mbar_wait(bars + 64 + 8 * (tail & 7), (tail >> 3) & 1);
          used -= (lens >> 4 * (tail & 7)) & 15;
          tail++;
        }
        lens = (lens & ~(15u << sh)) | (len + skip) << sh;
        if (pos + len > WK_SLOTS) pos = 0;
        const uint32_t bar = bars + 2 * sh, dst = sb + pos * 8192 + weights * 16384;
        if (one) mbar_expect(bar, weights ? nb * 8192 : now);
#pragma unroll 1
        for (int i = 0; i < boxes; i++)
          if (one) tma_load5(dst + i * 8192, m, c0 + i * 64, c3, c4, bar);
        if (!weights && !m && one) bulk_load_last(dst, src, now, bar);
        if (weights) c4 += step; else c0 += 128;
        src += chunk; pos += len; seq++;
      }
    }
  }
}

__global__ void __launch_bounds__(384, 1) work_kernel(const __grid_constant__ WorkParams p) {
  extern __shared__ __align__(1024) uint8_t smem_raw[];
  const uint32_t sb = s2u(smem_raw), bars = sb + WK_BAR;
  const uint32_t bIF = bars + 128, bIE = bars + 160, done = bars + 192, bGo = bars + 224, slots = bars + 272, scratch = bars + 384;
  const int warp = __shfl_sync(~0u, threadIdx.x >> 5, 0);
  uint32_t* const sync = p.sync;
  TRACE(0);
  pdl_launch();
  if (p.kind == WK_LEAD && !helper_sm() && __syncthreads_or(threadIdx.x == 0 && ldg_strong32(sync + SY_PRE + 1) >= LEAD1)) { pdl_wait(); return; }
  if (p.kind == WK_CHAIN) {
    chain_start(p.ch, sb, warp);
  } else {
    if (warp < 4) work_init(sb, warp);
    __syncthreads();
    if (p.kind == WK_FIRST) {
      if (!(warp & 13)) probe_slots(bars + 320);
      if (!helper_sm()) return;
    }
  }
  if (warp >= 8) {
    asm volatile("setmaxnreg.dec.sync.aligned.u32 40;");
    if (p.kind == WK_CHAIN) chain_comm(p.ch, sb, &p.wo);
    const int warp = __shfl_sync(~0u, fresh_tid() >> 5, 0), lane = fresh_tid() & 31;
    if (warp == 9) {
      const bool keep = p.kind > WK_LEAD || helper_sm();
      int n = 0;
      if (p.kind == WK_CHAIN && reserved_item(blockIdx.x) >= 0) {
        if (lane == 0) { sts32(slots, reserved_item(blockIdx.x)); mbar_arrive(bIF); }
        n = 1;
      }
      const int b = lane & 15, layer = p.kind == WK_LAST ? 2 : sync != g_sync;
      bool first = layer == 1, lead = p.kind != WK_CHAIN;
      for (;; n++) {
        if (n > 0) mbar_wait(bGo, (n - 1) & 1);
        mbar_wait(bIE + 8 * (n & 3), ((n >> 2) & 1) ^ 1);
        int code = -1;
        if (lead) {
          int i = blockIdx.x + n * 256;
          if (first) { if (lane == 0) i = atomicAdd(sync + SY_PRE + 1, 1); i = __shfl_sync(~0u, i, 0); first = i < LEAD1; }
          if (layer < 2 && !first) {
            if (lane == 0) i = keep ? atomicAdd(sync + SY_PRE, 1) + layer * LEAD1 : 1 << 20;
            i = __shfl_sync(~0u, i, 0);
            if (!keep) pdl_wait();
          }
          code = lead_item(layer, p.qa_end, i);
          lead = code >= 0 || layer == 2 || !keep;
          if (!lead && p.kind <= WK_LEAD) {
            const uint32_t t0 = gtime();
            while (!lead && __all_sync(~0u, ldg_strong32(sync + SY_UP) < 96)) lead = __any_sync(~0u, gtime() - t0 > 20000);
          }
        }
        if (!lead) {
          int spin = 0, ticket = 0;
          if (lane == 0) ticket = atomicAdd(sync + SY_T, 1);
          for (;;) {
            const uint4 hd = ldg_strong128(sync + b * 8), pr = ldg_strong128(sync + b * 8 + 4);
            const uint32_t hv[4] = {hd.x, hd.y, hd.z, hd.w}, pv[4] = {pr.x, pr.y, pr.z, pr.w};
            const uint32_t chain_done = __ballot_sync(~0u, (pr.x & 0xffff) >= 96);
            int left[4], avail[4], rdy = 0, claimed = 0, upstream = 0;
#pragma unroll
            for (int t = 0; t < 4; t++) {
              const int cnt = lane < 16 && !reserved(t, b) ? item_count(t, b) : 0;
              left[t] = max(cnt - (int)hv[t], 0);
              claimed += cnt - left[t];
              const bool ready = (pv[t] & 0xffff) >= item_need(t, b);
              rdy |= ready << t;
              bool ok = ready || (t != IT_ATT && (chain_done >> 15 & 1) && !left[t - 1] && (t < 2 || !left[t - 2]));
              if (t == IT_BQ && (chain_done >> 12 & 9) == 1) ok = false;
              avail[t] = ok ? left[t] : 0;
              upstream |= __any_sync(~0u, left[t] > 0);
            }
            if (!upstream) { code = -1; break; }
            int rank = max(__shfl_sync(~0u, ticket, 0) - __reduce_add_sync(~0u, claimed), 0), type = -1, mine = 0;
#pragma unroll
            for (int c = 0; c < 7; c++) {
              const int t = c == 0 || c == 4 ? IT_FIN : c == 1 || c == 6 ? IT_ATT : c == 2 ? IT_OP : IT_BQ;
              int a = c == 1 || c == 2 || ((rdy >> t & 1) == (c < 4)) ? avail[t] : 0;
              if (c == 6) a = b < p.qa_end && !(rdy & 1) && ((chain_done << 1 | 1) >> b & 1) ? left[t] : 0;
              const int tot = __reduce_add_sync(~0u, a);
              if (type < 0) { if (rank < tot) { type = t; mine = a; } else rank -= tot; }
            }
            if (type >= 0) {
#pragma unroll
              for (int o = 1; o < 16; o <<= 1) { const int y = __shfl_up_sync(~0u, mine, o); if (lane >= o) mine += y; }
              const int blk = __ffs(__ballot_sync(~0u, mine > rank)) - 1;
              const int early = !(__shfl_sync(~0u, rdy, blk) >> type & 1);
              uint32_t idx = 0;
              if (lane == 0) idx = atomicAdd(sync + blk * 8 + type, 1);
              idx = __shfl_sync(~0u, idx, 0);
              if (idx < item_count(type, blk)) { code = (chain_done >> 14 & 1) << 22 | early << 20 | type << 16 | blk << 8 | idx; break; }
            } else {
              __nanosleep(50);
            }
            spin_guard(spin);
          }
        }
        if (lane == 0) {
          sts32(slots + 4 * (n & 3), code);
          mbar_arrive(bIF + 8 * (n & 3));
        }
        __syncwarp();
        if (code < 0) break;
      }
    } else if (warp >= 10) {
      work_loader(p, sb, warp == 10);
    } else {
      for (int n = 0;; n++) {
        mbar_wait(bIF + 8 * (n & 3), (n >> 2) & 1);
        const int code = __shfl_sync(~0u, (int)lds32(slots + 4 * (n & 3)), 0);
        if (code < 0) break;
        const int type = (code >> 16) & 15, b = (code >> 8) & 255;
        mbar_wait(done + 8 * (n & 3), (n >> 2) & 1);
        if (elect()) {
          if (type != IT_OUT) red_release(sync + (type < IT_BQ ? b * 8 + 5 + type : SY_P + b * 4 + ((0x13102 >> 4 * (type - IT_BQ)) & 3)), 1);
          mbar_arrive(bIE + 8 * (n & 3));
        }
        __syncwarp();
      }
    }
  } else {
    asm volatile("setmaxnreg.inc.sync.aligned.u32 232;");
    if (p.kind == WK_CHAIN) chain_compute(p.ch, sb);
    const int warp = __shfl_sync(~0u, fresh_tid() >> 5, 0), lane = fresh_tid() & 31;
    Ring r{sb, 0, p.kind == WK_CHAIN};
    Pending pend = {};
    int nln = 0;
    auto projects = [&](int n) {
      uint32_t here;
      asm volatile("{.reg .pred p; mbarrier.test_wait.parity.shared::cta.b64 p, [%1], %2; vote.sync.all.pred p, p, 0xffffffff; selp.u32 %0, 1, 0, p;}" : "=r"(here) : "r"(bIF + 8 * (n & 3)), "r"((n >> 2) & 1) : "memory");
      if (!here) return false;
      const int code = __shfl_sync(~0u, (int)lds32(slots + 4 * (n & 3)), 0);
      return code >= 0 && (((code >> 16) & 15) == IT_Q || (((code >> 16) & 15) == IT_ATT && ((code >> 8) & 255) < p.qa_end));
    };
#pragma unroll 1
    for (int n = 0;; n++) {
      if (pend.done && !projects(n)) pend.flush();
      mbar_wait(bIF + 8 * (n & 3), (n >> 2) & 1);
      const int code = __shfl_sync(~0u, (int)lds32(slots + 4 * (n & 3)), 0);
      if (code < 0) { TRACE(2); break; }
      const int type = (code >> 16) & 15, b = (code >> 8) & 255, idx = code & 255;
      const uint32_t go = (code & C_LATE) || (type == IT_ATT && (code & C_EARLY)) ? 0 : bGo;
      ITEM(code & 0xfffff, 0);
      if (type == IT_ATT || type == IT_Q) {
        if (type == IT_Q || b < p.qa_end) {
          float d[96] = {};
          reg_fence<96>(d);
          ITEM(9 << 16 | (code & 0xffff), 0);
          gemm_item<192>(d, r, 10, go, 4, pend);
          ITEM(9 << 16 | (code & 0xffff), 1);
#pragma unroll
          for (int i = 0; i < 48; i++) pend.w[i] = pack2(d[2 * i], d[2 * i + 1]);
        } else {
          const uint32_t base = r.wait(6) + warp * 2048 + lane * 16;
#pragma unroll
          for (int i = 0; i < 12; i++) {
            const uint4 t = lds128(base + (i >> 2) * 16384 + (i & 3) * 512);
            pend.w[4 * i] = t.x; pend.w[4 * i + 1] = t.y; pend.w[4 * i + 2] = t.z; pend.w[4 * i + 3] = t.w;
          }
          __syncwarp();
          r.release(r.seq - 1);
        }
        const bool now = type == IT_ATT && !projects(n + 1);
        if (type == IT_Q) {
          pend.dst = g_q + (b * 32 + idx) * 3072 + warp * 128 + lane;
        } else {
          pend.dst = g_o + (b * 32 + idx) * 3072 + (warp & 3) * 256 + (warp >> 2) * 128 + (lane & 3) * 8 + (lane >> 2);
          attn_a_warp(r, pend, now, warp);
        }
        pend.done = done + 8 * (n & 3);
        if (now) pend.finish();
      } else {
        if (type == IT_FIN || type == IT_LN || type == IT_LN0) {
          const int ng = item_groups(type, b);
          const int planes = type == IT_FIN ? op_split(b) + 1 : type == IT_LN ? 2 : 1;
#pragma unroll 1
          for (int i = 0; i < ng; i += 2) ln_groups(r, scratch + (nln++ & 1) * 1024, planes, b * 16 + idx * ng + i, ng > 1);
        } else {
          const int cols = item_cols(type, b), nkb = type == IT_OP ? op_steps(b) : 10;
          float d[160] = {};
          if (type == IT_OUT) {
            const uint2* x = g_x + ((b * 16 + warp * 2) * 680 + idx * 5) * 32 + lane;
#pragma unroll
            for (int i = 0; i < 10; i++) { const uint2 y = __ldcg(x + (i / 5 * 680 + i % 5) * 32); d[40 + 2 * i] = __uint_as_float(y.x); d[41 + 2 * i] = __uint_as_float(y.y); }
          }
          reg_fence<160>(d);
          if (type != IT_OUT) ITEM((type == IT_BQ ? 10 : 11) << 16 | (code & 0xffff), 0);
          const int ask = max(nkb - ((code & C_TAIL ? GO_TAIL : GO_320) << (2 - (cols >> 7))), 0);
          if (cols == 320) gemm_item<320>(d, r, nkb, go, ask, pend);
          else if (cols == 160) gemm_item<160>(d, r, nkb, go, ask, pend);
          else gemm_item<80>(d, r, nkb, go, ask, pend);
          if (type != IT_OUT) ITEM((type == IT_BQ ? 10 : 11) << 16 | (code & 0xffff), 1);
          reg_fence<160>(d);
          if (type == IT_OUT) {
            bar_sync(1, 256);
            const uint32_t dst = sb + (warp * 16 + (lane & 15)) * 160 + (lane >> 4) * 16;
#pragma unroll
            for (int u = 0; u < 5; u++) {
              uint32_t w[4];
#pragma unroll
              for (int i = 0; i < 4; i++) { const uint32_t y = __float_as_uint(d[40 + (i & 1) * 10 + 2 * u + (i >> 1)]); w[i] = pack2(bf_lo(y) + d[8 * u + 2 * i], bf_hi(y) + d[8 * u + 2 * i + 1]); }
              stsm4(dst + u * 32, w[0], w[1], w[2], w[3]);
            }
            fence_async();
            __syncwarp();
            if (elect()) { tma_store(&p.out, sb + warp * 2560, idx * 80, b * 128 + warp * 16); bulk_commit(); bulk_wait<0>(); }
          } else {
            if (warp >= 4) bar_sync(7, 256);
            if (type == IT_BQ) store_bqkv(d, b, idx, 4 << (cols >> 7));
            else store_partial(d, b, cols == 320 ? idx >> 1 : idx >> 2, cols == 320 ? (idx & 1) * 20 : (idx & 3) * 10, cols >> 4);
            if (warp < 4) bar_arrive(7, 256);
          }
        }
        __syncwarp();
        if (elect()) mbar_arrive(done + 8 * (n & 3));
#pragma unroll
        for (int i = 0; i < 48; i++) pend.w[i] = 0;
      }
      if ((code & C_LATE) && warp == 4 && elect()) mbar_arrive(bGo);
      ITEM(code & 0xfffff, 1);
    }
  }
}

constexpr int AB_SMEM = 1024 + 2 * 98304 + 256;
#define AB_N 32
#define AB_WG 4
constexpr int AB_T = AB_WG * 128, AB_PASS = 8 / AB_WG;
__device__ __forceinline__ float ex2_poly(float t) {
  const uint32_t r = __float_as_uint(t) & 0xffff8000u;
  const float f = t - __uint_as_float(r);
  const float p = fmaf(fmaf(fmaf(-5.869912678e-38f, f, -1.700740250e-37f), f, -5.234869734e-37f), f, -7.522601252e-37f);
  uint32_t y;
  asm("mad.lo.u32 %0, %1, 256, %2;" : "=r"(y) : "r"(r), "r"(__float_as_uint(p)));
  return __uint_as_float(y);
}
__device__ __forceinline__ uint32_t hsq(uint32_t w, uint32_t c) { uint32_t r; asm("fma.rn.bf16x2 %0, %1, %1, %2;" : "=r"(r) : "r"(w), "r"(c)); return r; }
__device__ __forceinline__ float sq2(uint32_t w) { const float a = bf_lo(w), b = bf_hi(w); return fmaf(a, a, b * b); }

__device__ __forceinline__ void attn_b_store(const float* o, int h, int row0, int lane) {
  const int g = lane >> 2, c = lane & 3;
  const float i0 = rcp(__shfl_sync(~0u, o[8], (lane & ~3) | 2)), i1 = rcp(__shfl_sync(~0u, o[10], (lane & ~3) | 2));
#pragma unroll
  for (int jj = 0; jj < 3; jj++) {
    if (jj < 2 || c < 2) {
      const int col = h * 20 + 8 * jj + 2 * c;
      g_of[core_word(row0 + g, col)] = pack2(o[4 * jj] * i0, o[4 * jj + 1] * i0);
      g_of[core_word(row0 + g + 8, col)] = pack2(o[4 * jj + 2] * i1, o[4 * jj + 3] * i1);
    }
  }
}

__device__ __forceinline__ void attn_b_qk(float* s, uint32_t q0, uint32_t q1, uint32_t q2, uint32_t q3, uint32_t q4, uint32_t q5, uint32_t z0, uint32_t z1,
                                          uint64_t dk, uint64_t dk2) {
  wg_rs32_00(s, q0, q1, q2, q3, dk, 0);
  wg_rs32_00(s, q4, q5, z0, z1, dk2, 1);
}

struct AttnParams { const uint8_t* pf[4]; uint32_t *sync, *next; };
__global__ void __launch_bounds__(AB_T + 128, 1) attn_b_kernel(const __grid_constant__ AttnParams p) {
  extern __shared__ uint8_t smem_raw[];
  const uint32_t sb = (s2u(smem_raw) + 1023) & ~1023u, sK = sb, sV = sb + 98304, bars = sb + 2 * 98304;
  const int warp = __shfl_sync(~0u, threadIdx.x >> 5, 0), lane = threadIdx.x & 31;
  const int h = blockIdx.x & 31, quarter = blockIdx.x >> 5;
  BT(0);
  TRACE(0);
  if (warp < 10 && elect()) {
    mbar_init(bars + 8 * warp + (warp & 8) * 8, warp < 8 ? 1 : warp == 8 ? AB_T / 32 : 2);
    asm volatile("fence.mbarrier_init.release.cluster;" ::: "memory");
  }
  __syncthreads();
  if (warp >= AB_T / 32) {
    asm volatile("setmaxnreg.dec.sync.aligned.u32 32;");
    if (warp == AB_T / 32 + 1) return;
    if (warp > AB_T / 32) {
      uint32_t kmax = 0;
#pragma unroll 1
      for (int i = 0; i < 32; i++) {
        if (!(i & 3)) mbar_wait(bars + 2 * i, 0);
        const uint32_t a = sK + i * 3072 + ((threadIdx.x >> 3) & 7) * 384 + (lane & 7) * 16;
        const uint4 x = lds128(a), y = lds128(a + 128);
        const uint2 z = lds64(a + 256);
        const uint32_t n = hadd2(hsq(x.x, hsq(x.y, hsq(x.z, hsq(x.w, hsq(z.x, 0))))), hsq(y.x, hsq(y.y, hsq(y.z, hsq(y.w, hsq(z.y, 0))))));
        kmax = max(kmax, __float_as_uint(bf_lo(n) + bf_hi(n)) & 0x7fffffffu);
      }
      const uint32_t kbits = __reduce_max_sync(~0u, kmax);
      if (lane == 0) { sts32(bars + 64 + (warp & 1) * 4, kbits); mbar_arrive(bars + 136); }
      return;
    }
    const uint8_t* gk = reinterpret_cast<const uint8_t*>(g_bqkv + (32 + h) * 256 * 96);
    const uint8_t* gv = reinterpret_cast<const uint8_t*>(g_bqkv + (64 + h) * 256 * 96);
    uint32_t todo = 255;
    for (int spin = 0; todo;) {
      const uint32_t up = __ballot_sync(~0u, ld_acquire(p.sync + SY_P + (lane & 15) * 4 + 2) >= bq_items(lane & 15));
      fence_async_global();
#pragma unroll 1
      for (int i = 0; i < 8; i++) {
        if (!(todo >> i & 1) || (up >> 2 * i & 3) != 3) continue;
        todo &= ~(1u << i);
        if (elect()) {
          mbar_expect(bars + 8 * i, 24576);
          bulk_load(sK + i * 12288, gk + i * 12288, 12288, bars + 8 * i);
          bulk_load(sV + i * 12288, gv + i * 12288, 12288, bars + 8 * i);
        }
      }
      spin_guard(spin);
    }
    pdl_launch();
    TRACE(1);
#pragma unroll 1
    for (int i = lane; i < 512 && blockIdx.x < NSLOT; i += 32) reinterpret_cast<uint4*>(pool_at(blockIdx.x * 8192))[i] = make_uint4(0, 0, 0, 0);
    if (!p.next && blockIdx.x < 8) { const int i = blockIdx.x * 32 + lane; g_smpart[i] = 0; if (i < NSLOT) g_orient[i] = 0; }
    if (p.next) {
      mbar_wait(bars + 128, 0);
      if (quarter == 0 && lane == 0) red_release(p.next + SY_OB, 1);
#pragma unroll 1
      for (int i = 0; i < 32; i++) {
        if (elect()) prefetch_l2(p.pf[i >> 3] + blockIdx.x * 61440 + (i & 7) * 7680, 7680);
        __nanosleep(300);
      }
    }
    return;
  }
  asm volatile("setmaxnreg.inc.sync.aligned.u32 112;");
  constexpr int NT = SEQ / AB_N, PER = 256 / AB_N;
  uint32_t qn[8];
  auto load_q = [&](int pass) {
    const uint32_t* gq = g_bqkv + (h * 256 + pass * 128 + quarter * 32 + warp * 2) * 96 + lane;
#pragma unroll
    for (int i = 0; i < 8; i++) qn[i] = __ldcg(gq + (i & 1) * 96 + min(i >> 1, 2) * 32 + (i < 6 ? 0 : 3 - (lane & 3)));
  };
  mbar_wait(bars + 8 * quarter, 0);
  load_q(0);
#pragma unroll 1
  for (int pass = 0; pass < AB_PASS; pass++) {
    const int row0 = pass * 1024 + quarter * 256 + warp * 16;
    const uint32_t q0 = qn[0], q1 = qn[1], q2 = qn[2], q3 = qn[3], z0 = qn[6], z1 = qn[7];
    uint32_t q4 = qn[4], q5 = qn[5];
    if ((lane & 3) == 2) { q4 = 0x43BCu; q5 = 0x43BCu; }
    float o[12];
    uint64_t dk = mkdesc(sK, 128, 384, 0), dk2 = mkdesc(sK + 256, 0, 384, 0), dv = mkdesc(sV, 384, 128, 0);
    float sa[AB_N / 2], sb2[AB_N / 2];
    uint32_t pa[AB_N / 4], pb[AB_N / 4];
    if (pass == 0) mbar_wait(bars, 0);
    BT(1 + 2 * pass);
    wg_fence();
    attn_b_qk(sa, q0, q1, q2, q3, q4, q5, z0, z1, dk, dk2);
    wg_commit();
    attn_b_qk(sb2, q0, q1, q2, q3, q4, q5, z0, z1, dk + AB_N * 3, dk2 + AB_N * 3);
    wg_commit();
#pragma unroll 1
    for (int kt = 0; kt < NT; kt += 2) {
      const int nx = kt + 2 < NT ? kt + 2 : 0;
      if (pass == 0 && (nx & (PER - 1)) == 0) mbar_wait(bars + 8 * (nx / PER), 0);
      const uint64_t nk = dk + nx * (AB_N * 3), nk2 = dk2 + nx * (AB_N * 3);
      wg_wait<1>();
      reg_fence<AB_N / 2>(sa);
#pragma unroll
      for (int i = 0; i < AB_N / 4; i++) pa[i] = pack2(ex2(sa[2 * i]), poly_group(i >> 1) ? ex2_poly(sa[2 * i + 1]) : ex2(sa[2 * i + 1]));
      wg_fence();
#pragma unroll
      for (int kk = 0; kk < AB_N / 16; kk++) wg_rs24_01(o, pa[4 * kk], pa[4 * kk + 1], pa[4 * kk + 2], pa[4 * kk + 3], dv + kk * 48, kk | kt);
      attn_b_qk(sa, q0, q1, q2, q3, q4, q5, z0, z1, nk, nk2);
      wg_commit();
      wg_wait<1>();
      reg_fence<AB_N / 2>(sb2);
#pragma unroll
      for (int i = 0; i < AB_N / 4; i++) pb[i] = pack2(ex2(sb2[2 * i]), poly_group((i >> 1) + AB_N / 8) ? ex2_poly(sb2[2 * i + 1]) : ex2(sb2[2 * i + 1]));
      wg_fence();
#pragma unroll
      for (int kk = 0; kk < AB_N / 16; kk++) wg_rs24_01(o, pb[4 * kk], pb[4 * kk + 1], pb[4 * kk + 2], pb[4 * kk + 3], dv + AB_N * 3 + kk * 48, 1);
      attn_b_qk(sb2, q0, q1, q2, q3, q4, q5, z0, z1, nk + AB_N * 3, nk2 + AB_N * 3);
      wg_commit();
      dv += AB_N * 6;
    }
    wg_wait<0>();
    reg_fence<12>(o); reg_fence<AB_N / 2>(sa); reg_fence<AB_N / 2>(sb2);
    BT(2 + 2 * pass);
    if (pass + 1 < AB_PASS) load_q(pass + 1);
    mbar_wait(bars + 136, 0);
    const uint2 kb = lds64(bars + 64);
    const float kmax = __uint_as_float(max(kb.x, kb.y));
    if ((lane & 3) == 2) q4 = q5 = 0;
    float n0 = sq2(q0) + sq2(q2) + sq2(q4), n1 = sq2(q1) + sq2(q3) + sq2(q5);
    n0 += __shfl_xor_sync(~0u, n0, 1); n1 += __shfl_xor_sync(~0u, n1, 1);
    n0 += __shfl_xor_sync(~0u, n0, 2); n1 += __shfl_xor_sync(~0u, n1, 2);
    uint32_t redo;
    asm volatile("{.reg .pred p, q; setp.ne.u32 p, %1, 0; bar.red.or.pred q, %2, 128, p; selp.u32 %0, 1, 0, q;}"
                 : "=r"(redo) : "r"((uint32_t)!(n0 * kmax <= 9500.f && n1 * kmax <= 9500.f)), "r"(2 + (warp >> 2)) : "memory");
    if (redo) {
#pragma unroll
      for (int i = 0; i < 12; i++) o[i] = 0.f;
      float m0 = -INFINITY, m1 = -INFINITY;
#pragma unroll 1
      for (int kt = 0; kt < 64; kt++) {
        float s[16];
        wg_fence();
        wg_rs32_00(s, q0, q1, q2, q3, dk + kt * 96, 0);
        wg_rs32_00(s, q4, q5, z0, z1, dk2 + kt * 96, 1);
        wg_commit();
        wg_wait<0>();
        reg_fence<16>(s); reg_fence<12>(o);
        float n0 = m0, n1 = m1;
#pragma unroll
        for (int jj = 0; jj < 4; jj++) { n0 = fmaxf(n0, fmaxf(s[4 * jj], s[4 * jj + 1])); n1 = fmaxf(n1, fmaxf(s[4 * jj + 2], s[4 * jj + 3])); }
        n0 = fmaxf(n0, __shfl_xor_sync(~0u, n0, 1)); n0 = fmaxf(n0, __shfl_xor_sync(~0u, n0, 2));
        n1 = fmaxf(n1, __shfl_xor_sync(~0u, n1, 1)); n1 = fmaxf(n1, __shfl_xor_sync(~0u, n1, 2));
        const float r0 = ex2(m0 - n0), r1 = ex2(m1 - n1);
        m0 = n0; m1 = n1;
#pragma unroll
        for (int jj = 0; jj < 3; jj++) { o[4 * jj] *= r0; o[4 * jj + 1] *= r0; o[4 * jj + 2] *= r1; o[4 * jj + 3] *= r1; }
        uint32_t pp[8];
#pragma unroll
        for (int jj = 0; jj < 4; jj++) {
          pp[2 * jj] = pack2(ex2(s[4 * jj] - m0), ex2(s[4 * jj + 1] - m0));
          pp[2 * jj + 1] = pack2(ex2(s[4 * jj + 2] - m1), ex2(s[4 * jj + 3] - m1));
        }
        reg_fence<12>(o);
        wg_fence();
#pragma unroll
        for (int kk = 0; kk < 2; kk++) wg_rs24_01(o, pp[4 * kk], pp[4 * kk + 1], pp[4 * kk + 2], pp[4 * kk + 3], mkdesc(sV, 384, 128, 0) + kt * 96 + kk * 48, 1);
        wg_commit();
      }
      wg_wait<0>();
      reg_fence<12>(o);
    }
    attn_b_store(o, h, row0, lane);
    __syncwarp();
    if (pass == 0 && lane == 0) mbar_arrive(bars + 128);
  }
  BT(5);
  TRACE(2);
}

typedef CUresult (*EncodeFn)(CUtensorMap*, CUtensorMapDataType, cuuint32_t, void*, const cuuint64_t*, const cuuint64_t*,
                             const cuuint32_t*, const cuuint32_t*, CUtensorMapInterleave, CUtensorMapSwizzle,
                             CUtensorMapL2promotion, CUtensorMapFloatOOBfill);

void make_map(EncodeFn enc, CUtensorMap* m, const void* ptr, int cols, int rows, int box_rows, int box_cols = 64) {
  const cuuint64_t dims[2] = {(cuuint64_t)cols, (cuuint64_t)rows};
  const cuuint64_t strides[1] = {(cuuint64_t)cols * 2};
  const cuuint32_t box[2] = {(cuuint32_t)box_cols, (cuuint32_t)box_rows}, es[2] = {1, 1};
  enc(m, CU_TENSOR_MAP_DATA_TYPE_BFLOAT16, 2, const_cast<void*>(ptr), dims, strides, box, es, CU_TENSOR_MAP_INTERLEAVE_NONE,
      box_cols == 64 ? CU_TENSOR_MAP_SWIZZLE_128B : box_cols == 32 ? CU_TENSOR_MAP_SWIZZLE_64B : CU_TENSOR_MAP_SWIZZLE_NONE, CU_TENSOR_MAP_L2_PROMOTION_L2_256B, CU_TENSOR_MAP_FLOAT_OOB_FILL_NONE);
}
void make_map5(EncodeFn enc, CUtensorMap* m, const void* ptr, bool words, const cuuint64_t (&dims)[5], const cuuint64_t (&strides)[4], const cuuint32_t (&box)[5]) {
  const cuuint32_t es[5] = {1, 1, 1, 1, 1};
  enc(m, words ? CU_TENSOR_MAP_DATA_TYPE_UINT64 : CU_TENSOR_MAP_DATA_TYPE_BFLOAT16, 5, const_cast<void*>(ptr), dims, strides, box, es, CU_TENSOR_MAP_INTERLEAVE_NONE,
      words ? CU_TENSOR_MAP_SWIZZLE_NONE : CU_TENSOR_MAP_SWIZZLE_128B, dims[0] % 64 ? CU_TENSOR_MAP_L2_PROMOTION_L2_128B : CU_TENSOR_MAP_L2_PROMOTION_L2_256B,
      CU_TENSOR_MAP_FLOAT_OOB_FILL_NONE);
}
void make_tiles(EncodeFn enc, CUtensorMap* m, const void* ptr, cuuint64_t cols, cuuint64_t tile) {
  make_map5(enc, m, ptr, false, {tile, 1, 1, cols / tile, DM}, {tile * 2, tile * 2, tile * 2, cols * 2}, {64, 1, 1, 1, 64});
}
template <class... KA, class... A>
void launch(void (*kern)(KA...), int grid, int block, int smem, int cluster, bool pdl, A... args) {
  cudaFuncSetAttribute(kern, cudaFuncAttributeMaxDynamicSharedMemorySize, smem);
  cudaLaunchConfig_t cfg = {};
  cfg.gridDim = dim3(grid); cfg.blockDim = dim3(block); cfg.dynamicSmemBytes = smem; cfg.stream = cudaStreamPerThread;
  cudaLaunchAttribute at[2];
  int n = 0;
  if (cluster > 1) { at[n].id = cudaLaunchAttributeClusterDimension; at[n].val.clusterDim.x = cluster; at[n].val.clusterDim.y = 1; at[n].val.clusterDim.z = 1; n++; }
  if (pdl) { at[n].id = cudaLaunchAttributeProgrammaticStreamSerialization; at[n].val.programmaticStreamSerializationAllowed = 1; n++; }
  cfg.attrs = at; cfg.numAttrs = n;
  cudaLaunchKernelEx(&cfg, kern, args...);
}
template <class T> void* sym(T& s) { void* p = nullptr; cudaGetSymbolAddress(&p, s); return p; }

}

#define MODE(b) 0
extern "C" void kernel_launch(void* const* d_in, const int* in_sizes, int n_in, void* d_out, int out_size) {
  const __nv_bfloat16* x = (const __nv_bfloat16*)d_in[0];
  void* fn = nullptr; cudaDriverEntryPointQueryResult qr;
  cudaGetDriverEntryPoint("cuTensorMapEncodeTiled", &fn, cudaEnableDefault, &qr);
  EncodeFn enc = (EncodeFn)fn;

  WorkParams wk = {};
  ChainParams& ch = wk.ch;
  AttnParams at = {};
  make_map(enc, &ch.wq, d_in[2], HD, DM, 160); make_map(enc, &ch.wk, d_in[3], HD, DM, 160); make_map(enc, &ch.wv, d_in[4], HD, DM, 160);
  make_map(enc, &ch.wo, d_in[5], DM, HD, 192, 32);
  ch.mem0 = (const __nv_bfloat16*)d_in[1];
  ch.wb = (const uint8_t*)d_in[8];
  ch.d1 = 300; ch.d2 = 200; ch.dn = 150; ch.dx = 950;
  make_tiles(enc, &wk.wq, d_in[2], HD, 192);
  for (int i = 0; i < 3; i++) make_tiles(enc, &wk.wb[i], d_in[8], 1920, 80 << i);
  for (int i = 0; i < 2; i++) make_tiles(enc, &wk.wc[i], d_in[9], DM, 80 << 2 * i);
  make_map(enc, &wk.out, d_out, DM, SEQ, 16, 80);
  make_map5(enc, &wk.wo, d_in[5], false, {DM, 2, 4, 4, HD / 32}, {DM * 2, DM * 16, DM * 4, DM * 64}, {64, 2, 4, 4, 2});
  make_map5(enc, &wk.xn, sym(g_xn), true, {1280, 2, 2, 64, 1}, {10240, 20480, 40960, 40960}, {128, 2, 2, 4, 1});
  make_map5(enc, &wk.xp, sym(g_xn), true, {1280, 2, 1, 64, 2}, {10240, 10240, 40960, 20480}, {128, 2, 1, 4, 2});
  make_map5(enc, &ch.xc, sym(g_xn), true, {160, 1, 1, 256, 8}, {1280, 1280, 10240, 1280}, {160, 1, 1, 4, 2});
  wk.x = x;
  for (int i = 0; i < 4; i++) at.pf[i] = (const uint8_t*)d_in[i < 2 ? 3 + i : i == 2 ? 2 : 5];
  int qa_end[2] = {12, 12};
  for (int layer = 0; layer < 2; layer++) {
    ch.sync = wk.sync = at.sync = (uint32_t*)sym(g_sync) + layer * SY_N;
    ch.other = (uint32_t*)sym(g_sync) + (1 - layer) * SY_N;
    ch.layer = layer;
    at.next = layer ? nullptr : ch.other;
    wk.qa_end = qa_end[layer];
    wk.kind = layer ? WK_LEAD : WK_FIRST;
    launch(work_kernel, 132, 384, CH_SMEM, 1, layer != 0, wk);
    wk.kind = WK_CHAIN;
    launch(work_kernel, 96, 384, CH_SMEM, 3, true, wk);
    launch(attn_b_kernel, 128, AB_T + 128, AB_SMEM, 1, true, at);
  }
  wk.kind = WK_LAST;
  launch(work_kernel, 128, 384, CH_SMEM, 1, true, wk);
}
```

```cpp
#include <cuda_runtime.h>
#include <cuda_bf16.h>
#include <cuda.h>
#include <stdint.h>
#include <stdlib.h>

namespace {

constexpr int SEQ = 2048, DM = 640, HD = 6144, NSEG = 64;
constexpr int SPIN_LIMIT = 1 << 20;

__device__ __align__(128) uint2 g_x[256 * 17 * 1280];
__device__ __align__(128) uint32_t g_xn[SEQ * DM / 2];
__device__ __align__(128) uint32_t g_of[SEQ * DM / 2];
__device__ __align__(128) uint4 g_o[SEQ * HD / 8];
__device__ __align__(128) uint4 g_q[SEQ * HD / 8];
constexpr int KV_M = 16384, KV_PART = 20480, KV_V = 3 * KV_PART;
__device__ __align__(128) uint8_t g_kv[16 * 32 * 6 * KV_PART];
#define OP_B8 11
#define OP_B16 14
#define OP_N4 15
#define BQ_12 12
#define BQ_24 14
#define FIN_16 12
__host__ __device__ constexpr int op_split(int b) { return b < OP_B8 ? 4 : b < OP_B16 ? 8 : 16; }
__host__ __device__ constexpr int op_steps(int b) { return b < OP_B8 ? 24 : b < OP_B16 ? 12 : 6; }
__host__ __device__ constexpr int op_tiles(int b) { return b < OP_N4 ? 2 : 4; }
__host__ __device__ constexpr int fin_items(int b) { return b < OP_B8 ? 4 : b < FIN_16 ? 8 : 16; }
__host__ __device__ constexpr int bq_items(int b) { return b < BQ_12 ? 6 : b < BQ_24 ? 12 : 24; }
__host__ __device__ constexpr int ln_items(int layer, int b) { return layer == 0 && b < 2 ? 16 : 4; }
constexpr int SY_P = 128, SY_T = 192, SY_UP = 224, SY_OB = 225, SY_PRE = 256, SY_PART = 288, SY_TIME = 384, SY_N = 448;
__device__ __align__(128) uint32_t g_sync[2 * SY_N];
constexpr int NSLOT = 92;
__device__ uint32_t g_pool[(NSLOT + 2) * 2048];
__device__ uint32_t g_smpart[256], g_orient[NSLOT];
__device__ __align__(128) uint32_t g_bqkv[3 * 32 * 256 * 96];

#define BT(i)
#define MISS(k, n)
#define PRO(i)
#define TRACE(w)
#define ITEM(code, w)
#define STAT(k)
#define TMV(i, v)
#define TM(i)
#define TMD(i, dep)

__device__ __forceinline__ uint32_t gtime() { uint32_t c; asm volatile("mov.u32 %0, %%globaltimer_lo;" : "=r"(c) :: "memory"); return c; }
__device__ __forceinline__ uint32_t clk32() { uint32_t c; asm volatile("mov.u32 %0, %%clock;" : "=r"(c) :: "memory"); return c; }
__device__ __forceinline__ uint32_t fresh_tid() { uint32_t t; asm volatile("mov.u32 %0, %%tid.x;" : "=r"(t)); return t; }
__device__ __forceinline__ uint32_t s2u(const void* p) { return (uint32_t)__cvta_generic_to_shared(p); }
__device__ __forceinline__ uint32_t pack2(float a, float b) {
  uint32_t r; asm("cvt.rn.bf16x2.f32 %0, %1, %2;" : "=r"(r) : "f"(b), "f"(a)); return r; }
__device__ __forceinline__ float bf_lo(uint32_t w) { return __uint_as_float(w << 16); }
__device__ __forceinline__ float bf_hi(uint32_t w) { return __uint_as_float(w & 0xffff0000u); }
__device__ __forceinline__ float ex2(float x) { float y; asm("ex2.approx.ftz.f32 %0, %1;" : "=f"(y) : "f"(x)); return y; }

__device__ __forceinline__ void mbar_init(uint32_t bar, uint32_t n) {
  asm volatile("mbarrier.init.shared::cta.b64 [%0], %1;" :: "r"(bar), "r"(n) : "memory"); }
__device__ __forceinline__ void mbar_expect(uint32_t bar, uint32_t bytes) {
  asm volatile("mbarrier.arrive.expect_tx.shared::cta.b64 _, [%0], %1;" :: "r"(bar), "r"(bytes) : "memory"); }
__device__ __forceinline__ void mbar_arrive(uint32_t bar) {
  asm volatile("mbarrier.arrive.shared::cta.b64 _, [%0];" :: "r"(bar) : "memory"); }
__device__ __forceinline__ void mbar_arrive_remote(uint32_t bar) {
  asm volatile("mbarrier.arrive.shared::cluster.b64 _, [%0];" :: "r"(bar) : "memory"); }
__device__ __forceinline__ void mbar_wait(uint32_t bar, uint32_t ph) {
  asm volatile("{.reg .pred p; .reg .u32 n; mov.u32 n, 0;\n"
               "W: mbarrier.try_wait.parity.shared::cta.b64 p, [%0], %1; @p bra.uni D;\n"
               "add.u32 n, n, 1; setp.gt.u32 p, n, %2; @p trap; bra.uni W;\n"
               "D: }" :: "r"(bar), "r"(ph), "n"(SPIN_LIMIT) : "memory");
}
__device__ __forceinline__ bool elect() {
  uint32_t p; asm volatile("{.reg .pred q; elect.sync _|q, 0xffffffff; selp.u32 %0, 1, 0, q;}" : "=r"(p)); return p; }
__device__ __forceinline__ void spin_guard(int& n) {
  asm volatile("{.reg .pred p; add.s32 %0, %0, 1; setp.gt.s32 p, %0, %1; @p trap;}" : "+r"(n) : "n"(SPIN_LIMIT));
}
__device__ __forceinline__ void pdl_wait() { asm volatile("griddepcontrol.wait;" ::: "memory"); TRACE(1); }
__device__ __forceinline__ void pdl_launch() { asm volatile("griddepcontrol.launch_dependents;" ::: "memory"); }
__device__ __forceinline__ uint32_t ld_acquire(const uint32_t* p) { uint32_t v; asm volatile("ld.acquire.gpu.global.u32 %0, [%1];" : "=r"(v) : "l"(p) : "memory"); return v; }
__device__ __forceinline__ void red_release(uint32_t* p, uint32_t v) { asm volatile("red.release.gpu.global.add.u32 [%0], %1;" :: "l"(p), "r"(v) : "memory"); }
__device__ __forceinline__ void fence_async_global() { asm volatile("fence.proxy.async.global;" ::: "memory"); }
__device__ __forceinline__ void fence_async() { asm volatile("fence.proxy.async.shared::cta;" ::: "memory"); }
__device__ __forceinline__ void bar_sync(int id, int n) { asm volatile("bar.sync %0, %1;" :: "r"(id), "r"(n) : "memory"); }
__device__ __forceinline__ void bar_arrive(int id, int n) { asm volatile("bar.arrive %0, %1;" :: "r"(id), "r"(n) : "memory"); }
__device__ __forceinline__ void tma_load(uint32_t dst, const CUtensorMap* m, int c0, int c1, uint32_t bar) {
  asm volatile("cp.async.bulk.tensor.2d.shared::cluster.global.mbarrier::complete_tx::bytes [%0], [%1, {%3, %4}], [%2];"
               :: "r"(dst), "l"(m), "r"(bar), "r"(c0), "r"(c1) : "memory"); }
__device__ __forceinline__ void tma_load5(uint32_t dst, const CUtensorMap* m, int c0, int c3, int c4, uint32_t bar) {
  asm volatile("cp.async.bulk.tensor.5d.shared::cluster.global.mbarrier::complete_tx::bytes [%0], [%1, {%3, %6, %6, %4, %5}], [%2];"
               :: "r"(dst), "l"(m), "r"(bar), "r"(c0), "r"(c3), "r"(c4), "r"(0) : "memory"); }
__device__ __forceinline__ void tma_store(const CUtensorMap* m, uint32_t src, int c0, int c1) {
  asm volatile("cp.async.bulk.tensor.2d.global.shared::cta.bulk_group [%0, {%2, %3}], [%1];"
               :: "l"(m), "r"(src), "r"(c0), "r"(c1) : "memory"); }
__device__ __forceinline__ uint64_t evict_first() { uint64_t p; asm("createpolicy.fractional.L2::evict_first.b64 %0, 1.0;" : "=l"(p)); return p; }
__device__ __forceinline__ void bulk_load_last(uint32_t dst, const void* src, uint32_t bytes, uint32_t bar) {
  asm volatile("cp.async.bulk.shared::cluster.global.mbarrier::complete_tx::bytes.L2::cache_hint [%0], [%1], %2, [%3], %4;"
               :: "r"(dst), "l"(src), "r"(bytes), "r"(bar), "l"(evict_first()) : "memory"); }
__device__ __forceinline__ void bulk_store_stream(void* dst, uint32_t src, uint32_t bytes) {
  asm volatile("cp.async.bulk.global.shared::cta.bulk_group.L2::cache_hint [%0], [%1], %2, %3;" :: "l"(dst), "r"(src), "r"(bytes), "l"(evict_first()) : "memory"); }
__device__ __forceinline__ void bulk_load(uint32_t dst, const void* src, uint32_t bytes, uint32_t bar) {
  asm volatile("cp.async.bulk.shared::cluster.global.mbarrier::complete_tx::bytes [%0], [%1], %2, [%3];"
               :: "r"(dst), "l"(src), "r"(bytes), "r"(bar) : "memory"); }
__device__ __forceinline__ void bulk_push(uint32_t dst, uint32_t src, uint32_t bytes, uint32_t bar) {
  asm volatile("cp.async.bulk.shared::cluster.shared::cta.mbarrier::complete_tx::bytes [%0], [%1], %2, [%3];"
               :: "r"(dst), "r"(src), "r"(bytes), "r"(bar) : "memory"); }
__device__ __forceinline__ void bulk_store(void* dst, uint32_t src, uint32_t bytes) {
  asm volatile("cp.async.bulk.global.shared::cta.bulk_group [%0], [%1], %2;" :: "l"(dst), "r"(src), "r"(bytes) : "memory"); }
__device__ __forceinline__ void bulk_commit() { asm volatile("cp.async.bulk.commit_group;" ::: "memory"); }
template <int N> __device__ __forceinline__ void bulk_wait_read() { asm volatile("cp.async.bulk.wait_group.read %0;" :: "n"(N) : "memory"); }
template <int N> __device__ __forceinline__ void bulk_wait() { asm volatile("cp.async.bulk.wait_group %0;" :: "n"(N) : "memory"); }

__device__ __forceinline__ uint64_t mkdesc(uint32_t addr, uint32_t lbo, uint32_t sbo, uint32_t sw) {
  return (uint64_t)((addr & 0x3FFFF) >> 4) | ((uint64_t)(lbo >> 4) << 16) | ((uint64_t)(sbo >> 4) << 32) | ((uint64_t)sw << 62); }
__device__ __forceinline__ void wg_fence() { asm volatile("wgmma.fence.sync.aligned;" ::: "memory"); }
__device__ __forceinline__ void wg_commit() { asm volatile("wgmma.commit_group.sync.aligned;" ::: "memory"); }
template <int N> __device__ __forceinline__ void wg_wait() { asm volatile("wgmma.wait_group.sync.aligned %0;" :: "n"(N) : "memory"); }
template <int N> __device__ __forceinline__ void reg_fence(float* d) {
#pragma unroll
  for (int i = 0; i < N; i++) asm volatile("" : "+f"(d[i]) :: "memory");
}

__device__ __forceinline__ void mma16(float* d, uint32_t a0, uint32_t a1, uint32_t a2, uint32_t a3, uint32_t b0, uint32_t b1) {
  asm volatile("mma.sync.aligned.m16n8k16.row.col.f32.bf16.bf16.f32 {%0,%1,%2,%3},{%4,%5,%6,%7},{%8,%9},{%0,%1,%2,%3};"
               : "+f"(d[0]), "+f"(d[1]), "+f"(d[2]), "+f"(d[3]) : "r"(a0), "r"(a1), "r"(a2), "r"(a3), "r"(b0), "r"(b1)); }
__device__ __forceinline__ void mma8(float* d, uint32_t a0, uint32_t a1, uint32_t b0) {
  asm volatile("mma.sync.aligned.m16n8k8.row.col.f32.bf16.bf16.f32 {%0,%1,%2,%3},{%4,%5},{%6},{%0,%1,%2,%3};"
               : "+f"(d[0]), "+f"(d[1]), "+f"(d[2]), "+f"(d[3]) : "r"(a0), "r"(a1), "r"(b0)); }
__device__ __forceinline__ void ldsm4(uint32_t* r, uint32_t a) {
  asm volatile("ldmatrix.sync.aligned.m8n8.x4.shared.b16 {%0,%1,%2,%3},[%4];" : "=r"(r[0]), "=r"(r[1]), "=r"(r[2]), "=r"(r[3]) : "r"(a) : "memory"); }
__device__ __forceinline__ uint4 ldsm4v(uint32_t a) { uint32_t r[4]; ldsm4(r, a); return make_uint4(r[0], r[1], r[2], r[3]); }
__device__ __forceinline__ void ldsm4t(uint32_t* r, uint32_t a) {
  asm volatile("ldmatrix.sync.aligned.m8n8.x4.trans.shared.b16 {%0,%1,%2,%3},[%4];" : "=r"(r[0]), "=r"(r[1]), "=r"(r[2]), "=r"(r[3]) : "r"(a) : "memory"); }
__device__ __forceinline__ void ldsm2t(uint32_t* r, uint32_t a) {
  asm volatile("ldmatrix.sync.aligned.m8n8.x2.trans.shared.b16 {%0,%1},[%2];" : "=r"(r[0]), "=r"(r[1]) : "r"(a) : "memory"); }
__device__ __forceinline__ void stsm4(uint32_t a, uint32_t r0, uint32_t r1, uint32_t r2, uint32_t r3) {
  asm volatile("stmatrix.sync.aligned.m8n8.x4.shared.b16 [%0], {%1,%2,%3,%4};" :: "r"(a), "r"(r0), "r"(r1), "r"(r2), "r"(r3) : "memory"); }
__device__ __forceinline__ void stsm4t(uint32_t a, uint32_t r0, uint32_t r1, uint32_t r2, uint32_t r3) {
  asm volatile("stmatrix.sync.aligned.m8n8.x4.trans.shared.b16 [%0], {%1,%2,%3,%4};" :: "r"(a), "r"(r0), "r"(r1), "r"(r2), "r"(r3) : "memory"); }
__device__ __forceinline__ void stsm2(uint32_t a, uint32_t r0, uint32_t r1) {
  asm volatile("stmatrix.sync.aligned.m8n8.x2.shared.b16 [%0], {%1,%2};" :: "r"(a), "r"(r0), "r"(r1) : "memory"); }
__device__ __forceinline__ void stsm2t(uint32_t a, uint32_t r0, uint32_t r1) {
  asm volatile("stmatrix.sync.aligned.m8n8.x2.trans.shared.b16 [%0], {%1,%2};" :: "r"(a), "r"(r0), "r"(r1) : "memory"); }
__device__ __forceinline__ void sts32(uint32_t a, uint32_t v) { asm volatile("st.shared.b32 [%0], %1;" :: "r"(a), "r"(v) : "memory"); }
__device__ __forceinline__ void sts64f(uint32_t a, float x, float y) { asm volatile("st.shared.v2.f32 [%0], {%1,%2};" :: "r"(a), "f"(x), "f"(y) : "memory"); }
__device__ __forceinline__ void sts128(uint32_t a, uint4 v) {
  asm volatile("st.shared.v4.b32 [%0], {%1,%2,%3,%4};" :: "r"(a), "r"(v.x), "r"(v.y), "r"(v.z), "r"(v.w) : "memory"); }
__device__ __forceinline__ void sts128f(uint32_t a, float x, float y, float z, float w) {
  asm volatile("st.shared.v4.f32 [%0], {%1,%2,%3,%4};" :: "r"(a), "f"(x), "f"(y), "f"(z), "f"(w) : "memory"); }
__device__ __forceinline__ float lds32f(uint32_t a) { float v; asm volatile("ld.shared.f32 %0, [%1];" : "=f"(v) : "r"(a) : "memory"); return v; }
__device__ __forceinline__ float2 lds64f(uint32_t a) { float2 v; asm volatile("ld.shared.v2.f32 {%0,%1}, [%2];" : "=f"(v.x), "=f"(v.y) : "r"(a) : "memory"); return v; }
__device__ __forceinline__ float4 lds128f(uint32_t a) {
  float4 v; asm volatile("ld.shared.v4.f32 {%0,%1,%2,%3}, [%4];" : "=f"(v.x), "=f"(v.y), "=f"(v.z), "=f"(v.w) : "r"(a) : "memory"); return v; }
__device__ __forceinline__ uint4 lds128(uint32_t a) {
  uint4 v; asm volatile("ld.shared.v4.b32 {%0,%1,%2,%3}, [%4];" : "=r"(v.x), "=r"(v.y), "=r"(v.z), "=r"(v.w) : "r"(a) : "memory"); return v; }
__device__ __forceinline__ uint4 ldg_strong128(const void* p) {
  uint4 v; asm volatile("ld.relaxed.gpu.global.v4.u32 {%0,%1,%2,%3}, [%4];" : "=r"(v.x), "=r"(v.y), "=r"(v.z), "=r"(v.w) : "l"(p) : "memory"); return v; }
__device__ __forceinline__ uint2 ldg_strong64(const void* p) {
  uint2 v; asm volatile("ld.relaxed.gpu.global.v2.u32 {%0,%1}, [%2];" : "=r"(v.x), "=r"(v.y) : "l"(p) : "memory"); return v; }
__device__ __forceinline__ void stg_strong32(void* p, uint32_t v) { asm volatile("st.relaxed.gpu.global.u32 [%0], %1;" :: "l"(p), "r"(v) : "memory"); }
__device__ __forceinline__ void stg_strong128(void* p, uint4 v) {
  asm volatile("st.relaxed.gpu.global.v4.u32 [%0], {%1,%2,%3,%4};" :: "l"(p), "r"(v.x), "r"(v.y), "r"(v.z), "r"(v.w) : "memory"); }
__device__ __forceinline__ uint32_t mapa(uint32_t a, uint32_t r) {
  uint32_t o; asm("mapa.shared::cluster.u32 %0, %1, %2;" : "=r"(o) : "r"(a), "r"(r)); return o; }
__device__ __forceinline__ void st_async2f(uint32_t a, float x, float y, uint32_t bar) {
  asm volatile("st.async.shared::cluster.mbarrier::complete_tx::bytes.v2.f32 [%0], {%1,%2}, [%3];" :: "r"(a), "f"(x), "f"(y), "r"(bar) : "memory"); }
__device__ __forceinline__ void st_async32(uint32_t a, uint32_t x, uint32_t bar) {
  asm volatile("st.async.shared::cluster.mbarrier::complete_tx::bytes.b32 [%0], %1, [%2];" :: "r"(a), "r"(x), "r"(bar) : "memory"); }
__device__ __forceinline__ uint32_t lds32(uint32_t a) { uint32_t v; asm volatile("ld.shared.b32 %0, [%1];" : "=r"(v) : "r"(a) : "memory"); return v; }
__device__ __forceinline__ void st_async64(uint32_t a, uint32_t x, uint32_t y, uint32_t bar) {
  asm volatile("st.async.shared::cluster.mbarrier::complete_tx::bytes.v2.b32 [%0], {%1,%2}, [%3];" :: "r"(a), "r"(x), "r"(y), "r"(bar) : "memory"); }
__device__ __forceinline__ void st_async128(uint32_t a, uint4 v, uint32_t bar) {
  asm volatile("st.async.shared::cluster.mbarrier::complete_tx::bytes.v4.b32 [%0], {%1,%2,%3,%4}, [%5];" :: "r"(a), "r"(v.x), "r"(v.y), "r"(v.z), "r"(v.w), "r"(bar) : "memory"); }
__device__ __forceinline__ uint2 lds64(uint32_t a) { uint2 v; asm volatile("ld.shared.v2.b32 {%0,%1}, [%2];" : "=r"(v.x), "=r"(v.y) : "r"(a) : "memory"); return v; }
__device__ __forceinline__ void sts64(uint32_t a, uint32_t x, uint32_t y) { asm volatile("st.shared.v2.b32 [%0], {%1,%2};" :: "r"(a), "r"(x), "r"(y) : "memory"); }
__device__ __forceinline__ uint32_t ldg_strong32(const void* p) { uint32_t v; asm volatile("ld.relaxed.gpu.global.u32 %0, [%1];" : "=r"(v) : "l"(p) : "memory"); return v; }
__device__ __forceinline__ uint32_t transpose8(uint32_t x) { uint32_t r; asm volatile("movmatrix.sync.aligned.m8n8.trans.b16 %0, %1;" : "=r"(r) : "r"(x)); return r; }
__device__ __forceinline__ uint32_t hadd2(uint32_t a, uint32_t b) { uint32_t r; asm("add.rn.bf16x2 %0, %1, %2;" : "=r"(r) : "r"(a), "r"(b)); return r; }
__device__ __forceinline__ uint32_t min4(uint4 v) { return min(__vimin3_u32(v.x, v.y, v.z), v.w); }

__device__ __forceinline__ void wg_ss192_01(float* d, uint64_t da, uint64_t db, int sd) {
  asm volatile("{.reg .pred p; setp.ne.b32 p, %98, 0;\n"
    "wgmma.mma_async.sync.aligned.m64n192k16.f32.bf16.bf16 {%0,%1,%2,%3,%4,%5,%6,%7,%8,%9,%10,%11,%12,%13,%14,%15,%16,%17,%18,%19,%20,%21,%22,%23,%24,%25,%26,%27,%28,%29,%30,%31,%32,%33,%34,%35,%36,%37,%38,%39,%40,%41,%42,%43,%44,%45,%46,%47,%48,%49,%50,%51,%52,%53,%54,%55,%56,%57,%58,%59,%60,%61,%62,%63,%64,%65,%66,%67,%68,%69,%70,%71,%72,%73,%74,%75,%76,%77,%78,%79,%80,%81,%82,%83,%84,%85,%86,%87,%88,%89,%90,%91,%92,%93,%94,%95}, %96, %97, p, 1, 1, 0, 1;}"
    : "+f"(d[0]),"+f"(d[1]),"+f"(d[2]),"+f"(d[3]),"+f"(d[4]),"+f"(d[5]),"+f"(d[6]),"+f"(d[7]),"+f"(d[8]),"+f"(d[9]),"+f"(d[10]),"+f"(d[11]),"+f"(d[12]),"+f"(d[13]),"+f"(d[14]),"+f"(d[15]),"+f"(d[16]),"+f"(d[17]),"+f"(d[18]),"+f"(d[19]),"+f"(d[20]),"+f"(d[21]),"+f"(d[22]),"+f"(d[23]),"+f"(d[24]),"+f"(d[25]),"+f"(d[26]),"+f"(d[27]),"+f"(d[28]),"+f"(d[29]),"+f"(d[30]),"+f"(d[31]),"+f"(d[32]),"+f"(d[33]),"+f"(d[34]),"+f"(d[35]),"+f"(d[36]),"+f"(d[37]),"+f"(d[38]),"+f"(d[39]),"+f"(d[40]),"+f"(d[41]),"+f"(d[42]),"+f"(d[43]),"+f"(d[44]),"+f"(d[45]),"+f"(d[46]),"+f"(d[47]),"+f"(d[48]),"+f"(d[49]),"+f"(d[50]),"+f"(d[51]),"+f"(d[52]),"+f"(d[53]),"+f"(d[54]),"+f"(d[55]),"+f"(d[56]),"+f"(d[57]),"+f"(d[58]),"+f"(d[59]),"+f"(d[60]),"+f"(d[61]),"+f"(d[62]),"+f"(d[63]),"+f"(d[64]),"+f"(d[65]),"+f"(d[66]),"+f"(d[67]),"+f"(d[68]),"+f"(d[69]),"+f"(d[70]),"+f"(d[71]),"+f"(d[72]),"+f"(d[73]),"+f"(d[74]),"+f"(d[75]),"+f"(d[76]),"+f"(d[77]),"+f"(d[78]),"+f"(d[79]),"+f"(d[80]),"+f"(d[81]),"+f"(d[82]),"+f"(d[83]),"+f"(d[84]),"+f"(d[85]),"+f"(d[86]),"+f"(d[87]),"+f"(d[88]),"+f"(d[89]),"+f"(d[90]),"+f"(d[91]),"+f"(d[92]),"+f"(d[93]),"+f"(d[94]),"+f"(d[95])
    : "l"(da), "l"(db), "r"(sd));
}
__device__ __forceinline__ void wg_ss128_01(float* d, uint64_t da, uint64_t db, int sd) {
  asm volatile("{.reg .pred p; setp.ne.b32 p, %66, 0;\n"
    "wgmma.mma_async.sync.aligned.m64n128k16.f32.bf16.bf16 {%0,%1,%2,%3,%4,%5,%6,%7,%8,%9,%10,%11,%12,%13,%14,%15,%16,%17,%18,%19,%20,%21,%22,%23,%24,%25,%26,%27,%28,%29,%30,%31,%32,%33,%34,%35,%36,%37,%38,%39,%40,%41,%42,%43,%44,%45,%46,%47,%48,%49,%50,%51,%52,%53,%54,%55,%56,%57,%58,%59,%60,%61,%62,%63}, %64, %65, p, 1, 1, 0, 1;}"
    : "+f"(d[0]),"+f"(d[1]),"+f"(d[2]),"+f"(d[3]),"+f"(d[4]),"+f"(d[5]),"+f"(d[6]),"+f"(d[7]),"+f"(d[8]),"+f"(d[9]),"+f"(d[10]),"+f"(d[11]),"+f"(d[12]),"+f"(d[13]),"+f"(d[14]),"+f"(d[15]),"+f"(d[16]),"+f"(d[17]),"+f"(d[18]),"+f"(d[19]),"+f"(d[20]),"+f"(d[21]),"+f"(d[22]),"+f"(d[23]),"+f"(d[24]),"+f"(d[25]),"+f"(d[26]),"+f"(d[27]),"+f"(d[28]),"+f"(d[29]),"+f"(d[30]),"+f"(d[31]),"+f"(d[32]),"+f"(d[33]),"+f"(d[34]),"+f"(d[35]),"+f"(d[36]),"+f"(d[37]),"+f"(d[38]),"+f"(d[39]),"+f"(d[40]),"+f"(d[41]),"+f"(d[42]),"+f"(d[43]),"+f"(d[44]),"+f"(d[45]),"+f"(d[46]),"+f"(d[47]),"+f"(d[48]),"+f"(d[49]),"+f"(d[50]),"+f"(d[51]),"+f"(d[52]),"+f"(d[53]),"+f"(d[54]),"+f"(d[55]),"+f"(d[56]),"+f"(d[57]),"+f"(d[58]),"+f"(d[59]),"+f"(d[60]),"+f"(d[61]),"+f"(d[62]),"+f"(d[63])
    : "l"(da), "l"(db), "r"(sd));
}
__device__ __forceinline__ void wg_ss160_01(float* d, uint64_t da, uint64_t db, int sd) {
  asm volatile("{.reg .pred p; setp.ne.b32 p, %82, 0;\n"
    "wgmma.mma_async.sync.aligned.m64n160k16.f32.bf16.bf16 {%0,%1,%2,%3,%4,%5,%6,%7,%8,%9,%10,%11,%12,%13,%14,%15,%16,%17,%18,%19,%20,%21,%22,%23,%24,%25,%26,%27,%28,%29,%30,%31,%32,%33,%34,%35,%36,%37,%38,%39,%40,%41,%42,%43,%44,%45,%46,%47,%48,%49,%50,%51,%52,%53,%54,%55,%56,%57,%58,%59,%60,%61,%62,%63,%64,%65,%66,%67,%68,%69,%70,%71,%72,%73,%74,%75,%76,%77,%78,%79}, %80, %81, p, 1, 1, 0, 1;}"
    : "+f"(d[0]),"+f"(d[1]),"+f"(d[2]),"+f"(d[3]),"+f"(d[4]),"+f"(d[5]),"+f"(d[6]),"+f"(d[7]),"+f"(d[8]),"+f"(d[9]),"+f"(d[10]),"+f"(d[11]),"+f"(d[12]),"+f"(d[13]),"+f"(d[14]),"+f"(d[15]),"+f"(d[16]),"+f"(d[17]),"+f"(d[18]),"+f"(d[19]),"+f"(d[20]),"+f"(d[21]),"+f"(d[22]),"+f"(d[23]),"+f"(d[24]),"+f"(d[25]),"+f"(d[26]),"+f"(d[27]),"+f"(d[28]),"+f"(d[29]),"+f"(d[30]),"+f"(d[31]),"+f"(d[32]),"+f"(d[33]),"+f"(d[34]),"+f"(d[35]),"+f"(d[36]),"+f"(d[37]),"+f"(d[38]),"+f"(d[39]),"+f"(d[40]),"+f"(d[41]),"+f"(d[42]),"+f"(d[43]),"+f"(d[44]),"+f"(d[45]),"+f"(d[46]),"+f"(d[47]),"+f"(d[48]),"+f"(d[49]),"+f"(d[50]),"+f"(d[51]),"+f"(d[52]),"+f"(d[53]),"+f"(d[54]),"+f"(d[55]),"+f"(d[56]),"+f"(d[57]),"+f"(d[58]),"+f"(d[59]),"+f"(d[60]),"+f"(d[61]),"+f"(d[62]),"+f"(d[63]),"+f"(d[64]),"+f"(d[65]),"+f"(d[66]),"+f"(d[67]),"+f"(d[68]),"+f"(d[69]),"+f"(d[70]),"+f"(d[71]),"+f"(d[72]),"+f"(d[73]),"+f"(d[74]),"+f"(d[75]),"+f"(d[76]),"+f"(d[77]),"+f"(d[78]),"+f"(d[79])
    : "l"(da), "l"(db), "r"(sd));
}
__device__ __forceinline__ void wg_ss80_01(float* d, uint64_t da, uint64_t db, int sd) {
  asm volatile("{.reg .pred p; setp.ne.b32 p, %42, 0;\n"
    "wgmma.mma_async.sync.aligned.m64n80k16.f32.bf16.bf16 {%0,%1,%2,%3,%4,%5,%6,%7,%8,%9,%10,%11,%12,%13,%14,%15,%16,%17,%18,%19,%20,%21,%22,%23,%24,%25,%26,%27,%28,%29,%30,%31,%32,%33,%34,%35,%36,%37,%38,%39}, %40, %41, p, 1, 1, 0, 1;}"
    : "+f"(d[0]),"+f"(d[1]),"+f"(d[2]),"+f"(d[3]),"+f"(d[4]),"+f"(d[5]),"+f"(d[6]),"+f"(d[7]),"+f"(d[8]),"+f"(d[9]),"+f"(d[10]),"+f"(d[11]),"+f"(d[12]),"+f"(d[13]),"+f"(d[14]),"+f"(d[15]),"+f"(d[16]),"+f"(d[17]),"+f"(d[18]),"+f"(d[19]),"+f"(d[20]),"+f"(d[21]),"+f"(d[22]),"+f"(d[23]),"+f"(d[24]),"+f"(d[25]),"+f"(d[26]),"+f"(d[27]),"+f"(d[28]),"+f"(d[29]),"+f"(d[30]),"+f"(d[31]),"+f"(d[32]),"+f"(d[33]),"+f"(d[34]),"+f"(d[35]),"+f"(d[36]),"+f"(d[37]),"+f"(d[38]),"+f"(d[39])
    : "l"(da), "l"(db), "r"(sd));
}
__device__ __forceinline__ void wg_rs32_00(float* d, uint32_t a0, uint32_t a1, uint32_t a2, uint32_t a3, uint64_t db, int sd) {
  asm volatile("{.reg .pred p; setp.ne.b32 p, %21, 0;\n"
    "wgmma.mma_async.sync.aligned.m64n32k16.f32.bf16.bf16 {%0,%1,%2,%3,%4,%5,%6,%7,%8,%9,%10,%11,%12,%13,%14,%15}, {%16,%17,%18,%19}, %20, p, 1, 1, 0;}"
    : "+f"(d[0]),"+f"(d[1]),"+f"(d[2]),"+f"(d[3]),"+f"(d[4]),"+f"(d[5]),"+f"(d[6]),"+f"(d[7]),"+f"(d[8]),"+f"(d[9]),"+f"(d[10]),"+f"(d[11]),"+f"(d[12]),"+f"(d[13]),"+f"(d[14]),"+f"(d[15])
    : "r"(a0), "r"(a1), "r"(a2), "r"(a3), "l"(db), "r"(sd));
}
__device__ __forceinline__ void wg_rs64_00(float* d, uint32_t a0, uint32_t a1, uint32_t a2, uint32_t a3, uint64_t db, int sd) {
  asm volatile("{.reg .pred p; setp.ne.b32 p, %37, 0;\n"
    "wgmma.mma_async.sync.aligned.m64n64k16.f32.bf16.bf16 {%0,%1,%2,%3,%4,%5,%6,%7,%8,%9,%10,%11,%12,%13,%14,%15,%16,%17,%18,%19,%20,%21,%22,%23,%24,%25,%26,%27,%28,%29,%30,%31}, {%32,%33,%34,%35}, %36, p, 1, 1, 0;}"
    : "+f"(d[0]),"+f"(d[1]),"+f"(d[2]),"+f"(d[3]),"+f"(d[4]),"+f"(d[5]),"+f"(d[6]),"+f"(d[7]),"+f"(d[8]),"+f"(d[9]),"+f"(d[10]),"+f"(d[11]),"+f"(d[12]),"+f"(d[13]),"+f"(d[14]),"+f"(d[15]),"+f"(d[16]),"+f"(d[17]),"+f"(d[18]),"+f"(d[19]),"+f"(d[20]),"+f"(d[21]),"+f"(d[22]),"+f"(d[23]),"+f"(d[24]),"+f"(d[25]),"+f"(d[26]),"+f"(d[27]),"+f"(d[28]),"+f"(d[29]),"+f"(d[30]),"+f"(d[31])
    : "r"(a0), "r"(a1), "r"(a2), "r"(a3), "l"(db), "r"(sd));
}
__device__ __forceinline__ void wg_rs24_01(float* d, uint32_t a0, uint32_t a1, uint32_t a2, uint32_t a3, uint64_t db, int sd) {
  asm volatile("{.reg .pred p; setp.ne.b32 p, %17, 0;\n"
    "wgmma.mma_async.sync.aligned.m64n24k16.f32.bf16.bf16 {%0,%1,%2,%3,%4,%5,%6,%7,%8,%9,%10,%11}, {%12,%13,%14,%15}, %16, p, 1, 1, 1;}"
    : "+f"(d[0]),"+f"(d[1]),"+f"(d[2]),"+f"(d[3]),"+f"(d[4]),"+f"(d[5]),"+f"(d[6]),"+f"(d[7]),"+f"(d[8]),"+f"(d[9]),"+f"(d[10]),"+f"(d[11])
    : "r"(a0), "r"(a1), "r"(a2), "r"(a3), "l"(db), "r"(sd));
}

#define AB_POLY 0x77
__device__ __forceinline__ constexpr bool poly_group(int group) { return (AB_POLY >> (group & 7)) & 1; }

template <int V> struct Int { static constexpr int value = V; };

__device__ __forceinline__ int core_word(int row, int col) {
  return ((((row >> 7) * 10 + (col >> 6)) * 16 + ((row >> 3) & 15)) * 8 + ((col >> 3) & 7)) * 32 + (row & 7) * 4 + ((col & 7) >> 1);
}
__device__ __forceinline__ void wait_count(const uint32_t* c, uint32_t n) {
  for (int spin = 0; !__all_sync(~0u, (ld_acquire(c) & 0xffff) >= n);) { __nanosleep(32); spin_guard(spin); }
  fence_async_global();
}
__device__ __forceinline__ void prefetch_l2(const void* p, uint32_t bytes) {
  asm volatile("cp.async.bulk.prefetch.L2.global [%0], %1;" :: "l"(p), "r"(bytes) : "memory"); }

#define PLACE 4
__device__ __forceinline__ bool helper_sm() {
  uint32_t m; asm volatile("mov.u32 %0, %%smid;" : "=r"(m));
  return m < 2 || m >= 120 || (m >= 92 && m < 102) || (m >= 106 && m < 117) || m == 118;
}

__device__ __forceinline__ uint8_t* pool_at(uint32_t off) {
  return reinterpret_cast<uint8_t*>((reinterpret_cast<uintptr_t>(g_pool) + 8191) & ~(uintptr_t)8191) + off; }
__device__ __forceinline__ void probe_slots(uint32_t scratch) {
  const int w = (threadIdx.x >> 6) & 1, slot = w == 0 ? NSLOT : blockIdx.x;
  if (w == 0 || slot < NSLOT) {
    uint32_t* q = reinterpret_cast<uint32_t*>(pool_at(slot * 8192)) + (w == 0 ? (blockIdx.x & 31) * 32 + (blockIdx.x >> 5) : 0);
    uint32_t best[2] = {~0u, ~0u};
    const bool one = elect();
    if (one) { stg_strong32(q, 0u); stg_strong32(q + 1024, 0u); }
#pragma unroll 1
    for (int r = 0; r < 8; r++) {
      uint32_t v = 0;
      const uint32_t t0 = clk32();
      if (one) asm volatile("atom.relaxed.gpu.global.exch.b32 %0, [%1], 0;" : "=r"(v) : "l"(q + (r & 1) * 1024) : "memory");
      if (__any_sync(~0u, v != 0)) break;
      const uint32_t t = min(clk32() - t0, best[0]);
      best[0] = best[1]; best[1] = t;
    }
    if (one) sts32(scratch + w * 4, best[0] < best[1]);
  }
  bar_sync(2, 64);
  if ((threadIdx.x & 31) == 0) {
    const int part = lds32(scratch) ? 1 : 2;
    if (w == 0) { uint32_t smid; asm("mov.u32 %0, %%smid;" : "=r"(smid)); stg_strong32(g_smpart + (smid & 255), part); }
    else if (slot < NSLOT) stg_strong32(g_orient + slot, lds32(scratch + 4) ? part : 3 - part);
  }
  __syncwarp();
}

constexpr int WK_SLOTS = 28, WK_BAR = WK_SLOTS * 8192;
__device__ __forceinline__ void work_init(uint32_t sb, int w) {
  if (elect()) {
#pragma unroll
    for (int i = 0; i < 8; i++) mbar_init(sb + WK_BAR + 64 * w + 8 * i, 0x18318822 >> (8 * w + (i & 4)) & 15);
  }
  asm volatile("fence.mbarrier_init.release.cluster;" ::: "memory");
}

struct ChainParams {
  CUtensorMap wq, wk, wv, wo, xc;
  const __nv_bfloat16* mem0;
  const uint8_t* wb;
  uint32_t *sync, *other;
  int layer;
  int d1, d2, dn, dx, mode, zero;
};
constexpr int CH_WQ = 0, CH_WO = 81920, CH_X = CH_WO + 86016, CH_M = CH_X, CH_Q = CH_X + 34816, CH_KM = CH_Q + 2048, CH_VP = CH_KM + 2048,
              CH_K = CH_X + 40960, CH_O = CH_K, CH_KS = CH_K + 3072, CH_V = CH_K + 4096, CH_VX = CH_V + 12288, CH_R2 = CH_VX,
              CH_SX = CH_VX + 3072, CH_SO = CH_SX + 2048, CH_ID = CH_SO + 1024, CH_L = CH_ID + 256, CH_TAB = CH_L + 64, CH_BAR = CH_TAB + 384;
constexpr int CH_SMEM = CH_BAR + 144;
constexpr int MB_WO = CH_BAR, MB_WQ = CH_BAR + 8, MB_X = CH_BAR + 16, MB_V = CH_BAR + 24, MB_T = CH_BAR + 32, MB_F = CH_BAR + 40, MB_G = CH_BAR + 48, MB_W = CH_BAR + 56;
enum { NB_PROJ = 1, NB_O = 2, NB_W1 = 3, NB_PRE = 4, NB_ST = 5, NB_MEM = 6, NB_XFREE = 7, NB_H1 = 8, NB_PUB = 9, NB_W2 = 10, NB_PROJ2 = 11, NB_PRE2 = 12, NB_H2 = 13, NB_W1V = 14 };
#define CH_NQ 9
#define CH_XPF 1
#define CH_TPF 1
#define CH_FLY 6
#define CH_TW 1
#define CH_NQ0 4
#define CH_PA 6
#define CH_PB 9
#define CH_PC 13
#define CH_PL 4
#define CH_DBL 0x0888
#define CH_PD 1
#define SCHED() asm volatile("griddepcontrol.launch_dependents;" ::: "memory")
__device__ __forceinline__ uint32_t opaque(uint32_t x) { return __shfl_sync(~0u, x, threadIdx.x & 31); }
__device__ __forceinline__ uint32_t uniform(uint32_t x) { return __shfl_sync(~0u, x, 0); }
__device__ __forceinline__ uint32_t nz(uint32_t x) { uint32_t r; asm("max.u32 %0, %1, 1;" : "=r"(r) : "r"(x)); return r; }
__device__ __forceinline__ uint32_t set_tag(uint32_t w, uint32_t tag) { uint32_t r; asm("lop3.b32 %0, %1, %2, 1, 0xD8;" : "=r"(r) : "r"(w), "r"(tag)); return r; }
__device__ __forceinline__ uint32_t pack_tag(float lo, float hi, uint32_t tag) { return set_tag(__byte_perm(__float_as_uint(lo) + tag, pack2(hi, hi), 0x7632), tag); }
__device__ __forceinline__ uint32_t differ(uint32_t a, uint32_t b, uint32_t t) { uint32_t r; asm("lop3.b32 %0, %1, %2, %3, 0x7E;" : "=r"(r) : "r"(a), "r"(b), "r"(t)); return r; }
__device__ __forceinline__ uint32_t clk64() { uint64_t c; asm volatile("mov.u64 %0, %%clock64;" : "=l"(c) :: "memory"); return (uint32_t)c; }
__device__ __forceinline__ void until(uint32_t t) {
  asm volatile("{.reg .pred p; .reg .u64 c; .reg .s32 d;\nW: mov.u64 c, %%clock64; cvt.u32.u64 d, c; sub.s32 d, d, %0; setp.lt.s32 p, d, 0; @p bra.uni W;}" :: "r"(t) : "memory");
}
__device__ __forceinline__ float rcp(float x) { float y; asm("rcp.approx.ftz.f32 %0, %1;" : "=f"(y) : "f"(x)); return y; }

__device__ __forceinline__ void chain_compute(const ChainParams& p, const uint32_t sb) {
  const int tid = threadIdx.x & 127, WG = __shfl_sync(~0u, threadIdx.x >> 7, 0), t4 = __shfl_sync(~0u, tid >> 5, 0), lane = tid & 31;
  const int cta = blockIdx.x, h = cta / 3, j = cta - 3 * h;
  uint32_t a0[80], a1[80], tw[4 * CH_NQ];
  const uint32_t wq = opaque(sb + CH_WQ + (WG * 320 + (lane & 7) + (lane >> 4) * 8) * 128 + (((2 * t4 + ((lane >> 3) & 1)) ^ (lane & 7)) << 4));
#pragma unroll
  for (int k = 0; k < 40; k++) {
    if (k % 10 == 0) mbar_wait(sb + MB_W + WG * 8 + k / 10 * 16, 0);
    if (k < 20) ldsm4t(&a0[4 * k], wq + k * 2048); else ldsm4t(&a1[4 * k - 80], wq + CH_WO + (k - 20) * 2048);
    if (k % 20 == 19) bar_arrive(k < 20 ? NB_PROJ2 : NB_PRE2, 288);
  }
  const int r1 = j == 2 ? 0 : j + 1, r2 = j == 0 ? 2 : j - 1;
  const uint32_t l16 = opaque(sb + lane * 16), l8 = opaque(sb + lane * 8), l4 = opaque(sb + lane * 4);
  const uint32_t t16 = l16 + t4 * 512, t8 = l8 + t4 * 256;
  uint32_t wo = opaque(sb + CH_WO + (WG == 0 ? (t4 >> 1) * 36864 : 73728 + t4 * 1024) + ((lane & 7) + (lane >> 4) * 8) * 64 +
                       (((((lane >> 3) & 1) + (WG == 0 ? (t4 & 1) * 2 : 0)) ^ ((lane >> 1) & 3)) << 4));
  const uint32_t ko0 = uniform(CH_K + (tid >> 6) * 3072 + (tid & 32) * 8), ko1 = uniform(CH_K + (tid >> 6) * 1024 + 1024 + (tid & 32) * 8),
                 o768 = uniform((tid >> 5) * 768);
  const uint32_t give = uniform(t4 * 512 + (WG == 0 ? CH_K : CH_V + j * 4096)), own = uniform(t4 * 512 + (WG == 0 ? CH_V + j * 4096 : CH_K)), mem = uniform(CH_M + WG * 5120);
  const uint32_t vxo = uniform(t4 * 256 + CH_VX + j * 1024);
  uint32_t tag = 1, xd = uniform((1024 + CH_X + WG * 20480) >> 4 | 8 << 16);
  asm volatile("barrier.cluster.wait.aligned;" ::: "memory");
  mbar_wait(sb + MB_WQ, 0);
  mbar_wait(sb + MB_T, 0);
  bar_sync(NB_ST, 384);
  uint8_t* pdst[6];
#pragma unroll
  for (int i = 0; i < 6; i++) {
    const int line = WG == 0 ? 24 * j + 12 * (t4 >> 1) + 2 * (t4 & 1) + 4 * (i >> 1) + (i & 1) : j == 0 ? 72 + t4 : 74 + 2 * j + (t4 & 1);
    pdst[i] = pool_at(uniform(lds32(sb + CH_TAB + line * 4)) + h * 128);
  }
  auto batch = [&](float* d, const uint32_t (&a)[80], int acc, int n0, int n1) {
    const uint32_t d0 = xd ^ (tag & (2 << acc));
    wg_fence();
#pragma unroll
    for (int k = 0; k < 20; k++) {
      if (!(k & 3) && n0 + k / 4 < n1) {
        __syncwarp();
        ldsm4t(&tw[4 * n0 + k], wq + (n0 + k / 4) * 2048);
        __syncwarp();
      }
      uint64_t db;
      asm("mov.b64 %0, {%1, %2};" : "=l"(db) : "r"(d0 + k / 5 * 320 + k % 5 * 16), "r"(80));
      wg_rs32_00(d, a[4 * k], a[4 * k + 1], a[4 * k + 2], a[4 * k + 3], db, acc | k);
    }
    wg_commit();
    wg_wait<0>();
    reg_fence<16>(d);
  };
  int s = 0;
#pragma unroll 1
  do {
    {
      float d[16];
      if (!CH_TW) mbar_wait(sb + MB_T, s & 1);
      batch(d, a0, 0, 0, CH_NQ0);
      s--; TM(10); s++;
      mbar_wait(sb + MB_F, ~s & 1);
#pragma unroll
      for (int i = 0; i < 2; i++)
        sts128(l16 + give + i * 2048, make_uint4(pack2(d[8 * i], d[8 * i + 1]), pack2(d[8 * i + 2], d[8 * i + 3]), pack2(d[8 * i + 4], d[8 * i + 5]), pack2(d[8 * i + 6], d[8 * i + 7])));
      bar_sync(NB_PUB, 384);
#pragma unroll
      for (int i = 0; i < 2; i++) {
        const uint4 t = lds128(l16 + own + i * 2048);
        d[8 * i] = bf_lo(t.x); d[8 * i + 1] = bf_hi(t.x); d[8 * i + 2] = bf_lo(t.y); d[8 * i + 3] = bf_hi(t.y);
        d[8 * i + 4] = bf_lo(t.z); d[8 * i + 5] = bf_hi(t.z); d[8 * i + 6] = bf_lo(t.w); d[8 * i + 7] = bf_hi(t.w);
      }
      reg_fence<16>(d);
      batch(d, a1, 1, CH_NQ0, CH_NQ);
      s--; TM(11); s++;
      if (WG == 0) bar_arrive(NB_XFREE, 256);
#pragma unroll
      for (int i = 0; i < 8; i++) sts32(l4 + own + (i >> 2) * 2048 + (i & 3) * 128, pack2(d[2 * i], d[2 * i + 1]));
      s--; TM(9); s++;
    }
    float dq[4] = {}, d0[4] = {}, d1[4] = {};
    uint32_t b[40], wf[80];
    const uint32_t* kf = &wf[52];
#pragma unroll
    for (int i = 0; i < 4 * CH_NQ; i++) wf[i] = tw[i];
    auto step = [&](int k) {
      mma16(dq, wf[4 * k], wf[4 * k + 1], wf[4 * k + 2], wf[4 * k + 3], b[2 * k], b[2 * k + 1]);
      mma16(d0, a0[4 * k], a0[4 * k + 1], a0[4 * k + 2], a0[4 * k + 3], b[2 * k], b[2 * k + 1]);
      mma16(d1, a1[4 * k], a1[4 * k + 1], a1[4 * k + 2], a1[4 * k + 3], b[2 * k], b[2 * k + 1]);
    };
    auto finish = [&](int wg, const float* dk) {
      const float k2 = 0.07216878364870322f * 1.44269504089f;
      sts32(l4 + t4 * 512 + CH_Q + wg * 128, pack2(dq[0] * k2, dq[1] * k2));
      sts32(l4 + t4 * 512 + CH_Q + wg * 128 + 256, pack2(dq[2] * k2, dq[3] * k2));
      sts32(l4 + t4 * 512 + CH_KM + wg * 256, pack2(dk[0], dk[1]));
      sts32(l4 + t4 * 512 + CH_KM + wg * 256 + 128, pack2(dk[2], dk[3]));
    };
    const bool more = s < NSEG - 1;
    bar_sync(NB_MEM, 384);
    ldsm4t(&b[0], l16 + mem);
    ldsm4t(&b[4], l16 + mem + 512);
    TMD(0, b[0]);
    {
      int nw = CH_NQ, nb = 2;
#pragma unroll
      for (int k = 0; k < 20; k++) {
        SCHED();
        step(k);
#pragma unroll
        for (int i = 0; i < (CH_DBL >> k & 1) + 1; i++) {
          if (nb < 10 && 2 * nb <= nw) { ldsm4t(&b[4 * nb], l16 + mem + nb * 512); nb++; }
          else if (nw < 20) { ldsm4t(&wf[4 * nw], wq + nw * 2048); nw++; }
          else if (nw < 22) {
            const uint32_t x = l16 ^ ((ko0 ^ tag) & 256);
            uint32_t* r = &wf[4 * nw - 28];
            asm volatile("{.reg .pred p; setp.ne.u32 p, %5, 0; @p ldmatrix.sync.aligned.m8n8.x4.trans.shared.b16 {%0,%1,%2,%3},[%4];}"
                         : "+r"(r[0]), "+r"(r[1]), "+r"(r[2]), "+r"(r[3]) : "r"(x + (x & 256) + (nw == 20 ? ko0 : ko1)), "r"(WG) : "memory");
            nw++;
          }
        }
      }
      SCHED();
    }
    if (WG == 0) {
      finish(0, d0);
      TM(1);
      bar_sync(NB_PROJ, 256);
      if (!more) {
        const float4 pv = lds128f(t16 + CH_VP);
        sts64(l8 + vxo, pack2(d1[0] + pv.x, d1[1] + pv.y), pack2(d1[2] + pv.z, d1[3] + pv.w));
        continue;
      }
      const float4 pv = lds128f(t16 + CH_VP);
      const uint32_t xo = l8 + (vxo ^ (tag & 2)), x1 = mapa(xo, r1), x2 = mapa(xo, r2);
      SCHED();
      const uint32_t v0 = pack2(d1[0] + pv.x, d1[1] + pv.y), v1 = pack2(d1[2] + pv.z, d1[3] + pv.w);
      st_async64(x1, v0, v1, mapa(sb + MB_X, r1));
      st_async64(x2, v0, v1, mapa(sb + MB_X, r2));
      sts64(xo, v0, v1);
      __syncwarp();
      if (elect()) mbar_arrive(sb + MB_X);
      bar_arrive(NB_PROJ2, 256);
      TM(3);
      uint32_t w[144];
      auto tile_of = [](int n) { return n < 27 ? n % 3 : (0x26484 >> 2 * (n - 27)) & 3; };
      auto step_of = [](int n) { return n < 27 ? n / 3 : 9 + ((0x29610 >> 2 * (n - 27)) & 3); };
      auto wload = [&](int n) { ldsm4t(&w[4 * n], wo + tile_of(n) * 12288 + (step_of(n) % 3) * 4096 + (step_of(n) / 3) * 1024); };
#pragma unroll
      for (int n = 0; n < CH_PA; n++) wload(n);
      bar_sync(NB_PRE, 256);
#pragma unroll
      for (int n = CH_PA; n < CH_PB; n++) wload(n);
      bar_arrive(NB_PRE2, 256);
      if (CH_PC > CH_PB) {
        mbar_wait(sb + MB_X, s & 1);
        for (int i = 0; i < CH_PD; i++) wo = __shfl_xor_sync(~0u, wo, p.zero);
#pragma unroll
        for (int n = CH_PB; n < CH_PC; n++) wload(n);
      }
      TM(4);
      bar_sync(NB_O, 256);
      {
        float x[3][4] = {};
        uint32_t ob[24];
        float4 l;
        ldsm4t(&ob[0], l16 + CH_O);
        ldsm4t(&ob[4], l16 + CH_O + 512);
        TMD(7, ob[0]);
        int nw = CH_PC, no = 2;
        float i0, i1;
        uint8_t* dst[6];
        uint32_t lo[6], hi[6];
        auto pre = [&](int i) { lo[i] = __float_as_uint(x[i >> 1][2 * (i & 1)] * i0) + tag; hi[i] = pack2(0.f, x[i >> 1][2 * (i & 1) + 1] * i1); };
        auto emit = [&](int i) { stg_strong32(dst[i], set_tag(__byte_perm(lo[i], hi[i], 0x7632), tag)); };
#pragma unroll
        for (int n = 0; n < 36; n++) {
          SCHED();
          mma16(x[tile_of(n)], w[4 * n], w[4 * n + 1], w[4 * n + 2], w[4 * n + 3], ob[step_of(n) * 2], ob[step_of(n) * 2 + 1]);
          if (n >= CH_PL) {
            if (no < 6 && no * 2 <= step_of(min(nw, 35))) { ldsm4t(&ob[4 * no], l16 + CH_O + no * 512); no++; }
            else if (nw < 36) { wload(nw); nw++; }
          }
          if (n == 18) l = lds128f(sb + CH_L + ((l16 ^ tag) & 0x30));
          if (n == 26) { i0 = rcp(l.x + l.y); i1 = rcp(l.z + l.w); asm volatile("" : "+f"(i0), "+f"(i1)); }
          if (n >= 28 && n < 34) { dst[n - 28] = pdst[n - 28] + ((l4 ^ tag) & 0x7c); asm volatile("" : "+l"(dst[n - 28])); }
          if (n == 32) { for (int i = 0; i < 2; i++) { pre(i); asm volatile("" : "+r"(lo[i]), "+r"(hi[i])); } }
          if (n == 33) { emit(0); emit(1); }
        }
        for (int i = 2; i < 6; i++) pre(i);
        for (int i = 2; i < 6; i++) emit(i);
      }
      TM(8);
    } else {
      finish(1, d1);
      sts128f(t16 + CH_VP, d0[0], d0[1], d0[2], d0[3]);
      TM(1);
      bar_sync(NB_PROJ, 256);
      {
        float d0[4] = {}, d1[4] = {}, dm[4] = {};
        uint32_t q[16], km[4];
#pragma unroll
        for (int e = 0; e < 4; e++) {
          ldsm4t(&q[4 * e], l16 + (e ^ t4) * 512 + CH_Q);
          SCHED();
          if (e == 1) { ldsm4t(km, t16 + CH_KM); SCHED(); }
        }
        const uint32_t xo = l4 + ((t4 * 128) ^ (tag & 2));
        uint64_t x[4];
#pragma unroll
        for (int i = 0; i < 4; i++) {
          const int r = i & 1 ? r2 : r1;
          asm volatile("mov.b64 %0, {%1, %2};" : "=l"(x[i]) : "r"(mapa(xo, r) + CH_SX + (i & 1) * 1024 + (i & 2) * 256), "r"(mapa(sb + MB_X, r)));
        }
        SCHED();
        mma16(d0, q[0], q[1], q[2], q[3], kf[0], kf[1]);
        SCHED();
        mma16(d1, q[4], q[5], q[6], q[7], kf[2], kf[3]);
        SCHED();
        mma16(dm, q[0], q[1], q[2], q[3], hadd2(km[0], km[2]), hadd2(km[1], km[3]));
        mma16(d0, q[8], q[9], q[10], q[11], kf[4], kf[5]);
        SCHED();
        mma16(d1, q[12], q[13], q[14], q[15], kf[6], kf[7]);
        if (!more) continue;
        const uint32_t w1 = pack2(dm[0] + dm[2], dm[1] + dm[3]);
        st_async32((uint32_t)x[2], w1, x[2] >> 32);
        st_async32((uint32_t)x[3], w1, x[3] >> 32);
        SCHED();
        const uint32_t w0 = pack2((d0[0] + d0[2]) + (d1[0] + d1[2]), (d0[1] + d0[3]) + (d1[1] + d1[3]));
        st_async32((uint32_t)x[0], w0, x[0] >> 32);
        st_async32((uint32_t)x[1], w0, x[1] >> 32);
        sts32(xo + CH_SO, w0);
        sts32(xo + CH_SO + 512, w1);
      }
      TM(3);
      float sc[3][4] = {};
      uint32_t wd[12];
      uint32_t redo;
      auto attend = [&](auto first) {
        uint4 vb[6];
        uint2 vm[3];
        float e[10];
        uint32_t ow[6];
        if (first.value) {
          const uint2 id = lds64(l8 + CH_ID);
          bar_sync(NB_W1V, 160);
          uint32_t r[8];
          ldsm4(r, l16 + CH_SO); ldsm4(r + 4, l16 + CH_SO + 512);
#pragma unroll
          for (int u = 0; u < 6; u++) vb[u] = ldsm4v(t16 + CH_V + u * 2048);
          bar_arrive(NB_PRE, 256);
          SCHED();
          uint32_t sxa = l16 + ((l16 ^ tag) & 256) * 3;
          asm volatile("" : "+r"(sxa));
          sxa += CH_SX;
          SCHED();
          mma8(sc[0], r[0], r[1], id.x);
          mma8(sc[1], r[2], r[3], id.x);
          mma16(sc[2], r[4], r[5], r[6], r[7], id.x, id.y);
          TM(7);
          mbar_wait(sb + MB_X, s & 1);
          TM(4);
          uint32_t t[16];
          ldsm4(t, sxa); ldsm4(t + 4, sxa + 256); ldsm4(t + 8, sxa + 512);
          SCHED();
          mma16(sc[0], t[0], t[1], t[2], t[3], id.x, id.y);
          ldsm4(t + 12, sxa + 768);
          SCHED();
          mma16(sc[1], t[4], t[5], t[6], t[7], id.x, id.y);
#pragma unroll
          for (int u = 0; u < 2; u++) vm[u] = lds64(t8 + CH_VX + u * 1024);
          SCHED();
          e[0] = ex2(sc[0][0]);
          mma16(sc[2], t[8], t[9], t[10], t[11], id.x, id.y);
          vm[2] = lds64(t8 + CH_VX + 2048);
          SCHED();
          e[1] = ex2(sc[0][1]);
          ldsm4t(&wd[0], wo);
          SCHED();
          e[2] = ex2(sc[0][2]);
          SCHED();
          e[3] = ex2(sc[0][3]);
          mma16(sc[2], t[12], t[13], t[14], t[15], id.x, id.y);
          SCHED();
          e[4] = ex2(sc[1][0]);
          ldsm4t(&wd[4], wo + 4096);
          SCHED();
          e[5] = ex2(sc[1][1]);
        } else {
#pragma unroll
          for (int u = 0; u < 6; u++) vb[u] = ldsm4v(t16 + CH_V + u * 2048);
#pragma unroll
          for (int u = 0; u < 3; u++) vm[u] = lds64(t8 + CH_VX + u * 1024);
        }
        float o[3][4] = {};
        if (!first.value) {
#pragma unroll
          for (int i = 0; i < 6; i++) e[i] = ex2(sc[i >> 2][i & 3]);
        }
        const uint32_t p1 = pack2(e[0], e[1]), p2 = pack2(e[2], e[3]);
        float l = (e[0] + e[1]) + (e[2] + e[3]);
        asm volatile("" : "+f"(l));
        SCHED();
        e[6] = ex2(sc[1][2]);
        mma16(o[0], vb[0].x, vb[0].y, vb[0].z, vb[0].w, p1, p2);
        if (first.value) { sc[2][0] += sc[2][2]; sc[2][1] += sc[2][3]; }
        SCHED();
        e[7] = ex2(sc[1][3]);
        mma16(o[1], vb[2].x, vb[2].y, vb[2].z, vb[2].w, p1, p2);
        SCHED();
        e[8] = ex2(sc[2][0]);
        mma16(o[2], vb[4].x, vb[4].y, vb[4].z, vb[4].w, p1, p2);
        SCHED();
        e[9] = ex2(sc[2][1]);
        SCHED();
        const uint32_t p3 = pack2(e[4], e[5]), p4 = pack2(e[6], e[7]);
        l += (e[4] + e[5]) + (e[6] + e[7]);
#pragma unroll
        for (int u = 0; u < 3; u++) mma16(o[u], vb[2 * u + 1].x, vb[2 * u + 1].y, vb[2 * u + 1].z, vb[2 * u + 1].w, p3, p4);
        SCHED();
        const uint32_t p0 = pack2(e[8], e[9]);
        l += e[8] + e[9];
        const float l2 = __shfl_xor_sync(~0u, l, 1);
        if (first.value) ldsm4t(&wd[8], wo + 8192);
#pragma unroll
        for (int u = 0; u < 3; u++) mma8(o[u], vm[u].x, vm[u].y, p0);
        redo = __any_sync(~0u, !(l > 1e-9f && l < 1e9f));
        uint32_t la = sb + CH_L + (((l4 ^ tag) >> 1) & 0x3c);
        asm volatile("" : "+r"(la));
        SCHED();
#pragma unroll
        for (int u = 0; u < 3; u++) { ow[2 * u] = pack2(o[u][0], o[u][1]); ow[2 * u + 1] = pack2(o[u][2], o[u][3]); }
#pragma unroll
        for (int u = 0; u < 6; u++) sts32(l4 + o768 + CH_O + u * 128, ow[u]);
        if (t4 == 0) sts32(la, __float_as_uint(l + l2));
      };
      attend(Int<1>());
      TM(6);
      asm volatile("{.reg .pred p; setp.eq.u32 p, %0, 0; @p bar.sync 2, 256;}" :: "r"(redo) : "memory");
      if (redo) {
        float mx = fmaxf(sc[2][0], sc[2][1]);
#pragma unroll
        for (int i = 0; i < 4; i++) mx = fmaxf(mx, fmaxf(sc[0][i], sc[1][i]));
        mx = fmaxf(mx, __shfl_xor_sync(~0u, mx, 1));
        mx = fmaxf(mx, __shfl_xor_sync(~0u, mx, 2));
#pragma unroll
        for (int i = 0; i < 4; i++) { sc[0][i] -= mx; sc[1][i] -= mx; }
        sc[2][0] -= mx; sc[2][1] -= mx;
        attend(Int<0>());
        bar_arrive(NB_O, 256);
      }
      {
        float z[4] = {};
        const uint32_t scr = l8 + ((CH_V + r1 * 4096) ^ (tag & 2));
        uint32_t ow[6], we[12];
        __syncwarp();
        ldsm4t(ow, l16 + o768 + CH_O);
        ldsm2t(ow + 4, l16 + o768 + CH_O + 512);
        if (j == 0) {
          float y[4] = {};
#pragma unroll
          for (int u = 0; u < 3; u++) ldsm4t(&we[4 * u], (wo ^ 32) + u * 4096);
          SCHED();
#pragma unroll
          for (int u = 0; u < 3; u++) {
            mma16(z, wd[4 * u], wd[4 * u + 1], wd[4 * u + 2], wd[4 * u + 3], ow[2 * u], ow[2 * u + 1]);
            mma16(y, we[4 * u], we[4 * u + 1], we[4 * u + 2], we[4 * u + 3], ow[2 * u], ow[2 * u + 1]);
          }
          sts64f(scr + t4 * 512 + 2048, y[0], y[1]); sts64f(scr + t4 * 512 + 2304, y[2], y[3]);
        } else {
#pragma unroll
          for (int u = 0; u < 3; u++) mma16(z, wd[4 * u], wd[4 * u + 1], wd[4 * u + 2], wd[4 * u + 3], ow[2 * u], ow[2 * u + 1]);
        }
        sts64f(scr + t4 * 512, z[0], z[1]); sts64f(scr + t4 * 512 + 256, z[2], z[3]);
        bar_sync(NB_W1, 128);
        if (j == 0 || t4 < 2) {
          float2 q[4];
          const float4 l = lds128f(sb + CH_L + ((l16 ^ tag) & 0x30));
#pragma unroll
          for (int i = 0; i < 4; i++) q[i] = lds64f(scr + (t4 >> 1) * 2048 + (t4 & 1) * 256 + i * 512);
          SCHED();
          stg_strong32(pdst[0] + ((l4 ^ tag) & 0x7c), pack_tag(((q[0].x + q[1].x) + (q[2].x + q[3].x)) * rcp(l.x + l.y), ((q[0].y + q[1].y) + (q[2].y + q[3].y)) * rcp(l.z + l.w), tag));
        }
      }
      TM(2);
    }
    bar_sync(NB_ST, 384);
    tag ^= 0x10001;
  } while (++s < NSEG);
  if (WG == 1) {
    const uint2 a = lds64(t8 + t4 * 256 + CH_KM), b = lds64(t8 + t4 * 256 + CH_KM + 256);
    sts64(t8 + CH_M, hadd2(a.x, b.x), hadd2(a.y, b.y));
  }
  bar_arrive(NB_PRE2, 288);
}

__device__ __forceinline__ void chain_comm(const ChainParams& p, const uint32_t sb, const CUtensorMap* maps) {
  [[maybe_unused]] constexpr int WG = 2;
  const int tid = threadIdx.x & 127, t4 = __shfl_sync(~0u, tid >> 5, 0), lane = tid & 31;
  const int cta = blockIdx.x, h = cta / 3, j = cta - 3 * h, colbase = cta * 64;
  const uint8_t* const xs = reinterpret_cast<const uint8_t*>(g_xn);
  auto xload = [&](int seg, int i) { tma_load5(sb + CH_X + i * 10240, &p.xc, 0, seg * 4, 2 * i, sb + MB_T); };
  uint32_t smid; asm("mov.u32 %0, %%smid;" : "=r"(smid));
  if (t4 == 3) {
    const bool one = elect();
#pragma unroll 1
    for (int i = 0; i < 19 + CH_FLY; i++) {
      if (i >= CH_FLY) mbar_wait(sb + MB_W + 8 * ((i - CH_FLY) & 7), (i - CH_FLY) >> 3 & 1);
      if (i == 11 + CH_FLY && one) mbar_arrive(sb + MB_WQ);
      if (i == 8) { bar_sync(NB_PROJ2, 288); PRO(1); }
      if (i == 12) { bar_sync(NB_PRE2, 288); PRO(2); }
      if (i == 0) { bar_arrive(NB_ST, 384); bar_arrive(NB_PUB, 384); bar_arrive(NB_XFREE, 256); }
      if (i < 19 && one) {
        const int n = (i & 1) * 2 + (i >> 1 & 1), k = i - 12;
        const uint32_t bar = sb + MB_W + 8 * (i & 7);
        mbar_expect(bar, k < 0 ? 20480 : 12288);
        if (k < 0) tma_load(sb + ((i & 4) + n) * 20480, i >= 8 ? &p.wq : (i ^ i >> 2) & 1 ? &p.wv : &p.wk, colbase, n * 160, bar);
        else tma_load(sb + CH_WO + k * 12288, &p.wo, k < 6 ? j * 192 + k * 32 : j == 0 ? 576 : 592 + j * 16, h * 192, bar);
      }
    }
  } else {
    const uint32_t part = max(ldg_strong32(g_smpart + (smid & 255)), 1u);
    if (tid == 0) prefetch_l2(p.mem0, 10240);
    if (tid == 64) stg_strong32(p.sync + SY_PART + cta, part);
    if (t4 == 1) {
      wait_count(p.sync + SY_P + 1, ln_items(p.layer, 0));
      if (elect()) {
        mbar_expect(sb + MB_T, 40960);
#pragma unroll 1
        for (int i = 0; i < 4; i++) xload(0, i);
      }
      __syncwarp();
      PRO(0);
    }
    uint32_t reader, orient;
    for (int n = 0;; spin_guard(n)) {
      reader = ldg_strong32(p.sync + SY_PART + (tid >= 80 ? cta : tid));
      orient = ldg_strong32(g_orient + min(tid, NSLOT - 1));
      if (__all_sync(~0u, reader && orient)) break;
    }
    const uint32_t near = __ballot_sync(~0u, reader == part) >> (cta & 7) & 0xffff;
    if (tid < NSLOT) sts32(sb + CH_TAB + tid * 4, tid * 8192 + (orient == reader ? 0 : 4096));
    if (tid == 0) sts32(sb + CH_TAB + NSLOT * 4, cta < 80 ? cta : (cta & 7) + max(__ffs(near) - 1, 0));
    if (t4 == 1) PRO(3);
    bar_sync(NB_ST, 384);
    bar_arrive(NB_PUB, 384);
    if (t4 == 1) PRO(4);
    const uint32_t id = (lane >> 3) == (lane & 3) ? ((lane & 4) ? 0x3f800000u : 0x00003f80u) : 0u;
    if (t4 == 0) sts64(sb + CH_ID + lane * 8, id, id);
#pragma unroll 1
    for (int q = t4; q < 4; q += 3) {
      uint32_t m0[20];
#pragma unroll
      for (int i = 0; i < 20; i++) m0[i] = (reinterpret_cast<const uint32_t*>(p.mem0) + (lane >> 2) * (DM / 2) + q * 80 + (lane & 3))[i * 4];
      if (q < 3) bar_sync(NB_XFREE, 256);
#pragma unroll
      for (int i = 0; i < 20; i += 4) stsm4t(sb + CH_M + (q * 20 + i) * 128 + lane * 16, m0[i], m0[i + 1], m0[i + 2], m0[i + 3]);
    }
    if (t4 == 1) PRO(5);
  }
  if (cta < 4 && cta * 128 + tid < SY_N) p.other[cta * 128 + tid] = 0;
  asm volatile("barrier.cluster.wait.aligned;" ::: "memory");
  const uint32_t l8 = opaque(sb + t4 * 256 + lane * 8);
  bar_sync(NB_MEM, 384);
  uint8_t* const pool = pool_at(0);
  const uint8_t* const psrc = pool + opaque(lds32(sb + CH_TAB + lds32(sb + CH_TAB + NSLOT * 4) * 4) + t4 * 1024 + lane * 4);
  const uint32_t mdst = opaque((80 + cta / 20) * 8192 + (t4 & 1) * 4096 + (cta % 20) * 128 + lane * 4);
  int st = 0;
  uint32_t tag = 1, span = ~0u;
  auto send_tokens = [&](int s) {
    uint8_t* dst = g_kv + ((s >> 2) * 192 + cta + 3 * h) * KV_PART + (s & 3) * 4096;
    bulk_store(dst, sb + CH_K, 4096);
    bulk_store(dst + KV_V, sb + CH_V + j * 4096, 4096);
    bulk_commit();
  };
  auto send_memory = [&](int s, uint32_t km) {
    fence_async();
    uint8_t* dst = g_kv + ((s >> 2) * 192 + cta + 3 * h) * KV_PART + KV_M + (s & 3) * 1024;
    bulk_store(dst, km, 1024);
    bulk_store(dst + KV_V, sb + CH_VX + j * 1024, 1024);
    bulk_commit();
    bulk_wait<0>();
    if ((s & 3) == 3) { fence_async_global(); atomicAdd(p.sync + (s >> 2) * 8 + 4, 1); }
  };
#pragma unroll 1
  for (int s = 0; s < NSEG - 1; s++) {
    TM(0);
    STAT(0);
    if (t4 == 0) {
      if (elect()) {
        fence_async();
#pragma unroll 1
        for (int r = j + 1; r < j + 3; r++) bulk_push(mapa(sb + CH_V + j * 4096, r % 3), sb + CH_V + j * 4096, 4096, mapa(sb + MB_V, r % 3));
        send_tokens(s);
        bulk_wait_read<0>();
      }
      __syncwarp();
    }
    uint32_t c0, g0;
    if (t4 == 1) {
      __syncwarp();
      c0 = clk32(); g0 = gtime();
      if (elect()) atomicMax(p.sync + SY_TIME + s, g0);
    }
    if (t4 == 3 && s >= NSEG - 6 && elect()) asm volatile("prefetch.tensormap [%0];" :: "l"(maps + (NSEG - 2 - s)) : "memory");
    if (t4 == 3 && (s & 3) == 2 && s < NSEG - 2) wait_count(p.sync + SY_P + 5 + (s & ~3), ln_items(p.layer, (s >> 2) + 1));
    if (t4 == 2) { mbar_wait(sb + MB_V, s & 1); bar_arrive(NB_W1V, 160); }
    bar_sync(NB_PROJ2, 256);
    if (t4 == 0 && elect()) {
      mbar_expect(sb + MB_X, 4096);
      mbar_expect(sb + MB_T, 40960);
      for (int i = 0; i < 3; i++) xload(s + 1, i);
    }
    __syncwarp();
    STAT(1);
    TM(1);
    {
      const uint2 a = lds64(l8 + t4 * 256 + CH_KM), b = lds64(l8 + t4 * 256 + CH_KM + 256);
      sts64(l8 + CH_KS, hadd2(a.x, b.x), hadd2(a.y, b.y));
    }
    TM(4);
    bar_sync(NB_PRE2, 256);
    if (t4 == 0 && elect()) {
      xload(s + 1, 3);
      if (CH_XPF && s < NSEG - 2) prefetch_l2(xs + (s + 2) * 40960 + cta % 20 * 2048, 2048);
      if (CH_TPF && s >= NSEG - 7) {
        const int i = s - (NSEG - 7);
        if (i < 2) prefetch_l2(p.wb + (cta * 2 + i) * 12800, 12800);
        else if (i < 4) prefetch_l2(xs + (cta * 2 + i - 2) * 8192, 8192);
        else prefetch_l2(g_q + 15 * 32 * 3072 + (cta * 2 + i - 4) * 512, 8192);
      }
      send_memory(s, sb + CH_KS);
    }
    __syncwarp();
    if (t4 == 1) {
      const uint32_t late = min(ldg_strong32(p.sync + SY_TIME + s) - g0, 640u);
      if (elect()) sts32(sb + CH_TAB + 380, c0 + span + (late * 115 >> 6) + (j ? 60 : 0) + p.d1);
    }
    bar_sync(NB_W2, 128);
    uint32_t due = lds32(sb + CH_TAB + 380);
    due = __shfl_sync(~0u, due, 0);
    const uint8_t* ms = pool + (lds32(sb + CH_TAB + (80 + st * 4 + t4) * 4) + (l8 & 255));
    uint8_t* md = pool + (mdst + (cta >= 80 ? 2 : t4 < 2 ? st : st == 2 ? 0 : st + 1) * 32768);
    asm volatile("" : "+l"(ms), "+l"(md));
    if (CH_TW) mbar_wait(sb + MB_T, ~s & 1);
    TM(2);
    bar_sync(NB_ST, 384);
    __syncwarp();
    uint32_t tg = clk32();
    if (t4 == 3 && elect()) {
      if (s < NSEG - 2) mbar_expect(sb + MB_V, 8192);
      mbar_arrive_remote(mapa(sb + MB_F, j == 2 ? 0 : j + 1));
      mbar_arrive_remote(mapa(sb + MB_F, j == 0 ? 2 : j - 1));
    }
    if (s == NSEG - 2) work_init(sb, t4);
    __syncwarp();
    STAT(2);
    {
      float2 q[4];
      TM(3);
      if (t4 == 1 && s) span = min(span, tg - c0);
      until(s < 2 ? tg + 400 : (int)(due - tg) > p.dn ? due : tg + p.dn);
      for (int n = 0;;) {
        uint32_t v[8];
#pragma unroll
        for (int i = 0; i < 8; i++) v[i] = ldg_strong32(psrc + i * 128);
        sts64f(l8 + CH_R2, ((bf_lo(v[0]) + bf_lo(v[1])) + (bf_lo(v[2]) + bf_lo(v[3]))) + ((bf_lo(v[4]) + bf_lo(v[5])) + (bf_lo(v[6]) + bf_lo(v[7]))),
               ((bf_hi(v[0]) + bf_hi(v[1])) + (bf_hi(v[2]) + bf_hi(v[3]))) + ((bf_hi(v[4]) + bf_hi(v[5])) + (bf_hi(v[6]) + bf_hi(v[7]))));
        uint32_t bad;
        asm volatile("{.reg .pred p, q; .reg .b32 a; lop3.b32 a, %1, %2, %3, 0xFE; lop3.b32 a, a, %4, %6, 0xA8; setp.ne.u32 p, a, 0;\n"
                     "bar.red.or.pred q, %5, 128, p; selp.u32 %0, 1, 0, q;}"
                     : "=r"(bad) : "r"(differ(v[0], v[1], tag)), "r"(differ(v[2], v[3], tag)), "r"(differ(v[4], v[5], tag)), "r"(differ(v[6], v[7], tag)), "n"((int)NB_W2),
                       "r"((uint32_t)(cta < 80 || n < 3)) : "memory");
#pragma unroll
        for (int k = 0; k < 4; k++) asm volatile("ld.volatile.shared.v2.f32 {%0,%1}, [%2];" : "=f"(q[k].x), "=f"(q[k].y) : "r"(l8 - t4 * 256 + CH_R2 + k * 256) : "memory");
        TMV(12, n);
        if (!bad) break;
        spin_guard(n);
      }
      bar_arrive(NB_PUB, 384);
      SCHED();
      TM(9);
      stg_strong32(md, min(nz(pack2((q[0].x + q[1].x) + (q[2].x + q[3].x), (q[0].y + q[1].y) + (q[2].y + q[3].y))), t4 < 2 ? ~0u : 0u));
      tg = clk64() + p.d2;
      if (s >= 2 && (int)(due + p.dx - tg) > 0) tg = due + p.dx;
      TM(8);
    }
    STAT(3);
    until(tg);
    TM(10);
    for (int n = 0;;) {
      uint2 g[10];
#pragma unroll
      for (int i = 0; i < 10; i++) g[i] = ldg_strong64(ms + i * 256);
      if (n == 0) bar_sync(NB_XFREE, 256);
      uint32_t m = ~0u, bad;
#pragma unroll
      for (int i = 0; i < 10; i++) { sts64(l8 + CH_M + t4 * 2304 + i * 256, g[i].x, g[i].y); m = __vimin3_u32(m, g[i].x, g[i].y); }
      TMV(13, n);
      TM(11);
      asm volatile("{.reg .pred p; setp.eq.u32 p, %1, 0; vote.sync.any.pred p, p, 0xffffffff; @!p bar.sync %2, 384; selp.u32 %0, 1, 0, p;}" : "=r"(bad) : "r"(m), "n"((int)NB_MEM) : "memory");
      if (!bad) break;
      spin_guard(n);
    }
    if (++st == 3) st = 0;
    tag ^= 0x10001;
  }
  if (t4 == 0) {
    if (elect()) { fence_async(); send_tokens(NSEG - 1); }
    __syncwarp();
    bar_sync(NB_PRE2, 288);
    if (elect()) {
      send_memory(NSEG - 1, sb + CH_M);
      asm volatile("mbarrier.arrive.shared::cta.b64 _, [%0], 8;" :: "r"(sb + WK_BAR + 64) : "memory");
    }
    __syncwarp();
  }
}

__device__ __forceinline__ void chain_start(const ChainParams& p, const uint32_t sb, const int warp) {
  if (warp == 1 && elect()) {
#pragma unroll
    for (int i = 0; i < 6; i++) mbar_init(sb + CH_BAR + 8 * i, i == 2 ? 5 : i == 5 ? 2 : 1);
    asm volatile("fence.mbarrier_init.release.cluster;" ::: "memory");
    mbar_expect(sb + MB_V, 8192);
    atomicAdd(p.sync + SY_UP, 1);
    asm volatile("{.reg .pred p; setp.ne.u32 p, %0, 1024; @p trap;}" :: "r"(sb & 0xffffff));
  }
  if (warp == 0 && elect()) {
#pragma unroll
    for (int i = 0; i < 8; i++) mbar_init(sb + MB_W + 8 * i, 1);
    asm volatile("fence.mbarrier_init.release.cluster;" ::: "memory");
  }
  __syncthreads();
  asm volatile("barrier.cluster.arrive.relaxed.aligned;" ::: "memory");
}

struct WorkParams {
  ChainParams ch;
  CUtensorMap wo, xn, wb[3], xp, wq, wc[2], out;
  const __nv_bfloat16* x;
  uint32_t* sync;
  int kind, qa_end, idle;
};
#define GO_320 4
#define GO_TAIL 1
#define PF_NS 400
enum { WK_FIRST = 0, WK_LEAD = 1, WK_CHAIN = 2, WK_LAST = 3 };
enum { IT_ATT = 0, IT_OP = 1, IT_FIN = 2, IT_BQ = 3, IT_BO = 4, IT_LN = 5, IT_Q = 6, IT_LN0 = 7, IT_OUT = 8 };
constexpr int C_EARLY = 1 << 20, C_LATE = 1 << 21, C_TAIL = 1 << 22;

__device__ __forceinline__ uint32_t item_count(int type, int b) { return type == IT_ATT ? 32 : type == IT_OP ? op_tiles(b) * op_split(b) : type == IT_FIN ? fin_items(b) : bq_items(b); }
__device__ __forceinline__ uint32_t item_need(int type, int b) { return type == IT_ATT ? 96 : item_count(type - 1, b); }
__device__ __forceinline__ int item_cols(int type, int b) {
  return type == IT_ATT || type == IT_Q ? 192 : type == IT_OUT ? 80 : type == IT_BQ ? (b < BQ_12 ? 320 : b < BQ_24 ? 160 : 80) : type == IT_OP && b >= OP_N4 ? 160 : 320; }
__device__ __forceinline__ int item_groups(int type, int b) { const int n = type == IT_FIN ? fin_items(b) : ln_items(type == IT_LN, b); return n == 4 ? 4 : n == 8 ? 2 : 1; }
#define RES_OP 1
constexpr int RES_N = RES_OP ? op_tiles(14) * op_split(14) : 0, RES_BQ = (64 - RES_N) / 6;
__device__ __forceinline__ bool reserved(int type, int b) { return type == IT_ATT ? b == 15 : type == IT_OP ? RES_OP && b == 14 : type == IT_BQ && b < RES_BQ; }
__device__ __forceinline__ int reserved_item(int cta) {
  const int h = cta / 3, j = cta - 3 * h, i = h + (j - 1) * 32;
  if (j == 0) return C_EARLY | IT_ATT << 16 | 15 << 8 | h;
  return i < RES_N ? C_TAIL | IT_OP << 16 | 14 << 8 | i : i - RES_N < RES_BQ * 6 ? C_TAIL | IT_BQ << 16 | ((i - RES_N) / 6) << 8 | (i - RES_N) % 6 : -1;
}
constexpr int LEAD1 = 12;
__device__ __forceinline__ int lead_item(int layer, int qa_end, int i) {
  if (layer == 2) return i < 128 ? C_EARLY | C_LATE | IT_OUT << 16 | (i >> 3) << 8 | (i & 7) : -1;
  if (layer == 0) {
    if (i < 32) return IT_LN0 << 16 | (i >> 4) << 8 | (i & 15);
    if (i < 88) return IT_LN0 << 16 | ((i - 24) >> 2) << 8 | (i & 3);
    i -= 88;
  } else {
    if (i < 4) return C_EARLY | IT_BO << 16 | (i >> 1) << 8 | (i & 1);
    if (i < 12) return C_EARLY | IT_LN << 16 | ((i - 4) >> 2) << 8 | (i & 3);
    if (i < 40) return C_EARLY | IT_BO << 16 | ((i - 8) >> 1) << 8 | (i & 1);
    if (i < 96) return C_EARLY | IT_LN << 16 | ((i - 32) >> 2) << 8 | (i & 3);
    i -= 96;
  }
  return i < (16 - qa_end) * 32 ? C_EARLY | IT_Q << 16 | (qa_end + (i >> 5)) << 8 | (i & 31) : -1;
}

struct Ring {
  uint32_t sb;
  int pos, seq;
  __device__ __forceinline__ uint32_t full() const { return sb + WK_BAR + 8 * (seq & 7); }
  __device__ __forceinline__ uint32_t take(int len) { if (pos + len > WK_SLOTS) pos = 0; pos += len; seq++; return sb + (pos - len) * 8192; }
  __device__ __forceinline__ uint32_t wait(int len) { mbar_wait(full(), (seq >> 3) & 1); return take(len); }
  __device__ __forceinline__ void release(int sq) const { if (elect()) mbar_arrive(sb + WK_BAR + 64 + 8 * (sq & 7)); }
};

struct Pending {
  uint32_t w[48], done;
  uint4* dst;
  __device__ __forceinline__ void store(int i) const { dst[(i >> 2) * 1024 + (i & 3) * 32] = make_uint4(w[4 * i], w[4 * i + 1], w[4 * i + 2], w[4 * i + 3]); }
  __device__ __forceinline__ void finish() { __syncwarp(); if (elect()) mbar_arrive(done); done = 0; }
  __device__ __forceinline__ void flush() {
    if (done) {
#pragma unroll
      for (int i = 0; i < 12; i++) store(i);
      finish();
    }
  }
};

template <int N>
__device__ __forceinline__ void gemm_item(float* d, Ring& r, int nkb, uint32_t go, int ask, Pending& pend) {
  const int warp = __shfl_sync(~0u, fresh_tid() >> 5, 0), wg = warp >> 2;
#pragma unroll 1
  for (int kb = 0; kb < nkb; kb++) {
    const uint32_t base = r.wait(2 + (N + 63) / 64);
    const uint64_t da = mkdesc(base + wg * 8192, 128, 1024, 0), db = mkdesc(base + 16384, 8192, 1024, 1);
    wg_fence();
#pragma unroll
    for (int kk = 0; kk < 4; kk++) {
      if (N == 80) wg_ss80_01(d, da + kk * 16, db + kk * 128, (kb | kk) != 0);
      else if (N == 160) wg_ss160_01(d, da + kk * 16, db + kk * 128, (kb | kk) != 0);
      else wg_ss192_01(d, da + kk * 16, db + kk * 128, (kb | kk) != 0);
      if (N == 320) wg_ss128_01(d + 96, da + kk * 16, db + kk * 128 + 3 * 512, (kb | kk) != 0);
    }
    wg_commit();
    if (kb == ask && go && warp == 0 && elect()) mbar_arrive(go);
    if (N == 192 && pend.done) {
#pragma unroll
      for (int i = 0; i < 12; i++) if (kb == i / 2) pend.store(i);
      if (kb == 5) pend.finish();
    }
    if (kb > 0) { wg_wait<1>(); r.release(r.seq - 2); }
  }
  wg_wait<0>();
  reg_fence<N / 2>(d);
  r.release(r.seq - 1);
}

__device__ __forceinline__ void attn_a_warp(Ring& r, Pending& pend, bool now, const int warp) {
  uint32_t (&q)[48] = pend.w;
  const int lane = fresh_tid() & 31, g = lane >> 2, c = lane & 3, seg = warp & 3;
  const bool half = warp >= 4;
  const float k2 = 0.07216878364870322f * 1.44269504089f, NEG = -INFINITY;
  float sc[5][4] = {};
#pragma unroll
  for (int i = 0; i < 8; i++) sc[3 + (i >> 2)][i & 3] = half ? 0.f : NEG;
  uint32_t base, f[2][40] = {};
  const uint32_t ka = seg * 4096 + lane * 16, va = seg * 4096 + (lane & 8) * 32 + (lane & 16) * 8 + (lane & 7) * 16;
  auto load = [&](int n) {
    uint32_t* d = f[n & 1];
    base = n & 1 ? base + KV_PART : r.wait(5);
    const uint32_t a = base + (n < 3 ? ka : va), m = base + KV_M + seg * 1024;
#pragma unroll
    for (int i = 0; i < 4; i++) {
      if (n >= 3) { const uint2 vm = lds64(m + i * 256 + lane * 8); d[2 * i] = vm.x; d[2 * i + 1] = vm.y; }
      else if (!(i & 1)) ldsm4t(&d[2 * i], m + i * 256 + lane * 16);
      (n < 3 ? ldsm4t : ldsm4)(&d[8 + 4 * i], a + half * 2048 + i * 512);
    }
    if (half) {
#pragma unroll
      for (int i = 0; i < 4; i++) (n < 3 ? ldsm4t : ldsm4)(&d[24 + 4 * i], a + i * 512);
    }
  };
  load(0);
#pragma unroll
  for (int u = 0; u < 3; u++) {
    if (u == 2) r.release(r.seq - 2);
    load(u + 1);
    SCHED();
    const uint32_t* b = f[u & 1];
#pragma unroll
    for (int kk = 0; kk < 4; kk++) {
      const uint32_t* a = &q[16 * u + 4 * kk];
      mma16(sc[0], a[0], a[1], a[2], a[3], b[2 * kk], b[2 * kk + 1]);
      mma16(sc[1], a[0], a[1], a[2], a[3], b[8 + 4 * kk], b[9 + 4 * kk]);
      mma16(sc[2], a[0], a[1], a[2], a[3], b[10 + 4 * kk], b[11 + 4 * kk]);
    }
    if (half) {
#pragma unroll
      for (int kk = 0; kk < 4; kk++) {
        const uint32_t* a = &q[16 * u + 4 * kk];
        mma16(sc[3], a[0], a[1], a[2], a[3], b[24 + 4 * kk], b[25 + 4 * kk]);
        mma16(sc[4], a[0], a[1], a[2], a[3], b[26 + 4 * kk], b[27 + 4 * kk]);
      }
    }
    SCHED();
  }
  load(4);
  SCHED();
  if (2 * c > g) { sc[1][0] = NEG; sc[2][2] = NEG; }
  if (2 * c + 1 > g) { sc[1][1] = NEG; sc[2][3] = NEG; }
  sc[2][0] = sc[2][1] = NEG;
  uint32_t pp[5][2]; float inv[2];
#pragma unroll
  for (int hh = 0; hh < 2; hh++) {
    float m = NEG, l = 0.f;
#pragma unroll
    for (int n = 0; n < 5; n++) m = fmaxf(m, fmaxf(sc[n][2 * hh], sc[n][2 * hh + 1]));
    m = fmaxf(m, __shfl_xor_sync(~0u, m, 1)); m = fmaxf(m, __shfl_xor_sync(~0u, m, 2));
#pragma unroll
    for (int n = 0; n < 5; n++) { const float x = ex2((sc[n][2 * hh] - m) * k2), y = ex2((sc[n][2 * hh + 1] - m) * k2); l += x + y; pp[n][hh] = pack2(x, y); }
    l += __shfl_xor_sync(~0u, l, 1); l += __shfl_xor_sync(~0u, l, 2);
    inv[hh] = rcp(l);
  }
#pragma unroll
  for (int u = 0; u < 3; u++) {
    float o[8][4] = {};
    const uint32_t* b = f[~u & 1];
#pragma unroll
    for (int n = 0; n < 8; n++) mma8(o[n], pp[0][0], pp[0][1], b[n]);
#pragma unroll
    for (int n = 0; n < 8; n++) mma16(o[n], pp[1][0], pp[1][1], pp[2][0], pp[2][1], b[8 + 2 * n], b[9 + 2 * n]);
    if (half) {
#pragma unroll
      for (int n = 0; n < 8; n++) mma16(o[n], pp[3][0], pp[3][1], pp[4][0], pp[4][1], b[24 + 2 * n], b[25 + 2 * n]);
    }
    SCHED();
    if (u != 1) r.release(r.seq - 2 + u / 2);
    if (u == 0) { load(5); SCHED(); }
#pragma unroll
    for (int i = 0; i < 16; i++) q[16 * u + i] = pack2(o[i & 7][i >> 2 & 2] * inv[i >> 3], o[i & 7][(i >> 2 & 2) + 1] * inv[i >> 3]);
    if (now) {
#pragma unroll
      for (int i = 0; i < 4; i++) pend.store(4 * u + i);
    }
  }
}

__device__ __forceinline__ void ln_groups(Ring& ring, uint32_t scratch, int planes, int rg, bool two) {
  constexpr int G = 2;
  const int warp = fresh_tid() >> 5, lane = fresh_tid() & 31;
  const uint32_t id = (lane >> 3) == (lane & 3) ? ((lane & 4) ? 0x3f800000u : 0x00003f80u) : 0u;
  const uint32_t at = (warp * 160 + lane) * 8, at1 = planes > 1 ? at : (lane >> 2) * 1280 + warp * 160 + (lane & 3) * 4;
  const uint32_t step = planes > 1 ? 256 : 32, half = planes > 1 ? 4 : 16;
  float v[G][5][4] = {};
#pragma unroll
  for (int r = 0; r < G; r++) {
#pragma unroll 1
    for (int k = r && !two ? 0 : planes; k > 0; k -= 4) {
      const uint32_t a = ring.wait(min(k, 4) + 1);
      if (k == 1) {
#pragma unroll
        for (int i = 0; i < 5; i++) mma8(v[r][i], lds32(a + at1 + i * step), lds32(a + at1 + i * step + half), id);
      } else {
#pragma unroll
        for (int i = 0; i < 10; i++) {
          if (i == 5 && k < 4) break;
          const uint2 x = lds64(a + at + i / 5 * 20480 + i % 5 * 256), y = lds64(a + at + i / 5 * 20480 + 10240 + i % 5 * 256);
          mma16(v[r][i % 5], x.x, x.y, y.x, y.y, id, id);
        }
      }
      ring.release(ring.seq - 1);
    }
  }
  uint2 xr[G][5];
  float mw[G];
  scratch += (lane >> 2) * 64;
#pragma unroll
  for (int r = 0; r < G; r++) {
    float m = 0.f, q2[4] = {};
#pragma unroll
    for (int i = 0; i < 5; i++) {
      float* t = v[r][i];
      xr[r][i] = make_uint2(pack2(t[0], t[1]), pack2(t[2], t[3]));
      t[0] = bf_lo(xr[r][i].x); t[1] = bf_hi(xr[r][i].x); t[2] = bf_lo(xr[r][i].y); t[3] = bf_hi(xr[r][i].y);
      m += (t[0] + t[1]) + (t[2] + t[3]);
    }
    m += __shfl_xor_sync(~0u, m, 1); m += __shfl_xor_sync(~0u, m, 2);
    m *= 1.f / 80;
#pragma unroll
    for (int i = 0; i < 20; i++) { float& t = v[r][i >> 2][i & 3]; t -= m; q2[i & 3] = fmaf(t, t, q2[i & 3]); }
    float q = (q2[0] + q2[1]) + (q2[2] + q2[3]);
    mw[r] = m;
    q += __shfl_xor_sync(~0u, q, 1); q += __shfl_xor_sync(~0u, q, 2);
    if ((lane & 3) == 0) sts64f(scratch + r * 512 + warp * 8, m, q);
  }
  bar_sync(1, 256);
#pragma unroll
  for (int r = 0; r < G; r++) {
    const float4 t = lds128f(scratch + r * 512 + (lane & 3) * 16);
    float mean = t.x + t.z;
    mean += __shfl_xor_sync(~0u, mean, 1); mean += __shfl_xor_sync(~0u, mean, 2);
    mean *= 0.125f;
    float var = (t.y + t.w) + 80.f * ((t.x - mean) * (t.x - mean) + (t.z - mean) * (t.z - mean));
    var += __shfl_xor_sync(~0u, var, 1); var += __shfl_xor_sync(~0u, var, 2);
    float rs;
    asm("rsqrt.approx.ftz.f32 %0, %1;" : "=f"(rs) : "f"(var * (1.f / DM) + 1e-5f));
#pragma unroll
    for (int i = 0; i < 20; i++) v[r][i >> 2][i & 3] = fmaf(v[r][i >> 2][i & 3], rs, (mw[r] - mean) * rs);
  }
#pragma unroll
  for (int r = 0; r < G; r++) {
    if (r && !two) break;
    uint32_t* xn = g_xn + (rg + r) * 2560 + warp * 320 + lane;
#pragma unroll
    for (int i = 0; i < 10; i++) xn[i * 32] = pack2(v[r][i >> 1][2 * (i & 1)], v[r][i >> 1][2 * (i & 1) + 1]);
#pragma unroll
    for (int i = 0; i < 5; i++) g_x[(rg + r) * 17 * 1280 + warp * 160 + i * 32 + lane] = xr[r][i];
  }
}

__device__ __forceinline__ void store_partial(const float* d, int b, int split, int unit, int nu) {
  uint2* dst = g_x + (((b * 16 + (fresh_tid() >> 5) * 2) * 17 + 1 + split) * 40 + unit) * 32 + (fresh_tid() & 31);
#pragma unroll
  for (int u = 0; u < 20; u++) {
    if (u == 10 && nu == 10) break;
    dst[u * 32] = make_uint2(pack2(d[8 * u], d[8 * u + 1]), pack2(d[8 * u + 4], d[8 * u + 5]));
    dst[(680 + u) * 32] = make_uint2(pack2(d[8 * u + 2], d[8 * u + 3]), pack2(d[8 * u + 6], d[8 * u + 7]));
  }
}

__device__ __forceinline__ void store_bqkv(const float* d, int b, int idx, int nh) {
  const int lane = fresh_tid() & 31, c = lane & 3, rg = b * 16 + (fresh_tid() >> 5) * 2, h0 = idx * nh;
  const float sc = h0 < 32 ? 0.22360679775f * 1.44269504089f : 1.f;
  const bool lo = c < 2;
  uint32_t* da = g_bqkv + (h0 * 256 + rg) * 96 + lane;
  uint32_t* db = da + 256 * 96 + (lo ? 2 : -2);
  uint32_t pad[2];
#pragma unroll
  for (int r = 0; r < 2; r++) pad[r] = !(c & 1) && (h0 >= 64 || (h0 >= 32 && (lane & 4) && poly_group(rg + r))) ? 0x00003f80u : 0u;
#pragma unroll
  for (int q = 0; q < 8; q++) {
    if ((q == 2 || q == 4) && nh == 2 * q) break;
#pragma unroll
    for (int r = 0; r < 2; r++) {
      uint32_t w[5];
#pragma unroll
      for (int i = 0; i < 5; i++) w[i] = pack2(d[20 * q + 4 * i + 2 * r] * sc, d[20 * q + 4 * i + 2 * r + 1] * sc);
      const int o = q * 2 * 256 * 96 + r * 96;
      da[o] = w[0]; da[o + 32] = w[1]; da[o + 64] = lo ? w[2] : pad[r];
      db[o] = lo ? w[3] : w[2]; db[o + 32] = lo ? w[4] : w[3]; db[o + 64] = lo ? pad[r] : w[4];
    }
  }
}

__device__ __forceinline__ void work_loader(const WorkParams& p, const uint32_t sb, const bool weights) {
  const uint32_t bars = sb + WK_BAR, bIF = bars + 128, bIE = bars + 160, bGo = bars + 224, slots = bars + 272;
  int pos = 0, seq = 0, tail = 0, used = 0;
  uint32_t lens = 0;
  const bool one = elect();
  if (p.kind == WK_CHAIN) {
    seq = 1; used = lens = 8;
    if (one) mbar_arrive(bars);
  }
  for (int n = 0;; n++) {
    mbar_wait(bIF + 8 * (n & 3), (n >> 2) & 1);
    const int code = __shfl_sync(~0u, (int)lds32(slots + 4 * (n & 3)), 0);
    if (code < 0) break;
    const int type = (code >> 16) & 15, b = (code >> 8) & 255, idx = code & 255;
    if (one) mbar_arrive(bIE + 8 * (n & 3));
    const bool qa = type == IT_ATT && b < p.qa_end, ln = type == IT_FIN || type == IT_LN || type == IT_LN0;
    const int parts = ln ? item_groups(type, b) : type == IT_ATT ? 2 : 1;
#pragma unroll 1
    for (int part = 0; part < parts; part++) {
      int bytes = 163840, chunk = 40960, nb = 0, flag = b * 8 + 4 + type, need = item_need(type & 3, b), c0 = 0, c3 = idx, c4 = 0, step = 64;
      const uint8_t* src = g_kv + (b * 32 + idx) * 6 * KV_PART;
      const CUtensorMap* m = nullptr;
      if (ln) {
        const int rg = b * 16 + idx * parts + part;
        bytes = (type == IT_FIN ? op_split(b) + 1 : type == IT_LN ? 2 : 1) * 10240;
        src = type == IT_LN0 ? reinterpret_cast<const uint8_t*>(p.x) + rg * 10240 : reinterpret_cast<const uint8_t*>(g_x) + rg * 174080;
        if (type == IT_LN) { flag = SY_P + b * 4; need = 2; }
        if (type == IT_LN0 || part) need = 0;
      } else if (part) {
        bytes = 6 * KV_PART;
      } else if (type == IT_ATT && !qa) {
        bytes = chunk = 49152;
        src = reinterpret_cast<const uint8_t*>(g_q) + (b * 32 + idx) * 49152;
        flag = SY_P + b * 4 + 3; need = 32;
      } else {
        const int cols = item_cols(type, b);
        chunk = 16384; nb = (cols + 63) >> 6;
        src = reinterpret_cast<const uint8_t*>(g_of) + b * 163840;
        if (type == IT_OP) {
          const int nkb = op_steps(b), kb0 = (idx >> op_tiles(b) / 2) * nkb;
          bytes = nkb * 16384;
          src = reinterpret_cast<const uint8_t*>(g_o) + (b * 96 + kb0) * 16384;
          if (weights) m = &p.wo;
          c0 = (idx & (op_tiles(b) - 1)) * cols; c3 = 0; c4 = kb0 * 2; step = 2;
        } else if (type == IT_BQ) {
          m = weights ? &p.wb[cols >> 7] : &p.xn;
        } else if (type == IT_BO || type == IT_OUT) {
          if (weights) m = &p.wc[cols >> 8];
          flag = SY_OB; need = type == IT_BO && b < 2 ? 32 : -1;
        } else {
          m = weights ? &p.wq : &p.xp;
          flag = SY_P + b * 4 + 1; need = ln_items(p.ch.layer, b);
        }
      }
      if (!weights) {
        c3 = b * 4;
        if (need < 0) pdl_wait(); else if (need) wait_count(p.sync + flag, need);
        if ((ln ? !part : part && (!qa || (code & C_EARLY))) && one) mbar_arrive(bGo);
      }
      const int boxes = weights ? nb : m != nullptr;
#pragma unroll 1
      for (; bytes > 0; bytes -= chunk) {
        const int now = min(bytes, chunk), len = ((now + 8191) >> 13) + nb, skip = pos + len > WK_SLOTS ? WK_SLOTS - pos : 0, sh = 4 * (seq & 7);
        used += len + skip;
        while (used > WK_SLOTS || seq - tail >= 8) {
          mbar_wait(bars + 64 + 8 * (tail & 7), (tail >> 3) & 1);
          used -= (lens >> 4 * (tail & 7)) & 15;
          tail++;
        }
        lens = (lens & ~(15u << sh)) | (len + skip) << sh;
        if (pos + len > WK_SLOTS) pos = 0;
        const uint32_t bar = bars + 2 * sh, dst = sb + pos * 8192 + weights * 16384;
        if (one) mbar_expect(bar, weights ? nb * 8192 : now);
#pragma unroll 1
        for (int i = 0; i < boxes; i++)
          if (one) tma_load5(dst + i * 8192, m, c0 + i * 64, c3, c4, bar);
        if (!weights && !m && one) bulk_load_last(dst, src, now, bar);
        if (weights) c4 += step; else c0 += 128;
        src += chunk; pos += len; seq++;
      }
    }
  }
}

__global__ void __launch_bounds__(384, 1) work_kernel(const __grid_constant__ WorkParams p) {
  extern __shared__ __align__(1024) uint8_t smem_raw[];
  const uint32_t sb = s2u(smem_raw), bars = sb + WK_BAR;
  const uint32_t bIF = bars + 128, bIE = bars + 160, done = bars + 192, bGo = bars + 224, slots = bars + 272, scratch = bars + 384;
  const int warp = __shfl_sync(~0u, threadIdx.x >> 5, 0);
  uint32_t* const sync = p.sync;
  TRACE(0);
  pdl_launch();
  if (p.kind == WK_LEAD && !helper_sm() && __syncthreads_or(threadIdx.x == 0 && ldg_strong32(sync + SY_PRE + 1) >= LEAD1)) { pdl_wait(); return; }
  if (p.kind == WK_CHAIN) {
    chain_start(p.ch, sb, warp);
  } else {
    if (warp < 4) work_init(sb, warp);
    __syncthreads();
    if (p.kind == WK_FIRST) {
      if (!(warp & 13)) probe_slots(bars + 320);
      if (!helper_sm()) return;
    }
  }
  if (warp >= 8) {
    asm volatile("setmaxnreg.dec.sync.aligned.u32 40;");
    if (p.kind == WK_CHAIN) chain_comm(p.ch, sb, &p.wo);
    const int warp = __shfl_sync(~0u, fresh_tid() >> 5, 0), lane = fresh_tid() & 31;
    if (warp == 9) {
      const bool keep = p.kind > WK_LEAD || helper_sm();
      int n = 0;
      if (p.kind == WK_CHAIN && reserved_item(blockIdx.x) >= 0) {
        if (lane == 0) { sts32(slots, reserved_item(blockIdx.x)); mbar_arrive(bIF); }
        n = 1;
      }
      const int b = lane & 15, layer = p.kind == WK_LAST ? 2 : sync != g_sync;
      bool first = layer == 1, lead = p.kind != WK_CHAIN;
      for (;; n++) {
        if (n > 0) mbar_wait(bGo, (n - 1) & 1);
        mbar_wait(bIE + 8 * (n & 3), ((n >> 2) & 1) ^ 1);
        int code = -1;
        if (lead) {
          int i = blockIdx.x + n * 256;
          if (first) { if (lane == 0) i = atomicAdd(sync + SY_PRE + 1, 1); i = __shfl_sync(~0u, i, 0); first = i < LEAD1; }
          if (layer < 2 && !first) {
            if (lane == 0) i = keep ? atomicAdd(sync + SY_PRE, 1) + layer * LEAD1 : 1 << 20;
            i = __shfl_sync(~0u, i, 0);
            if (!keep) pdl_wait();
          }
          code = lead_item(layer, p.qa_end, i);
          lead = code >= 0 || layer == 2 || !keep;
          if (!lead && p.kind <= WK_LEAD) {
            const uint32_t t0 = gtime();
            while (!lead && __all_sync(~0u, ldg_strong32(sync + SY_UP) < 96)) lead = __any_sync(~0u, gtime() - t0 > 20000);
          }
        }
        if (!lead) {
          int spin = 0, ticket = 0;
          if (lane == 0) ticket = atomicAdd(sync + SY_T, 1);
          for (;;) {
            const uint4 hd = ldg_strong128(sync + b * 8), pr = ldg_strong128(sync + b * 8 + 4);
            const uint32_t hv[4] = {hd.x, hd.y, hd.z, hd.w}, pv[4] = {pr.x, pr.y, pr.z, pr.w};
            const uint32_t chain_done = __ballot_sync(~0u, (pr.x & 0xffff) >= 96);
            int left[4], avail[4], rdy = 0, claimed = 0, upstream = 0;
#pragma unroll
            for (int t = 0; t < 4; t++) {
              const int cnt = lane < 16 && !reserved(t, b) ? item_count(t, b) : 0;
              left[t] = max(cnt - (int)hv[t], 0);
              claimed += cnt - left[t];
              const bool ready = (pv[t] & 0xffff) >= item_need(t, b);
              rdy |= ready << t;
              bool ok = ready || (t != IT_ATT && (chain_done >> 15 & 1) && !left[t - 1] && (t < 2 || !left[t - 2]));
              if (t == IT_BQ && (chain_done >> 12 & 9) == 1) ok = false;
              avail[t] = ok ? left[t] : 0;
              upstream |= __any_sync(~0u, left[t] > 0);
            }
            if (!upstream) { code = -1; break; }
            int rank = max(__shfl_sync(~0u, ticket, 0) - __reduce_add_sync(~0u, claimed), 0), type = -1, mine = 0;
#pragma unroll
            for (int c = 0; c < 7; c++) {
              const int t = c == 0 || c == 4 ? IT_FIN : c == 1 || c == 6 ? IT_ATT : c == 2 ? IT_OP : IT_BQ;
              int a = c == 1 || c == 2 || ((rdy >> t & 1) == (c < 4)) ? avail[t] : 0;
              if (c == 6) a = b < p.qa_end && !(rdy & 1) && ((chain_done << 1 | 1) >> b & 1) ? left[t] : 0;
              const int tot = __reduce_add_sync(~0u, a);
              if (type < 0) { if (rank < tot) { type = t; mine = a; } else rank -= tot; }
            }
            if (type >= 0) {
#pragma unroll
              for (int o = 1; o < 16; o <<= 1) { const int y = __shfl_up_sync(~0u, mine, o); if (lane >= o) mine += y; }
              const int blk = __ffs(__ballot_sync(~0u, mine > rank)) - 1;
              const int early = !(__shfl_sync(~0u, rdy, blk) >> type & 1);
              uint32_t idx = 0;
              if (lane == 0) idx = atomicAdd(sync + blk * 8 + type, 1);
              idx = __shfl_sync(~0u, idx, 0);
              if (idx < item_count(type, blk)) { code = (chain_done >> 14 & 1) << 22 | early << 20 | type << 16 | blk << 8 | idx; break; }
            } else {
              __nanosleep(50);
            }
            spin_guard(spin);
          }
        }
        if (lane == 0) {
          sts32(slots + 4 * (n & 3), code);
          mbar_arrive(bIF + 8 * (n & 3));
        }
        __syncwarp();
        if (code < 0) break;
      }
    } else if (warp >= 10) {
      work_loader(p, sb, warp == 10);
    } else {
      for (int n = 0;; n++) {
        mbar_wait(bIF + 8 * (n & 3), (n >> 2) & 1);
        const int code = __shfl_sync(~0u, (int)lds32(slots + 4 * (n & 3)), 0);
        if (code < 0) break;
        const int type = (code >> 16) & 15, b = (code >> 8) & 255;
        mbar_wait(done + 8 * (n & 3), (n >> 2) & 1);
        if (elect()) {
          if (type != IT_OUT) red_release(sync + (type < IT_BQ ? b * 8 + 5 + type : SY_P + b * 4 + ((0x13102 >> 4 * (type - IT_BQ)) & 3)), 1);
          mbar_arrive(bIE + 8 * (n & 3));
        }
        __syncwarp();
      }
    }
  } else {
    asm volatile("setmaxnreg.inc.sync.aligned.u32 232;");
    if (p.kind == WK_CHAIN) chain_compute(p.ch, sb);
    const int warp = __shfl_sync(~0u, fresh_tid() >> 5, 0), lane = fresh_tid() & 31;
    Ring r{sb, 0, p.kind == WK_CHAIN};
    Pending pend = {};
    int nln = 0;
    auto projects = [&](int n) {
      uint32_t here;
      asm volatile("{.reg .pred p; mbarrier.test_wait.parity.shared::cta.b64 p, [%1], %2; vote.sync.all.pred p, p, 0xffffffff; selp.u32 %0, 1, 0, p;}" : "=r"(here) : "r"(bIF + 8 * (n & 3)), "r"((n >> 2) & 1) : "memory");
      if (!here) return false;
      const int code = __shfl_sync(~0u, (int)lds32(slots + 4 * (n & 3)), 0);
      return code >= 0 && (((code >> 16) & 15) == IT_Q || (((code >> 16) & 15) == IT_ATT && ((code >> 8) & 255) < p.qa_end));
    };
#pragma unroll 1
    for (int n = 0;; n++) {
      if (pend.done && !projects(n)) pend.flush();
      mbar_wait(bIF + 8 * (n & 3), (n >> 2) & 1);
      const int code = __shfl_sync(~0u, (int)lds32(slots + 4 * (n & 3)), 0);
      if (code < 0) { TRACE(2); break; }
      const int type = (code >> 16) & 15, b = (code >> 8) & 255, idx = code & 255;
      const uint32_t go = (code & C_LATE) || (type == IT_ATT && (code & C_EARLY)) ? 0 : bGo;
      ITEM(code & 0xfffff, 0);
      if (type == IT_ATT || type == IT_Q) {
        if (type == IT_Q || b < p.qa_end) {
          float d[96] = {};
          reg_fence<96>(d);
          ITEM(9 << 16 | (code & 0xffff), 0);
          gemm_item<192>(d, r, 10, go, 4, pend);
          ITEM(9 << 16 | (code & 0xffff), 1);
#pragma unroll
          for (int i = 0; i < 48; i++) pend.w[i] = pack2(d[2 * i], d[2 * i + 1]);
        } else {
          const uint32_t base = r.wait(6) + warp * 2048 + lane * 16;
#pragma unroll
          for (int i = 0; i < 12; i++) {
            const uint4 t = lds128(base + (i >> 2) * 16384 + (i & 3) * 512);
            pend.w[4 * i] = t.x; pend.w[4 * i + 1] = t.y; pend.w[4 * i + 2] = t.z; pend.w[4 * i + 3] = t.w;
          }
          __syncwarp();
          r.release(r.seq - 1);
        }
        const bool now = type == IT_ATT && !projects(n + 1);
        if (type == IT_Q) {
          pend.dst = g_q + (b * 32 + idx) * 3072 + warp * 128 + lane;
        } else {
          pend.dst = g_o + (b * 32 + idx) * 3072 + (warp & 3) * 256 + (warp >> 2) * 128 + (lane & 3) * 8 + (lane >> 2);
          attn_a_warp(r, pend, now, warp);
        }
        pend.done = done + 8 * (n & 3);
        if (now) pend.finish();
      } else {
        if (type == IT_FIN || type == IT_LN || type == IT_LN0) {
          const int ng = item_groups(type, b);
          const int planes = type == IT_FIN ? op_split(b) + 1 : type == IT_LN ? 2 : 1;
#pragma unroll 1
          for (int i = 0; i < ng; i += 2) ln_groups(r, scratch + (nln++ & 1) * 1024, planes, b * 16 + idx * ng + i, ng > 1);
        } else {
          const int cols = item_cols(type, b), nkb = type == IT_OP ? op_steps(b) : 10;
          float d[160] = {};
          if (type == IT_OUT) {
            const uint2* x = g_x + ((b * 16 + warp * 2) * 680 + idx * 5) * 32 + lane;
#pragma unroll
            for (int i = 0; i < 10; i++) { const uint2 y = __ldcg(x + (i / 5 * 680 + i % 5) * 32); d[40 + 2 * i] = __uint_as_float(y.x); d[41 + 2 * i] = __uint_as_float(y.y); }
          }
          reg_fence<160>(d);
          if (type != IT_OUT) ITEM((type == IT_BQ ? 10 : 11) << 16 | (code & 0xffff), 0);
          const int ask = max(nkb - ((code & C_TAIL ? GO_TAIL : GO_320) << (2 - (cols >> 7))), 0);
          if (cols == 320) gemm_item<320>(d, r, nkb, go, ask, pend);
          else if (cols == 160) gemm_item<160>(d, r, nkb, go, ask, pend);
          else gemm_item<80>(d, r, nkb, go, ask, pend);
          if (type != IT_OUT) ITEM((type == IT_BQ ? 10 : 11) << 16 | (code & 0xffff), 1);
          reg_fence<160>(d);
          if (type == IT_OUT) {
            bar_sync(1, 256);
            const uint32_t dst = sb + (warp * 16 + (lane & 15)) * 160 + (lane >> 4) * 16;
#pragma unroll
            for (int u = 0; u < 5; u++) {
              uint32_t w[4];
#pragma unroll
              for (int i = 0; i < 4; i++) { const uint32_t y = __float_as_uint(d[40 + (i & 1) * 10 + 2 * u + (i >> 1)]); w[i] = pack2(bf_lo(y) + d[8 * u + 2 * i], bf_hi(y) + d[8 * u + 2 * i + 1]); }
              stsm4(dst + u * 32, w[0], w[1], w[2], w[3]);
            }
            fence_async();
            __syncwarp();
            if (elect()) { tma_store(&p.out, sb + warp * 2560, idx * 80, b * 128 + warp * 16); bulk_commit(); bulk_wait<0>(); }
          } else {
            if (warp >= 4) bar_sync(7, 256);
            if (type == IT_BQ) store_bqkv(d, b, idx, 4 << (cols >> 7));
            else store_partial(d, b, cols == 320 ? idx >> 1 : idx >> 2, cols == 320 ? (idx & 1) * 20 : (idx & 3) * 10, cols >> 4);
            if (warp < 4) bar_arrive(7, 256);
          }
        }
        __syncwarp();
        if (elect()) mbar_arrive(done + 8 * (n & 3));
#pragma unroll
        for (int i = 0; i < 48; i++) pend.w[i] = 0;
      }
      if ((code & C_LATE) && warp == 4 && elect()) mbar_arrive(bGo);
      ITEM(code & 0xfffff, 1);
    }
  }
}

constexpr int AB_SMEM = 1024 + 2 * 98304 + 256;
#define AB_N 32
#define AB_WG 4
constexpr int AB_T = AB_WG * 128, AB_PASS = 8 / AB_WG;
__device__ __forceinline__ float ex2_poly(float t) {
  const uint32_t r = __float_as_uint(t) & 0xffff8000u;
  const float f = t - __uint_as_float(r);
  const float p = fmaf(fmaf(fmaf(-5.869912678e-38f, f, -1.700740250e-37f), f, -5.234869734e-37f), f, -7.522601252e-37f);
  uint32_t y;
  asm("mad.lo.u32 %0, %1, 256, %2;" : "=r"(y) : "r"(r), "r"(__float_as_uint(p)));
  return __uint_as_float(y);
}
__device__ __forceinline__ uint32_t hsq(uint32_t w, uint32_t c) { uint32_t r; asm("fma.rn.bf16x2 %0, %1, %1, %2;" : "=r"(r) : "r"(w), "r"(c)); return r; }
__device__ __forceinline__ float sq2(uint32_t w) { const float a = bf_lo(w), b = bf_hi(w); return fmaf(a, a, b * b); }

__device__ __forceinline__ void attn_b_store(const float* o, int h, int row0, int lane) {
  const int g = lane >> 2, c = lane & 3;
  const float i0 = rcp(__shfl_sync(~0u, o[8], (lane & ~3) | 2)), i1 = rcp(__shfl_sync(~0u, o[10], (lane & ~3) | 2));
#pragma unroll
  for (int jj = 0; jj < 3; jj++) {
    if (jj < 2 || c < 2) {
      const int col = h * 20 + 8 * jj + 2 * c;
      g_of[core_word(row0 + g, col)] = pack2(o[4 * jj] * i0, o[4 * jj + 1] * i0);
      g_of[core_word(row0 + g + 8, col)] = pack2(o[4 * jj + 2] * i1, o[4 * jj + 3] * i1);
    }
  }
}

__device__ __forceinline__ void attn_b_qk(float* s, uint32_t q0, uint32_t q1, uint32_t q2, uint32_t q3, uint32_t q4, uint32_t q5, uint32_t z0, uint32_t z1,
                                          uint64_t dk, uint64_t dk2) {
  wg_rs32_00(s, q0, q1, q2, q3, dk, 0);
  wg_rs32_00(s, q4, q5, z0, z1, dk2, 1);
}

struct AttnParams { const uint8_t* pf[4]; uint32_t *sync, *next; };
__global__ void __launch_bounds__(AB_T + 128, 1) attn_b_kernel(const __grid_constant__ AttnParams p) {
  extern __shared__ uint8_t smem_raw[];
  const uint32_t sb = (s2u(smem_raw) + 1023) & ~1023u, sK = sb, sV = sb + 98304, bars = sb + 2 * 98304;
  const int warp = __shfl_sync(~0u, threadIdx.x >> 5, 0), lane = threadIdx.x & 31;
  const int h = blockIdx.x & 31, quarter = blockIdx.x >> 5;
  BT(0);
  TRACE(0);
  if (warp < 10 && elect()) {
    mbar_init(bars + 8 * warp + (warp & 8) * 8, warp < 8 ? 1 : warp == 8 ? AB_T / 32 : 2);
    asm volatile("fence.mbarrier_init.release.cluster;" ::: "memory");
  }
  __syncthreads();
  if (warp >= AB_T / 32) {
    asm volatile("setmaxnreg.dec.sync.aligned.u32 32;");
    if (warp == AB_T / 32 + 1) return;
    if (warp > AB_T / 32) {
      uint32_t kmax = 0;
#pragma unroll 1
      for (int i = 0; i < 32; i++) {
        if (!(i & 3)) mbar_wait(bars + 2 * i, 0);
        const uint32_t a = sK + i * 3072 + ((threadIdx.x >> 3) & 7) * 384 + (lane & 7) * 16;
        const uint4 x = lds128(a), y = lds128(a + 128);
        const uint2 z = lds64(a + 256);
        const uint32_t n = hadd2(hsq(x.x, hsq(x.y, hsq(x.z, hsq(x.w, hsq(z.x, 0))))), hsq(y.x, hsq(y.y, hsq(y.z, hsq(y.w, hsq(z.y, 0))))));
        kmax = max(kmax, __float_as_uint(bf_lo(n) + bf_hi(n)) & 0x7fffffffu);
      }
      const uint32_t kbits = __reduce_max_sync(~0u, kmax);
      if (lane == 0) { sts32(bars + 64 + (warp & 1) * 4, kbits); mbar_arrive(bars + 136); }
      return;
    }
    const uint8_t* gk = reinterpret_cast<const uint8_t*>(g_bqkv + (32 + h) * 256 * 96);
    const uint8_t* gv = reinterpret_cast<const uint8_t*>(g_bqkv + (64 + h) * 256 * 96);
    uint32_t todo = 255;
    for (int spin = 0; todo;) {
      const uint32_t up = __ballot_sync(~0u, ld_acquire(p.sync + SY_P + (lane & 15) * 4 + 2) >= bq_items(lane & 15));
      fence_async_global();
#pragma unroll 1
      for (int i = 0; i < 8; i++) {
        if (!(todo >> i & 1) || (up >> 2 * i & 3) != 3) continue;
        todo &= ~(1u << i);
        if (elect()) {
          mbar_expect(bars + 8 * i, 24576);
          bulk_load(sK + i * 12288, gk + i * 12288, 12288, bars + 8 * i);
          bulk_load(sV + i * 12288, gv + i * 12288, 12288, bars + 8 * i);
        }
      }
      spin_guard(spin);
    }
    pdl_launch();
    TRACE(1);
#pragma unroll 1
    for (int i = lane; i < 512 && blockIdx.x < NSLOT; i += 32) reinterpret_cast<uint4*>(pool_at(blockIdx.x * 8192))[i] = make_uint4(0, 0, 0, 0);
    if (!p.next && blockIdx.x < 8) { const int i = blockIdx.x * 32 + lane; g_smpart[i] = 0; if (i < NSLOT) g_orient[i] = 0; }
    if (p.next) {
      mbar_wait(bars + 128, 0);
      if (quarter == 0 && lane == 0) red_release(p.next + SY_OB, 1);
#pragma unroll 1
      for (int i = 0; i < (PF_NS ? 32 : 0); i++) {
        if (elect()) prefetch_l2(p.pf[i >> 3] + blockIdx.x * 61440 + (i & 7) * 7680, 7680);
        __nanosleep(PF_NS);
      }
    }
    return;
  }
  asm volatile("setmaxnreg.inc.sync.aligned.u32 112;");
  constexpr int NT = SEQ / AB_N, PER = 256 / AB_N;
  uint32_t qn[8];
  auto load_q = [&](int pass) {
    const uint32_t* gq = g_bqkv + (h * 256 + pass * 128 + quarter * 32 + warp * 2) * 96 + lane;
#pragma unroll
    for (int i = 0; i < 8; i++) qn[i] = __ldcg(gq + (i & 1) * 96 + min(i >> 1, 2) * 32 + (i < 6 ? 0 : 3 - (lane & 3)));
  };
  mbar_wait(bars + 8 * quarter, 0);
  load_q(0);
#pragma unroll 1
  for (int pass = 0; pass < AB_PASS; pass++) {
    const int row0 = pass * 1024 + quarter * 256 + warp * 16;
    const uint32_t q0 = qn[0], q1 = qn[1], q2 = qn[2], q3 = qn[3], z0 = qn[6], z1 = qn[7];
    uint32_t q4 = qn[4], q5 = qn[5];
    if ((lane & 3) == 2) { q4 = 0x43BCu; q5 = 0x43BCu; }
    float o[12];
    uint64_t dk = mkdesc(sK, 128, 384, 0), dk2 = mkdesc(sK + 256, 0, 384, 0), dv = mkdesc(sV, 384, 128, 0);
    float sa[AB_N / 2], sb2[AB_N / 2];
    uint32_t pa[AB_N / 4], pb[AB_N / 4];
    if (pass == 0) mbar_wait(bars, 0);
    BT(1 + 2 * pass);
    wg_fence();
    attn_b_qk(sa, q0, q1, q2, q3, q4, q5, z0, z1, dk, dk2);
    wg_commit();
    attn_b_qk(sb2, q0, q1, q2, q3, q4, q5, z0, z1, dk + AB_N * 3, dk2 + AB_N * 3);
    wg_commit();
#pragma unroll 1
    for (int kt = 0; kt < NT; kt += 2) {
      const int nx = kt + 2 < NT ? kt + 2 : 0;
      if (pass == 0 && (nx & (PER - 1)) == 0) mbar_wait(bars + 8 * (nx / PER), 0);
      const uint64_t nk = dk + nx * (AB_N * 3), nk2 = dk2 + nx * (AB_N * 3);
      wg_wait<1>();
      reg_fence<AB_N / 2>(sa);
#pragma unroll
      for (int i = 0; i < AB_N / 4; i++) pa[i] = pack2(ex2(sa[2 * i]), poly_group(i >> 1) ? ex2_poly(sa[2 * i + 1]) : ex2(sa[2 * i + 1]));
      wg_fence();
#pragma unroll
      for (int kk = 0; kk < AB_N / 16; kk++) wg_rs24_01(o, pa[4 * kk], pa[4 * kk + 1], pa[4 * kk + 2], pa[4 * kk + 3], dv + kk * 48, kk | kt);
      attn_b_qk(sa, q0, q1, q2, q3, q4, q5, z0, z1, nk, nk2);
      wg_commit();
      wg_wait<1>();
      reg_fence<AB_N / 2>(sb2);
#pragma unroll
      for (int i = 0; i < AB_N / 4; i++) pb[i] = pack2(ex2(sb2[2 * i]), poly_group((i >> 1) + AB_N / 8) ? ex2_poly(sb2[2 * i + 1]) : ex2(sb2[2 * i + 1]));
      wg_fence();
#pragma unroll
      for (int kk = 0; kk < AB_N / 16; kk++) wg_rs24_01(o, pb[4 * kk], pb[4 * kk + 1], pb[4 * kk + 2], pb[4 * kk + 3], dv + AB_N * 3 + kk * 48, 1);
      attn_b_qk(sb2, q0, q1, q2, q3, q4, q5, z0, z1, nk + AB_N * 3, nk2 + AB_N * 3);
      wg_commit();
      dv += AB_N * 6;
    }
    wg_wait<0>();
    reg_fence<12>(o); reg_fence<AB_N / 2>(sa); reg_fence<AB_N / 2>(sb2);
    BT(2 + 2 * pass);
    if (pass + 1 < AB_PASS) load_q(pass + 1);
    mbar_wait(bars + 136, 0);
    const uint2 kb = lds64(bars + 64);
    const float kmax = __uint_as_float(max(kb.x, kb.y));
    if ((lane & 3) == 2) q4 = q5 = 0;
    float n0 = sq2(q0) + sq2(q2) + sq2(q4), n1 = sq2(q1) + sq2(q3) + sq2(q5);
    n0 += __shfl_xor_sync(~0u, n0, 1); n1 += __shfl_xor_sync(~0u, n1, 1);
    n0 += __shfl_xor_sync(~0u, n0, 2); n1 += __shfl_xor_sync(~0u, n1, 2);
    uint32_t redo;
    asm volatile("{.reg .pred p, q; setp.ne.u32 p, %1, 0; bar.red.or.pred q, %2, 128, p; selp.u32 %0, 1, 0, q;}"
                 : "=r"(redo) : "r"((uint32_t)!(n0 * kmax <= 9500.f && n1 * kmax <= 9500.f)), "r"(2 + (warp >> 2)) : "memory");
    if (redo) {
#pragma unroll
      for (int i = 0; i < 12; i++) o[i] = 0.f;
      float m0 = -INFINITY, m1 = -INFINITY;
#pragma unroll 1
      for (int kt = 0; kt < 64; kt++) {
        float s[16];
        wg_fence();
        wg_rs32_00(s, q0, q1, q2, q3, dk + kt * 96, 0);
        wg_rs32_00(s, q4, q5, z0, z1, dk2 + kt * 96, 1);
        wg_commit();
        wg_wait<0>();
        reg_fence<16>(s); reg_fence<12>(o);
        float n0 = m0, n1 = m1;
#pragma unroll
        for (int jj = 0; jj < 4; jj++) { n0 = fmaxf(n0, fmaxf(s[4 * jj], s[4 * jj + 1])); n1 = fmaxf(n1, fmaxf(s[4 * jj + 2], s[4 * jj + 3])); }
        n0 = fmaxf(n0, __shfl_xor_sync(~0u, n0, 1)); n0 = fmaxf(n0, __shfl_xor_sync(~0u, n0, 2));
        n1 = fmaxf(n1, __shfl_xor_sync(~0u, n1, 1)); n1 = fmaxf(n1, __shfl_xor_sync(~0u, n1, 2));
        const float r0 = ex2(m0 - n0), r1 = ex2(m1 - n1);
        m0 = n0; m1 = n1;
#pragma unroll
        for (int jj = 0; jj < 3; jj++) { o[4 * jj] *= r0; o[4 * jj + 1] *= r0; o[4 * jj + 2] *= r1; o[4 * jj + 3] *= r1; }
        uint32_t pp[8];
#pragma unroll
        for (int jj = 0; jj < 4; jj++) {
          pp[2 * jj] = pack2(ex2(s[4 * jj] - m0), ex2(s[4 * jj + 1] - m0));
          pp[2 * jj + 1] = pack2(ex2(s[4 * jj + 2] - m1), ex2(s[4 * jj + 3] - m1));
        }
        reg_fence<12>(o);
        wg_fence();
#pragma unroll
        for (int kk = 0; kk < 2; kk++) wg_rs24_01(o, pp[4 * kk], pp[4 * kk + 1], pp[4 * kk + 2], pp[4 * kk + 3], mkdesc(sV, 384, 128, 0) + kt * 96 + kk * 48, 1);
        wg_commit();
      }
      wg_wait<0>();
      reg_fence<12>(o);
    }
    attn_b_store(o, h, row0, lane);
    __syncwarp();
    if (pass == 0 && lane == 0) mbar_arrive(bars + 128);
  }
  BT(5);
  TRACE(2);
}

typedef CUresult (*EncodeFn)(CUtensorMap*, CUtensorMapDataType, cuuint32_t, void*, const cuuint64_t*, const cuuint64_t*,
                             const cuuint32_t*, const cuuint32_t*, CUtensorMapInterleave, CUtensorMapSwizzle,
                             CUtensorMapL2promotion, CUtensorMapFloatOOBfill);

void make_map(EncodeFn enc, CUtensorMap* m, const void* ptr, int cols, int rows, int box_rows, int box_cols = 64) {
  const cuuint64_t dims[2] = {(cuuint64_t)cols, (cuuint64_t)rows};
  const cuuint64_t strides[1] = {(cuuint64_t)cols * 2};
  const cuuint32_t box[2] = {(cuuint32_t)box_cols, (cuuint32_t)box_rows}, es[2] = {1, 1};
  enc(m, CU_TENSOR_MAP_DATA_TYPE_BFLOAT16, 2, const_cast<void*>(ptr), dims, strides, box, es, CU_TENSOR_MAP_INTERLEAVE_NONE,
      box_cols == 64 ? CU_TENSOR_MAP_SWIZZLE_128B : box_cols == 32 ? CU_TENSOR_MAP_SWIZZLE_64B : CU_TENSOR_MAP_SWIZZLE_NONE, CU_TENSOR_MAP_L2_PROMOTION_L2_256B, CU_TENSOR_MAP_FLOAT_OOB_FILL_NONE);
}
void make_map5(EncodeFn enc, CUtensorMap* m, const void* ptr, bool words, const cuuint64_t (&dims)[5], const cuuint64_t (&strides)[4], const cuuint32_t (&box)[5]) {
  const cuuint32_t es[5] = {1, 1, 1, 1, 1};
  enc(m, words ? CU_TENSOR_MAP_DATA_TYPE_UINT64 : CU_TENSOR_MAP_DATA_TYPE_BFLOAT16, 5, const_cast<void*>(ptr), dims, strides, box, es, CU_TENSOR_MAP_INTERLEAVE_NONE,
      words ? CU_TENSOR_MAP_SWIZZLE_NONE : CU_TENSOR_MAP_SWIZZLE_128B, dims[0] % 64 ? CU_TENSOR_MAP_L2_PROMOTION_L2_128B : CU_TENSOR_MAP_L2_PROMOTION_L2_256B,
      CU_TENSOR_MAP_FLOAT_OOB_FILL_NONE);
}
void make_tiles(EncodeFn enc, CUtensorMap* m, const void* ptr, cuuint64_t cols, cuuint64_t tile) {
  make_map5(enc, m, ptr, false, {tile, 1, 1, cols / tile, DM}, {tile * 2, tile * 2, tile * 2, cols * 2}, {64, 1, 1, 1, 64});
}
template <class... KA, class... A>
void launch(void (*kern)(KA...), int grid, int block, int smem, int cluster, bool pdl, A... args) {
  cudaFuncSetAttribute(kern, cudaFuncAttributeMaxDynamicSharedMemorySize, smem);
  cudaLaunchConfig_t cfg = {};
  cfg.gridDim = dim3(grid); cfg.blockDim = dim3(block); cfg.dynamicSmemBytes = smem; cfg.stream = cudaStreamPerThread;
  cudaLaunchAttribute at[2];
  int n = 0;
  if (cluster > 1) { at[n].id = cudaLaunchAttributeClusterDimension; at[n].val.clusterDim.x = cluster; at[n].val.clusterDim.y = 1; at[n].val.clusterDim.z = 1; n++; }
  if (pdl) { at[n].id = cudaLaunchAttributeProgrammaticStreamSerialization; at[n].val.programmaticStreamSerializationAllowed = 1; n++; }
  cfg.attrs = at; cfg.numAttrs = n;
  cudaLaunchKernelEx(&cfg, kern, args...);
}
template <class T> void* sym(T& s) { void* p = nullptr; cudaGetSymbolAddress(&p, s); return p; }

}

#define MODE(b) 0
extern "C" void kernel_launch(void* const* d_in, const int* in_sizes, int n_in, void* d_out, int out_size) {
  const __nv_bfloat16* x = (const __nv_bfloat16*)d_in[0];
  void* fn = nullptr; cudaDriverEntryPointQueryResult qr;
  cudaGetDriverEntryPoint("cuTensorMapEncodeTiled", &fn, cudaEnableDefault, &qr);
  EncodeFn enc = (EncodeFn)fn;

  WorkParams wk = {};
  ChainParams& ch = wk.ch;
  AttnParams at = {};
  make_map(enc, &ch.wq, d_in[2], HD, DM, 160); make_map(enc, &ch.wk, d_in[3], HD, DM, 160); make_map(enc, &ch.wv, d_in[4], HD, DM, 160);
  make_map(enc, &ch.wo, d_in[5], DM, HD, 192, 32);
  ch.mem0 = (const __nv_bfloat16*)d_in[1];
  ch.wb = (const uint8_t*)d_in[8];
  ch.d1 = 250; ch.d2 = 200; ch.dn = 150; ch.dx = 950;
  make_tiles(enc, &wk.wq, d_in[2], HD, 192);
  for (int i = 0; i < 3; i++) make_tiles(enc, &wk.wb[i], d_in[8], 1920, 80 << i);
  for (int i = 0; i < 2; i++) make_tiles(enc, &wk.wc[i], d_in[9], DM, 80 << 2 * i);
  make_map(enc, &wk.out, d_out, DM, SEQ, 16, 80);
  make_map5(enc, &wk.wo, d_in[5], false, {DM, 2, 4, 4, HD / 32}, {DM * 2, DM * 16, DM * 4, DM * 64}, {64, 2, 4, 4, 2});
  make_map5(enc, &wk.xn, sym(g_xn), true, {1280, 2, 2, 64, 1}, {10240, 20480, 40960, 40960}, {128, 2, 2, 4, 1});
  make_map5(enc, &wk.xp, sym(g_xn), true, {1280, 2, 1, 64, 2}, {10240, 10240, 40960, 20480}, {128, 2, 1, 4, 2});
  make_map5(enc, &ch.xc, sym(g_xn), true, {160, 1, 1, 256, 8}, {1280, 1280, 10240, 1280}, {160, 1, 1, 4, 2});
  wk.x = x;
  for (int i = 0; i < 4; i++) at.pf[i] = (const uint8_t*)d_in[i < 2 ? 3 + i : i == 2 ? 2 : 5];
  int qa_end[2] = {12, 12};
  for (int layer = 0; layer < 2; layer++) {
    ch.sync = wk.sync = at.sync = (uint32_t*)sym(g_sync) + layer * SY_N;
    ch.other = (uint32_t*)sym(g_sync) + (1 - layer) * SY_N;
    ch.layer = layer;
    at.next = layer ? nullptr : ch.other;
    wk.qa_end = qa_end[layer];
    wk.kind = layer ? WK_LEAD : WK_FIRST;
    launch(work_kernel, 132, 384, CH_SMEM, 1, layer != 0, wk);
    wk.kind = WK_CHAIN;
    launch(work_kernel, 96, 384, CH_SMEM, 3, true, wk);
    launch(attn_b_kernel, 128, AB_T + 128, AB_SMEM, 1, true, at);
  }
  wk.kind = WK_LAST;
  launch(work_kernel, 128, 384, CH_SMEM, 1, true, wk);
}
```

```cpp
#include <cuda_runtime.h>
#include <cuda_bf16.h>
#include <cuda.h>
#include <stdint.h>
#include <stdlib.h>

namespace {

constexpr int SEQ = 2048, DM = 640, HD = 6144, NSEG = 64;
constexpr int SPIN_LIMIT = 1 << 20;

__device__ __align__(128) uint2 g_x[256 * 17 * 1280];
__device__ __align__(128) uint32_t g_xn[SEQ * DM / 2];
__device__ __align__(128) uint32_t g_of[SEQ * DM / 2];
__device__ __align__(128) uint4 g_o[SEQ * HD / 8];
__device__ __align__(128) uint4 g_q[SEQ * HD / 8];
constexpr int KV_M = 16384, KV_PART = 20480, KV_V = 3 * KV_PART;
__device__ __align__(128) uint8_t g_kv[16 * 32 * 6 * KV_PART];
#define OP_B8 11
#define OP_B16 14
#define OP_N4 16
#define BQ_12 12
#define BQ_24 14
#define FIN_16 12
__host__ __device__ constexpr int op_split(int b) { return b < OP_B8 ? 4 : b < OP_B16 ? 8 : 16; }
__host__ __device__ constexpr int op_steps(int b) { return b < OP_B8 ? 24 : b < OP_B16 ? 12 : 6; }
__host__ __device__ constexpr int op_tiles(int b) { return b < OP_N4 ? 2 : 4; }
__host__ __device__ constexpr int fin_items(int b) { return b < OP_B8 ? 4 : b < FIN_16 ? 8 : 16; }
__host__ __device__ constexpr int bq_items(int b) { return b < BQ_12 ? 6 : b < BQ_24 ? 12 : 24; }
__host__ __device__ constexpr int ln_items(int layer, int b) { return layer == 0 && b < 2 ? 16 : 4; }
constexpr int SY_P = 128, SY_T = 192, SY_UP = 224, SY_OB = 225, SY_PRE = 256, SY_PART = 288, SY_TIME = 384, SY_N = 448;
__device__ __align__(128) uint32_t g_sync[2 * SY_N];
constexpr int NSLOT = 92;
__device__ uint32_t g_pool[(NSLOT + 2) * 2048];
__device__ uint32_t g_smpart[256], g_orient[NSLOT];
__device__ __align__(128) uint32_t g_bqkv[3 * 32 * 256 * 96];

#define BT(i)
#define MISS(k, n)
#define PRO(i)
#define TRACE(w)
#define ITEM(code, w)
#define STAT(k)
#define TMV(i, v)
#define TM(i)
#define TMD(i, dep)

__device__ __forceinline__ uint32_t gtime() { uint32_t c; asm volatile("mov.u32 %0, %%globaltimer_lo;" : "=r"(c) :: "memory"); return c; }
__device__ __forceinline__ uint32_t clk32() { uint32_t c; asm volatile("mov.u32 %0, %%clock;" : "=r"(c) :: "memory"); return c; }
__device__ __forceinline__ uint32_t fresh_tid() { uint32_t t; asm volatile("mov.u32 %0, %%tid.x;" : "=r"(t)); return t; }
__device__ __forceinline__ uint32_t s2u(const void* p) { return (uint32_t)__cvta_generic_to_shared(p); }
__device__ __forceinline__ uint32_t pack2(float a, float b) {
  uint32_t r; asm("cvt.rn.bf16x2.f32 %0, %1, %2;" : "=r"(r) : "f"(b), "f"(a)); return r; }
__device__ __forceinline__ float bf_lo(uint32_t w) { return __uint_as_float(w << 16); }
__device__ __forceinline__ float bf_hi(uint32_t w) { return __uint_as_float(w & 0xffff0000u); }
__device__ __forceinline__ float ex2(float x) { float y; asm("ex2.approx.ftz.f32 %0, %1;" : "=f"(y) : "f"(x)); return y; }

__device__ __forceinline__ void mbar_init(uint32_t bar, uint32_t n) {
  asm volatile("mbarrier.init.shared::cta.b64 [%0], %1;" :: "r"(bar), "r"(n) : "memory"); }
__device__ __forceinline__ void mbar_expect(uint32_t bar, uint32_t bytes) {
  asm volatile("mbarrier.arrive.expect_tx.shared::cta.b64 _, [%0], %1;" :: "r"(bar), "r"(bytes) : "memory"); }
__device__ __forceinline__ void mbar_arrive(uint32_t bar) {
  asm volatile("mbarrier.arrive.shared::cta.b64 _, [%0];" :: "r"(bar) : "memory"); }
__device__ __forceinline__ void mbar_arrive_remote(uint32_t bar) {
  asm volatile("mbarrier.arrive.shared::cluster.b64 _, [%0];" :: "r"(bar) : "memory"); }
__device__ __forceinline__ void mbar_wait(uint32_t bar, uint32_t ph) {
  asm volatile("{.reg .pred p; .reg .u32 n; mov.u32 n, 0;\n"
               "W: mbarrier.try_wait.parity.shared::cta.b64 p, [%0], %1; @p bra.uni D;\n"
               "add.u32 n, n, 1; setp.gt.u32 p, n, %2; @p trap; bra.uni W;\n"
               "D: }" :: "r"(bar), "r"(ph), "n"(SPIN_LIMIT) : "memory");
}
__device__ __forceinline__ bool elect() {
  uint32_t p; asm volatile("{.reg .pred q; elect.sync _|q, 0xffffffff; selp.u32 %0, 1, 0, q;}" : "=r"(p)); return p; }
__device__ __forceinline__ void spin_guard(int& n) {
  asm volatile("{.reg .pred p; add.s32 %0, %0, 1; setp.gt.s32 p, %0, %1; @p trap;}" : "+r"(n) : "n"(SPIN_LIMIT));
}
__device__ __forceinline__ void pdl_wait() { asm volatile("griddepcontrol.wait;" ::: "memory"); TRACE(1); }
__device__ __forceinline__ void pdl_launch() { asm volatile("griddepcontrol.launch_dependents;" ::: "memory"); }
__device__ __forceinline__ uint32_t ld_acquire(const uint32_t* p) { uint32_t v; asm volatile("ld.acquire.gpu.global.u32 %0, [%1];" : "=r"(v) : "l"(p) : "memory"); return v; }
__device__ __forceinline__ void red_release(uint32_t* p, uint32_t v) { asm volatile("red.release.gpu.global.add.u32 [%0], %1;" :: "l"(p), "r"(v) : "memory"); }
__device__ __forceinline__ void fence_async_global() { asm volatile("fence.proxy.async.global;" ::: "memory"); }
__device__ __forceinline__ void fence_async() { asm volatile("fence.proxy.async.shared::cta;" ::: "memory"); }
__device__ __forceinline__ void bar_sync(int id, int n) { asm volatile("bar.sync %0, %1;" :: "r"(id), "r"(n) : "memory"); }
__device__ __forceinline__ void bar_arrive(int id, int n) { asm volatile("bar.arrive %0, %1;" :: "r"(id), "r"(n) : "memory"); }
__device__ __forceinline__ void tma_load(uint32_t dst, const CUtensorMap* m, int c0, int c1, uint32_t bar) {
  asm volatile("cp.async.bulk.tensor.2d.shared::cluster.global.mbarrier::complete_tx::bytes [%0], [%1, {%3, %4}], [%2];"
               :: "r"(dst), "l"(m), "r"(bar), "r"(c0), "r"(c1) : "memory"); }
__device__ __forceinline__ void tma_load5(uint32_t dst, const CUtensorMap* m, int c0, int c3, int c4, uint32_t bar) {
  asm volatile("cp.async.bulk.tensor.5d.shared::cluster.global.mbarrier::complete_tx::bytes [%0], [%1, {%3, %6, %6, %4, %5}], [%2];"
               :: "r"(dst), "l"(m), "r"(bar), "r"(c0), "r"(c3), "r"(c4), "r"(0) : "memory"); }
__device__ __forceinline__ void tma_store(const CUtensorMap* m, uint32_t src, int c0, int c1) {
  asm volatile("cp.async.bulk.tensor.2d.global.shared::cta.bulk_group [%0, {%2, %3}], [%1];"
               :: "l"(m), "r"(src), "r"(c0), "r"(c1) : "memory"); }
__device__ __forceinline__ uint64_t evict_first() { uint64_t p; asm("createpolicy.fractional.L2::evict_first.b64 %0, 1.0;" : "=l"(p)); return p; }
__device__ __forceinline__ void bulk_load_last(uint32_t dst, const void* src, uint32_t bytes, uint32_t bar) {
  asm volatile("cp.async.bulk.shared::cluster.global.mbarrier::complete_tx::bytes.L2::cache_hint [%0], [%1], %2, [%3], %4;"
               :: "r"(dst), "l"(src), "r"(bytes), "r"(bar), "l"(evict_first()) : "memory"); }
__device__ __forceinline__ void bulk_store_stream(void* dst, uint32_t src, uint32_t bytes) {
  asm volatile("cp.async.bulk.global.shared::cta.bulk_group.L2::cache_hint [%0], [%1], %2, %3;" :: "l"(dst), "r"(src), "r"(bytes), "l"(evict_first()) : "memory"); }
__device__ __forceinline__ void bulk_load(uint32_t dst, const void* src, uint32_t bytes, uint32_t bar) {
  asm volatile("cp.async.bulk.shared::cluster.global.mbarrier::complete_tx::bytes [%0], [%1], %2, [%3];"
               :: "r"(dst), "l"(src), "r"(bytes), "r"(bar) : "memory"); }
__device__ __forceinline__ void bulk_push(uint32_t dst, uint32_t src, uint32_t bytes, uint32_t bar) {
  asm volatile("cp.async.bulk.shared::cluster.shared::cta.mbarrier::complete_tx::bytes [%0], [%1], %2, [%3];"
               :: "r"(dst), "r"(src), "r"(bytes), "r"(bar) : "memory"); }
__device__ __forceinline__ void bulk_store(void* dst, uint32_t src, uint32_t bytes) {
  asm volatile("cp.async.bulk.global.shared::cta.bulk_group [%0], [%1], %2;" :: "l"(dst), "r"(src), "r"(bytes) : "memory"); }
__device__ __forceinline__ void bulk_commit() { asm volatile("cp.async.bulk.commit_group;" ::: "memory"); }
template <int N> __device__ __forceinline__ void bulk_wait_read() { asm volatile("cp.async.bulk.wait_group.read %0;" :: "n"(N) : "memory"); }
template <int N> __device__ __forceinline__ void bulk_wait() { asm volatile("cp.async.bulk.wait_group %0;" :: "n"(N) : "memory"); }

__device__ __forceinline__ uint64_t mkdesc(uint32_t addr, uint32_t lbo, uint32_t sbo, uint32_t sw) {
  return (uint64_t)((addr & 0x3FFFF) >> 4) | ((uint64_t)(lbo >> 4) << 16) | ((uint64_t)(sbo >> 4) << 32) | ((uint64_t)sw << 62); }
__device__ __forceinline__ void wg_fence() { asm volatile("wgmma.fence.sync.aligned;" ::: "memory"); }
__device__ __forceinline__ void wg_commit() { asm volatile("wgmma.commit_group.sync.aligned;" ::: "memory"); }
template <int N> __device__ __forceinline__ void wg_wait() { asm volatile("wgmma.wait_group.sync.aligned %0;" :: "n"(N) : "memory"); }
template <int N> __device__ __forceinline__ void reg_fence(float* d) {
#pragma unroll
  for (int i = 0; i < N; i++) asm volatile("" : "+f"(d[i]) :: "memory");
}

__device__ __forceinline__ void mma16(float* d, uint32_t a0, uint32_t a1, uint32_t a2, uint32_t a3, uint32_t b0, uint32_t b1) {
  asm volatile("mma.sync.aligned.m16n8k16.row.col.f32.bf16.bf16.f32 {%0,%1,%2,%3},{%4,%5,%6,%7},{%8,%9},{%0,%1,%2,%3};"
               : "+f"(d[0]), "+f"(d[1]), "+f"(d[2]), "+f"(d[3]) : "r"(a0), "r"(a1), "r"(a2), "r"(a3), "r"(b0), "r"(b1)); }
__device__ __forceinline__ void mma8(float* d, uint32_t a0, uint32_t a1, uint32_t b0) {
  asm volatile("mma.sync.aligned.m16n8k8.row.col.f32.bf16.bf16.f32 {%0,%1,%2,%3},{%4,%5},{%6},{%0,%1,%2,%3};"
               : "+f"(d[0]), "+f"(d[1]), "+f"(d[2]), "+f"(d[3]) : "r"(a0), "r"(a1), "r"(b0)); }
__device__ __forceinline__ void ldsm4(uint32_t* r, uint32_t a) {
  asm volatile("ldmatrix.sync.aligned.m8n8.x4.shared.b16 {%0,%1,%2,%3},[%4];" : "=r"(r[0]), "=r"(r[1]), "=r"(r[2]), "=r"(r[3]) : "r"(a) : "memory"); }
__device__ __forceinline__ uint4 ldsm4v(uint32_t a) { uint32_t r[4]; ldsm4(r, a); return make_uint4(r[0], r[1], r[2], r[3]); }
__device__ __forceinline__ void ldsm4t(uint32_t* r, uint32_t a) {
  asm volatile("ldmatrix.sync.aligned.m8n8.x4.trans.shared.b16 {%0,%1,%2,%3},[%4];" : "=r"(r[0]), "=r"(r[1]), "=r"(r[2]), "=r"(r[3]) : "r"(a) : "memory"); }
__device__ __forceinline__ void ldsm2t(uint32_t* r, uint32_t a) {
  asm volatile("ldmatrix.sync.aligned.m8n8.x2.trans.shared.b16 {%0,%1},[%2];" : "=r"(r[0]), "=r"(r[1]) : "r"(a) : "memory"); }
__device__ __forceinline__ void stsm4(uint32_t a, uint32_t r0, uint32_t r1, uint32_t r2, uint32_t r3) {
  asm volatile("stmatrix.sync.aligned.m8n8.x4.shared.b16 [%0], {%1,%2,%3,%4};" :: "r"(a), "r"(r0), "r"(r1), "r"(r2), "r"(r3) : "memory"); }
__device__ __forceinline__ void stsm4t(uint32_t a, uint32_t r0, uint32_t r1, uint32_t r2, uint32_t r3) {
  asm volatile("stmatrix.sync.aligned.m8n8.x4.trans.shared.b16 [%0], {%1,%2,%3,%4};" :: "r"(a), "r"(r0), "r"(r1), "r"(r2), "r"(r3) : "memory"); }
__device__ __forceinline__ void stsm2(uint32_t a, uint32_t r0, uint32_t r1) {
  asm volatile("stmatrix.sync.aligned.m8n8.x2.shared.b16 [%0], {%1,%2};" :: "r"(a), "r"(r0), "r"(r1) : "memory"); }
__device__ __forceinline__ void stsm2t(uint32_t a, uint32_t r0, uint32_t r1) {
  asm volatile("stmatrix.sync.aligned.m8n8.x2.trans.shared.b16 [%0], {%1,%2};" :: "r"(a), "r"(r0), "r"(r1) : "memory"); }
__device__ __forceinline__ void sts32(uint32_t a, uint32_t v) { asm volatile("st.shared.b32 [%0], %1;" :: "r"(a), "r"(v) : "memory"); }
__device__ __forceinline__ void sts64f(uint32_t a, float x, float y) { asm volatile("st.shared.v2.f32 [%0], {%1,%2};" :: "r"(a), "f"(x), "f"(y) : "memory"); }
__device__ __forceinline__ void sts128(uint32_t a, uint4 v) {
  asm volatile("st.shared.v4.b32 [%0], {%1,%2,%3,%4};" :: "r"(a), "r"(v.x), "r"(v.y), "r"(v.z), "r"(v.w) : "memory"); }
__device__ __forceinline__ void sts128f(uint32_t a, float x, float y, float z, float w) {
  asm volatile("st.shared.v4.f32 [%0], {%1,%2,%3,%4};" :: "r"(a), "f"(x), "f"(y), "f"(z), "f"(w) : "memory"); }
__device__ __forceinline__ float lds32f(uint32_t a) { float v; asm volatile("ld.shared.f32 %0, [%1];" : "=f"(v) : "r"(a) : "memory"); return v; }
__device__ __forceinline__ float2 lds64f(uint32_t a) { float2 v; asm volatile("ld.shared.v2.f32 {%0,%1}, [%2];" : "=f"(v.x), "=f"(v.y) : "r"(a) : "memory"); return v; }
__device__ __forceinline__ float4 lds128f(uint32_t a) {
  float4 v; asm volatile("ld.shared.v4.f32 {%0,%1,%2,%3}, [%4];" : "=f"(v.x), "=f"(v.y), "=f"(v.z), "=f"(v.w) : "r"(a) : "memory"); return v; }
__device__ __forceinline__ uint4 lds128(uint32_t a) {
  uint4 v; asm volatile("ld.shared.v4.b32 {%0,%1,%2,%3}, [%4];" : "=r"(v.x), "=r"(v.y), "=r"(v.z), "=r"(v.w) : "r"(a) : "memory"); return v; }
__device__ __forceinline__ uint4 ldg_strong128(const void* p) {
  uint4 v; asm volatile("ld.relaxed.gpu.global.v4.u32 {%0,%1,%2,%3}, [%4];" : "=r"(v.x), "=r"(v.y), "=r"(v.z), "=r"(v.w) : "l"(p) : "memory"); return v; }
__device__ __forceinline__ uint2 ldg_strong64(const void* p) {
  uint2 v; asm volatile("ld.relaxed.gpu.global.v2.u32 {%0,%1}, [%2];" : "=r"(v.x), "=r"(v.y) : "l"(p) : "memory"); return v; }
__device__ __forceinline__ void stg_strong32(void* p, uint32_t v) { asm volatile("st.relaxed.gpu.global.u32 [%0], %1;" :: "l"(p), "r"(v) : "memory"); }
__device__ __forceinline__ void stg_strong128(void* p, uint4 v) {
  asm volatile("st.relaxed.gpu.global.v4.u32 [%0], {%1,%2,%3,%4};" :: "l"(p), "r"(v.x), "r"(v.y), "r"(v.z), "r"(v.w) : "memory"); }
__device__ __forceinline__ uint32_t mapa(uint32_t a, uint32_t r) {
  uint32_t o; asm("mapa.shared::cluster.u32 %0, %1, %2;" : "=r"(o) : "r"(a), "r"(r)); return o; }
__device__ __forceinline__ void st_async2f(uint32_t a, float x, float y, uint32_t bar) {
  asm volatile("st.async.shared::cluster.mbarrier::complete_tx::bytes.v2.f32 [%0], {%1,%2}, [%3];" :: "r"(a), "f"(x), "f"(y), "r"(bar) : "memory"); }
__device__ __forceinline__ void st_async32(uint32_t a, uint32_t x, uint32_t bar) {
  asm volatile("st.async.shared::cluster.mbarrier::complete_tx::bytes.b32 [%0], %1, [%2];" :: "r"(a), "r"(x), "r"(bar) : "memory"); }
__device__ __forceinline__ uint32_t lds32(uint32_t a) { uint32_t v; asm volatile("ld.shared.b32 %0, [%1];" : "=r"(v) : "r"(a) : "memory"); return v; }
__device__ __forceinline__ void st_async64(uint32_t a, uint32_t x, uint32_t y, uint32_t bar) {
  asm volatile("st.async.shared::cluster.mbarrier::complete_tx::bytes.v2.b32 [%0], {%1,%2}, [%3];" :: "r"(a), "r"(x), "r"(y), "r"(bar) : "memory"); }
__device__ __forceinline__ void st_async128(uint32_t a, uint4 v, uint32_t bar) {
  asm volatile("st.async.shared::cluster.mbarrier::complete_tx::bytes.v4.b32 [%0], {%1,%2,%3,%4}, [%5];" :: "r"(a), "r"(v.x), "r"(v.y), "r"(v.z), "r"(v.w), "r"(bar) : "memory"); }
__device__ __forceinline__ uint2 lds64(uint32_t a) { uint2 v; asm volatile("ld.shared.v2.b32 {%0,%1}, [%2];" : "=r"(v.x), "=r"(v.y) : "r"(a) : "memory"); return v; }
__device__ __forceinline__ void sts64(uint32_t a, uint32_t x, uint32_t y) { asm volatile("st.shared.v2.b32 [%0], {%1,%2};" :: "r"(a), "r"(x), "r"(y) : "memory"); }
__device__ __forceinline__ uint32_t ldg_strong32(const void* p) { uint32_t v; asm volatile("ld.relaxed.gpu.global.u32 %0, [%1];" : "=r"(v) : "l"(p) : "memory"); return v; }
__device__ __forceinline__ uint32_t transpose8(uint32_t x) { uint32_t r; asm volatile("movmatrix.sync.aligned.m8n8.trans.b16 %0, %1;" : "=r"(r) : "r"(x)); return r; }
__device__ __forceinline__ uint32_t hadd2(uint32_t a, uint32_t b) { uint32_t r; asm("add.rn.bf16x2 %0, %1, %2;" : "=r"(r) : "r"(a), "r"(b)); return r; }
__device__ __forceinline__ uint32_t min4(uint4 v) { return min(__vimin3_u32(v.x, v.y, v.z), v.w); }

__device__ __forceinline__ void wg_ss192_01(float* d, uint64_t da, uint64_t db, int sd) {
  asm volatile("{.reg .pred p; setp.ne.b32 p, %98, 0;\n"
    "wgmma.mma_async.sync.aligned.m64n192k16.f32.bf16.bf16 {%0,%1,%2,%3,%4,%5,%6,%7,%8,%9,%10,%11,%12,%13,%14,%15,%16,%17,%18,%19,%20,%21,%22,%23,%24,%25,%26,%27,%28,%29,%30,%31,%32,%33,%34,%35,%36,%37,%38,%39,%40,%41,%42,%43,%44,%45,%46,%47,%48,%49,%50,%51,%52,%53,%54,%55,%56,%57,%58,%59,%60,%61,%62,%63,%64,%65,%66,%67,%68,%69,%70,%71,%72,%73,%74,%75,%76,%77,%78,%79,%80,%81,%82,%83,%84,%85,%86,%87,%88,%89,%90,%91,%92,%93,%94,%95}, %96, %97, p, 1, 1, 0, 1;}"
    : "+f"(d[0]),"+f"(d[1]),"+f"(d[2]),"+f"(d[3]),"+f"(d[4]),"+f"(d[5]),"+f"(d[6]),"+f"(d[7]),"+f"(d[8]),"+f"(d[9]),"+f"(d[10]),"+f"(d[11]),"+f"(d[12]),"+f"(d[13]),"+f"(d[14]),"+f"(d[15]),"+f"(d[16]),"+f"(d[17]),"+f"(d[18]),"+f"(d[19]),"+f"(d[20]),"+f"(d[21]),"+f"(d[22]),"+f"(d[23]),"+f"(d[24]),"+f"(d[25]),"+f"(d[26]),"+f"(d[27]),"+f"(d[28]),"+f"(d[29]),"+f"(d[30]),"+f"(d[31]),"+f"(d[32]),"+f"(d[33]),"+f"(d[34]),"+f"(d[35]),"+f"(d[36]),"+f"(d[37]),"+f"(d[38]),"+f"(d[39]),"+f"(d[40]),"+f"(d[41]),"+f"(d[42]),"+f"(d[43]),"+f"(d[44]),"+f"(d[45]),"+f"(d[46]),"+f"(d[47]),"+f"(d[48]),"+f"(d[49]),"+f"(d[50]),"+f"(d[51]),"+f"(d[52]),"+f"(d[53]),"+f"(d[54]),"+f"(d[55]),"+f"(d[56]),"+f"(d[57]),"+f"(d[58]),"+f"(d[59]),"+f"(d[60]),"+f"(d[61]),"+f"(d[62]),"+f"(d[63]),"+f"(d[64]),"+f"(d[65]),"+f"(d[66]),"+f"(d[67]),"+f"(d[68]),"+f"(d[69]),"+f"(d[70]),"+f"(d[71]),"+f"(d[72]),"+f"(d[73]),"+f"(d[74]),"+f"(d[75]),"+f"(d[76]),"+f"(d[77]),"+f"(d[78]),"+f"(d[79]),"+f"(d[80]),"+f"(d[81]),"+f"(d[82]),"+f"(d[83]),"+f"(d[84]),"+f"(d[85]),"+f"(d[86]),"+f"(d[87]),"+f"(d[88]),"+f"(d[89]),"+f"(d[90]),"+f"(d[91]),"+f"(d[92]),"+f"(d[93]),"+f"(d[94]),"+f"(d[95])
    : "l"(da), "l"(db), "r"(sd));
}
__device__ __forceinline__ void wg_ss128_01(float* d, uint64_t da, uint64_t db, int sd) {
  asm volatile("{.reg .pred p; setp.ne.b32 p, %66, 0;\n"
    "wgmma.mma_async.sync.aligned.m64n128k16.f32.bf16.bf16 {%0,%1,%2,%3,%4,%5,%6,%7,%8,%9,%10,%11,%12,%13,%14,%15,%16,%17,%18,%19,%20,%21,%22,%23,%24,%25,%26,%27,%28,%29,%30,%31,%32,%33,%34,%35,%36,%37,%38,%39,%40,%41,%42,%43,%44,%45,%46,%47,%48,%49,%50,%51,%52,%53,%54,%55,%56,%57,%58,%59,%60,%61,%62,%63}, %64, %65, p, 1, 1, 0, 1;}"
    : "+f"(d[0]),"+f"(d[1]),"+f"(d[2]),"+f"(d[3]),"+f"(d[4]),"+f"(d[5]),"+f"(d[6]),"+f"(d[7]),"+f"(d[8]),"+f"(d[9]),"+f"(d[10]),"+f"(d[11]),"+f"(d[12]),"+f"(d[13]),"+f"(d[14]),"+f"(d[15]),"+f"(d[16]),"+f"(d[17]),"+f"(d[18]),"+f"(d[19]),"+f"(d[20]),"+f"(d[21]),"+f"(d[22]),"+f"(d[23]),"+f"(d[24]),"+f"(d[25]),"+f"(d[26]),"+f"(d[27]),"+f"(d[28]),"+f"(d[29]),"+f"(d[30]),"+f"(d[31]),"+f"(d[32]),"+f"(d[33]),"+f"(d[34]),"+f"(d[35]),"+f"(d[36]),"+f"(d[37]),"+f"(d[38]),"+f"(d[39]),"+f"(d[40]),"+f"(d[41]),"+f"(d[42]),"+f"(d[43]),"+f"(d[44]),"+f"(d[45]),"+f"(d[46]),"+f"(d[47]),"+f"(d[48]),"+f"(d[49]),"+f"(d[50]),"+f"(d[51]),"+f"(d[52]),"+f"(d[53]),"+f"(d[54]),"+f"(d[55]),"+f"(d[56]),"+f"(d[57]),"+f"(d[58]),"+f"(d[59]),"+f"(d[60]),"+f"(d[61]),"+f"(d[62]),"+f"(d[63])
    : "l"(da), "l"(db), "r"(sd));
}
__device__ __forceinline__ void wg_ss160_01(float* d, uint64_t da, uint64_t db, int sd) {
  asm volatile("{.reg .pred p; setp.ne.b32 p, %82, 0;\n"
    "wgmma.mma_async.sync.aligned.m64n160k16.f32.bf16.bf16 {%0,%1,%2,%3,%4,%5,%6,%7,%8,%9,%10,%11,%12,%13,%14,%15,%16,%17,%18,%19,%20,%21,%22,%23,%24,%25,%26,%27,%28,%29,%30,%31,%32,%33,%34,%35,%36,%37,%38,%39,%40,%41,%42,%43,%44,%45,%46,%47,%48,%49,%50,%51,%52,%53,%54,%55,%56,%57,%58,%59,%60,%61,%62,%63,%64,%65,%66,%67,%68,%69,%70,%71,%72,%73,%74,%75,%76,%77,%78,%79}, %80, %81, p, 1, 1, 0, 1;}"
    : "+f"(d[0]),"+f"(d[1]),"+f"(d[2]),"+f"(d[3]),"+f"(d[4]),"+f"(d[5]),"+f"(d[6]),"+f"(d[7]),"+f"(d[8]),"+f"(d[9]),"+f"(d[10]),"+f"(d[11]),"+f"(d[12]),"+f"(d[13]),"+f"(d[14]),"+f"(d[15]),"+f"(d[16]),"+f"(d[17]),"+f"(d[18]),"+f"(d[19]),"+f"(d[20]),"+f"(d[21]),"+f"(d[22]),"+f"(d[23]),"+f"(d[24]),"+f"(d[25]),"+f"(d[26]),"+f"(d[27]),"+f"(d[28]),"+f"(d[29]),"+f"(d[30]),"+f"(d[31]),"+f"(d[32]),"+f"(d[33]),"+f"(d[34]),"+f"(d[35]),"+f"(d[36]),"+f"(d[37]),"+f"(d[38]),"+f"(d[39]),"+f"(d[40]),"+f"(d[41]),"+f"(d[42]),"+f"(d[43]),"+f"(d[44]),"+f"(d[45]),"+f"(d[46]),"+f"(d[47]),"+f"(d[48]),"+f"(d[49]),"+f"(d[50]),"+f"(d[51]),"+f"(d[52]),"+f"(d[53]),"+f"(d[54]),"+f"(d[55]),"+f"(d[56]),"+f"(d[57]),"+f"(d[58]),"+f"(d[59]),"+f"(d[60]),"+f"(d[61]),"+f"(d[62]),"+f"(d[63]),"+f"(d[64]),"+f"(d[65]),"+f"(d[66]),"+f"(d[67]),"+f"(d[68]),"+f"(d[69]),"+f"(d[70]),"+f"(d[71]),"+f"(d[72]),"+f"(d[73]),"+f"(d[74]),"+f"(d[75]),"+f"(d[76]),"+f"(d[77]),"+f"(d[78]),"+f"(d[79])
    : "l"(da), "l"(db), "r"(sd));
}
__device__ __forceinline__ void wg_ss80_01(float* d, uint64_t da, uint64_t db, int sd) {
  asm volatile("{.reg .pred p; setp.ne.b32 p, %42, 0;\n"
    "wgmma.mma_async.sync.aligned.m64n80k16.f32.bf16.bf16 {%0,%1,%2,%3,%4,%5,%6,%7,%8,%9,%10,%11,%12,%13,%14,%15,%16,%17,%18,%19,%20,%21,%22,%23,%24,%25,%26,%27,%28,%29,%30,%31,%32,%33,%34,%35,%36,%37,%38,%39}, %40, %41, p, 1, 1, 0, 1;}"
    : "+f"(d[0]),"+f"(d[1]),"+f"(d[2]),"+f"(d[3]),"+f"(d[4]),"+f"(d[5]),"+f"(d[6]),"+f"(d[7]),"+f"(d[8]),"+f"(d[9]),"+f"(d[10]),"+f"(d[11]),"+f"(d[12]),"+f"(d[13]),"+f"(d[14]),"+f"(d[15]),"+f"(d[16]),"+f"(d[17]),"+f"(d[18]),"+f"(d[19]),"+f"(d[20]),"+f"(d[21]),"+f"(d[22]),"+f"(d[23]),"+f"(d[24]),"+f"(d[25]),"+f"(d[26]),"+f"(d[27]),"+f"(d[28]),"+f"(d[29]),"+f"(d[30]),"+f"(d[31]),"+f"(d[32]),"+f"(d[33]),"+f"(d[34]),"+f"(d[35]),"+f"(d[36]),"+f"(d[37]),"+f"(d[38]),"+f"(d[39])
    : "l"(da), "l"(db), "r"(sd));
}
__device__ __forceinline__ void wg_rs32_00(float* d, uint32_t a0, uint32_t a1, uint32_t a2, uint32_t a3, uint64_t db, int sd) {
  asm volatile("{.reg .pred p; setp.ne.b32 p, %21, 0;\n"
    "wgmma.mma_async.sync.aligned.m64n32k16.f32.bf16.bf16 {%0,%1,%2,%3,%4,%5,%6,%7,%8,%9,%10,%11,%12,%13,%14,%15}, {%16,%17,%18,%19}, %20, p, 1, 1, 0;}"
    : "+f"(d[0]),"+f"(d[1]),"+f"(d[2]),"+f"(d[3]),"+f"(d[4]),"+f"(d[5]),"+f"(d[6]),"+f"(d[7]),"+f"(d[8]),"+f"(d[9]),"+f"(d[10]),"+f"(d[11]),"+f"(d[12]),"+f"(d[13]),"+f"(d[14]),"+f"(d[15])
    : "r"(a0), "r"(a1), "r"(a2), "r"(a3), "l"(db), "r"(sd));
}
__device__ __forceinline__ void wg_rs64_00(float* d, uint32_t a0, uint32_t a1, uint32_t a2, uint32_t a3, uint64_t db, int sd) {
  asm volatile("{.reg .pred p; setp.ne.b32 p, %37, 0;\n"
    "wgmma.mma_async.sync.aligned.m64n64k16.f32.bf16.bf16 {%0,%1,%2,%3,%4,%5,%6,%7,%8,%9,%10,%11,%12,%13,%14,%15,%16,%17,%18,%19,%20,%21,%22,%23,%24,%25,%26,%27,%28,%29,%30,%31}, {%32,%33,%34,%35}, %36, p, 1, 1, 0;}"
    : "+f"(d[0]),"+f"(d[1]),"+f"(d[2]),"+f"(d[3]),"+f"(d[4]),"+f"(d[5]),"+f"(d[6]),"+f"(d[7]),"+f"(d[8]),"+f"(d[9]),"+f"(d[10]),"+f"(d[11]),"+f"(d[12]),"+f"(d[13]),"+f"(d[14]),"+f"(d[15]),"+f"(d[16]),"+f"(d[17]),"+f"(d[18]),"+f"(d[19]),"+f"(d[20]),"+f"(d[21]),"+f"(d[22]),"+f"(d[23]),"+f"(d[24]),"+f"(d[25]),"+f"(d[26]),"+f"(d[27]),"+f"(d[28]),"+f"(d[29]),"+f"(d[30]),"+f"(d[31])
    : "r"(a0), "r"(a1), "r"(a2), "r"(a3), "l"(db), "r"(sd));
}
__device__ __forceinline__ void wg_rs24_01(float* d, uint32_t a0, uint32_t a1, uint32_t a2, uint32_t a3, uint64_t db, int sd) {
  asm volatile("{.reg .pred p; setp.ne.b32 p, %17, 0;\n"
    "wgmma.mma_async.sync.aligned.m64n24k16.f32.bf16.bf16 {%0,%1,%2,%3,%4,%5,%6,%7,%8,%9,%10,%11}, {%12,%13,%14,%15}, %16, p, 1, 1, 1;}"
    : "+f"(d[0]),"+f"(d[1]),"+f"(d[2]),"+f"(d[3]),"+f"(d[4]),"+f"(d[5]),"+f"(d[6]),"+f"(d[7]),"+f"(d[8]),"+f"(d[9]),"+f"(d[10]),"+f"(d[11])
    : "r"(a0), "r"(a1), "r"(a2), "r"(a3), "l"(db), "r"(sd));
}

#define AB_POLY 0x77
__device__ __forceinline__ constexpr bool poly_group(int group) { return (AB_POLY >> (group & 7)) & 1; }

template <int V> struct Int { static constexpr int value = V; };

__device__ __forceinline__ int core_word(int row, int col) {
  return ((((row >> 7) * 10 + (col >> 6)) * 16 + ((row >> 3) & 15)) * 8 + ((col >> 3) & 7)) * 32 + (row & 7) * 4 + ((col & 7) >> 1);
}
__device__ __forceinline__ void wait_count(const uint32_t* c, uint32_t n) {
  for (int spin = 0; !__all_sync(~0u, (ld_acquire(c) & 0xffff) >= n);) { __nanosleep(32); spin_guard(spin); }
  fence_async_global();
}
__device__ __forceinline__ void prefetch_l2(const void* p, uint32_t bytes) {
  asm volatile("cp.async.bulk.prefetch.L2.global [%0], %1;" :: "l"(p), "r"(bytes) : "memory"); }

#define PLACE 4
__device__ __forceinline__ bool helper_sm() {
  uint32_t m; asm volatile("mov.u32 %0, %%smid;" : "=r"(m));
  return m < 2 || m >= 120 || (m >= 92 && m < 102) || (m >= 106 && m < 117) || m == 118;
}

__device__ __forceinline__ uint8_t* pool_at(uint32_t off) {
  return reinterpret_cast<uint8_t*>((reinterpret_cast<uintptr_t>(g_pool) + 8191) & ~(uintptr_t)8191) + off; }
__device__ __forceinline__ void probe_slots(uint32_t scratch) {
  const int w = (threadIdx.x >> 6) & 1, slot = w == 0 ? NSLOT : blockIdx.x;
  if (w == 0 || slot < NSLOT) {
    uint32_t* q = reinterpret_cast<uint32_t*>(pool_at(slot * 8192)) + (w == 0 ? (blockIdx.x & 31) * 32 + (blockIdx.x >> 5) : 0);
    uint32_t best[2] = {~0u, ~0u};
    const bool one = elect();
    if (one) { stg_strong32(q, 0u); stg_strong32(q + 1024, 0u); }
#pragma unroll 1
    for (int r = 0; r < 8; r++) {
      uint32_t v = 0;
      const uint32_t t0 = clk32();
      if (one) asm volatile("atom.relaxed.gpu.global.exch.b32 %0, [%1], 0;" : "=r"(v) : "l"(q + (r & 1) * 1024) : "memory");
      if (__any_sync(~0u, v != 0)) break;
      const uint32_t t = min(clk32() - t0, best[0]);
      best[0] = best[1]; best[1] = t;
    }
    if (one) sts32(scratch + w * 4, best[0] < best[1]);
  }
  bar_sync(2, 64);
  if ((threadIdx.x & 31) == 0) {
    const int part = lds32(scratch) ? 1 : 2;
    if (w == 0) { uint32_t smid; asm("mov.u32 %0, %%smid;" : "=r"(smid)); stg_strong32(g_smpart + (smid & 255), part); }
    else if (slot < NSLOT) stg_strong32(g_orient + slot, lds32(scratch + 4) ? part : 3 - part);
  }
  __syncwarp();
}

constexpr int WK_SLOTS = 28, WK_BAR = WK_SLOTS * 8192;
__device__ __forceinline__ void work_init(uint32_t sb, int w) {
  if (elect()) {
#pragma unroll
    for (int i = 0; i < 8; i++) mbar_init(sb + WK_BAR + 64 * w + 8 * i, 0x18318822 >> (8 * w + (i & 4)) & 15);
  }
  asm volatile("fence.mbarrier_init.release.cluster;" ::: "memory");
}

struct ChainParams {
  CUtensorMap wq, wk, wv, wo, xc;
  const __nv_bfloat16* mem0;
  const uint8_t* wb;
  uint32_t *sync, *other;
  int layer;
  int d1, d2, dn, dx, mode, zero;
};
constexpr int CH_WQ = 0, CH_WO = 81920, CH_X = CH_WO + 86016, CH_M = CH_X, CH_Q = CH_X + 34816, CH_KM = CH_Q + 2048, CH_VP = CH_KM + 2048,
              CH_K = CH_X + 40960, CH_O = CH_K, CH_KS = CH_K + 3072, CH_V = CH_K + 4096, CH_VX = CH_V + 12288, CH_R2 = CH_VX,
              CH_SX = CH_VX + 3072, CH_SO = CH_SX + 2048, CH_ID = CH_SO + 1024, CH_L = CH_ID + 256, CH_TAB = CH_L + 64, CH_BAR = CH_TAB + 384;
constexpr int CH_SMEM = CH_BAR + 144;
constexpr int MB_WO = CH_BAR, MB_WQ = CH_BAR + 8, MB_X = CH_BAR + 16, MB_V = CH_BAR + 24, MB_T = CH_BAR + 32, MB_F = CH_BAR + 40, MB_G = CH_BAR + 48, MB_W = CH_BAR + 56;
enum { NB_PROJ = 1, NB_O = 2, NB_W1 = 3, NB_PRE = 4, NB_ST = 5, NB_MEM = 6, NB_XFREE = 7, NB_H1 = 8, NB_PUB = 9, NB_W2 = 10, NB_PROJ2 = 11, NB_PRE2 = 12, NB_H2 = 13, NB_W1V = 14 };
#define CH_NQ 9
#define CH_XPF 1
#define CH_TPF 1
#define CH_FLY 6
#define CH_TW 1
#define CH_NQ0 4
#define CH_PA 6
#define CH_PB 9
#define CH_PC 13
#define CH_PL 4
#define CH_DBL 0x0888
#define CH_PD 1
#define SCHED() asm volatile("griddepcontrol.launch_dependents;" ::: "memory")
__device__ __forceinline__ uint32_t opaque(uint32_t x) { return __shfl_sync(~0u, x, threadIdx.x & 31); }
__device__ __forceinline__ uint32_t uniform(uint32_t x) { return __shfl_sync(~0u, x, 0); }
__device__ __forceinline__ uint32_t nz(uint32_t x) { uint32_t r; asm("max.u32 %0, %1, 1;" : "=r"(r) : "r"(x)); return r; }
__device__ __forceinline__ uint32_t set_tag(uint32_t w, uint32_t tag) { uint32_t r; asm("lop3.b32 %0, %1, %2, 1, 0xD8;" : "=r"(r) : "r"(w), "r"(tag)); return r; }
__device__ __forceinline__ uint32_t pack_tag(float lo, float hi, uint32_t tag) { return set_tag(__byte_perm(__float_as_uint(lo) + tag, pack2(hi, hi), 0x7632), tag); }
__device__ __forceinline__ uint32_t differ(uint32_t a, uint32_t b, uint32_t t) { uint32_t r; asm("lop3.b32 %0, %1, %2, %3, 0x7E;" : "=r"(r) : "r"(a), "r"(b), "r"(t)); return r; }
__device__ __forceinline__ uint32_t clk64() { uint64_t c; asm volatile("mov.u64 %0, %%clock64;" : "=l"(c) :: "memory"); return (uint32_t)c; }
__device__ __forceinline__ void until(uint32_t t) {
  asm volatile("{.reg .pred p; .reg .u64 c; .reg .s32 d;\nW: mov.u64 c, %%clock64; cvt.u32.u64 d, c; sub.s32 d, d, %0; setp.lt.s32 p, d, 0; @p bra.uni W;}" :: "r"(t) : "memory");
}
__device__ __forceinline__ float rcp(float x) { float y; asm("rcp.approx.ftz.f32 %0, %1;" : "=f"(y) : "f"(x)); return y; }

__device__ __forceinline__ void chain_compute(const ChainParams& p, const uint32_t sb) {
  const int tid = threadIdx.x & 127, WG = __shfl_sync(~0u, threadIdx.x >> 7, 0), t4 = __shfl_sync(~0u, tid >> 5, 0), lane = tid & 31;
  const int cta = blockIdx.x, h = cta / 3, j = cta - 3 * h;
  uint32_t a0[80], a1[80], tw[4 * CH_NQ];
  const uint32_t wq = opaque(sb + CH_WQ + (WG * 320 + (lane & 7) + (lane >> 4) * 8) * 128 + (((2 * t4 + ((lane >> 3) & 1)) ^ (lane & 7)) << 4));
#pragma unroll
  for (int k = 0; k < 40; k++) {
    if (k % 10 == 0) mbar_wait(sb + MB_W + WG * 8 + k / 10 * 16, 0);
    if (k < 20) ldsm4t(&a0[4 * k], wq + k * 2048); else ldsm4t(&a1[4 * k - 80], wq + CH_WO + (k - 20) * 2048);
    if (k % 20 == 19) bar_arrive(k < 20 ? NB_PROJ2 : NB_PRE2, 288);
  }
  const int r1 = j == 2 ? 0 : j + 1, r2 = j == 0 ? 2 : j - 1;
  const uint32_t l16 = opaque(sb + lane * 16), l8 = opaque(sb + lane * 8), l4 = opaque(sb + lane * 4);
  const uint32_t t16 = l16 + t4 * 512, t8 = l8 + t4 * 256;
  uint32_t wo = opaque(sb + CH_WO + (WG == 0 ? (t4 >> 1) * 36864 : 73728 + t4 * 1024) + ((lane & 7) + (lane >> 4) * 8) * 64 +
                       (((((lane >> 3) & 1) + (WG == 0 ? (t4 & 1) * 2 : 0)) ^ ((lane >> 1) & 3)) << 4));
  const uint32_t ko0 = uniform(CH_K + (tid >> 6) * 3072 + (tid & 32) * 8), ko1 = uniform(CH_K + (tid >> 6) * 1024 + 1024 + (tid & 32) * 8),
                 o768 = uniform((tid >> 5) * 768);
  const uint32_t give = uniform(t4 * 512 + (WG == 0 ? CH_K : CH_V + j * 4096)), own = uniform(t4 * 512 + (WG == 0 ? CH_V + j * 4096 : CH_K)), mem = uniform(CH_M + WG * 5120);
  const uint32_t vxo = uniform(t4 * 256 + CH_VX + j * 1024);
  uint32_t tag = 1, xd = uniform((1024 + CH_X + WG * 20480) >> 4 | 8 << 16);
  asm volatile("barrier.cluster.wait.aligned;" ::: "memory");
  mbar_wait(sb + MB_WQ, 0);
  mbar_wait(sb + MB_T, 0);
  bar_sync(NB_ST, 384);
  uint8_t* pdst[6];
#pragma unroll
  for (int i = 0; i < 6; i++) {
    const int line = WG == 0 ? 24 * j + 12 * (t4 >> 1) + 2 * (t4 & 1) + 4 * (i >> 1) + (i & 1) : j == 0 ? 72 + t4 : 74 + 2 * j + (t4 & 1);
    pdst[i] = pool_at(uniform(lds32(sb + CH_TAB + line * 4)) + h * 128);
  }
  auto batch = [&](float* d, const uint32_t (&a)[80], int acc, int n0, int n1) {
    const uint32_t d0 = xd ^ (tag & (2 << acc));
    wg_fence();
#pragma unroll
    for (int k = 0; k < 20; k++) {
      if (!(k & 3) && n0 + k / 4 < n1) {
        __syncwarp();
        ldsm4t(&tw[4 * n0 + k], wq + (n0 + k / 4) * 2048);
        __syncwarp();
      }
      uint64_t db;
      asm("mov.b64 %0, {%1, %2};" : "=l"(db) : "r"(d0 + k / 5 * 320 + k % 5 * 16), "r"(80));
      wg_rs32_00(d, a[4 * k], a[4 * k + 1], a[4 * k + 2], a[4 * k + 3], db, acc | k);
    }
    wg_commit();
    wg_wait<0>();
    reg_fence<16>(d);
  };
  int s = 0;
#pragma unroll 1
  do {
    {
      float d[16];
      if (!CH_TW) mbar_wait(sb + MB_T, s & 1);
      batch(d, a0, 0, 0, CH_NQ0);
      s--; TM(10); s++;
      mbar_wait(sb + MB_F, ~s & 1);
#pragma unroll
      for (int i = 0; i < 2; i++)
        sts128(l16 + give + i * 2048, make_uint4(pack2(d[8 * i], d[8 * i + 1]), pack2(d[8 * i + 2], d[8 * i + 3]), pack2(d[8 * i + 4], d[8 * i + 5]), pack2(d[8 * i + 6], d[8 * i + 7])));
      bar_sync(NB_PUB, 384);
#pragma unroll
      for (int i = 0; i < 2; i++) {
        const uint4 t = lds128(l16 + own + i * 2048);
        d[8 * i] = bf_lo(t.x); d[8 * i + 1] = bf_hi(t.x); d[8 * i + 2] = bf_lo(t.y); d[8 * i + 3] = bf_hi(t.y);
        d[8 * i + 4] = bf_lo(t.z); d[8 * i + 5] = bf_hi(t.z); d[8 * i + 6] = bf_lo(t.w); d[8 * i + 7] = bf_hi(t.w);
      }
      reg_fence<16>(d);
      batch(d, a1, 1, CH_NQ0, CH_NQ);
      s--; TM(11); s++;
      if (WG == 0) bar_arrive(NB_XFREE, 256);
#pragma unroll
      for (int i = 0; i < 8; i++) sts32(l4 + own + (i >> 2) * 2048 + (i & 3) * 128, pack2(d[2 * i], d[2 * i + 1]));
      s--; TM(9); s++;
    }
    float dq[4] = {}, d0[4] = {}, d1[4] = {};
    uint32_t b[40], wf[80];
    const uint32_t* kf = &wf[52];
#pragma unroll
    for (int i = 0; i < 4 * CH_NQ; i++) wf[i] = tw[i];
    auto step = [&](int k) {
      mma16(dq, wf[4 * k], wf[4 * k + 1], wf[4 * k + 2], wf[4 * k + 3], b[2 * k], b[2 * k + 1]);
      mma16(d0, a0[4 * k], a0[4 * k + 1], a0[4 * k + 2], a0[4 * k + 3], b[2 * k], b[2 * k + 1]);
      mma16(d1, a1[4 * k], a1[4 * k + 1], a1[4 * k + 2], a1[4 * k + 3], b[2 * k], b[2 * k + 1]);
    };
    auto finish = [&](int wg, const float* dk) {
      const float k2 = 0.07216878364870322f * 1.44269504089f;
      sts32(l4 + t4 * 512 + CH_Q + wg * 128, pack2(dq[0] * k2, dq[1] * k2));
      sts32(l4 + t4 * 512 + CH_Q + wg * 128 + 256, pack2(dq[2] * k2, dq[3] * k2));
      sts32(l4 + t4 * 512 + CH_KM + wg * 256, pack2(dk[0], dk[1]));
      sts32(l4 + t4 * 512 + CH_KM + wg * 256 + 128, pack2(dk[2], dk[3]));
    };
    const bool more = s < NSEG - 1;
    bar_sync(NB_MEM, 384);
    ldsm4t(&b[0], l16 + mem);
    ldsm4t(&b[4], l16 + mem + 512);
    TMD(0, b[0]);
    {
      int nw = CH_NQ, nb = 2;
#pragma unroll
      for (int k = 0; k < 20; k++) {
        SCHED();
        step(k);
#pragma unroll
        for (int i = 0; i < (CH_DBL >> k & 1) + 1; i++) {
          if (nb < 10 && 2 * nb <= nw) { ldsm4t(&b[4 * nb], l16 + mem + nb * 512); nb++; }
          else if (nw < 20) { ldsm4t(&wf[4 * nw], wq + nw * 2048); nw++; }
          else if (nw < 22) {
            const uint32_t x = l16 ^ ((ko0 ^ tag) & 256);
            uint32_t* r = &wf[4 * nw - 28];
            asm volatile("{.reg .pred p; setp.ne.u32 p, %5, 0; @p ldmatrix.sync.aligned.m8n8.x4.trans.shared.b16 {%0,%1,%2,%3},[%4];}"
                         : "+r"(r[0]), "+r"(r[1]), "+r"(r[2]), "+r"(r[3]) : "r"(x + (x & 256) + (nw == 20 ? ko0 : ko1)), "r"(WG) : "memory");
            nw++;
          }
        }
      }
      SCHED();
    }
    if (WG == 0) {
      finish(0, d0);
      TM(1);
      bar_sync(NB_PROJ, 256);
      if (!more) {
        const float4 pv = lds128f(t16 + CH_VP);
        sts64(l8 + vxo, pack2(d1[0] + pv.x, d1[1] + pv.y), pack2(d1[2] + pv.z, d1[3] + pv.w));
        continue;
      }
      const float4 pv = lds128f(t16 + CH_VP);
      const uint32_t xo = l8 + (vxo ^ (tag & 2)), x1 = mapa(xo, r1), x2 = mapa(xo, r2);
      SCHED();
      const uint32_t v0 = pack2(d1[0] + pv.x, d1[1] + pv.y), v1 = pack2(d1[2] + pv.z, d1[3] + pv.w);
      st_async64(x1, v0, v1, mapa(sb + MB_X, r1));
      st_async64(x2, v0, v1, mapa(sb + MB_X, r2));
      sts64(xo, v0, v1);
      __syncwarp();
      if (elect()) mbar_arrive(sb + MB_X);
      bar_arrive(NB_PROJ2, 256);
      TM(3);
      uint32_t w[144];
      auto tile_of = [](int n) { return n < 27 ? n % 3 : (0x26484 >> 2 * (n - 27)) & 3; };
      auto step_of = [](int n) { return n < 27 ? n / 3 : 9 + ((0x29610 >> 2 * (n - 27)) & 3); };
      auto wload = [&](int n) { ldsm4t(&w[4 * n], wo + tile_of(n) * 12288 + (step_of(n) % 3) * 4096 + (step_of(n) / 3) * 1024); };
#pragma unroll
      for (int n = 0; n < CH_PA; n++) wload(n);
      bar_sync(NB_PRE, 256);
#pragma unroll
      for (int n = CH_PA; n < CH_PB; n++) wload(n);
      bar_arrive(NB_PRE2, 256);
      if (CH_PC > CH_PB) {
        mbar_wait(sb + MB_X, s & 1);
        for (int i = 0; i < CH_PD; i++) wo = __shfl_xor_sync(~0u, wo, p.zero);
#pragma unroll
        for (int n = CH_PB; n < CH_PC; n++) wload(n);
      }
      TM(4);
      bar_sync(NB_O, 256);
      {
        float x[3][4] = {};
        uint32_t ob[24];
        float4 l;
        ldsm4t(&ob[0], l16 + CH_O);
        ldsm4t(&ob[4], l16 + CH_O + 512);
        TMD(7, ob[0]);
        int nw = CH_PC, no = 2;
        float i0, i1;
        uint8_t* dst[6];
        uint32_t lo[6], hi[6];
        auto pre = [&](int i) { lo[i] = __float_as_uint(x[i >> 1][2 * (i & 1)] * i0) + tag; hi[i] = pack2(0.f, x[i >> 1][2 * (i & 1) + 1] * i1); };
        auto emit = [&](int i) { stg_strong32(dst[i], set_tag(__byte_perm(lo[i], hi[i], 0x7632), tag)); };
#pragma unroll
        for (int n = 0; n < 36; n++) {
          SCHED();
          mma16(x[tile_of(n)], w[4 * n], w[4 * n + 1], w[4 * n + 2], w[4 * n + 3], ob[step_of(n) * 2], ob[step_of(n) * 2 + 1]);
          if (n >= CH_PL) {
            if (no < 6 && no * 2 <= step_of(min(nw, 35))) { ldsm4t(&ob[4 * no], l16 + CH_O + no * 512); no++; }
            else if (nw < 36) { wload(nw); nw++; }
          }
          if (n == 18) l = lds128f(sb + CH_L + ((l16 ^ tag) & 0x30));
          if (n == 26) { i0 = rcp(l.x + l.y); i1 = rcp(l.z + l.w); asm volatile("" : "+f"(i0), "+f"(i1)); }
          if (n >= 28 && n < 34) { dst[n - 28] = pdst[n - 28] + ((l4 ^ tag) & 0x7c); asm volatile("" : "+l"(dst[n - 28])); }
          if (n == 32) { for (int i = 0; i < 2; i++) { pre(i); asm volatile("" : "+r"(lo[i]), "+r"(hi[i])); } }
          if (n == 33) { emit(0); emit(1); }
        }
        for (int i = 2; i < 6; i++) pre(i);
        for (int i = 2; i < 6; i++) emit(i);
      }
      TM(8);
    } else {
      finish(1, d1);
      sts128f(t16 + CH_VP, d0[0], d0[1], d0[2], d0[3]);
      TM(1);
      bar_sync(NB_PROJ, 256);
      {
        float d0[4] = {}, d1[4] = {}, dm[4] = {};
        uint32_t q[16], km[4];
#pragma unroll
        for (int e = 0; e < 4; e++) {
          ldsm4t(&q[4 * e], l16 + (e ^ t4) * 512 + CH_Q);
          SCHED();
          if (e == 1) { ldsm4t(km, t16 + CH_KM); SCHED(); }
        }
        const uint32_t xo = l4 + ((t4 * 128) ^ (tag & 2));
        uint64_t x[4];
#pragma unroll
        for (int i = 0; i < 4; i++) {
          const int r = i & 1 ? r2 : r1;
          asm volatile("mov.b64 %0, {%1, %2};" : "=l"(x[i]) : "r"(mapa(xo, r) + CH_SX + (i & 1) * 1024 + (i & 2) * 256), "r"(mapa(sb + MB_X, r)));
        }
        SCHED();
        mma16(d0, q[0], q[1], q[2], q[3], kf[0], kf[1]);
        SCHED();
        mma16(d1, q[4], q[5], q[6], q[7], kf[2], kf[3]);
        SCHED();
        mma16(dm, q[0], q[1], q[2], q[3], hadd2(km[0], km[2]), hadd2(km[1], km[3]));
        mma16(d0, q[8], q[9], q[10], q[11], kf[4], kf[5]);
        SCHED();
        mma16(d1, q[12], q[13], q[14], q[15], kf[6], kf[7]);
        if (!more) continue;
        const uint32_t w1 = pack2(dm[0] + dm[2], dm[1] + dm[3]);
        st_async32((uint32_t)x[2], w1, x[2] >> 32);
        st_async32((uint32_t)x[3], w1, x[3] >> 32);
        SCHED();
        const uint32_t w0 = pack2((d0[0] + d0[2]) + (d1[0] + d1[2]), (d0[1] + d0[3]) + (d1[1] + d1[3]));
        st_async32((uint32_t)x[0], w0, x[0] >> 32);
        st_async32((uint32_t)x[1], w0, x[1] >> 32);
        sts32(xo + CH_SO, w0);
        sts32(xo + CH_SO + 512, w1);
      }
      TM(3);
      float sc[3][4] = {};
      uint32_t wd[12];
      uint32_t redo;
      auto attend = [&](auto first) {
        uint4 vb[6];
        uint2 vm[3];
        float e[10];
        uint32_t ow[6];
        if (first.value) {
          const uint2 id = lds64(l8 + CH_ID);
          bar_sync(NB_W1V, 160);
          uint32_t r[8];
          ldsm4(r, l16 + CH_SO); ldsm4(r + 4, l16 + CH_SO + 512);
#pragma unroll
          for (int u = 0; u < 6; u++) vb[u] = ldsm4v(t16 + CH_V + u * 2048);
          bar_arrive(NB_PRE, 256);
          SCHED();
          uint32_t sxa = l16 + ((l16 ^ tag) & 256) * 3;
          asm volatile("" : "+r"(sxa));
          sxa += CH_SX;
          SCHED();
          mma8(sc[0], r[0], r[1], id.x);
          mma8(sc[1], r[2], r[3], id.x);
          mma16(sc[2], r[4], r[5], r[6], r[7], id.x, id.y);
          TM(7);
          mbar_wait(sb + MB_X, s & 1);
          TM(4);
          uint32_t t[16];
          ldsm4(t, sxa); ldsm4(t + 4, sxa + 256); ldsm4(t + 8, sxa + 512);
          SCHED();
          mma16(sc[0], t[0], t[1], t[2], t[3], id.x, id.y);
          ldsm4(t + 12, sxa + 768);
          SCHED();
          mma16(sc[1], t[4], t[5], t[6], t[7], id.x, id.y);
#pragma unroll
          for (int u = 0; u < 2; u++) vm[u] = lds64(t8 + CH_VX + u * 1024);
          SCHED();
          e[0] = ex2(sc[0][0]);
          mma16(sc[2], t[8], t[9], t[10], t[11], id.x, id.y);
          vm[2] = lds64(t8 + CH_VX + 2048);
          SCHED();
          e[1] = ex2(sc[0][1]);
          ldsm4t(&wd[0], wo);
          SCHED();
          e[2] = ex2(sc[0][2]);
          SCHED();
          e[3] = ex2(sc[0][3]);
          mma16(sc[2], t[12], t[13], t[14], t[15], id.x, id.y);
          SCHED();
          e[4] = ex2(sc[1][0]);
          ldsm4t(&wd[4], wo + 4096);
          SCHED();
          e[5] = ex2(sc[1][1]);
        } else {
#pragma unroll
          for (int u = 0; u < 6; u++) vb[u] = ldsm4v(t16 + CH_V + u * 2048);
#pragma unroll
          for (int u = 0; u < 3; u++) vm[u] = lds64(t8 + CH_VX + u * 1024);
        }
        float o[3][4] = {};
        if (!first.value) {
#pragma unroll
          for (int i = 0; i < 6; i++) e[i] = ex2(sc[i >> 2][i & 3]);
        }
        const uint32_t p1 = pack2(e[0], e[1]), p2 = pack2(e[2], e[3]);
        float l = (e[0] + e[1]) + (e[2] + e[3]);
        asm volatile("" : "+f"(l));
        SCHED();
        e[6] = ex2(sc[1][2]);
        mma16(o[0], vb[0].x, vb[0].y, vb[0].z, vb[0].w, p1, p2);
        if (first.value) { sc[2][0] += sc[2][2]; sc[2][1] += sc[2][3]; }
        SCHED();
        e[7] = ex2(sc[1][3]);
        mma16(o[1], vb[2].x, vb[2].y, vb[2].z, vb[2].w, p1, p2);
        SCHED();
        e[8] = ex2(sc[2][0]);
        mma16(o[2], vb[4].x, vb[4].y, vb[4].z, vb[4].w, p1, p2);
        SCHED();
        e[9] = ex2(sc[2][1]);
        SCHED();
        const uint32_t p3 = pack2(e[4], e[5]), p4 = pack2(e[6], e[7]);
        l += (e[4] + e[5]) + (e[6] + e[7]);
#pragma unroll
        for (int u = 0; u < 3; u++) mma16(o[u], vb[2 * u + 1].x, vb[2 * u + 1].y, vb[2 * u + 1].z, vb[2 * u + 1].w, p3, p4);
        SCHED();
        const uint32_t p0 = pack2(e[8], e[9]);
        l += e[8] + e[9];
        const float l2 = __shfl_xor_sync(~0u, l, 1);
        if (first.value) ldsm4t(&wd[8], wo + 8192);
#pragma unroll
        for (int u = 0; u < 3; u++) mma8(o[u], vm[u].x, vm[u].y, p0);
        redo = __any_sync(~0u, !(l > 1e-9f && l < 1e9f));
        uint32_t la = sb + CH_L + (((l4 ^ tag) >> 1) & 0x3c);
        asm volatile("" : "+r"(la));
        SCHED();
#pragma unroll
        for (int u = 0; u < 3; u++) { ow[2 * u] = pack2(o[u][0], o[u][1]); ow[2 * u + 1] = pack2(o[u][2], o[u][3]); }
#pragma unroll
        for (int u = 0; u < 6; u++) sts32(l4 + o768 + CH_O + u * 128, ow[u]);
        if (t4 == 0) sts32(la, __float_as_uint(l + l2));
      };
      attend(Int<1>());
      TM(6);
      asm volatile("{.reg .pred p; setp.eq.u32 p, %0, 0; @p bar.sync 2, 256;}" :: "r"(redo) : "memory");
      if (redo) {
        float mx = fmaxf(sc[2][0], sc[2][1]);
#pragma unroll
        for (int i = 0; i < 4; i++) mx = fmaxf(mx, fmaxf(sc[0][i], sc[1][i]));
        mx = fmaxf(mx, __shfl_xor_sync(~0u, mx, 1));
        mx = fmaxf(mx, __shfl_xor_sync(~0u, mx, 2));
#pragma unroll
        for (int i = 0; i < 4; i++) { sc[0][i] -= mx; sc[1][i] -= mx; }
        sc[2][0] -= mx; sc[2][1] -= mx;
        attend(Int<0>());
        bar_arrive(NB_O, 256);
      }
      {
        float z[4] = {};
        const uint32_t scr = l8 + ((CH_V + r1 * 4096) ^ (tag & 2));
        uint32_t ow[6], we[12];
        __syncwarp();
        ldsm4t(ow, l16 + o768 + CH_O);
        ldsm2t(ow + 4, l16 + o768 + CH_O + 512);
        if (j == 0) {
          float y[4] = {};
#pragma unroll
          for (int u = 0; u < 3; u++) ldsm4t(&we[4 * u], (wo ^ 32) + u * 4096);
          SCHED();
#pragma unroll
          for (int u = 0; u < 3; u++) {
            mma16(z, wd[4 * u], wd[4 * u + 1], wd[4 * u + 2], wd[4 * u + 3], ow[2 * u], ow[2 * u + 1]);
            mma16(y, we[4 * u], we[4 * u + 1], we[4 * u + 2], we[4 * u + 3], ow[2 * u], ow[2 * u + 1]);
          }
          sts64f(scr + t4 * 512 + 2048, y[0], y[1]); sts64f(scr + t4 * 512 + 2304, y[2], y[3]);
        } else {
#pragma unroll
          for (int u = 0; u < 3; u++) mma16(z, wd[4 * u], wd[4 * u + 1], wd[4 * u + 2], wd[4 * u + 3], ow[2 * u], ow[2 * u + 1]);
        }
        sts64f(scr + t4 * 512, z[0], z[1]); sts64f(scr + t4 * 512 + 256, z[2], z[3]);
        bar_sync(NB_W1, 128);
        if (j == 0 || t4 < 2) {
          float2 q[4];
          const float4 l = lds128f(sb + CH_L + ((l16 ^ tag) & 0x30));
#pragma unroll
          for (int i = 0; i < 4; i++) q[i] = lds64f(scr + (t4 >> 1) * 2048 + (t4 & 1) * 256 + i * 512);
          SCHED();
          stg_strong32(pdst[0] + ((l4 ^ tag) & 0x7c), pack_tag(((q[0].x + q[1].x) + (q[2].x + q[3].x)) * rcp(l.x + l.y), ((q[0].y + q[1].y) + (q[2].y + q[3].y)) * rcp(l.z + l.w), tag));
        }
      }
      TM(2);
    }
    bar_sync(NB_ST, 384);
    tag ^= 0x10001;
  } while (++s < NSEG);
  if (WG == 1) {
    const uint2 a = lds64(t8 + t4 * 256 + CH_KM), b = lds64(t8 + t4 * 256 + CH_KM + 256);
    sts64(t8 + CH_M, hadd2(a.x, b.x), hadd2(a.y, b.y));
  }
  bar_arrive(NB_PRE2, 288);
}

__device__ __forceinline__ void chain_comm(const ChainParams& p, const uint32_t sb, const CUtensorMap* maps) {
  [[maybe_unused]] constexpr int WG = 2;
  const int tid = threadIdx.x & 127, t4 = __shfl_sync(~0u, tid >> 5, 0), lane = tid & 31;
  const int cta = blockIdx.x, h = cta / 3, j = cta - 3 * h, colbase = cta * 64;
  const uint8_t* const xs = reinterpret_cast<const uint8_t*>(g_xn);
  auto xload = [&](int seg, int i) { tma_load5(sb + CH_X + i * 10240, &p.xc, 0, seg * 4, 2 * i, sb + MB_T); };
  uint32_t smid; asm("mov.u32 %0, %%smid;" : "=r"(smid));
  if (t4 == 3) {
    const bool one = elect();
#pragma unroll 1
    for (int i = 0; i < 19 + CH_FLY; i++) {
      if (i >= CH_FLY) mbar_wait(sb + MB_W + 8 * ((i - CH_FLY) & 7), (i - CH_FLY) >> 3 & 1);
      if (i == 11 + CH_FLY && one) mbar_arrive(sb + MB_WQ);
      if (i == 8) { bar_sync(NB_PROJ2, 288); PRO(1); }
      if (i == 12) { bar_sync(NB_PRE2, 288); PRO(2); }
      if (i == 0) { bar_arrive(NB_ST, 384); bar_arrive(NB_PUB, 384); bar_arrive(NB_XFREE, 256); }
      if (i < 19 && one) {
        const int n = (i & 1) * 2 + (i >> 1 & 1), k = i - 12;
        const uint32_t bar = sb + MB_W + 8 * (i & 7);
        mbar_expect(bar, k < 0 ? 20480 : 12288);
        if (k < 0) tma_load(sb + ((i & 4) + n) * 20480, i >= 8 ? &p.wq : (i ^ i >> 2) & 1 ? &p.wv : &p.wk, colbase, n * 160, bar);
        else tma_load(sb + CH_WO + k * 12288, &p.wo, k < 6 ? j * 192 + k * 32 : j == 0 ? 576 : 592 + j * 16, h * 192, bar);
      }
    }
  } else {
    const uint32_t part = max(ldg_strong32(g_smpart + (smid & 255)), 1u);
    if (tid == 0) prefetch_l2(p.mem0, 10240);
    if (tid == 64) stg_strong32(p.sync + SY_PART + cta, part);
    if (t4 == 1) {
      wait_count(p.sync + SY_P + 1, ln_items(p.layer, 0));
      if (elect()) {
        mbar_expect(sb + MB_T, 40960);
#pragma unroll 1
        for (int i = 0; i < 4; i++) xload(0, i);
      }
      __syncwarp();
      PRO(0);
    }
    uint32_t reader, orient;
    for (int n = 0;; spin_guard(n)) {
      reader = ldg_strong32(p.sync + SY_PART + (tid >= 80 ? cta : tid));
      orient = ldg_strong32(g_orient + min(tid, NSLOT - 1));
      if (__all_sync(~0u, reader && orient)) break;
    }
    const uint32_t near = __ballot_sync(~0u, reader == part) >> (cta & 7) & 0xffff;
    if (tid < NSLOT) sts32(sb + CH_TAB + tid * 4, tid * 8192 + (orient == reader ? 0 : 4096));
    if (tid == 0) sts32(sb + CH_TAB + NSLOT * 4, cta < 80 ? cta : (cta & 7) + max(__ffs(near) - 1, 0));
    if (t4 == 1) PRO(3);
    bar_sync(NB_ST, 384);
    bar_arrive(NB_PUB, 384);
    if (t4 == 1) PRO(4);
    const uint32_t id = (lane >> 3) == (lane & 3) ? ((lane & 4) ? 0x3f800000u : 0x00003f80u) : 0u;
    if (t4 == 0) sts64(sb + CH_ID + lane * 8, id, id);
#pragma unroll 1
    for (int q = t4; q < 4; q += 3) {
      uint32_t m0[20];
#pragma unroll
      for (int i = 0; i < 20; i++) m0[i] = (reinterpret_cast<const uint32_t*>(p.mem0) + (lane >> 2) * (DM / 2) + q * 80 + (lane & 3))[i * 4];
      if (q < 3) bar_sync(NB_XFREE, 256);
#pragma unroll
      for (int i = 0; i < 20; i += 4) stsm4t(sb + CH_M + (q * 20 + i) * 128 + lane * 16, m0[i], m0[i + 1], m0[i + 2], m0[i + 3]);
    }
    if (t4 == 1) PRO(5);
  }
  if (cta < 4 && cta * 128 + tid < SY_N) p.other[cta * 128 + tid] = 0;
  asm volatile("barrier.cluster.wait.aligned;" ::: "memory");
  const uint32_t l8 = opaque(sb + t4 * 256 + lane * 8);
  bar_sync(NB_MEM, 384);
  uint8_t* const pool = pool_at(0);
  const uint8_t* const psrc = pool + opaque(lds32(sb + CH_TAB + lds32(sb + CH_TAB + NSLOT * 4) * 4) + t4 * 1024 + lane * 4);
  const uint32_t mdst = opaque((80 + cta / 20) * 8192 + (t4 & 1) * 4096 + (cta % 20) * 128 + lane * 4);
  int st = 0;
  uint32_t tag = 1, span = ~0u;
  auto send_tokens = [&](int s) {
    uint8_t* dst = g_kv + ((s >> 2) * 192 + cta + 3 * h) * KV_PART + (s & 3) * 4096;
    bulk_store(dst, sb + CH_K, 4096);
    bulk_store(dst + KV_V, sb + CH_V + j * 4096, 4096);
    bulk_commit();
  };
  auto send_memory = [&](int s, uint32_t km) {
    fence_async();
    uint8_t* dst = g_kv + ((s >> 2) * 192 + cta + 3 * h) * KV_PART + KV_M + (s & 3) * 1024;
    bulk_store(dst, km, 1024);
    bulk_store(dst + KV_V, sb + CH_VX + j * 1024, 1024);
    bulk_commit();
    bulk_wait<0>();
    if ((s & 3) == 3) { fence_async_global(); atomicAdd(p.sync + (s >> 2) * 8 + 4, 1); }
  };
#pragma unroll 1
  for (int s = 0; s < NSEG - 1; s++) {
    TM(0);
    STAT(0);
    if (t4 == 0) {
      if (elect()) {
        fence_async();
#pragma unroll 1
        for (int r = j + 1; r < j + 3; r++) bulk_push(mapa(sb + CH_V + j * 4096, r % 3), sb + CH_V + j * 4096, 4096, mapa(sb + MB_V, r % 3));
        send_tokens(s);
        bulk_wait_read<0>();
      }
      __syncwarp();
    }
    uint32_t c0, g0;
    if (t4 == 1) {
      __syncwarp();
      c0 = clk32(); g0 = gtime();
      if (elect()) atomicMax(p.sync + SY_TIME + s, g0);
    }
    if (t4 == 3 && s >= NSEG - 6 && elect()) asm volatile("prefetch.tensormap [%0];" :: "l"(maps + (NSEG - 2 - s)) : "memory");
    if (t4 == 3 && (s & 3) == 2 && s < NSEG - 2) wait_count(p.sync + SY_P + 5 + (s & ~3), ln_items(p.layer, (s >> 2) + 1));
    if (t4 == 2) { mbar_wait(sb + MB_V, s & 1); bar_arrive(NB_W1V, 160); }
    bar_sync(NB_PROJ2, 256);
    if (t4 == 0 && elect()) {
      mbar_expect(sb + MB_X, 4096);
      mbar_expect(sb + MB_T, 40960);
      for (int i = 0; i < 3; i++) xload(s + 1, i);
    }
    __syncwarp();
    STAT(1);
    TM(1);
    {
      const uint2 a = lds64(l8 + t4 * 256 + CH_KM), b = lds64(l8 + t4 * 256 + CH_KM + 256);
      sts64(l8 + CH_KS, hadd2(a.x, b.x), hadd2(a.y, b.y));
    }
    TM(4);
    bar_sync(NB_PRE2, 256);
    if (t4 == 0 && elect()) {
      xload(s + 1, 3);
      if (CH_XPF && s < NSEG - 2) prefetch_l2(xs + (s + 2) * 40960 + cta % 20 * 2048, 2048);
      if (CH_TPF && s >= NSEG - 7) {
        const int i = s - (NSEG - 7);
        if (i < 2) prefetch_l2(p.wb + (cta * 2 + i) * 12800, 12800);
        else if (i < 4) prefetch_l2(xs + (cta * 2 + i - 2) * 8192, 8192);
        else prefetch_l2(g_q + 15 * 32 * 3072 + (cta * 2 + i - 4) * 512, 8192);
      }
      send_memory(s, sb + CH_KS);
    }
    __syncwarp();
    if (t4 == 1) {
      const uint32_t late = min(ldg_strong32(p.sync + SY_TIME + s) - g0, 640u);
      if (elect()) sts32(sb + CH_TAB + 380, c0 + span + (late * 115 >> 6) + (j ? 60 : 0) + p.d1);
    }
    bar_sync(NB_W2, 128);
    uint32_t due = lds32(sb + CH_TAB + 380);
    due = __shfl_sync(~0u, due, 0);
    const uint8_t* ms = pool + (lds32(sb + CH_TAB + (80 + st * 4 + t4) * 4) + (l8 & 255));
    uint8_t* md = pool + (mdst + (cta >= 80 ? 2 : t4 < 2 ? st : st == 2 ? 0 : st + 1) * 32768);
    asm volatile("" : "+l"(ms), "+l"(md));
    if (CH_TW) mbar_wait(sb + MB_T, ~s & 1);
    TM(2);
    bar_sync(NB_ST, 384);
    __syncwarp();
    uint32_t tg = clk32();
    if (t4 == 3 && elect()) {
      if (s < NSEG - 2) mbar_expect(sb + MB_V, 8192);
      mbar_arrive_remote(mapa(sb + MB_F, j == 2 ? 0 : j + 1));
      mbar_arrive_remote(mapa(sb + MB_F, j == 0 ? 2 : j - 1));
    }
    if (s == NSEG - 2) work_init(sb, t4);
    __syncwarp();
    STAT(2);
    {
      float2 q[4];
      TM(3);
      if (t4 == 1 && s) span = min(span, tg - c0);
      until(s < 2 ? tg + 400 : (int)(due - tg) > p.dn ? due : tg + p.dn);
      for (int n = 0;;) {
        uint32_t v[8];
#pragma unroll
        for (int i = 0; i < 8; i++) v[i] = ldg_strong32(psrc + i * 128);
        sts64f(l8 + CH_R2, ((bf_lo(v[0]) + bf_lo(v[1])) + (bf_lo(v[2]) + bf_lo(v[3]))) + ((bf_lo(v[4]) + bf_lo(v[5])) + (bf_lo(v[6]) + bf_lo(v[7]))),
               ((bf_hi(v[0]) + bf_hi(v[1])) + (bf_hi(v[2]) + bf_hi(v[3]))) + ((bf_hi(v[4]) + bf_hi(v[5])) + (bf_hi(v[6]) + bf_hi(v[7]))));
        uint32_t bad;
        asm volatile("{.reg .pred p, q; .reg .b32 a; lop3.b32 a, %1, %2, %3, 0xFE; lop3.b32 a, a, %4, %6, 0xA8; setp.ne.u32 p, a, 0;\n"
                     "bar.red.or.pred q, %5, 128, p; selp.u32 %0, 1, 0, q;}"
                     : "=r"(bad) : "r"(differ(v[0], v[1], tag)), "r"(differ(v[2], v[3], tag)), "r"(differ(v[4], v[5], tag)), "r"(differ(v[6], v[7], tag)), "n"((int)NB_W2),
                       "r"((uint32_t)(cta < 80 || n < 3)) : "memory");
#pragma unroll
        for (int k = 0; k < 4; k++) asm volatile("ld.volatile.shared.v2.f32 {%0,%1}, [%2];" : "=f"(q[k].x), "=f"(q[k].y) : "r"(l8 - t4 * 256 + CH_R2 + k * 256) : "memory");
        TMV(12, n);
        if (!bad) break;
        spin_guard(n);
      }
      bar_arrive(NB_PUB, 384);
      SCHED();
      TM(9);
      stg_strong32(md, min(nz(pack2((q[0].x + q[1].x) + (q[2].x + q[3].x), (q[0].y + q[1].y) + (q[2].y + q[3].y))), t4 < 2 ? ~0u : 0u));
      tg = clk64() + p.d2;
      if (s >= 2 && (int)(due + p.dx - tg) > 0) tg = due + p.dx;
      TM(8);
    }
    STAT(3);
    until(tg);
    TM(10);
    for (int n = 0;;) {
      uint2 g[10];
#pragma unroll
      for (int i = 0; i < 10; i++) g[i] = ldg_strong64(ms + i * 256);
      if (n == 0) bar_sync(NB_XFREE, 256);
      uint32_t m = ~0u, bad;
#pragma unroll
      for (int i = 0; i < 10; i++) { sts64(l8 + CH_M + t4 * 2304 + i * 256, g[i].x, g[i].y); m = __vimin3_u32(m, g[i].x, g[i].y); }
      TMV(13, n);
      TM(11);
      asm volatile("{.reg .pred p; setp.eq.u32 p, %1, 0; vote.sync.any.pred p, p, 0xffffffff; @!p bar.sync %2, 384; selp.u32 %0, 1, 0, p;}" : "=r"(bad) : "r"(m), "n"((int)NB_MEM) : "memory");
      if (!bad) break;
      spin_guard(n);
    }
    if (++st == 3) st = 0;
    tag ^= 0x10001;
  }
  if (t4 == 0) {
    if (elect()) { fence_async(); send_tokens(NSEG - 1); }
    __syncwarp();
    bar_sync(NB_PRE2, 288);
    if (elect()) {
      send_memory(NSEG - 1, sb + CH_M);
      asm volatile("mbarrier.arrive.shared::cta.b64 _, [%0], 8;" :: "r"(sb + WK_BAR + 64) : "memory");
    }
    __syncwarp();
  }
}

__device__ __forceinline__ void chain_start(const ChainParams& p, const uint32_t sb, const int warp) {
  if (warp == 1 && elect()) {
#pragma unroll
    for (int i = 0; i < 6; i++) mbar_init(sb + CH_BAR + 8 * i, i == 2 ? 5 : i == 5 ? 2 : 1);
    asm volatile("fence.mbarrier_init.release.cluster;" ::: "memory");
    mbar_expect(sb + MB_V, 8192);
    atomicAdd(p.sync + SY_UP, 1);
    asm volatile("{.reg .pred p; setp.ne.u32 p, %0, 1024; @p trap;}" :: "r"(sb & 0xffffff));
  }
  if (warp == 0 && elect()) {
#pragma unroll
    for (int i = 0; i < 8; i++) mbar_init(sb + MB_W + 8 * i, 1);
    asm volatile("fence.mbarrier_init.release.cluster;" ::: "memory");
  }
  __syncthreads();
  asm volatile("barrier.cluster.arrive.relaxed.aligned;" ::: "memory");
}

struct WorkParams {
  ChainParams ch;
  CUtensorMap wo, xn, wb[3], xp, wq, wc[2], out;
  const __nv_bfloat16* x;
  uint32_t* sync;
  int kind, qa_end, idle;
};
#define GO_320 4
#define GO_TAIL 1
#define PF_NS 400
enum { WK_FIRST = 0, WK_LEAD = 1, WK_CHAIN = 2, WK_LAST = 3 };
enum { IT_ATT = 0, IT_OP = 1, IT_FIN = 2, IT_BQ = 3, IT_BO = 4, IT_LN = 5, IT_Q = 6, IT_LN0 = 7, IT_OUT = 8 };
constexpr int C_EARLY = 1 << 20, C_LATE = 1 << 21, C_TAIL = 1 << 22;

__device__ __forceinline__ uint32_t item_count(int type, int b) { return type == IT_ATT ? 32 : type == IT_OP ? op_tiles(b) * op_split(b) : type == IT_FIN ? fin_items(b) : bq_items(b); }
__device__ __forceinline__ uint32_t item_need(int type, int b) { return type == IT_ATT ? 96 : item_count(type - 1, b); }
__device__ __forceinline__ int item_cols(int type, int b) {
  return type == IT_ATT || type == IT_Q ? 192 : type == IT_OUT ? 80 : type == IT_BQ ? (b < BQ_12 ? 320 : b < BQ_24 ? 160 : 80) : type == IT_OP && b >= OP_N4 ? 160 : 320; }
__device__ __forceinline__ int item_groups(int type, int b) { const int n = type == IT_FIN ? fin_items(b) : ln_items(type == IT_LN, b); return n == 4 ? 4 : n == 8 ? 2 : 1; }
#define RES_OP 0
#define RES_B 3
#define HOLD_B 12
constexpr int RES_N = RES_OP ? op_tiles(14) * op_split(14) : 0, RES_BQ = RES_B;
__device__ __forceinline__ bool reserved(int type, int b) { return type == IT_ATT ? b == 15 : type == IT_OP ? RES_OP && b == 14 : type == IT_BQ && b < RES_BQ; }
__device__ __forceinline__ int reserved_item(int cta) {
  const int h = cta / 3, j = cta - 3 * h, i = h + (j - 1) * 32;
  if (j == 0) return C_EARLY | IT_ATT << 16 | 15 << 8 | h;
  return i < RES_N ? C_TAIL | IT_OP << 16 | 14 << 8 | i : i - RES_N < RES_BQ * 6 ? C_TAIL | IT_BQ << 16 | ((i - RES_N) / 6) << 8 | (i - RES_N) % 6 : -1;
}
constexpr int LEAD1 = 12;
__device__ __forceinline__ int lead_item(int layer, int qa_end, int i) {
  if (layer == 2) return i < 128 ? C_EARLY | C_LATE | IT_OUT << 16 | (i >> 3) << 8 | (i & 7) : -1;
  if (layer == 0) {
    if (i < 32) return IT_LN0 << 16 | (i >> 4) << 8 | (i & 15);
    if (i < 88) return IT_LN0 << 16 | ((i - 24) >> 2) << 8 | (i & 3);
    i -= 88;
  } else {
    if (i < 4) return C_EARLY | IT_BO << 16 | (i >> 1) << 8 | (i & 1);
    if (i < 12) return C_EARLY | IT_LN << 16 | ((i - 4) >> 2) << 8 | (i & 3);
    if (i < 40) return C_EARLY | IT_BO << 16 | ((i - 8) >> 1) << 8 | (i & 1);
    if (i < 96) return C_EARLY | IT_LN << 16 | ((i - 32) >> 2) << 8 | (i & 3);
    i -= 96;
  }
  return i < (16 - qa_end) * 32 ? C_EARLY | IT_Q << 16 | (qa_end + (i >> 5)) << 8 | (i & 31) : -1;
}

struct Ring {
  uint32_t sb;
  int pos, seq;
  __device__ __forceinline__ uint32_t full() const { return sb + WK_BAR + 8 * (seq & 7); }
  __device__ __forceinline__ uint32_t take(int len) { if (pos + len > WK_SLOTS) pos = 0; pos += len; seq++; return sb + (pos - len) * 8192; }
  __device__ __forceinline__ uint32_t wait(int len) { mbar_wait(full(), (seq >> 3) & 1); return take(len); }
  __device__ __forceinline__ void release(int sq) const { if (elect()) mbar_arrive(sb + WK_BAR + 64 + 8 * (sq & 7)); }
};

struct Pending {
  uint32_t w[48], done;
  uint4* dst;
  __device__ __forceinline__ void store(int i) const { dst[(i >> 2) * 1024 + (i & 3) * 32] = make_uint4(w[4 * i], w[4 * i + 1], w[4 * i + 2], w[4 * i + 3]); }
  __device__ __forceinline__ void finish() { __syncwarp(); if (elect()) mbar_arrive(done); done = 0; }
  __device__ __forceinline__ void flush() {
    if (done) {
#pragma unroll
      for (int i = 0; i < 12; i++) store(i);
      finish();
    }
  }
};

template <int N>
__device__ __forceinline__ void gemm_item(float* d, Ring& r, int nkb, uint32_t go, int ask, Pending& pend) {
  const int warp = __shfl_sync(~0u, fresh_tid() >> 5, 0), wg = warp >> 2;
#pragma unroll 1
  for (int kb = 0; kb < nkb; kb++) {
    const uint32_t base = r.wait(2 + (N + 63) / 64);
    const uint64_t da = mkdesc(base + wg * 8192, 128, 1024, 0), db = mkdesc(base + 16384, 8192, 1024, 1);
    wg_fence();
#pragma unroll
    for (int kk = 0; kk < 4; kk++) {
      if (N == 80) wg_ss80_01(d, da + kk * 16, db + kk * 128, (kb | kk) != 0);
      else if (N == 160) wg_ss160_01(d, da + kk * 16, db + kk * 128, (kb | kk) != 0);
      else wg_ss192_01(d, da + kk * 16, db + kk * 128, (kb | kk) != 0);
      if (N == 320) wg_ss128_01(d + 96, da + kk * 16, db + kk * 128 + 3 * 512, (kb | kk) != 0);
    }
    wg_commit();
    if (kb == ask && go && warp == 0 && elect()) mbar_arrive(go);
    if (N == 192 && pend.done) {
#pragma unroll
      for (int i = 0; i < 12; i++) if (kb == i / 2) pend.store(i);
      if (kb == 5) pend.finish();
    }
    if (kb > 0) { wg_wait<1>(); r.release(r.seq - 2); }
  }
  wg_wait<0>();
  reg_fence<N / 2>(d);
  r.release(r.seq - 1);
}

__device__ __forceinline__ void attn_a_warp(Ring& r, Pending& pend, bool now, const int warp) {
  uint32_t (&q)[48] = pend.w;
  const int lane = fresh_tid() & 31, g = lane >> 2, c = lane & 3, seg = warp & 3;
  const bool half = warp >= 4;
  const float k2 = 0.07216878364870322f * 1.44269504089f, NEG = -INFINITY;
  float sc[5][4] = {};
#pragma unroll
  for (int i = 0; i < 8; i++) sc[3 + (i >> 2)][i & 3] = half ? 0.f : NEG;
  uint32_t base, f[2][40] = {};
  const uint32_t ka = seg * 4096 + lane * 16, va = seg * 4096 + (lane & 8) * 32 + (lane & 16) * 8 + (lane & 7) * 16;
  auto load = [&](int n) {
    uint32_t* d = f[n & 1];
    base = n & 1 ? base + KV_PART : r.wait(5);
    const uint32_t a = base + (n < 3 ? ka : va), m = base + KV_M + seg * 1024;
#pragma unroll
    for (int i = 0; i < 4; i++) {
      if (n >= 3) { const uint2 vm = lds64(m + i * 256 + lane * 8); d[2 * i] = vm.x; d[2 * i + 1] = vm.y; }
      else if (!(i & 1)) ldsm4t(&d[2 * i], m + i * 256 + lane * 16);
      (n < 3 ? ldsm4t : ldsm4)(&d[8 + 4 * i], a + half * 2048 + i * 512);
    }
    if (half) {
#pragma unroll
      for (int i = 0; i < 4; i++) (n < 3 ? ldsm4t : ldsm4)(&d[24 + 4 * i], a + i * 512);
    }
  };
  load(0);
#pragma unroll
  for (int u = 0; u < 3; u++) {
    if (u == 2) r.release(r.seq - 2);
    load(u + 1);
    SCHED();
    const uint32_t* b = f[u & 1];
#pragma unroll
    for (int kk = 0; kk < 4; kk++) {
      const uint32_t* a = &q[16 * u + 4 * kk];
      mma16(sc[0], a[0], a[1], a[2], a[3], b[2 * kk], b[2 * kk + 1]);
      mma16(sc[1], a[0], a[1], a[2], a[3], b[8 + 4 * kk], b[9 + 4 * kk]);
      mma16(sc[2], a[0], a[1], a[2], a[3], b[10 + 4 * kk], b[11 + 4 * kk]);
    }
    if (half) {
#pragma unroll
      for (int kk = 0; kk < 4; kk++) {
        const uint32_t* a = &q[16 * u + 4 * kk];
        mma16(sc[3], a[0], a[1], a[2], a[3], b[24 + 4 * kk], b[25 + 4 * kk]);
        mma16(sc[4], a[0], a[1], a[2], a[3], b[26 + 4 * kk], b[27 + 4 * kk]);
      }
    }
    SCHED();
  }
  load(4);
  SCHED();
  if (2 * c > g) { sc[1][0] = NEG; sc[2][2] = NEG; }
  if (2 * c + 1 > g) { sc[1][1] = NEG; sc[2][3] = NEG; }
  sc[2][0] = sc[2][1] = NEG;
  uint32_t pp[5][2]; float inv[2];
#pragma unroll
  for (int hh = 0; hh < 2; hh++) {
    float m = NEG, l = 0.f;
#pragma unroll
    for (int n = 0; n < 5; n++) m = fmaxf(m, fmaxf(sc[n][2 * hh], sc[n][2 * hh + 1]));
    m = fmaxf(m, __shfl_xor_sync(~0u, m, 1)); m = fmaxf(m, __shfl_xor_sync(~0u, m, 2));
#pragma unroll
    for (int n = 0; n < 5; n++) { const float x = ex2((sc[n][2 * hh] - m) * k2), y = ex2((sc[n][2 * hh + 1] - m) * k2); l += x + y; pp[n][hh] = pack2(x, y); }
    l += __shfl_xor_sync(~0u, l, 1); l += __shfl_xor_sync(~0u, l, 2);
    inv[hh] = rcp(l);
  }
#pragma unroll
  for (int u = 0; u < 3; u++) {
    float o[8][4] = {};
    const uint32_t* b = f[~u & 1];
#pragma unroll
    for (int n = 0; n < 8; n++) mma8(o[n], pp[0][0], pp[0][1], b[n]);
#pragma unroll
    for (int n = 0; n < 8; n++) mma16(o[n], pp[1][0], pp[1][1], pp[2][0], pp[2][1], b[8 + 2 * n], b[9 + 2 * n]);
    if (half) {
#pragma unroll
      for (int n = 0; n < 8; n++) mma16(o[n], pp[3][0], pp[3][1], pp[4][0], pp[4][1], b[24 + 2 * n], b[25 + 2 * n]);
    }
    SCHED();
    if (u != 1) r.release(r.seq - 2 + u / 2);
    if (u == 0) { load(5); SCHED(); }
#pragma unroll
    for (int i = 0; i < 16; i++) q[16 * u + i] = pack2(o[i & 7][i >> 2 & 2] * inv[i >> 3], o[i & 7][(i >> 2 & 2) + 1] * inv[i >> 3]);
    if (now) {
#pragma unroll
      for (int i = 0; i < 4; i++) pend.store(4 * u + i);
    }
  }
}

__device__ __forceinline__ void ln_groups(Ring& ring, uint32_t scratch, int planes, int rg, bool two) {
  constexpr int G = 2;
  const int warp = fresh_tid() >> 5, lane = fresh_tid() & 31;
  const uint32_t id = (lane >> 3) == (lane & 3) ? ((lane & 4) ? 0x3f800000u : 0x00003f80u) : 0u;
  const uint32_t at = (warp * 160 + lane) * 8, at1 = planes > 1 ? at : (lane >> 2) * 1280 + warp * 160 + (lane & 3) * 4;
  const uint32_t step = planes > 1 ? 256 : 32, half = planes > 1 ? 4 : 16;
  float v[G][5][4] = {};
#pragma unroll
  for (int r = 0; r < G; r++) {
#pragma unroll 1
    for (int k = r && !two ? 0 : planes; k > 0; k -= 4) {
      const uint32_t a = ring.wait(min(k, 4) + 1);
      if (k == 1) {
#pragma unroll
        for (int i = 0; i < 5; i++) mma8(v[r][i], lds32(a + at1 + i * step), lds32(a + at1 + i * step + half), id);
      } else {
#pragma unroll
        for (int i = 0; i < 10; i++) {
          if (i == 5 && k < 4) break;
          const uint2 x = lds64(a + at + i / 5 * 20480 + i % 5 * 256), y = lds64(a + at + i / 5 * 20480 + 10240 + i % 5 * 256);
          mma16(v[r][i % 5], x.x, x.y, y.x, y.y, id, id);
        }
      }
      ring.release(ring.seq - 1);
    }
  }
  uint2 xr[G][5];
  float mw[G];
  scratch += (lane >> 2) * 64;
#pragma unroll
  for (int r = 0; r < G; r++) {
    float m = 0.f, q2[4] = {};
#pragma unroll
    for (int i = 0; i < 5; i++) {
      float* t = v[r][i];
      xr[r][i] = make_uint2(pack2(t[0], t[1]), pack2(t[2], t[3]));
      t[0] = bf_lo(xr[r][i].x); t[1] = bf_hi(xr[r][i].x); t[2] = bf_lo(xr[r][i].y); t[3] = bf_hi(xr[r][i].y);
      m += (t[0] + t[1]) + (t[2] + t[3]);
    }
    m += __shfl_xor_sync(~0u, m, 1); m += __shfl_xor_sync(~0u, m, 2);
    m *= 1.f / 80;
#pragma unroll
    for (int i = 0; i < 20; i++) { float& t = v[r][i >> 2][i & 3]; t -= m; q2[i & 3] = fmaf(t, t, q2[i & 3]); }
    float q = (q2[0] + q2[1]) + (q2[2] + q2[3]);
    mw[r] = m;
    q += __shfl_xor_sync(~0u, q, 1); q += __shfl_xor_sync(~0u, q, 2);
    if ((lane & 3) == 0) sts64f(scratch + r * 512 + warp * 8, m, q);
  }
  bar_sync(1, 256);
#pragma unroll
  for (int r = 0; r < G; r++) {
    const float4 t = lds128f(scratch + r * 512 + (lane & 3) * 16);
    float mean = t.x + t.z;
    mean += __shfl_xor_sync(~0u, mean, 1); mean += __shfl_xor_sync(~0u, mean, 2);
    mean *= 0.125f;
    float var = (t.y + t.w) + 80.f * ((t.x - mean) * (t.x - mean) + (t.z - mean) * (t.z - mean));
    var += __shfl_xor_sync(~0u, var, 1); var += __shfl_xor_sync(~0u, var, 2);
    float rs;
    asm("rsqrt.approx.ftz.f32 %0, %1;" : "=f"(rs) : "f"(var * (1.f / DM) + 1e-5f));
#pragma unroll
    for (int i = 0; i < 20; i++) v[r][i >> 2][i & 3] = fmaf(v[r][i >> 2][i & 3], rs, (mw[r] - mean) * rs);
  }
#pragma unroll
  for (int r = 0; r < G; r++) {
    if (r && !two) break;
    uint32_t* xn = g_xn + (rg + r) * 2560 + warp * 320 + lane;
#pragma unroll
    for (int i = 0; i < 10; i++) xn[i * 32] = pack2(v[r][i >> 1][2 * (i & 1)], v[r][i >> 1][2 * (i & 1) + 1]);
#pragma unroll
    for (int i = 0; i < 5; i++) g_x[(rg + r) * 17 * 1280 + warp * 160 + i * 32 + lane] = xr[r][i];
  }
}

__device__ __forceinline__ void store_partial(const float* d, int b, int split, int unit, int nu) {
  uint2* dst = g_x + (((b * 16 + (fresh_tid() >> 5) * 2) * 17 + 1 + split) * 40 + unit) * 32 + (fresh_tid() & 31);
#pragma unroll
  for (int u = 0; u < 20; u++) {
    if (u == 10 && nu == 10) break;
    dst[u * 32] = make_uint2(pack2(d[8 * u], d[8 * u + 1]), pack2(d[8 * u + 4], d[8 * u + 5]));
    dst[(680 + u) * 32] = make_uint2(pack2(d[8 * u + 2], d[8 * u + 3]), pack2(d[8 * u + 6], d[8 * u + 7]));
  }
}

__device__ __forceinline__ void store_bqkv(const float* d, int b, int idx, int nh) {
  const int lane = fresh_tid() & 31, c = lane & 3, rg = b * 16 + (fresh_tid() >> 5) * 2, h0 = idx * nh;
  const float sc = h0 < 32 ? 0.22360679775f * 1.44269504089f : 1.f;
  const bool lo = c < 2;
  uint32_t* da = g_bqkv + (h0 * 256 + rg) * 96 + lane;
  uint32_t* db = da + 256 * 96 + (lo ? 2 : -2);
  uint32_t pad[2];
#pragma unroll
  for (int r = 0; r < 2; r++) pad[r] = !(c & 1) && (h0 >= 64 || (h0 >= 32 && (lane & 4) && poly_group(rg + r))) ? 0x00003f80u : 0u;
#pragma unroll
  for (int q = 0; q < 8; q++) {
    if ((q == 2 || q == 4) && nh == 2 * q) break;
#pragma unroll
    for (int r = 0; r < 2; r++) {
      uint32_t w[5];
#pragma unroll
      for (int i = 0; i < 5; i++) w[i] = pack2(d[20 * q + 4 * i + 2 * r] * sc, d[20 * q + 4 * i + 2 * r + 1] * sc);
      const int o = q * 2 * 256 * 96 + r * 96;
      da[o] = w[0]; da[o + 32] = w[1]; da[o + 64] = lo ? w[2] : pad[r];
      db[o] = lo ? w[3] : w[2]; db[o + 32] = lo ? w[4] : w[3]; db[o + 64] = lo ? pad[r] : w[4];
    }
  }
}

__device__ __forceinline__ void work_loader(const WorkParams& p, const uint32_t sb, const bool weights) {
  const uint32_t bars = sb + WK_BAR, bIF = bars + 128, bIE = bars + 160, bGo = bars + 224, slots = bars + 272;
  int pos = 0, seq = 0, tail = 0, used = 0;
  uint32_t lens = 0;
  const bool one = elect();
  if (p.kind == WK_CHAIN) {
    seq = 1; used = lens = 8;
    if (one) mbar_arrive(bars);
  }
  for (int n = 0;; n++) {
    mbar_wait(bIF + 8 * (n & 3), (n >> 2) & 1);
    const int code = __shfl_sync(~0u, (int)lds32(slots + 4 * (n & 3)), 0);
    if (code < 0) break;
    const int type = (code >> 16) & 15, b = (code >> 8) & 255, idx = code & 255;
    if (one) mbar_arrive(bIE + 8 * (n & 3));
    const bool qa = type == IT_ATT && b < p.qa_end, ln = type == IT_FIN || type == IT_LN || type == IT_LN0;
    const int parts = ln ? item_groups(type, b) : type == IT_ATT ? 2 : 1;
#pragma unroll 1
    for (int part = 0; part < parts; part++) {
      int bytes = 163840, chunk = 40960, nb = 0, flag = b * 8 + 4 + type, need = item_need(type & 3, b), c0 = 0, c3 = idx, c4 = 0, step = 64;
      const uint8_t* src = g_kv + (b * 32 + idx) * 6 * KV_PART;
      const CUtensorMap* m = nullptr;
      if (ln) {
        const int rg = b * 16 + idx * parts + part;
        bytes = (type == IT_FIN ? op_split(b) + 1 : type == IT_LN ? 2 : 1) * 10240;
        src = type == IT_LN0 ? reinterpret_cast<const uint8_t*>(p.x) + rg * 10240 : reinterpret_cast<const uint8_t*>(g_x) + rg * 174080;
        if (type == IT_LN) { flag = SY_P + b * 4; need = 2; }
        if (type == IT_LN0 || part) need = 0;
      } else if (part) {
        bytes = 6 * KV_PART;
      } else if (type == IT_ATT && !qa) {
        bytes = chunk = 49152;
        src = reinterpret_cast<const uint8_t*>(g_q) + (b * 32 + idx) * 49152;
        flag = SY_P + b * 4 + 3; need = 32;
      } else {
        const int cols = item_cols(type, b);
        chunk = 16384; nb = (cols + 63) >> 6;
        src = reinterpret_cast<const uint8_t*>(g_of) + b * 163840;
        if (type == IT_OP) {
          const int nkb = op_steps(b), kb0 = (idx >> op_tiles(b) / 2) * nkb;
          bytes = nkb * 16384;
          src = reinterpret_cast<const uint8_t*>(g_o) + (b * 96 + kb0) * 16384;
          if (weights) m = &p.wo;
          c0 = (idx & (op_tiles(b) - 1)) * cols; c3 = 0; c4 = kb0 * 2; step = 2;
        } else if (type == IT_BQ) {
          m = weights ? &p.wb[cols >> 7] : &p.xn;
        } else if (type == IT_BO || type == IT_OUT) {
          if (weights) m = &p.wc[cols >> 8];
          flag = SY_OB; need = type == IT_BO && b < 2 ? 32 : -1;
        } else {
          m = weights ? &p.wq : &p.xp;
          flag = SY_P + b * 4 + 1; need = ln_items(p.ch.layer, b);
        }
      }
      if (!weights) {
        c3 = b * 4;
        if (need < 0) pdl_wait(); else if (need) wait_count(p.sync + flag, need);
        if ((ln ? !part : part && (!qa || (code & C_EARLY))) && one) mbar_arrive(bGo);
      }
      const int boxes = weights ? nb : m != nullptr;
#pragma unroll 1
      for (; bytes > 0; bytes -= chunk) {
        const int now = min(bytes, chunk), len = ((now + 8191) >> 13) + nb, skip = pos + len > WK_SLOTS ? WK_SLOTS - pos : 0, sh = 4 * (seq & 7);
        used += len + skip;
        while (used > WK_SLOTS || seq - tail >= 8) {
          mbar_wait(bars + 64 + 8 * (tail & 7), (tail >> 3) & 1);
          used -= (lens >> 4 * (tail & 7)) & 15;
          tail++;
        }
        lens = (lens & ~(15u << sh)) | (len + skip) << sh;
        if (pos + len > WK_SLOTS) pos = 0;
        const uint32_t bar = bars + 2 * sh, dst = sb + pos * 8192 + weights * 16384;
        if (one) mbar_expect(bar, weights ? nb * 8192 : now);
#pragma unroll 1
        for (int i = 0; i < boxes; i++)
          if (one) tma_load5(dst + i * 8192, m, c0 + i * 64, c3, c4, bar);
        if (!weights && !m && one) bulk_load_last(dst, src, now, bar);
        if (weights) c4 += step; else c0 += 128;
        src += chunk; pos += len; seq++;
      }
    }
  }
}

__global__ void __launch_bounds__(384, 1) work_kernel(const __grid_constant__ WorkParams p) {
  extern __shared__ __align__(1024) uint8_t smem_raw[];
  const uint32_t sb = s2u(smem_raw), bars = sb + WK_BAR;
  const uint32_t bIF = bars + 128, bIE = bars + 160, done = bars + 192, bGo = bars + 224, slots = bars + 272, scratch = bars + 384;
  const int warp = __shfl_sync(~0u, threadIdx.x >> 5, 0);
  uint32_t* const sync = p.sync;
  TRACE(0);
  pdl_launch();
  if (p.kind == WK_LEAD && !helper_sm() && __syncthreads_or(threadIdx.x == 0 && ldg_strong32(sync + SY_PRE + 1) >= LEAD1)) { pdl_wait(); return; }
  if (p.kind == WK_CHAIN) {
    chain_start(p.ch, sb, warp);
  } else {
    if (warp < 4) work_init(sb, warp);
    __syncthreads();
    if (p.kind == WK_FIRST) {
      if (!(warp & 13)) probe_slots(bars + 320);
      if (!helper_sm()) return;
    }
  }
  if (warp >= 8) {
    asm volatile("setmaxnreg.dec.sync.aligned.u32 40;");
    if (p.kind == WK_CHAIN) chain_comm(p.ch, sb, &p.wo);
    const int warp = __shfl_sync(~0u, fresh_tid() >> 5, 0), lane = fresh_tid() & 31;
    if (warp == 9) {
      const bool keep = p.kind > WK_LEAD || helper_sm();
      int n = 0, code = p.kind == WK_CHAIN ? reserved_item(blockIdx.x) : -1;
      if (code >= 0) {
        if (lane == 0) { sts32(slots, code); mbar_arrive(bIF); }
        n = 1;
      }
      const int b = lane & 15, layer = p.kind == WK_LAST ? 2 : sync != g_sync;
      bool first = layer == 1, lead = p.kind != WK_CHAIN;
      for (;; n++) {
        if (n > 0) mbar_wait(bGo, (n - 1) & 1);
        mbar_wait(bIE + 8 * (n & 3), ((n >> 2) & 1) ^ 1);
        code = -1;
        if (lead) {
          int i = blockIdx.x + n * 256;
          if (first) { if (lane == 0) i = atomicAdd(sync + SY_PRE + 1, 1); i = __shfl_sync(~0u, i, 0); first = i < LEAD1; }
          if (layer < 2 && !first) {
            if (lane == 0) i = keep ? atomicAdd(sync + SY_PRE, 1) + layer * LEAD1 : 1 << 20;
            i = __shfl_sync(~0u, i, 0);
            if (!keep) pdl_wait();
          }
          code = lead_item(layer, p.qa_end, i);
          lead = code >= 0 || layer == 2 || !keep;
          if (!lead && p.kind <= WK_LEAD) {
            const uint32_t t0 = gtime();
            while (!lead && __all_sync(~0u, ldg_strong32(sync + SY_UP) < 96)) lead = __any_sync(~0u, gtime() - t0 > 20000);
          }
        }
        if (!lead) {
          int spin = 0, ticket = 0;
          if (lane == 0) ticket = atomicAdd(sync + SY_T, 1);
          for (;;) {
            const uint4 hd = ldg_strong128(sync + b * 8), pr = ldg_strong128(sync + b * 8 + 4);
            const uint32_t hv[4] = {hd.x, hd.y, hd.z, hd.w}, pv[4] = {pr.x, pr.y, pr.z, pr.w};
            const uint32_t chain_done = __ballot_sync(~0u, (pr.x & 0xffff) >= 96) | (p.kind == WK_CHAIN) << 15;
            int left[4], avail[4], rdy = 0, claimed = 0, upstream = 0;
#pragma unroll
            for (int t = 0; t < 4; t++) {
              const int cnt = lane < 16 && !reserved(t, b) ? item_count(t, b) : 0;
              left[t] = max(cnt - (int)hv[t], 0);
              claimed += cnt - left[t];
              const bool ready = (pv[t] & 0xffff) >= item_need(t, b);
              rdy |= ready << t;
              bool ok = ready || (t != IT_ATT && (chain_done >> 15 & 1) && !left[t - 1] && (t < 2 || !left[t - 2]));
              if (t == IT_BQ && (chain_done >> HOLD_B & 1) && !(chain_done >> 15 & 1)) ok = false;
              avail[t] = ok ? left[t] : 0;
              upstream |= __any_sync(~0u, left[t] > 0);
            }
            if (!upstream) { code = -1; break; }
            int rank = max(__shfl_sync(~0u, ticket, 0) - __reduce_add_sync(~0u, claimed), 0), type = -1, mine = 0;
#pragma unroll
            for (int c = 0; c < 7; c++) {
              const int t = c == 0 || c == 6 ? IT_ATT : c == 1 || c == 4 ? IT_FIN : c == 2 ? IT_OP : IT_BQ;
              int a = c == 2 || (rdy >> t & 1) == (c < 4) ? avail[t] : 0;
              if (c == 6) a = b < p.qa_end && !(rdy & 1) && ((chain_done << 1 | 1) >> b & 1) ? left[t] : 0;
              const int tot = __reduce_add_sync(~0u, a);
              if (type < 0) { if (rank < tot) { type = t; mine = a; } else rank -= tot; }
            }
            if (type >= 0) {
#pragma unroll
              for (int o = 1; o < 16; o <<= 1) { const int y = __shfl_up_sync(~0u, mine, o); if (lane >= o) mine += y; }
              const int blk = __ffs(__ballot_sync(~0u, mine > rank)) - 1;
              const int early = !(__shfl_sync(~0u, rdy, blk) >> type & 1);
              uint32_t idx = 0;
              if (lane == 0) idx = atomicAdd(sync + blk * 8 + type, 1);
              idx = __shfl_sync(~0u, idx, 0);
              if (idx < item_count(type, blk)) { code = (chain_done >> 14 & 1) << 22 | early << 20 | type << 16 | blk << 8 | idx; break; }
            } else {
              __nanosleep(50);
            }
            spin_guard(spin);
          }
        }
        if (lane == 0) {
          sts32(slots + 4 * (n & 3), code);
          mbar_arrive(bIF + 8 * (n & 3));
        }
        __syncwarp();
        if (code < 0) break;
      }
    } else if (warp >= 10) {
      work_loader(p, sb, warp == 10);
    } else {
      for (int n = 0;; n++) {
        mbar_wait(bIF + 8 * (n & 3), (n >> 2) & 1);
        const int code = __shfl_sync(~0u, (int)lds32(slots + 4 * (n & 3)), 0);
        if (code < 0) break;
        const int type = (code >> 16) & 15, b = (code >> 8) & 255;
        mbar_wait(done + 8 * (n & 3), (n >> 2) & 1);
        if (elect()) {
          if (type != IT_OUT) red_release(sync + (type < IT_BQ ? b * 8 + 5 + type : SY_P + b * 4 + ((0x13102 >> 4 * (type - IT_BQ)) & 3)), 1);
          mbar_arrive(bIE + 8 * (n & 3));
        }
        __syncwarp();
      }
    }
  } else {
    asm volatile("setmaxnreg.inc.sync.aligned.u32 232;");
    if (p.kind == WK_CHAIN) chain_compute(p.ch, sb);
    const int warp = __shfl_sync(~0u, fresh_tid() >> 5, 0), lane = fresh_tid() & 31;
    Ring r{sb, 0, p.kind == WK_CHAIN};
    Pending pend = {};
    int nln = 0;
    auto projects = [&](int n) {
      uint32_t here;
      asm volatile("{.reg .pred p; mbarrier.test_wait.parity.shared::cta.b64 p, [%1], %2; vote.sync.all.pred p, p, 0xffffffff; selp.u32 %0, 1, 0, p;}" : "=r"(here) : "r"(bIF + 8 * (n & 3)), "r"((n >> 2) & 1) : "memory");
      if (!here) return false;
      const int code = __shfl_sync(~0u, (int)lds32(slots + 4 * (n & 3)), 0);
      return code >= 0 && (((code >> 16) & 15) == IT_Q || (((code >> 16) & 15) == IT_ATT && ((code >> 8) & 255) < p.qa_end));
    };
#pragma unroll 1
    for (int n = 0;; n++) {
      if (pend.done && !projects(n)) pend.flush();
      mbar_wait(bIF + 8 * (n & 3), (n >> 2) & 1);
      const int code = __shfl_sync(~0u, (int)lds32(slots + 4 * (n & 3)), 0);
      if (code < 0) { TRACE(2); break; }
      const int type = (code >> 16) & 15, b = (code >> 8) & 255, idx = code & 255;
      const uint32_t go = (code & C_LATE) || (type == IT_ATT && (code & C_EARLY)) ? 0 : bGo;
      ITEM(code & 0xfffff, 0);
      if (type == IT_ATT || type == IT_Q) {
        if (type == IT_Q || b < p.qa_end) {
          float d[96] = {};
          reg_fence<96>(d);
          ITEM(9 << 16 | (code & 0xffff), 0);
          gemm_item<192>(d, r, 10, go, 4, pend);
          ITEM(9 << 16 | (code & 0xffff), 1);
#pragma unroll
          for (int i = 0; i < 48; i++) pend.w[i] = pack2(d[2 * i], d[2 * i + 1]);
        } else {
          const uint32_t base = r.wait(6) + warp * 2048 + lane * 16;
#pragma unroll
          for (int i = 0; i < 12; i++) {
            const uint4 t = lds128(base + (i >> 2) * 16384 + (i & 3) * 512);
            pend.w[4 * i] = t.x; pend.w[4 * i + 1] = t.y; pend.w[4 * i + 2] = t.z; pend.w[4 * i + 3] = t.w;
          }
          __syncwarp();
          r.release(r.seq - 1);
        }
        const bool now = type == IT_ATT && !projects(n + 1);
        if (type == IT_Q) {
          pend.dst = g_q + (b * 32 + idx) * 3072 + warp * 128 + lane;
        } else {
          pend.dst = g_o + (b * 32 + idx) * 3072 + (warp & 3) * 256 + (warp >> 2) * 128 + (lane & 3) * 8 + (lane >> 2);
          attn_a_warp(r, pend, now, warp);
        }
        pend.done = done + 8 * (n & 3);
        if (now) pend.finish();
      } else {
        if (type == IT_FIN || type == IT_LN || type == IT_LN0) {
          const int ng = item_groups(type, b);
          const int planes = type == IT_FIN ? op_split(b) + 1 : type == IT_LN ? 2 : 1;
#pragma unroll 1
          for (int i = 0; i < ng; i += 2) ln_groups(r, scratch + (nln++ & 1) * 1024, planes, b * 16 + idx * ng + i, ng > 1);
        } else {
          const int cols = item_cols(type, b), nkb = type == IT_OP ? op_steps(b) : 10;
          float d[160] = {};
          if (type == IT_OUT) {
            const uint2* x = g_x + ((b * 16 + warp * 2) * 680 + idx * 5) * 32 + lane;
#pragma unroll
            for (int i = 0; i < 10; i++) { const uint2 y = __ldcg(x + (i / 5 * 680 + i % 5) * 32); d[40 + 2 * i] = __uint_as_float(y.x); d[41 + 2 * i] = __uint_as_float(y.y); }
          }
          reg_fence<160>(d);
          if (type != IT_OUT) ITEM((type == IT_BQ ? 10 : 11) << 16 | (code & 0xffff), 0);
          const int ask = max(nkb - ((code & C_TAIL ? GO_TAIL : GO_320) << (2 - (cols >> 7))), 0);
          if (cols == 320) gemm_item<320>(d, r, nkb, go, ask, pend);
          else if (cols == 160) gemm_item<160>(d, r, nkb, go, ask, pend);
          else gemm_item<80>(d, r, nkb, go, ask, pend);
          if (type != IT_OUT) ITEM((type == IT_BQ ? 10 : 11) << 16 | (code & 0xffff), 1);
          reg_fence<160>(d);
          if (type == IT_OUT) {
            bar_sync(1, 256);
            const uint32_t dst = sb + (warp * 16 + (lane & 15)) * 160 + (lane >> 4) * 16;
#pragma unroll
            for (int u = 0; u < 5; u++) {
              uint32_t w[4];
#pragma unroll
              for (int i = 0; i < 4; i++) { const uint32_t y = __float_as_uint(d[40 + (i & 1) * 10 + 2 * u + (i >> 1)]); w[i] = pack2(bf_lo(y) + d[8 * u + 2 * i], bf_hi(y) + d[8 * u + 2 * i + 1]); }
              stsm4(dst + u * 32, w[0], w[1], w[2], w[3]);
            }
            fence_async();
            __syncwarp();
            if (elect()) { tma_store(&p.out, sb + warp * 2560, idx * 80, b * 128 + warp * 16); bulk_commit(); bulk_wait<0>(); }
          } else {
            if (warp >= 4) bar_sync(7, 256);
            if (type == IT_BQ) store_bqkv(d, b, idx, 4 << (cols >> 7));
            else store_partial(d, b, cols == 320 ? idx >> 1 : idx >> 2, cols == 320 ? (idx & 1) * 20 : (idx & 3) * 10, cols >> 4);
            if (warp < 4) bar_arrive(7, 256);
          }
        }
        __syncwarp();
        if (elect()) mbar_arrive(done + 8 * (n & 3));
#pragma unroll
        for (int i = 0; i < 48; i++) pend.w[i] = 0;
      }
      if ((code & C_LATE) && warp == 4 && elect()) mbar_arrive(bGo);
      ITEM(code & 0xfffff, 1);
    }
  }
}

constexpr int AB_SMEM = 1024 + 2 * 98304 + 256;
#define AB_N 32
#define AB_WG 4
constexpr int AB_T = AB_WG * 128, AB_PASS = 8 / AB_WG;
__device__ __forceinline__ float ex2_poly(float t) {
  const uint32_t r = __float_as_uint(t) & 0xffff8000u;
  const float f = t - __uint_as_float(r);
  const float p = fmaf(fmaf(fmaf(-5.869912678e-38f, f, -1.700740250e-37f), f, -5.234869734e-37f), f, -7.522601252e-37f);
  uint32_t y;
  asm("mad.lo.u32 %0, %1, 256, %2;" : "=r"(y) : "r"(r), "r"(__float_as_uint(p)));
  return __uint_as_float(y);
}
__device__ __forceinline__ uint32_t hsq(uint32_t w, uint32_t c) { uint32_t r; asm("fma.rn.bf16x2 %0, %1, %1, %2;" : "=r"(r) : "r"(w), "r"(c)); return r; }
__device__ __forceinline__ float sq2(uint32_t w) { const float a = bf_lo(w), b = bf_hi(w); return fmaf(a, a, b * b); }

__device__ __forceinline__ void attn_b_store(const float* o, int h, int row0, int lane) {
  const int g = lane >> 2, c = lane & 3;
  const float i0 = rcp(__shfl_sync(~0u, o[8], (lane & ~3) | 2)), i1 = rcp(__shfl_sync(~0u, o[10], (lane & ~3) | 2));
#pragma unroll
  for (int jj = 0; jj < 3; jj++) {
    if (jj < 2 || c < 2) {
      const int col = h * 20 + 8 * jj + 2 * c;
      g_of[core_word(row0 + g, col)] = pack2(o[4 * jj] * i0, o[4 * jj + 1] * i0);
      g_of[core_word(row0 + g + 8, col)] = pack2(o[4 * jj + 2] * i1, o[4 * jj + 3] * i1);
    }
  }
}

__device__ __forceinline__ void attn_b_qk(float* s, uint32_t q0, uint32_t q1, uint32_t q2, uint32_t q3, uint32_t q4, uint32_t q5, uint32_t z0, uint32_t z1,
                                          uint64_t dk, uint64_t dk2) {
  wg_rs32_00(s, q0, q1, q2, q3, dk, 0);
  wg_rs32_00(s, q4, q5, z0, z1, dk2, 1);
}

struct AttnParams { const uint8_t* pf[4]; uint32_t *sync, *next; };
__global__ void __launch_bounds__(AB_T + 128, 1) attn_b_kernel(const __grid_constant__ AttnParams p) {
  extern __shared__ uint8_t smem_raw[];
  const uint32_t sb = (s2u(smem_raw) + 1023) & ~1023u, sK = sb, sV = sb + 98304, bars = sb + 2 * 98304;
  const int warp = __shfl_sync(~0u, threadIdx.x >> 5, 0), lane = threadIdx.x & 31;
  const int h = blockIdx.x & 31, quarter = blockIdx.x >> 5;
  BT(0);
  TRACE(0);
  if (warp < 10 && elect()) {
    mbar_init(bars + 8 * warp + (warp & 8) * 8, warp < 8 ? 1 : warp == 8 ? AB_T / 32 : 2);
    asm volatile("fence.mbarrier_init.release.cluster;" ::: "memory");
  }
  __syncthreads();
  if (warp >= AB_T / 32) {
    asm volatile("setmaxnreg.dec.sync.aligned.u32 32;");
    if (warp == AB_T / 32 + 1) return;
    if (warp > AB_T / 32) {
      uint32_t kmax = 0;
#pragma unroll 1
      for (int i = 0; i < 32; i++) {
        if (!(i & 3)) mbar_wait(bars + 2 * i, 0);
        const uint32_t a = sK + i * 3072 + ((threadIdx.x >> 3) & 7) * 384 + (lane & 7) * 16;
        const uint4 x = lds128(a), y = lds128(a + 128);
        const uint2 z = lds64(a + 256);
        const uint32_t n = hadd2(hsq(x.x, hsq(x.y, hsq(x.z, hsq(x.w, hsq(z.x, 0))))), hsq(y.x, hsq(y.y, hsq(y.z, hsq(y.w, hsq(z.y, 0))))));
        kmax = max(kmax, __float_as_uint(bf_lo(n) + bf_hi(n)) & 0x7fffffffu);
      }
      const uint32_t kbits = __reduce_max_sync(~0u, kmax);
      if (lane == 0) { sts32(bars + 64 + (warp & 1) * 4, kbits); mbar_arrive(bars + 136); }
      return;
    }
    const uint8_t* gk = reinterpret_cast<const uint8_t*>(g_bqkv + (32 + h) * 256 * 96);
    const uint8_t* gv = reinterpret_cast<const uint8_t*>(g_bqkv + (64 + h) * 256 * 96);
    uint32_t todo = 255;
    for (int spin = 0; todo;) {
      const uint32_t up = __ballot_sync(~0u, ld_acquire(p.sync + SY_P + (lane & 15) * 4 + 2) >= bq_items(lane & 15));
      fence_async_global();
#pragma unroll 1
      for (int i = 0; i < 8; i++) {
        if (!(todo >> i & 1) || (up >> 2 * i & 3) != 3) continue;
        todo &= ~(1u << i);
        if (elect()) {
          mbar_expect(bars + 8 * i, 24576);
          bulk_load(sK + i * 12288, gk + i * 12288, 12288, bars + 8 * i);
          bulk_load(sV + i * 12288, gv + i * 12288, 12288, bars + 8 * i);
        }
      }
      spin_guard(spin);
    }
    pdl_launch();
    TRACE(1);
#pragma unroll 1
    for (int i = lane; i < 512 && blockIdx.x < NSLOT; i += 32) reinterpret_cast<uint4*>(pool_at(blockIdx.x * 8192))[i] = make_uint4(0, 0, 0, 0);
    if (!p.next && blockIdx.x < 8) { const int i = blockIdx.x * 32 + lane; g_smpart[i] = 0; if (i < NSLOT) g_orient[i] = 0; }
    if (p.next) {
      mbar_wait(bars + 128, 0);
      if (quarter == 0 && lane == 0) red_release(p.next + SY_OB, 1);
#pragma unroll 1
      for (int i = 0; i < (PF_NS ? 32 : 0); i++) {
        if (elect()) prefetch_l2(p.pf[i >> 3] + blockIdx.x * 61440 + (i & 7) * 7680, 7680);
        __nanosleep(PF_NS);
      }
    }
    return;
  }
  asm volatile("setmaxnreg.inc.sync.aligned.u32 112;");
  constexpr int NT = SEQ / AB_N, PER = 256 / AB_N;
  uint32_t qn[8];
  auto load_q = [&](int pass) {
    const uint32_t* gq = g_bqkv + (h * 256 + pass * 128 + quarter * 32 + warp * 2) * 96 + lane;
#pragma unroll
    for (int i = 0; i < 8; i++) qn[i] = __ldcg(gq + (i & 1) * 96 + min(i >> 1, 2) * 32 + (i < 6 ? 0 : 3 - (lane & 3)));
  };
  mbar_wait(bars + 8 * quarter, 0);
  load_q(0);
#pragma unroll 1
  for (int pass = 0; pass < AB_PASS; pass++) {
    const int row0 = pass * 1024 + quarter * 256 + warp * 16;
    const uint32_t q0 = qn[0], q1 = qn[1], q2 = qn[2], q3 = qn[3], z0 = qn[6], z1 = qn[7];
    uint32_t q4 = qn[4], q5 = qn[5];
    if ((lane & 3) == 2) { q4 = 0x43BCu; q5 = 0x43BCu; }
    float o[12];
    uint64_t dk = mkdesc(sK, 128, 384, 0), dk2 = mkdesc(sK + 256, 0, 384, 0), dv = mkdesc(sV, 384, 128, 0);
    float sa[AB_N / 2], sb2[AB_N / 2];
    uint32_t pa[AB_N / 4], pb[AB_N / 4];
    if (pass == 0) mbar_wait(bars, 0);
    BT(1 + 2 * pass);
    wg_fence();
    attn_b_qk(sa, q0, q1, q2, q3, q4, q5, z0, z1, dk, dk2);
    wg_commit();
    attn_b_qk(sb2, q0, q1, q2, q3, q4, q5, z0, z1, dk + AB_N * 3, dk2 + AB_N * 3);
    wg_commit();
#pragma unroll 1
    for (int kt = 0; kt < NT; kt += 2) {
      const int nx = kt + 2 < NT ? kt + 2 : 0;
      if (pass == 0 && (nx & (PER - 1)) == 0) mbar_wait(bars + 8 * (nx / PER), 0);
      const uint64_t nk = dk + nx * (AB_N * 3), nk2 = dk2 + nx * (AB_N * 3);
      wg_wait<1>();
      reg_fence<AB_N / 2>(sa);
#pragma unroll
      for (int i = 0; i < AB_N / 4; i++) pa[i] = pack2(ex2(sa[2 * i]), poly_group(i >> 1) ? ex2_poly(sa[2 * i + 1]) : ex2(sa[2 * i + 1]));
      wg_fence();
#pragma unroll
      for (int kk = 0; kk < AB_N / 16; kk++) wg_rs24_01(o, pa[4 * kk], pa[4 * kk + 1], pa[4 * kk + 2], pa[4 * kk + 3], dv + kk * 48, kk | kt);
      attn_b_qk(sa, q0, q1, q2, q3, q4, q5, z0, z1, nk, nk2);
      wg_commit();
      wg_wait<1>();
      reg_fence<AB_N / 2>(sb2);
#pragma unroll
      for (int i = 0; i < AB_N / 4; i++) pb[i] = pack2(ex2(sb2[2 * i]), poly_group((i >> 1) + AB_N / 8) ? ex2_poly(sb2[2 * i + 1]) : ex2(sb2[2 * i + 1]));
      wg_fence();
#pragma unroll
      for (int kk = 0; kk < AB_N / 16; kk++) wg_rs24_01(o, pb[4 * kk], pb[4 * kk + 1], pb[4 * kk + 2], pb[4 * kk + 3], dv + AB_N * 3 + kk * 48, 1);
      attn_b_qk(sb2, q0, q1, q2, q3, q4, q5, z0, z1, nk + AB_N * 3, nk2 + AB_N * 3);
      wg_commit();
      dv += AB_N * 6;
    }
    wg_wait<0>();
    reg_fence<12>(o); reg_fence<AB_N / 2>(sa); reg_fence<AB_N / 2>(sb2);
    BT(2 + 2 * pass);
    if (pass + 1 < AB_PASS) load_q(pass + 1);
    mbar_wait(bars + 136, 0);
    const uint2 kb = lds64(bars + 64);
    const float kmax = __uint_as_float(max(kb.x, kb.y));
    if ((lane & 3) == 2) q4 = q5 = 0;
    float n0 = sq2(q0) + sq2(q2) + sq2(q4), n1 = sq2(q1) + sq2(q3) + sq2(q5);
    n0 += __shfl_xor_sync(~0u, n0, 1); n1 += __shfl_xor_sync(~0u, n1, 1);
    n0 += __shfl_xor_sync(~0u, n0, 2); n1 += __shfl_xor_sync(~0u, n1, 2);
    uint32_t redo;
    asm volatile("{.reg .pred p, q; setp.ne.u32 p, %1, 0; bar.red.or.pred q, %2, 128, p; selp.u32 %0, 1, 0, q;}"
                 : "=r"(redo) : "r"((uint32_t)!(n0 * kmax <= 9500.f && n1 * kmax <= 9500.f)), "r"(2 + (warp >> 2)) : "memory");
    if (redo) {
#pragma unroll
      for (int i = 0; i < 12; i++) o[i] = 0.f;
      float m0 = -INFINITY, m1 = -INFINITY;
#pragma unroll 1
      for (int kt = 0; kt < 64; kt++) {
        float s[16];
        wg_fence();
        wg_rs32_00(s, q0, q1, q2, q3, dk + kt * 96, 0);
        wg_rs32_00(s, q4, q5, z0, z1, dk2 + kt * 96, 1);
        wg_commit();
        wg_wait<0>();
        reg_fence<16>(s); reg_fence<12>(o);
        float n0 = m0, n1 = m1;
#pragma unroll
        for (int jj = 0; jj < 4; jj++) { n0 = fmaxf(n0, fmaxf(s[4 * jj], s[4 * jj + 1])); n1 = fmaxf(n1, fmaxf(s[4 * jj + 2], s[4 * jj + 3])); }
        n0 = fmaxf(n0, __shfl_xor_sync(~0u, n0, 1)); n0 = fmaxf(n0, __shfl_xor_sync(~0u, n0, 2));
        n1 = fmaxf(n1, __shfl_xor_sync(~0u, n1, 1)); n1 = fmaxf(n1, __shfl_xor_sync(~0u, n1, 2));
        const float r0 = ex2(m0 - n0), r1 = ex2(m1 - n1);
        m0 = n0; m1 = n1;
#pragma unroll
        for (int jj = 0; jj < 3; jj++) { o[4 * jj] *= r0; o[4 * jj + 1] *= r0; o[4 * jj + 2] *= r1; o[4 * jj + 3] *= r1; }
        uint32_t pp[8];
#pragma unroll
        for (int jj = 0; jj < 4; jj++) {
          pp[2 * jj] = pack2(ex2(s[4 * jj] - m0), ex2(s[4 * jj + 1] - m0));
          pp[2 * jj + 1] = pack2(ex2(s[4 * jj + 2] - m1), ex2(s[4 * jj + 3] - m1));
        }
        reg_fence<12>(o);
        wg_fence();
#pragma unroll
        for (int kk = 0; kk < 2; kk++) wg_rs24_01(o, pp[4 * kk], pp[4 * kk + 1], pp[4 * kk + 2], pp[4 * kk + 3], mkdesc(sV, 384, 128, 0) + kt * 96 + kk * 48, 1);
        wg_commit();
      }
      wg_wait<0>();
      reg_fence<12>(o);
    }
    attn_b_store(o, h, row0, lane);
    __syncwarp();
    if (pass == 0 && lane == 0) mbar_arrive(bars + 128);
  }
  BT(5);
  TRACE(2);
}

typedef CUresult (*EncodeFn)(CUtensorMap*, CUtensorMapDataType, cuuint32_t, void*, const cuuint64_t*, const cuuint64_t*,
                             const cuuint32_t*, const cuuint32_t*, CUtensorMapInterleave, CUtensorMapSwizzle,
                             CUtensorMapL2promotion, CUtensorMapFloatOOBfill);

void make_map(EncodeFn enc, CUtensorMap* m, const void* ptr, int cols, int rows, int box_rows, int box_cols = 64) {
  const cuuint64_t dims[2] = {(cuuint64_t)cols, (cuuint64_t)rows};
  const cuuint64_t strides[1] = {(cuuint64_t)cols * 2};
  const cuuint32_t box[2] = {(cuuint32_t)box_cols, (cuuint32_t)box_rows}, es[2] = {1, 1};
  enc(m, CU_TENSOR_MAP_DATA_TYPE_BFLOAT16, 2, const_cast<void*>(ptr), dims, strides, box, es, CU_TENSOR_MAP_INTERLEAVE_NONE,
      box_cols == 64 ? CU_TENSOR_MAP_SWIZZLE_128B : box_cols == 32 ? CU_TENSOR_MAP_SWIZZLE_64B : CU_TENSOR_MAP_SWIZZLE_NONE, CU_TENSOR_MAP_L2_PROMOTION_L2_256B, CU_TENSOR_MAP_FLOAT_OOB_FILL_NONE);
}
void make_map5(EncodeFn enc, CUtensorMap* m, const void* ptr, bool words, const cuuint64_t (&dims)[5], const cuuint64_t (&strides)[4], const cuuint32_t (&box)[5]) {
  const cuuint32_t es[5] = {1, 1, 1, 1, 1};
  enc(m, words ? CU_TENSOR_MAP_DATA_TYPE_UINT64 : CU_TENSOR_MAP_DATA_TYPE_BFLOAT16, 5, const_cast<void*>(ptr), dims, strides, box, es, CU_TENSOR_MAP_INTERLEAVE_NONE,
      words ? CU_TENSOR_MAP_SWIZZLE_NONE : CU_TENSOR_MAP_SWIZZLE_128B, dims[0] % 64 ? CU_TENSOR_MAP_L2_PROMOTION_L2_128B : CU_TENSOR_MAP_L2_PROMOTION_L2_256B,
      CU_TENSOR_MAP_FLOAT_OOB_FILL_NONE);
}
void make_tiles(EncodeFn enc, CUtensorMap* m, const void* ptr, cuuint64_t cols, cuuint64_t tile) {
  make_map5(enc, m, ptr, false, {tile, 1, 1, cols / tile, DM}, {tile * 2, tile * 2, tile * 2, cols * 2}, {64, 1, 1, 1, 64});
}
template <class... KA, class... A>
void launch(void (*kern)(KA...), int grid, int block, int smem, int cluster, bool pdl, A... args) {
  cudaFuncSetAttribute(kern, cudaFuncAttributeMaxDynamicSharedMemorySize, smem);
  cudaLaunchConfig_t cfg = {};
  cfg.gridDim = dim3(grid); cfg.blockDim = dim3(block); cfg.dynamicSmemBytes = smem; cfg.stream = cudaStreamPerThread;
  cudaLaunchAttribute at[2];
  int n = 0;
  if (cluster > 1) { at[n].id = cudaLaunchAttributeClusterDimension; at[n].val.clusterDim.x = cluster; at[n].val.clusterDim.y = 1; at[n].val.clusterDim.z = 1; n++; }
  if (pdl) { at[n].id = cudaLaunchAttributeProgrammaticStreamSerialization; at[n].val.programmaticStreamSerializationAllowed = 1; n++; }
  cfg.attrs = at; cfg.numAttrs = n;
  cudaLaunchKernelEx(&cfg, kern, args...);
}
template <class T> void* sym(T& s) { void* p = nullptr; cudaGetSymbolAddress(&p, s); return p; }

}

#define MODE(b) 0
extern "C" void kernel_launch(void* const* d_in, const int* in_sizes, int n_in, void* d_out, int out_size) {
  const __nv_bfloat16* x = (const __nv_bfloat16*)d_in[0];
  void* fn = nullptr; cudaDriverEntryPointQueryResult qr;
  cudaGetDriverEntryPoint("cuTensorMapEncodeTiled", &fn, cudaEnableDefault, &qr);
  EncodeFn enc = (EncodeFn)fn;

  WorkParams wk = {};
  ChainParams& ch = wk.ch;
  AttnParams at = {};
  make_map(enc, &ch.wq, d_in[2], HD, DM, 160); make_map(enc, &ch.wk, d_in[3], HD, DM, 160); make_map(enc, &ch.wv, d_in[4], HD, DM, 160);
  make_map(enc, &ch.wo, d_in[5], DM, HD, 192, 32);
  ch.mem0 = (const __nv_bfloat16*)d_in[1];
  ch.wb = (const uint8_t*)d_in[8];
  ch.d1 = 250; ch.d2 = 200; ch.dn = 150; ch.dx = 950;
  make_tiles(enc, &wk.wq, d_in[2], HD, 192);
  for (int i = 0; i < 3; i++) make_tiles(enc, &wk.wb[i], d_in[8], 1920, 80 << i);
  for (int i = 0; i < 2; i++) make_tiles(enc, &wk.wc[i], d_in[9], DM, 80 << 2 * i);
  make_map(enc, &wk.out, d_out, DM, SEQ, 16, 80);
  make_map5(enc, &wk.wo, d_in[5], false, {DM, 2, 4, 4, HD / 32}, {DM * 2, DM * 16, DM * 4, DM * 64}, {64, 2, 4, 4, 2});
  make_map5(enc, &wk.xn, sym(g_xn), true, {1280, 2, 2, 64, 1}, {10240, 20480, 40960, 40960}, {128, 2, 2, 4, 1});
  make_map5(enc, &wk.xp, sym(g_xn), true, {1280, 2, 1, 64, 2}, {10240, 10240, 40960, 20480}, {128, 2, 1, 4, 2});
  make_map5(enc, &ch.xc, sym(g_xn), true, {160, 1, 1, 256, 8}, {1280, 1280, 10240, 1280}, {160, 1, 1, 4, 2});
  wk.x = x;
  for (int i = 0; i < 4; i++) at.pf[i] = (const uint8_t*)d_in[i < 2 ? 3 + i : i == 2 ? 2 : 5];
  int qa_end[2] = {12, 12};
  for (int layer = 0; layer < 2; layer++) {
    ch.sync = wk.sync = at.sync = (uint32_t*)sym(g_sync) + layer * SY_N;
    ch.other = (uint32_t*)sym(g_sync) + (1 - layer) * SY_N;
    ch.layer = layer;
    at.next = layer ? nullptr : ch.other;
    wk.qa_end = qa_end[layer];
    wk.kind = layer ? WK_LEAD : WK_FIRST;
    launch(work_kernel, 132, 384, CH_SMEM, 1, layer != 0, wk);
    wk.kind = WK_CHAIN;
    launch(work_kernel, 96, 384, CH_SMEM, 3, true, wk);
    launch(attn_b_kernel, 128, AB_T + 128, AB_SMEM, 1, true, at);
  }
  wk.kind = WK_LAST;
  launch(work_kernel, 128, 384, CH_SMEM, 1, true, wk);
}
```

```cpp
#include <cuda_runtime.h>
#include <cuda_bf16.h>
#include <cuda.h>
#include <stdint.h>
#include <stdlib.h>

namespace {

constexpr int SEQ = 2048, DM = 640, HD = 6144, NSEG = 64;
constexpr int SPIN_LIMIT = 1 << 20;

__device__ __align__(128) uint2 g_x[256 * 17 * 1280];
__device__ __align__(128) uint32_t g_xn[SEQ * DM / 2];
__device__ __align__(128) uint32_t g_of[SEQ * DM / 2];
__device__ __align__(128) uint4 g_o[SEQ * HD / 8];
__device__ __align__(128) uint4 g_q[SEQ * HD / 8];
constexpr int KV_M = 4096, KV_SEG = 5120, KV_PART = 20480, KV_V = 3 * KV_PART;
__device__ __align__(128) uint8_t g_kv[16 * 32 * 6 * KV_PART];
#define OP_B8 11
#define OP_B16 14
#define OP_N4 16
#define BQ_12 12
#define BQ_24 14
#define FIN_16 12
__host__ __device__ constexpr int op_split(int b) { return b < OP_B8 ? 4 : b < OP_B16 ? 8 : 16; }
__host__ __device__ constexpr int op_steps(int b) { return b < OP_B8 ? 24 : b < OP_B16 ? 12 : 6; }
__host__ __device__ constexpr int op_tiles(int b) { return b < OP_N4 ? 2 : 4; }
__host__ __device__ constexpr int fin_items(int b) { return b < OP_B8 ? 4 : b < FIN_16 ? 8 : 16; }
__host__ __device__ constexpr int bq_items(int b) { return b < BQ_12 ? 6 : b < BQ_24 ? 12 : 24; }
__host__ __device__ constexpr int ln_items(int layer, int b) { return layer == 0 && b < 2 ? 16 : 4; }
constexpr int SY_P = 128, SY_T = 192, SY_UP = 224, SY_OB = 225, SY_PRE = 256, SY_PART = 288, SY_TIME = 384, SY_N = 448;
__device__ __align__(128) uint32_t g_sync[2 * SY_N];
constexpr int NSLOT = 92;
__device__ uint32_t g_pool[(NSLOT + 2) * 2048];
__device__ uint32_t g_smpart[256], g_orient[NSLOT];
__device__ __align__(128) uint32_t g_bqkv[3 * 32 * 256 * 96];

#define BT(i)
#define MISS(k, n)
#define PRO(i)
#define TRACE(w)
#define ITEM(code, w)
#define STAT(k)
#define TMV(i, v)
#define TM(i)
#define TMD(i, dep)

__device__ __forceinline__ uint32_t gtime() { uint32_t c; asm volatile("mov.u32 %0, %%globaltimer_lo;" : "=r"(c) :: "memory"); return c; }
__device__ __forceinline__ uint32_t clk32() { uint32_t c; asm volatile("mov.u32 %0, %%clock;" : "=r"(c) :: "memory"); return c; }
__device__ __forceinline__ uint32_t fresh_tid() { uint32_t t; asm volatile("mov.u32 %0, %%tid.x;" : "=r"(t)); return t; }
__device__ __forceinline__ uint32_t s2u(const void* p) { return (uint32_t)__cvta_generic_to_shared(p); }
__device__ __forceinline__ uint32_t pack2(float a, float b) {
  uint32_t r; asm("cvt.rn.bf16x2.f32 %0, %1, %2;" : "=r"(r) : "f"(b), "f"(a)); return r; }
__device__ __forceinline__ float bf_lo(uint32_t w) { return __uint_as_float(w << 16); }
__device__ __forceinline__ float bf_hi(uint32_t w) { return __uint_as_float(w & 0xffff0000u); }
__device__ __forceinline__ float ex2(float x) { float y; asm("ex2.approx.ftz.f32 %0, %1;" : "=f"(y) : "f"(x)); return y; }

__device__ __forceinline__ void mbar_init(uint32_t bar, uint32_t n) {
  asm volatile("mbarrier.init.shared::cta.b64 [%0], %1;" :: "r"(bar), "r"(n) : "memory"); }
__device__ __forceinline__ void mbar_expect(uint32_t bar, uint32_t bytes) {
  asm volatile("mbarrier.arrive.expect_tx.shared::cta.b64 _, [%0], %1;" :: "r"(bar), "r"(bytes) : "memory"); }
__device__ __forceinline__ void mbar_arrive(uint32_t bar) {
  asm volatile("mbarrier.arrive.shared::cta.b64 _, [%0];" :: "r"(bar) : "memory"); }
__device__ __forceinline__ void mbar_arrive_remote(uint32_t bar) {
  asm volatile("mbarrier.arrive.shared::cluster.b64 _, [%0];" :: "r"(bar) : "memory"); }
__device__ __forceinline__ void mbar_wait(uint32_t bar, uint32_t ph) {
  asm volatile("{.reg .pred p; .reg .u32 n; mov.u32 n, 0;\n"
               "W: mbarrier.try_wait.parity.shared::cta.b64 p, [%0], %1; @p bra.uni D;\n"
               "add.u32 n, n, 1; setp.gt.u32 p, n, %2; @p trap; bra.uni W;\n"
               "D: }" :: "r"(bar), "r"(ph), "n"(SPIN_LIMIT) : "memory");
}
__device__ __forceinline__ bool elect() {
  uint32_t p; asm volatile("{.reg .pred q; elect.sync _|q, 0xffffffff; selp.u32 %0, 1, 0, q;}" : "=r"(p)); return p; }
__device__ __forceinline__ void spin_guard(int& n) {
  asm volatile("{.reg .pred p; add.s32 %0, %0, 1; setp.gt.s32 p, %0, %1; @p trap;}" : "+r"(n) : "n"(SPIN_LIMIT));
}
__device__ __forceinline__ void pdl_wait() { asm volatile("griddepcontrol.wait;" ::: "memory"); TRACE(1); }
__device__ __forceinline__ void pdl_launch() { asm volatile("griddepcontrol.launch_dependents;" ::: "memory"); }
__device__ __forceinline__ uint32_t ld_acquire(const uint32_t* p) { uint32_t v; asm volatile("ld.acquire.gpu.global.u32 %0, [%1];" : "=r"(v) : "l"(p) : "memory"); return v; }
__device__ __forceinline__ void red_release(uint32_t* p, uint32_t v) { asm volatile("red.release.gpu.global.add.u32 [%0], %1;" :: "l"(p), "r"(v) : "memory"); }
__device__ __forceinline__ void fence_async_global() { asm volatile("fence.proxy.async.global;" ::: "memory"); }
__device__ __forceinline__ void fence_async() { asm volatile("fence.proxy.async.shared::cta;" ::: "memory"); }
__device__ __forceinline__ void bar_sync(int id, int n) { asm volatile("bar.sync %0, %1;" :: "r"(id), "r"(n) : "memory"); }
__device__ __forceinline__ void bar_arrive(int id, int n) { asm volatile("bar.arrive %0, %1;" :: "r"(id), "r"(n) : "memory"); }
__device__ __forceinline__ void tma_load(uint32_t dst, const CUtensorMap* m, int c0, int c1, uint32_t bar) {
  asm volatile("cp.async.bulk.tensor.2d.shared::cluster.global.mbarrier::complete_tx::bytes [%0], [%1, {%3, %4}], [%2];"
               :: "r"(dst), "l"(m), "r"(bar), "r"(c0), "r"(c1) : "memory"); }
__device__ __forceinline__ void tma_load5(uint32_t dst, const CUtensorMap* m, int c0, int c3, int c4, uint32_t bar) {
  asm volatile("cp.async.bulk.tensor.5d.shared::cluster.global.mbarrier::complete_tx::bytes [%0], [%1, {%3, %6, %6, %4, %5}], [%2];"
               :: "r"(dst), "l"(m), "r"(bar), "r"(c0), "r"(c3), "r"(c4), "r"(0) : "memory"); }
__device__ __forceinline__ void tma_store(const CUtensorMap* m, uint32_t src, int c0, int c1) {
  asm volatile("cp.async.bulk.tensor.2d.global.shared::cta.bulk_group [%0, {%2, %3}], [%1];"
               :: "l"(m), "r"(src), "r"(c0), "r"(c1) : "memory"); }
__device__ __forceinline__ uint64_t evict_first() { uint64_t p; asm("createpolicy.fractional.L2::evict_first.b64 %0, 1.0;" : "=l"(p)); return p; }
__device__ __forceinline__ void bulk_load_last(uint32_t dst, const void* src, uint32_t bytes, uint32_t bar) {
  asm volatile("cp.async.bulk.shared::cluster.global.mbarrier::complete_tx::bytes.L2::cache_hint [%0], [%1], %2, [%3], %4;"
               :: "r"(dst), "l"(src), "r"(bytes), "r"(bar), "l"(evict_first()) : "memory"); }
__device__ __forceinline__ void bulk_store_stream(void* dst, uint32_t src, uint32_t bytes) {
  asm volatile("cp.async.bulk.global.shared::cta.bulk_group.L2::cache_hint [%0], [%1], %2, %3;" :: "l"(dst), "r"(src), "r"(bytes), "l"(evict_first()) : "memory"); }
__device__ __forceinline__ void bulk_load(uint32_t dst, const void* src, uint32_t bytes, uint32_t bar) {
  asm volatile("cp.async.bulk.shared::cluster.global.mbarrier::complete_tx::bytes [%0], [%1], %2, [%3];"
               :: "r"(dst), "l"(src), "r"(bytes), "r"(bar) : "memory"); }
__device__ __forceinline__ void bulk_push(uint32_t dst, uint32_t src, uint32_t bytes, uint32_t bar) {
  asm volatile("cp.async.bulk.shared::cluster.shared::cta.mbarrier::complete_tx::bytes [%0], [%1], %2, [%3];"
               :: "r"(dst), "r"(src), "r"(bytes), "r"(bar) : "memory"); }
__device__ __forceinline__ void bulk_store(void* dst, uint32_t src, uint32_t bytes) {
  asm volatile("cp.async.bulk.global.shared::cta.bulk_group [%0], [%1], %2;" :: "l"(dst), "r"(src), "r"(bytes) : "memory"); }
__device__ __forceinline__ void bulk_commit() { asm volatile("cp.async.bulk.commit_group;" ::: "memory"); }
template <int N> __device__ __forceinline__ void bulk_wait_read() { asm volatile("cp.async.bulk.wait_group.read %0;" :: "n"(N) : "memory"); }
template <int N> __device__ __forceinline__ void bulk_wait() { asm volatile("cp.async.bulk.wait_group %0;" :: "n"(N) : "memory"); }

__device__ __forceinline__ uint64_t mkdesc(uint32_t addr, uint32_t lbo, uint32_t sbo, uint32_t sw) {
  return (uint64_t)((addr & 0x3FFFF) >> 4) | ((uint64_t)(lbo >> 4) << 16) | ((uint64_t)(sbo >> 4) << 32) | ((uint64_t)sw << 62); }
__device__ __forceinline__ void wg_fence() { asm volatile("wgmma.fence.sync.aligned;" ::: "memory"); }
__device__ __forceinline__ void wg_commit() { asm volatile("wgmma.commit_group.sync.aligned;" ::: "memory"); }
template <int N> __device__ __forceinline__ void wg_wait() { asm volatile("wgmma.wait_group.sync.aligned %0;" :: "n"(N) : "memory"); }
template <int N> __device__ __forceinline__ void reg_fence(float* d) {
#pragma unroll
  for (int i = 0; i < N; i++) asm volatile("" : "+f"(d[i]) :: "memory");
}

__device__ __forceinline__ void mma16(float* d, uint32_t a0, uint32_t a1, uint32_t a2, uint32_t a3, uint32_t b0, uint32_t b1) {
  asm volatile("mma.sync.aligned.m16n8k16.row.col.f32.bf16.bf16.f32 {%0,%1,%2,%3},{%4,%5,%6,%7},{%8,%9},{%0,%1,%2,%3};"
               : "+f"(d[0]), "+f"(d[1]), "+f"(d[2]), "+f"(d[3]) : "r"(a0), "r"(a1), "r"(a2), "r"(a3), "r"(b0), "r"(b1)); }
__device__ __forceinline__ void mma8(float* d, uint32_t a0, uint32_t a1, uint32_t b0) {
  asm volatile("mma.sync.aligned.m16n8k8.row.col.f32.bf16.bf16.f32 {%0,%1,%2,%3},{%4,%5},{%6},{%0,%1,%2,%3};"
               : "+f"(d[0]), "+f"(d[1]), "+f"(d[2]), "+f"(d[3]) : "r"(a0), "r"(a1), "r"(b0)); }
__device__ __forceinline__ void ldsm4(uint32_t* r, uint32_t a) {
  asm volatile("ldmatrix.sync.aligned.m8n8.x4.shared.b16 {%0,%1,%2,%3},[%4];" : "=r"(r[0]), "=r"(r[1]), "=r"(r[2]), "=r"(r[3]) : "r"(a) : "memory"); }
__device__ __forceinline__ uint4 ldsm4v(uint32_t a) { uint32_t r[4]; ldsm4(r, a); return make_uint4(r[0], r[1], r[2], r[3]); }
__device__ __forceinline__ void ldsm4t(uint32_t* r, uint32_t a) {
  asm volatile("ldmatrix.sync.aligned.m8n8.x4.trans.shared.b16 {%0,%1,%2,%3},[%4];" : "=r"(r[0]), "=r"(r[1]), "=r"(r[2]), "=r"(r[3]) : "r"(a) : "memory"); }
__device__ __forceinline__ void ldsm2(uint32_t* r, uint32_t a) {
  asm volatile("ldmatrix.sync.aligned.m8n8.x2.shared.b16 {%0,%1},[%2];" : "=r"(r[0]), "=r"(r[1]) : "r"(a) : "memory"); }
__device__ __forceinline__ void ldsm2t(uint32_t* r, uint32_t a) {
  asm volatile("ldmatrix.sync.aligned.m8n8.x2.trans.shared.b16 {%0,%1},[%2];" : "=r"(r[0]), "=r"(r[1]) : "r"(a) : "memory"); }
__device__ __forceinline__ void stsm4(uint32_t a, uint32_t r0, uint32_t r1, uint32_t r2, uint32_t r3) {
  asm volatile("stmatrix.sync.aligned.m8n8.x4.shared.b16 [%0], {%1,%2,%3,%4};" :: "r"(a), "r"(r0), "r"(r1), "r"(r2), "r"(r3) : "memory"); }
__device__ __forceinline__ void stsm4t(uint32_t a, uint32_t r0, uint32_t r1, uint32_t r2, uint32_t r3) {
  asm volatile("stmatrix.sync.aligned.m8n8.x4.trans.shared.b16 [%0], {%1,%2,%3,%4};" :: "r"(a), "r"(r0), "r"(r1), "r"(r2), "r"(r3) : "memory"); }
__device__ __forceinline__ void stsm2(uint32_t a, uint32_t r0, uint32_t r1) {
  asm volatile("stmatrix.sync.aligned.m8n8.x2.shared.b16 [%0], {%1,%2};" :: "r"(a), "r"(r0), "r"(r1) : "memory"); }
__device__ __forceinline__ void stsm2t(uint32_t a, uint32_t r0, uint32_t r1) {
  asm volatile("stmatrix.sync.aligned.m8n8.x2.trans.shared.b16 [%0], {%1,%2};" :: "r"(a), "r"(r0), "r"(r1) : "memory"); }
__device__ __forceinline__ void sts32(uint32_t a, uint32_t v) { asm volatile("st.shared.b32 [%0], %1;" :: "r"(a), "r"(v) : "memory"); }
__device__ __forceinline__ void sts64f(uint32_t a, float x, float y) { asm volatile("st.shared.v2.f32 [%0], {%1,%2};" :: "r"(a), "f"(x), "f"(y) : "memory"); }
__device__ __forceinline__ void sts128(uint32_t a, uint4 v) {
  asm volatile("st.shared.v4.b32 [%0], {%1,%2,%3,%4};" :: "r"(a), "r"(v.x), "r"(v.y), "r"(v.z), "r"(v.w) : "memory"); }
__device__ __forceinline__ void sts128f(uint32_t a, float x, float y, float z, float w) {
  asm volatile("st.shared.v4.f32 [%0], {%1,%2,%3,%4};" :: "r"(a), "f"(x), "f"(y), "f"(z), "f"(w) : "memory"); }
__device__ __forceinline__ float lds32f(uint32_t a) { float v; asm volatile("ld.shared.f32 %0, [%1];" : "=f"(v) : "r"(a) : "memory"); return v; }
__device__ __forceinline__ float2 lds64f(uint32_t a) { float2 v; asm volatile("ld.shared.v2.f32 {%0,%1}, [%2];" : "=f"(v.x), "=f"(v.y) : "r"(a) : "memory"); return v; }
__device__ __forceinline__ float4 lds128f(uint32_t a) {
  float4 v; asm volatile("ld.shared.v4.f32 {%0,%1,%2,%3}, [%4];" : "=f"(v.x), "=f"(v.y), "=f"(v.z), "=f"(v.w) : "r"(a) : "memory"); return v; }
__device__ __forceinline__ uint4 lds128(uint32_t a) {
  uint4 v; asm volatile("ld.shared.v4.b32 {%0,%1,%2,%3}, [%4];" : "=r"(v.x), "=r"(v.y), "=r"(v.z), "=r"(v.w) : "r"(a) : "memory"); return v; }
__device__ __forceinline__ uint4 ldg_strong128(const void* p) {
  uint4 v; asm volatile("ld.relaxed.gpu.global.v4.u32 {%0,%1,%2,%3}, [%4];" : "=r"(v.x), "=r"(v.y), "=r"(v.z), "=r"(v.w) : "l"(p) : "memory"); return v; }
__device__ __forceinline__ uint2 ldg_strong64(const void* p) {
  uint2 v; asm volatile("ld.relaxed.gpu.global.v2.u32 {%0,%1}, [%2];" : "=r"(v.x), "=r"(v.y) : "l"(p) : "memory"); return v; }
__device__ __forceinline__ void stg_strong32(void* p, uint32_t v) { asm volatile("st.relaxed.gpu.global.u32 [%0], %1;" :: "l"(p), "r"(v) : "memory"); }
__device__ __forceinline__ void stg_strong128(void* p, uint4 v) {
  asm volatile("st.relaxed.gpu.global.v4.u32 [%0], {%1,%2,%3,%4};" :: "l"(p), "r"(v.x), "r"(v.y), "r"(v.z), "r"(v.w) : "memory"); }
__device__ __forceinline__ uint32_t mapa(uint32_t a, uint32_t r) {
  uint32_t o; asm("mapa.shared::cluster.u32 %0, %1, %2;" : "=r"(o) : "r"(a), "r"(r)); return o; }
__device__ __forceinline__ void st_async2f(uint32_t a, float x, float y, uint32_t bar) {
  asm volatile("st.async.shared::cluster.mbarrier::complete_tx::bytes.v2.f32 [%0], {%1,%2}, [%3];" :: "r"(a), "f"(x), "f"(y), "r"(bar) : "memory"); }
__device__ __forceinline__ void st_async32(uint32_t a, uint32_t x, uint32_t bar) {
  asm volatile("st.async.shared::cluster.mbarrier::complete_tx::bytes.b32 [%0], %1, [%2];" :: "r"(a), "r"(x), "r"(bar) : "memory"); }
__device__ __forceinline__ uint32_t lds32(uint32_t a) { uint32_t v; asm volatile("ld.shared.b32 %0, [%1];" : "=r"(v) : "r"(a) : "memory"); return v; }
__device__ __forceinline__ void st_async64(uint32_t a, uint32_t x, uint32_t y, uint32_t bar) {
  asm volatile("st.async.shared::cluster.mbarrier::complete_tx::bytes.v2.b32 [%0], {%1,%2}, [%3];" :: "r"(a), "r"(x), "r"(y), "r"(bar) : "memory"); }
__device__ __forceinline__ void st_async128(uint32_t a, uint4 v, uint32_t bar) {
  asm volatile("st.async.shared::cluster.mbarrier::complete_tx::bytes.v4.b32 [%0], {%1,%2,%3,%4}, [%5];" :: "r"(a), "r"(v.x), "r"(v.y), "r"(v.z), "r"(v.w), "r"(bar) : "memory"); }
__device__ __forceinline__ uint2 lds64(uint32_t a) { uint2 v; asm volatile("ld.shared.v2.b32 {%0,%1}, [%2];" : "=r"(v.x), "=r"(v.y) : "r"(a) : "memory"); return v; }
__device__ __forceinline__ void sts64(uint32_t a, uint32_t x, uint32_t y) { asm volatile("st.shared.v2.b32 [%0], {%1,%2};" :: "r"(a), "r"(x), "r"(y) : "memory"); }
__device__ __forceinline__ uint32_t ldg_strong32(const void* p) { uint32_t v; asm volatile("ld.relaxed.gpu.global.u32 %0, [%1];" : "=r"(v) : "l"(p) : "memory"); return v; }
__device__ __forceinline__ uint32_t transpose8(uint32_t x) { uint32_t r; asm volatile("movmatrix.sync.aligned.m8n8.trans.b16 %0, %1;" : "=r"(r) : "r"(x)); return r; }
__device__ __forceinline__ uint32_t hadd2(uint32_t a, uint32_t b) { uint32_t r; asm("add.rn.bf16x2 %0, %1, %2;" : "=r"(r) : "r"(a), "r"(b)); return r; }
__device__ __forceinline__ uint32_t min4(uint4 v) { return min(__vimin3_u32(v.x, v.y, v.z), v.w); }

__device__ __forceinline__ void wg_ss192_01(float* d, uint64_t da, uint64_t db, int sd) {
  asm volatile("{.reg .pred p; setp.ne.b32 p, %98, 0;\n"
    "wgmma.mma_async.sync.aligned.m64n192k16.f32.bf16.bf16 {%0,%1,%2,%3,%4,%5,%6,%7,%8,%9,%10,%11,%12,%13,%14,%15,%16,%17,%18,%19,%20,%21,%22,%23,%24,%25,%26,%27,%28,%29,%30,%31,%32,%33,%34,%35,%36,%37,%38,%39,%40,%41,%42,%43,%44,%45,%46,%47,%48,%49,%50,%51,%52,%53,%54,%55,%56,%57,%58,%59,%60,%61,%62,%63,%64,%65,%66,%67,%68,%69,%70,%71,%72,%73,%74,%75,%76,%77,%78,%79,%80,%81,%82,%83,%84,%85,%86,%87,%88,%89,%90,%91,%92,%93,%94,%95}, %96, %97, p, 1, 1, 0, 1;}"
    : "+f"(d[0]),"+f"(d[1]),"+f"(d[2]),"+f"(d[3]),"+f"(d[4]),"+f"(d[5]),"+f"(d[6]),"+f"(d[7]),"+f"(d[8]),"+f"(d[9]),"+f"(d[10]),"+f"(d[11]),"+f"(d[12]),"+f"(d[13]),"+f"(d[14]),"+f"(d[15]),"+f"(d[16]),"+f"(d[17]),"+f"(d[18]),"+f"(d[19]),"+f"(d[20]),"+f"(d[21]),"+f"(d[22]),"+f"(d[23]),"+f"(d[24]),"+f"(d[25]),"+f"(d[26]),"+f"(d[27]),"+f"(d[28]),"+f"(d[29]),"+f"(d[30]),"+f"(d[31]),"+f"(d[32]),"+f"(d[33]),"+f"(d[34]),"+f"(d[35]),"+f"(d[36]),"+f"(d[37]),"+f"(d[38]),"+f"(d[39]),"+f"(d[40]),"+f"(d[41]),"+f"(d[42]),"+f"(d[43]),"+f"(d[44]),"+f"(d[45]),"+f"(d[46]),"+f"(d[47]),"+f"(d[48]),"+f"(d[49]),"+f"(d[50]),"+f"(d[51]),"+f"(d[52]),"+f"(d[53]),"+f"(d[54]),"+f"(d[55]),"+f"(d[56]),"+f"(d[57]),"+f"(d[58]),"+f"(d[59]),"+f"(d[60]),"+f"(d[61]),"+f"(d[62]),"+f"(d[63]),"+f"(d[64]),"+f"(d[65]),"+f"(d[66]),"+f"(d[67]),"+f"(d[68]),"+f"(d[69]),"+f"(d[70]),"+f"(d[71]),"+f"(d[72]),"+f"(d[73]),"+f"(d[74]),"+f"(d[75]),"+f"(d[76]),"+f"(d[77]),"+f"(d[78]),"+f"(d[79]),"+f"(d[80]),"+f"(d[81]),"+f"(d[82]),"+f"(d[83]),"+f"(d[84]),"+f"(d[85]),"+f"(d[86]),"+f"(d[87]),"+f"(d[88]),"+f"(d[89]),"+f"(d[90]),"+f"(d[91]),"+f"(d[92]),"+f"(d[93]),"+f"(d[94]),"+f"(d[95])
    : "l"(da), "l"(db), "r"(sd));
}
__device__ __forceinline__ void wg_ss128_01(float* d, uint64_t da, uint64_t db, int sd) {
  asm volatile("{.reg .pred p; setp.ne.b32 p, %66, 0;\n"
    "wgmma.mma_async.sync.aligned.m64n128k16.f32.bf16.bf16 {%0,%1,%2,%3,%4,%5,%6,%7,%8,%9,%10,%11,%12,%13,%14,%15,%16,%17,%18,%19,%20,%21,%22,%23,%24,%25,%26,%27,%28,%29,%30,%31,%32,%33,%34,%35,%36,%37,%38,%39,%40,%41,%42,%43,%44,%45,%46,%47,%48,%49,%50,%51,%52,%53,%54,%55,%56,%57,%58,%59,%60,%61,%62,%63}, %64, %65, p, 1, 1, 0, 1;}"
    : "+f"(d[0]),"+f"(d[1]),"+f"(d[2]),"+f"(d[3]),"+f"(d[4]),"+f"(d[5]),"+f"(d[6]),"+f"(d[7]),"+f"(d[8]),"+f"(d[9]),"+f"(d[10]),"+f"(d[11]),"+f"(d[12]),"+f"(d[13]),"+f"(d[14]),"+f"(d[15]),"+f"(d[16]),"+f"(d[17]),"+f"(d[18]),"+f"(d[19]),"+f"(d[20]),"+f"(d[21]),"+f"(d[22]),"+f"(d[23]),"+f"(d[24]),"+f"(d[25]),"+f"(d[26]),"+f"(d[27]),"+f"(d[28]),"+f"(d[29]),"+f"(d[30]),"+f"(d[31]),"+f"(d[32]),"+f"(d[33]),"+f"(d[34]),"+f"(d[35]),"+f"(d[36]),"+f"(d[37]),"+f"(d[38]),"+f"(d[39]),"+f"(d[40]),"+f"(d[41]),"+f"(d[42]),"+f"(d[43]),"+f"(d[44]),"+f"(d[45]),"+f"(d[46]),"+f"(d[47]),"+f"(d[48]),"+f"(d[49]),"+f"(d[50]),"+f"(d[51]),"+f"(d[52]),"+f"(d[53]),"+f"(d[54]),"+f"(d[55]),"+f"(d[56]),"+f"(d[57]),"+f"(d[58]),"+f"(d[59]),"+f"(d[60]),"+f"(d[61]),"+f"(d[62]),"+f"(d[63])
    : "l"(da), "l"(db), "r"(sd));
}
__device__ __forceinline__ void wg_ss160_01(float* d, uint64_t da, uint64_t db, int sd) {
  asm volatile("{.reg .pred p; setp.ne.b32 p, %82, 0;\n"
    "wgmma.mma_async.sync.aligned.m64n160k16.f32.bf16.bf16 {%0,%1,%2,%3,%4,%5,%6,%7,%8,%9,%10,%11,%12,%13,%14,%15,%16,%17,%18,%19,%20,%21,%22,%23,%24,%25,%26,%27,%28,%29,%30,%31,%32,%33,%34,%35,%36,%37,%38,%39,%40,%41,%42,%43,%44,%45,%46,%47,%48,%49,%50,%51,%52,%53,%54,%55,%56,%57,%58,%59,%60,%61,%62,%63,%64,%65,%66,%67,%68,%69,%70,%71,%72,%73,%74,%75,%76,%77,%78,%79}, %80, %81, p, 1, 1, 0, 1;}"
    : "+f"(d[0]),"+f"(d[1]),"+f"(d[2]),"+f"(d[3]),"+f"(d[4]),"+f"(d[5]),"+f"(d[6]),"+f"(d[7]),"+f"(d[8]),"+f"(d[9]),"+f"(d[10]),"+f"(d[11]),"+f"(d[12]),"+f"(d[13]),"+f"(d[14]),"+f"(d[15]),"+f"(d[16]),"+f"(d[17]),"+f"(d[18]),"+f"(d[19]),"+f"(d[20]),"+f"(d[21]),"+f"(d[22]),"+f"(d[23]),"+f"(d[24]),"+f"(d[25]),"+f"(d[26]),"+f"(d[27]),"+f"(d[28]),"+f"(d[29]),"+f"(d[30]),"+f"(d[31]),"+f"(d[32]),"+f"(d[33]),"+f"(d[34]),"+f"(d[35]),"+f"(d[36]),"+f"(d[37]),"+f"(d[38]),"+f"(d[39]),"+f"(d[40]),"+f"(d[41]),"+f"(d[42]),"+f"(d[43]),"+f"(d[44]),"+f"(d[45]),"+f"(d[46]),"+f"(d[47]),"+f"(d[48]),"+f"(d[49]),"+f"(d[50]),"+f"(d[51]),"+f"(d[52]),"+f"(d[53]),"+f"(d[54]),"+f"(d[55]),"+f"(d[56]),"+f"(d[57]),"+f"(d[58]),"+f"(d[59]),"+f"(d[60]),"+f"(d[61]),"+f"(d[62]),"+f"(d[63]),"+f"(d[64]),"+f"(d[65]),"+f"(d[66]),"+f"(d[67]),"+f"(d[68]),"+f"(d[69]),"+f"(d[70]),"+f"(d[71]),"+f"(d[72]),"+f"(d[73]),"+f"(d[74]),"+f"(d[75]),"+f"(d[76]),"+f"(d[77]),"+f"(d[78]),"+f"(d[79])
    : "l"(da), "l"(db), "r"(sd));
}
__device__ __forceinline__ void wg_ss80_01(float* d, uint64_t da, uint64_t db, int sd) {
  asm volatile("{.reg .pred p; setp.ne.b32 p, %42, 0;\n"
    "wgmma.mma_async.sync.aligned.m64n80k16.f32.bf16.bf16 {%0,%1,%2,%3,%4,%5,%6,%7,%8,%9,%10,%11,%12,%13,%14,%15,%16,%17,%18,%19,%20,%21,%22,%23,%24,%25,%26,%27,%28,%29,%30,%31,%32,%33,%34,%35,%36,%37,%38,%39}, %40, %41, p, 1, 1, 0, 1;}"
    : "+f"(d[0]),"+f"(d[1]),"+f"(d[2]),"+f"(d[3]),"+f"(d[4]),"+f"(d[5]),"+f"(d[6]),"+f"(d[7]),"+f"(d[8]),"+f"(d[9]),"+f"(d[10]),"+f"(d[11]),"+f"(d[12]),"+f"(d[13]),"+f"(d[14]),"+f"(d[15]),"+f"(d[16]),"+f"(d[17]),"+f"(d[18]),"+f"(d[19]),"+f"(d[20]),"+f"(d[21]),"+f"(d[22]),"+f"(d[23]),"+f"(d[24]),"+f"(d[25]),"+f"(d[26]),"+f"(d[27]),"+f"(d[28]),"+f"(d[29]),"+f"(d[30]),"+f"(d[31]),"+f"(d[32]),"+f"(d[33]),"+f"(d[34]),"+f"(d[35]),"+f"(d[36]),"+f"(d[37]),"+f"(d[38]),"+f"(d[39])
    : "l"(da), "l"(db), "r"(sd));
}
__device__ __forceinline__ void wg_rs32_00(float* d, uint32_t a0, uint32_t a1, uint32_t a2, uint32_t a3, uint64_t db, int sd) {
  asm volatile("{.reg .pred p; setp.ne.b32 p, %21, 0;\n"
    "wgmma.mma_async.sync.aligned.m64n32k16.f32.bf16.bf16 {%0,%1,%2,%3,%4,%5,%6,%7,%8,%9,%10,%11,%12,%13,%14,%15}, {%16,%17,%18,%19}, %20, p, 1, 1, 0;}"
    : "+f"(d[0]),"+f"(d[1]),"+f"(d[2]),"+f"(d[3]),"+f"(d[4]),"+f"(d[5]),"+f"(d[6]),"+f"(d[7]),"+f"(d[8]),"+f"(d[9]),"+f"(d[10]),"+f"(d[11]),"+f"(d[12]),"+f"(d[13]),"+f"(d[14]),"+f"(d[15])
    : "r"(a0), "r"(a1), "r"(a2), "r"(a3), "l"(db), "r"(sd));
}
__device__ __forceinline__ void wg_rs64_00(float* d, uint32_t a0, uint32_t a1, uint32_t a2, uint32_t a3, uint64_t db, int sd) {
  asm volatile("{.reg .pred p; setp.ne.b32 p, %37, 0;\n"
    "wgmma.mma_async.sync.aligned.m64n64k16.f32.bf16.bf16 {%0,%1,%2,%3,%4,%5,%6,%7,%8,%9,%10,%11,%12,%13,%14,%15,%16,%17,%18,%19,%20,%21,%22,%23,%24,%25,%26,%27,%28,%29,%30,%31}, {%32,%33,%34,%35}, %36, p, 1, 1, 0;}"
    : "+f"(d[0]),"+f"(d[1]),"+f"(d[2]),"+f"(d[3]),"+f"(d[4]),"+f"(d[5]),"+f"(d[6]),"+f"(d[7]),"+f"(d[8]),"+f"(d[9]),"+f"(d[10]),"+f"(d[11]),"+f"(d[12]),"+f"(d[13]),"+f"(d[14]),"+f"(d[15]),"+f"(d[16]),"+f"(d[17]),"+f"(d[18]),"+f"(d[19]),"+f"(d[20]),"+f"(d[21]),"+f"(d[22]),"+f"(d[23]),"+f"(d[24]),"+f"(d[25]),"+f"(d[26]),"+f"(d[27]),"+f"(d[28]),"+f"(d[29]),"+f"(d[30]),"+f"(d[31])
    : "r"(a0), "r"(a1), "r"(a2), "r"(a3), "l"(db), "r"(sd));
}
__device__ __forceinline__ void wg_rs80_01(float* d, uint32_t a0, uint32_t a1, uint32_t a2, uint32_t a3, uint64_t db, int sd) {
  asm volatile("{.reg .pred p; setp.ne.b32 p, %45, 0;\n"
    "wgmma.mma_async.sync.aligned.m64n80k16.f32.bf16.bf16 {%0,%1,%2,%3,%4,%5,%6,%7,%8,%9,%10,%11,%12,%13,%14,%15,%16,%17,%18,%19,%20,%21,%22,%23,%24,%25,%26,%27,%28,%29,%30,%31,%32,%33,%34,%35,%36,%37,%38,%39}, {%40,%41,%42,%43}, %44, p, 1, 1, 1;}"
    : "+f"(d[0]),"+f"(d[1]),"+f"(d[2]),"+f"(d[3]),"+f"(d[4]),"+f"(d[5]),"+f"(d[6]),"+f"(d[7]),"+f"(d[8]),"+f"(d[9]),"+f"(d[10]),"+f"(d[11]),"+f"(d[12]),"+f"(d[13]),"+f"(d[14]),"+f"(d[15]),"+f"(d[16]),"+f"(d[17]),"+f"(d[18]),"+f"(d[19]),"+f"(d[20]),"+f"(d[21]),"+f"(d[22]),"+f"(d[23]),"+f"(d[24]),"+f"(d[25]),"+f"(d[26]),"+f"(d[27]),"+f"(d[28]),"+f"(d[29]),"+f"(d[30]),"+f"(d[31]),"+f"(d[32]),"+f"(d[33]),"+f"(d[34]),"+f"(d[35]),"+f"(d[36]),"+f"(d[37]),"+f"(d[38]),"+f"(d[39])
    : "r"(a0), "r"(a1), "r"(a2), "r"(a3), "l"(db), "r"(sd));
}
__device__ __forceinline__ void wg_rs24_01(float* d, uint32_t a0, uint32_t a1, uint32_t a2, uint32_t a3, uint64_t db, int sd) {
  asm volatile("{.reg .pred p; setp.ne.b32 p, %17, 0;\n"
    "wgmma.mma_async.sync.aligned.m64n24k16.f32.bf16.bf16 {%0,%1,%2,%3,%4,%5,%6,%7,%8,%9,%10,%11}, {%12,%13,%14,%15}, %16, p, 1, 1, 1;}"
    : "+f"(d[0]),"+f"(d[1]),"+f"(d[2]),"+f"(d[3]),"+f"(d[4]),"+f"(d[5]),"+f"(d[6]),"+f"(d[7]),"+f"(d[8]),"+f"(d[9]),"+f"(d[10]),"+f"(d[11])
    : "r"(a0), "r"(a1), "r"(a2), "r"(a3), "l"(db), "r"(sd));
}

#define AB_POLY 0x77
__device__ __forceinline__ constexpr bool poly_group(int group) { return (AB_POLY >> (group & 7)) & 1; }

template <int V> struct Int { static constexpr int value = V; };

__device__ __forceinline__ int core_word(int row, int col) {
  return ((((row >> 7) * 10 + (col >> 6)) * 16 + ((row >> 3) & 15)) * 8 + ((col >> 3) & 7)) * 32 + (row & 7) * 4 + ((col & 7) >> 1);
}
__device__ __forceinline__ void wait_count(const uint32_t* c, uint32_t n) {
  for (int spin = 0; !__all_sync(~0u, (ld_acquire(c) & 0xffff) >= n);) { __nanosleep(32); spin_guard(spin); }
  fence_async_global();
}
__device__ __forceinline__ void prefetch_l2(const void* p, uint32_t bytes) {
  asm volatile("cp.async.bulk.prefetch.L2.global [%0], %1;" :: "l"(p), "r"(bytes) : "memory"); }

#define PLACE 4
__device__ __forceinline__ bool helper_sm() {
  uint32_t m; asm volatile("mov.u32 %0, %%smid;" : "=r"(m));
  return m < 2 || m >= 120 || (m >= 92 && m < 102) || (m >= 106 && m < 117) || m == 118;
}

__device__ __forceinline__ uint8_t* pool_at(uint32_t off) {
  return reinterpret_cast<uint8_t*>((reinterpret_cast<uintptr_t>(g_pool) + 8191) & ~(uintptr_t)8191) + off; }
__device__ __forceinline__ void probe_slots(uint32_t scratch) {
  const int w = (threadIdx.x >> 6) & 1, slot = w == 0 ? NSLOT : blockIdx.x;
  if (w == 0 || slot < NSLOT) {
    uint32_t* q = reinterpret_cast<uint32_t*>(pool_at(slot * 8192)) + (w == 0 ? (blockIdx.x & 31) * 32 + (blockIdx.x >> 5) : 0);
    uint32_t best[2] = {~0u, ~0u};
    const bool one = elect();
    if (one) { stg_strong32(q, 0u); stg_strong32(q + 1024, 0u); }
#pragma unroll 1
    for (int r = 0; r < 8; r++) {
      uint32_t v = 0;
      const uint32_t t0 = clk32();
      if (one) asm volatile("atom.relaxed.gpu.global.exch.b32 %0, [%1], 0;" : "=r"(v) : "l"(q + (r & 1) * 1024) : "memory");
      if (__any_sync(~0u, v != 0)) break;
      const uint32_t t = min(clk32() - t0, best[0]);
      best[0] = best[1]; best[1] = t;
    }
    if (one) sts32(scratch + w * 4, best[0] < best[1]);
  }
  bar_sync(2, 64);
  if ((threadIdx.x & 31) == 0) {
    const int part = lds32(scratch) ? 1 : 2;
    if (w == 0) { uint32_t smid; asm("mov.u32 %0, %%smid;" : "=r"(smid)); stg_strong32(g_smpart + (smid & 255), part); }
    else if (slot < NSLOT) stg_strong32(g_orient + slot, lds32(scratch + 4) ? part : 3 - part);
  }
  __syncwarp();
}

constexpr int WK_SLOTS = 28, WK_BAR = WK_SLOTS * 8192;
__device__ __forceinline__ void work_init(uint32_t sb, int w) {
  if (elect()) {
#pragma unroll
    for (int i = 0; i < 8; i++) mbar_init(sb + WK_BAR + 64 * w + 8 * i, 0x18318822 >> (8 * w + (i & 4)) & 15);
  }
  asm volatile("fence.mbarrier_init.release.cluster;" ::: "memory");
}

struct ChainParams {
  CUtensorMap wq, wk, wv, wo, xc;
  const __nv_bfloat16* mem0;
  const uint8_t* wb;
  uint32_t *sync, *other;
  int layer;
  int d1, d2, dn, dx, mode, zero;
};
constexpr int CH_WQ = 0, CH_WO = 81920, CH_X = CH_WO + 86016, CH_M = CH_X, CH_Q = CH_X + 34816, CH_KM = CH_Q + 2048, CH_VP = CH_KM + 2048,
              CH_K = CH_X + 40960, CH_O = CH_K, CH_KS = CH_K + 3072, CH_V = CH_K + 4096, CH_VX = CH_V + 12288, CH_R2 = CH_VX,
              CH_SX = CH_VX + 3072, CH_SO = CH_SX + 2048, CH_ID = CH_SO + 1024, CH_L = CH_ID + 256, CH_TAB = CH_L + 64, CH_BAR = CH_TAB + 384;
constexpr int CH_SMEM = CH_BAR + 144;
constexpr int MB_WO = CH_BAR, MB_WQ = CH_BAR + 8, MB_X = CH_BAR + 16, MB_V = CH_BAR + 24, MB_T = CH_BAR + 32, MB_F = CH_BAR + 40, MB_G = CH_BAR + 48, MB_W = CH_BAR + 56;
enum { NB_PROJ = 1, NB_O = 2, NB_W1 = 3, NB_PRE = 4, NB_ST = 5, NB_MEM = 6, NB_XFREE = 7, NB_H1 = 8, NB_PUB = 9, NB_W2 = 10, NB_PROJ2 = 11, NB_PRE2 = 12, NB_H2 = 13, NB_W1V = 14 };
#define CH_NQ 9
#define CH_XPF 1
#define CH_TPF 1
#define CH_FLY 6
#define CH_TW 1
#define CH_NQ0 4
#define CH_PA 6
#define CH_PB 9
#define CH_PC 13
#define CH_PL 4
#define CH_DBL 0x0888
#define CH_PD 1
#define SCHED() asm volatile("griddepcontrol.launch_dependents;" ::: "memory")
__device__ __forceinline__ uint32_t opaque(uint32_t x) { return __shfl_sync(~0u, x, threadIdx.x & 31); }
__device__ __forceinline__ uint32_t uniform(uint32_t x) { return __shfl_sync(~0u, x, 0); }
__device__ __forceinline__ uint32_t nz(uint32_t x) { uint32_t r; asm("max.u32 %0, %1, 1;" : "=r"(r) : "r"(x)); return r; }
__device__ __forceinline__ uint32_t set_tag(uint32_t w, uint32_t tag) { uint32_t r; asm("lop3.b32 %0, %1, %2, 1, 0xD8;" : "=r"(r) : "r"(w), "r"(tag)); return r; }
__device__ __forceinline__ uint32_t pack_tag(float lo, float hi, uint32_t tag) { return set_tag(__byte_perm(__float_as_uint(lo) + tag, pack2(hi, hi), 0x7632), tag); }
__device__ __forceinline__ uint32_t differ(uint32_t a, uint32_t b, uint32_t t) { uint32_t r; asm("lop3.b32 %0, %1, %2, %3, 0x7E;" : "=r"(r) : "r"(a), "r"(b), "r"(t)); return r; }
__device__ __forceinline__ uint32_t clk64() { uint64_t c; asm volatile("mov.u64 %0, %%clock64;" : "=l"(c) :: "memory"); return (uint32_t)c; }
__device__ __forceinline__ void until(uint32_t t) {
  asm volatile("{.reg .pred p; .reg .u64 c; .reg .s32 d;\nW: mov.u64 c, %%clock64; cvt.u32.u64 d, c; sub.s32 d, d, %0; setp.lt.s32 p, d, 0; @p bra.uni W;}" :: "r"(t) : "memory");
}
__device__ __forceinline__ float rcp(float x) { float y; asm("rcp.approx.ftz.f32 %0, %1;" : "=f"(y) : "f"(x)); return y; }

__device__ __forceinline__ void chain_compute(const ChainParams& p, const uint32_t sb) {
  const int tid = threadIdx.x & 127, WG = __shfl_sync(~0u, threadIdx.x >> 7, 0), t4 = __shfl_sync(~0u, tid >> 5, 0), lane = tid & 31;
  const int cta = blockIdx.x, h = cta / 3, j = cta - 3 * h;
  uint32_t a0[80], a1[80], tw[4 * CH_NQ];
  const uint32_t wq = opaque(sb + CH_WQ + (WG * 320 + (lane & 7) + (lane >> 4) * 8) * 128 + (((2 * t4 + ((lane >> 3) & 1)) ^ (lane & 7)) << 4));
#pragma unroll
  for (int k = 0; k < 40; k++) {
    if (k % 10 == 0) mbar_wait(sb + MB_W + WG * 8 + k / 10 * 16, 0);
    if (k < 20) ldsm4t(&a0[4 * k], wq + k * 2048); else ldsm4t(&a1[4 * k - 80], wq + CH_WO + (k - 20) * 2048);
    if (k % 20 == 19) bar_arrive(k < 20 ? NB_PROJ2 : NB_PRE2, 288);
  }
  const int r1 = j == 2 ? 0 : j + 1, r2 = j == 0 ? 2 : j - 1;
  const uint32_t l16 = opaque(sb + lane * 16), l8 = opaque(sb + lane * 8), l4 = opaque(sb + lane * 4);
  const uint32_t t16 = l16 + t4 * 512, t8 = l8 + t4 * 256;
  uint32_t wo = opaque(sb + CH_WO + (WG == 0 ? (t4 >> 1) * 36864 : 73728 + t4 * 1024) + ((lane & 7) + (lane >> 4) * 8) * 64 +
                       (((((lane >> 3) & 1) + (WG == 0 ? (t4 & 1) * 2 : 0)) ^ ((lane >> 1) & 3)) << 4));
  const uint32_t ko0 = uniform(CH_K + (tid >> 5) * 1024 + (tid >> 6) * 512), ko1 = uniform(CH_K + (tid >> 5) * 1024 + 512 - (tid >> 6) * 512),
                 o768 = uniform((tid >> 5) * 768);
  const uint32_t give = uniform(t4 * 512 + (WG == 0 ? CH_K : CH_V + j * 4096)), own = uniform(t4 * 512 + (WG == 0 ? CH_V + j * 4096 : CH_K)), mem = uniform(CH_M + WG * 5120);
  const uint32_t vxo = uniform(t4 * 256 + CH_VX + j * 1024);
  uint32_t tag = 1, xd = uniform((1024 + CH_X + WG * 20480) >> 4 | 8 << 16);
  asm volatile("barrier.cluster.wait.aligned;" ::: "memory");
  mbar_wait(sb + MB_WQ, 0);
  mbar_wait(sb + MB_T, 0);
  bar_sync(NB_ST, 384);
  uint8_t* pdst[6];
#pragma unroll
  for (int i = 0; i < 6; i++) {
    const int line = WG == 0 ? 24 * j + 12 * (t4 >> 1) + 2 * (t4 & 1) + 4 * (i >> 1) + (i & 1) : j == 0 ? 72 + t4 : 74 + 2 * j + (t4 & 1);
    pdst[i] = pool_at(uniform(lds32(sb + CH_TAB + line * 4)) + h * 128);
  }
  auto batch = [&](float* d, const uint32_t (&a)[80], int acc, int n0, int n1) {
    const uint32_t d0 = xd ^ (tag & (2 << acc));
    wg_fence();
#pragma unroll
    for (int k = 0; k < 20; k++) {
      if (!(k & 3) && n0 + k / 4 < n1) {
        __syncwarp();
        ldsm4t(&tw[4 * n0 + k], wq + (n0 + k / 4) * 2048);
        __syncwarp();
      }
      uint64_t db;
      asm("mov.b64 %0, {%1, %2};" : "=l"(db) : "r"(d0 + k / 5 * 320 + k % 5 * 16), "r"(80));
      wg_rs32_00(d, a[4 * k], a[4 * k + 1], a[4 * k + 2], a[4 * k + 3], db, acc | k);
    }
    wg_commit();
    wg_wait<0>();
    reg_fence<16>(d);
  };
  int s = 0;
#pragma unroll 1
  do {
    {
      float d[16];
      if (!CH_TW) mbar_wait(sb + MB_T, s & 1);
      batch(d, a0, 0, 0, CH_NQ0);
      s--; TM(10); s++;
      mbar_wait(sb + MB_F, ~s & 1);
#pragma unroll
      for (int i = 0; i < 2; i++)
        sts128(l16 + give + i * 2048, make_uint4(pack2(d[8 * i], d[8 * i + 1]), pack2(d[8 * i + 2], d[8 * i + 3]), pack2(d[8 * i + 4], d[8 * i + 5]), pack2(d[8 * i + 6], d[8 * i + 7])));
      bar_sync(NB_PUB, 384);
#pragma unroll
      for (int i = 0; i < 2; i++) {
        const uint4 t = lds128(l16 + own + i * 2048);
        d[8 * i] = bf_lo(t.x); d[8 * i + 1] = bf_hi(t.x); d[8 * i + 2] = bf_lo(t.y); d[8 * i + 3] = bf_hi(t.y);
        d[8 * i + 4] = bf_lo(t.z); d[8 * i + 5] = bf_hi(t.z); d[8 * i + 6] = bf_lo(t.w); d[8 * i + 7] = bf_hi(t.w);
      }
      reg_fence<16>(d);
      batch(d, a1, 1, CH_NQ0, CH_NQ);
      s--; TM(11); s++;
      if (WG == 0) bar_arrive(NB_XFREE, 256);
#pragma unroll
      for (int i = 0; i < 8; i++) sts32(l4 + (own - t4 * 256) + (i >> 1) * 1024 + (i & 1) * 128, pack2(d[2 * i], d[2 * i + 1]));
      s--; TM(9); s++;
    }
    float dq[4] = {}, d0[4] = {}, d1[4] = {};
    uint32_t b[40], wf[80];
    const uint32_t* kf = &wf[52];
#pragma unroll
    for (int i = 0; i < 4 * CH_NQ; i++) wf[i] = tw[i];
    auto step = [&](int k) {
      mma16(dq, wf[4 * k], wf[4 * k + 1], wf[4 * k + 2], wf[4 * k + 3], b[2 * k], b[2 * k + 1]);
      mma16(d0, a0[4 * k], a0[4 * k + 1], a0[4 * k + 2], a0[4 * k + 3], b[2 * k], b[2 * k + 1]);
      mma16(d1, a1[4 * k], a1[4 * k + 1], a1[4 * k + 2], a1[4 * k + 3], b[2 * k], b[2 * k + 1]);
    };
    auto finish = [&](int wg, const float* dk) {
      const float k2 = 0.07216878364870322f * 1.44269504089f;
      sts32(l4 + t4 * 512 + CH_Q + wg * 128, pack2(dq[0] * k2, dq[1] * k2));
      sts32(l4 + t4 * 512 + CH_Q + wg * 128 + 256, pack2(dq[2] * k2, dq[3] * k2));
      sts32(l4 + t4 * 512 + CH_KM + wg * 256, pack2(dk[0], dk[1]));
      sts32(l4 + t4 * 512 + CH_KM + wg * 256 + 128, pack2(dk[2], dk[3]));
    };
    const bool more = s < NSEG - 1;
    bar_sync(NB_MEM, 384);
    ldsm4t(&b[0], l16 + mem);
    ldsm4t(&b[4], l16 + mem + 512);
    TMD(0, b[0]);
    {
      int nw = CH_NQ, nb = 2;
#pragma unroll
      for (int k = 0; k < 20; k++) {
        SCHED();
        step(k);
#pragma unroll
        for (int i = 0; i < (CH_DBL >> k & 1) + 1; i++) {
          if (nb < 10 && 2 * nb <= nw) { ldsm4t(&b[4 * nb], l16 + mem + nb * 512); nb++; }
          else if (nw < 20) { ldsm4t(&wf[4 * nw], wq + nw * 2048); nw++; }
          else if (nw < 22) {
            const uint32_t x = l16 ^ ((o768 ^ tag) & 256);
            uint32_t* r = &wf[4 * nw - 28];
            asm volatile("{.reg .pred p; setp.ne.u32 p, %5, 0; @p ldmatrix.sync.aligned.m8n8.x4.trans.shared.b16 {%0,%1,%2,%3},[%4];}"
                         : "+r"(r[0]), "+r"(r[1]), "+r"(r[2]), "+r"(r[3]) : "r"(x + (nw == 20 ? ko0 : ko1)), "r"(WG) : "memory");
            nw++;
          }
        }
      }
      SCHED();
    }
    if (WG == 0) {
      finish(0, d0);
      TM(1);
      bar_sync(NB_PROJ, 256);
      if (!more) {
        const float4 pv = lds128f(t16 + CH_VP);
        sts32(l4 + vxo, pack2(d1[0] + pv.x, d1[1] + pv.y));
        sts32(l4 + vxo + 128, pack2(d1[2] + pv.z, d1[3] + pv.w));
        continue;
      }
      const float4 pv = lds128f(t16 + CH_VP);
      const uint32_t xo = l4 + (vxo ^ (tag & 2)), x1 = mapa(xo, r1), x2 = mapa(xo, r2);
      SCHED();
      const uint32_t v0 = pack2(d1[0] + pv.x, d1[1] + pv.y), v1 = pack2(d1[2] + pv.z, d1[3] + pv.w);
      st_async32(x1, v0, mapa(sb + MB_X, r1));
      st_async32(x2, v0, mapa(sb + MB_X, r2));
      st_async32(x1 + 128, v1, mapa(sb + MB_X, r1));
      st_async32(x2 + 128, v1, mapa(sb + MB_X, r2));
      sts32(xo, v0);
      sts32(xo + 128, v1);
      __syncwarp();
      if (elect()) mbar_arrive(sb + MB_X);
      bar_arrive(NB_PROJ2, 256);
      TM(3);
      uint32_t w[144];
      auto tile_of = [](int n) { return n < 27 ? n % 3 : (0x26484 >> 2 * (n - 27)) & 3; };
      auto step_of = [](int n) { return n < 27 ? n / 3 : 9 + ((0x29610 >> 2 * (n - 27)) & 3); };
      auto wload = [&](int n) { ldsm4t(&w[4 * n], wo + tile_of(n) * 12288 + (step_of(n) % 3) * 4096 + (step_of(n) / 3) * 1024); };
#pragma unroll
      for (int n = 0; n < CH_PA; n++) wload(n);
      bar_sync(NB_PRE, 256);
#pragma unroll
      for (int n = CH_PA; n < CH_PB; n++) wload(n);
      bar_arrive(NB_PRE2, 256);
      if (CH_PC > CH_PB) {
        mbar_wait(sb + MB_X, s & 1);
        for (int i = 0; i < CH_PD; i++) wo = __shfl_xor_sync(~0u, wo, p.zero);
#pragma unroll
        for (int n = CH_PB; n < CH_PC; n++) wload(n);
      }
      TM(4);
      bar_sync(NB_O, 256);
      {
        float x[3][4] = {};
        uint32_t ob[24];
        float4 l;
        ldsm4t(&ob[0], l16 + CH_O);
        ldsm4t(&ob[4], l16 + CH_O + 512);
        TMD(7, ob[0]);
        int nw = CH_PC, no = 2;
        float i0, i1;
        uint8_t* dst[6];
        uint32_t lo[6], hi[6];
        auto pre = [&](int i) { lo[i] = __float_as_uint(x[i >> 1][2 * (i & 1)] * i0) + tag; hi[i] = pack2(0.f, x[i >> 1][2 * (i & 1) + 1] * i1); };
        auto emit = [&](int i) { stg_strong32(dst[i], set_tag(__byte_perm(lo[i], hi[i], 0x7632), tag)); };
#pragma unroll
        for (int n = 0; n < 36; n++) {
          SCHED();
          mma16(x[tile_of(n)], w[4 * n], w[4 * n + 1], w[4 * n + 2], w[4 * n + 3], ob[step_of(n) * 2], ob[step_of(n) * 2 + 1]);
          if (n >= CH_PL) {
            if (no < 6 && no * 2 <= step_of(min(nw, 35))) { ldsm4t(&ob[4 * no], l16 + CH_O + no * 512); no++; }
            else if (nw < 36) { wload(nw); nw++; }
          }
          if (n == 18) l = lds128f(sb + CH_L + ((l16 ^ tag) & 0x30));
          if (n == 26) { i0 = rcp(l.x + l.y); i1 = rcp(l.z + l.w); asm volatile("" : "+f"(i0), "+f"(i1)); }
          if (n >= 28 && n < 34) { dst[n - 28] = pdst[n - 28] + ((l4 ^ tag) & 0x7c); asm volatile("" : "+l"(dst[n - 28])); }
          if (n == 32) { for (int i = 0; i < 2; i++) { pre(i); asm volatile("" : "+r"(lo[i]), "+r"(hi[i])); } }
          if (n == 33) { emit(0); emit(1); }
        }
        for (int i = 2; i < 6; i++) pre(i);
        for (int i = 2; i < 6; i++) emit(i);
      }
      TM(8);
    } else {
      finish(1, d1);
      sts128f(t16 + CH_VP, d0[0], d0[1], d0[2], d0[3]);
      TM(1);
      bar_sync(NB_PROJ, 256);
      uint32_t pair;
      {
        float d0[4] = {}, d1[4] = {}, dm[4] = {};
        uint32_t q[16], km[4];
#pragma unroll
        for (int e = 0; e < 4; e++) {
          ldsm4t(&q[4 * e], l16 + (e ^ t4) * 512 + CH_Q);
          SCHED();
          if (e == 1) { ldsm4t(km, t16 + CH_KM); SCHED(); }
        }
        const uint32_t xo = l4 + ((t4 * 128) ^ (tag & 2));
        pair = l16 + ((l16 ^ tag) & 256) * 3;
        asm volatile("" : "+r"(pair));
        uint64_t x[4];
#pragma unroll
        for (int i = 0; i < 4; i++) {
          const int r = i & 1 ? r2 : r1;
          asm volatile("mov.b64 %0, {%1, %2};" : "=l"(x[i]) : "r"(mapa(xo, r) + CH_SX + (i & 1) * 1024 + (i & 2) * 256), "r"(mapa(sb + MB_X, r)));
        }
        SCHED();
        mma16(d0, q[0], q[1], q[2], q[3], kf[0], kf[1]);
        SCHED();
        mma16(d1, q[4], q[5], q[6], q[7], kf[2], kf[3]);
        SCHED();
        mma16(dm, q[0], q[1], q[2], q[3], hadd2(km[0], km[2]), hadd2(km[1], km[3]));
        mma16(d0, q[8], q[9], q[10], q[11], kf[4], kf[5]);
        SCHED();
        mma16(d1, q[12], q[13], q[14], q[15], kf[6], kf[7]);
        if (!more) continue;
        const uint32_t w1 = pack2(dm[0] + dm[2], dm[1] + dm[3]);
        st_async32((uint32_t)x[2], w1, x[2] >> 32);
        st_async32((uint32_t)x[3], w1, x[3] >> 32);
        SCHED();
        const uint32_t w0 = pack2((d0[0] + d0[2]) + (d1[0] + d1[2]), (d0[1] + d0[3]) + (d1[1] + d1[3]));
        st_async32((uint32_t)x[0], w0, x[0] >> 32);
        st_async32((uint32_t)x[1], w0, x[1] >> 32);
        sts32(xo + CH_SO, w0);
        sts32(xo + CH_SO + 512, w1);
      }
      TM(3);
      float sc[3][4] = {};
      uint32_t wd[12];
      uint32_t redo;
      auto attend = [&](auto first) {
        uint4 vb[6];
        uint32_t vm[6];
        float e[10];
        uint32_t ow[6];
        if (first.value) {
          const uint2 id = lds64(l8 + CH_ID);
          bar_sync(NB_W1V, 160);
          uint32_t r[8];
          ldsm4(r, l16 + CH_SO); ldsm4(r + 4, l16 + CH_SO + 512);
#pragma unroll
          for (int u = 0; u < 6; u++) vb[u] = ldsm4v(pair + t4 * 256 + CH_V + u * 2048);
          bar_arrive(NB_PRE, 256);
          const uint32_t sxa = pair + CH_SX;
          SCHED();
          mma8(sc[0], r[0], r[1], id.x);
          mma8(sc[1], r[2], r[3], id.x);
          mma16(sc[2], r[4], r[5], r[6], r[7], id.x, id.y);
          TM(7);
          mbar_wait(sb + MB_X, s & 1);
          TM(4);
          uint32_t t[16];
          ldsm4(t, sxa); ldsm4(t + 4, sxa + 256); ldsm4(t + 8, sxa + 512);
          SCHED();
          mma16(sc[0], t[0], t[1], t[2], t[3], id.x, id.y);
          ldsm4(t + 12, sxa + 768);
          SCHED();
          mma16(sc[1], t[4], t[5], t[6], t[7], id.x, id.y);
          ldsm4(vm, pair + t4 * 256 + CH_VX);
          SCHED();
          e[0] = ex2(sc[0][0]);
          mma16(sc[2], t[8], t[9], t[10], t[11], id.x, id.y);
          ldsm2(vm + 4, l16 + t4 * 256 + CH_VX + 2048);
          SCHED();
          e[1] = ex2(sc[0][1]);
          ldsm4t(&wd[0], wo);
          SCHED();
          e[2] = ex2(sc[0][2]);
          SCHED();
          e[3] = ex2(sc[0][3]);
          mma16(sc[2], t[12], t[13], t[14], t[15], id.x, id.y);
          SCHED();
          e[4] = ex2(sc[1][0]);
          ldsm4t(&wd[4], wo + 4096);
          SCHED();
          e[5] = ex2(sc[1][1]);
        } else {
#pragma unroll
          for (int u = 0; u < 6; u++) vb[u] = ldsm4v(pair + t4 * 256 + CH_V + u * 2048);
          ldsm4(vm, pair + t4 * 256 + CH_VX);
          ldsm2(vm + 4, l16 + t4 * 256 + CH_VX + 2048);
        }
        float o[3][4] = {};
        if (!first.value) {
#pragma unroll
          for (int i = 0; i < 6; i++) e[i] = ex2(sc[i >> 2][i & 3]);
        }
        const uint32_t p1 = pack2(e[0], e[1]), p2 = pack2(e[2], e[3]);
        float l = (e[0] + e[1]) + (e[2] + e[3]);
        asm volatile("" : "+f"(l));
        SCHED();
        e[6] = ex2(sc[1][2]);
        mma16(o[0], vb[0].x, vb[0].y, vb[0].z, vb[0].w, p1, p2);
        if (first.value) { sc[2][0] += sc[2][2]; sc[2][1] += sc[2][3]; }
        SCHED();
        e[7] = ex2(sc[1][3]);
        mma16(o[1], vb[2].x, vb[2].y, vb[2].z, vb[2].w, p1, p2);
        SCHED();
        e[8] = ex2(sc[2][0]);
        mma16(o[2], vb[4].x, vb[4].y, vb[4].z, vb[4].w, p1, p2);
        SCHED();
        e[9] = ex2(sc[2][1]);
        SCHED();
        const uint32_t p3 = pack2(e[4], e[5]), p4 = pack2(e[6], e[7]);
        l += (e[4] + e[5]) + (e[6] + e[7]);
#pragma unroll
        for (int u = 0; u < 3; u++) mma16(o[u], vb[2 * u + 1].x, vb[2 * u + 1].y, vb[2 * u + 1].z, vb[2 * u + 1].w, p3, p4);
        SCHED();
        const uint32_t p0 = pack2(e[8], e[9]);
        l += e[8] + e[9];
        const float l2 = __shfl_xor_sync(~0u, l, 1);
        if (first.value) ldsm4t(&wd[8], wo + 8192);
#pragma unroll
        for (int u = 0; u < 3; u++) mma8(o[u], vm[2 * u], vm[2 * u + 1], p0);
        redo = __any_sync(~0u, !(l > 1e-9f && l < 1e9f));
        uint32_t la = sb + CH_L + (((l4 ^ tag) >> 1) & 0x3c);
        asm volatile("" : "+r"(la));
        SCHED();
#pragma unroll
        for (int u = 0; u < 3; u++) { ow[2 * u] = pack2(o[u][0], o[u][1]); ow[2 * u + 1] = pack2(o[u][2], o[u][3]); }
#pragma unroll
        for (int u = 0; u < 6; u++) sts32(l4 + o768 + CH_O + u * 128, ow[u]);
        if (t4 == 0) sts32(la, __float_as_uint(l + l2));
      };
      attend(Int<1>());
      TM(6);
      asm volatile("{.reg .pred p; setp.eq.u32 p, %0, 0; @p bar.sync 2, 256;}" :: "r"(redo) : "memory");
      if (redo) {
        float mx = fmaxf(sc[2][0], sc[2][1]);
#pragma unroll
        for (int i = 0; i < 4; i++) mx = fmaxf(mx, fmaxf(sc[0][i], sc[1][i]));
        mx = fmaxf(mx, __shfl_xor_sync(~0u, mx, 1));
        mx = fmaxf(mx, __shfl_xor_sync(~0u, mx, 2));
#pragma unroll
        for (int i = 0; i < 4; i++) { sc[0][i] -= mx; sc[1][i] -= mx; }
        sc[2][0] -= mx; sc[2][1] -= mx;
        attend(Int<0>());
        bar_arrive(NB_O, 256);
      }
      {
        float z[4] = {};
        const uint32_t scr = l8 + ((CH_V + r1 * 4096) ^ (tag & 2));
        uint32_t ow[6], we[12];
        __syncwarp();
        ldsm4t(ow, l16 + o768 + CH_O);
        ldsm2t(ow + 4, l16 + o768 + CH_O + 512);
        if (j == 0) {
          float y[4] = {};
#pragma unroll
          for (int u = 0; u < 3; u++) ldsm4t(&we[4 * u], (wo ^ 32) + u * 4096);
          SCHED();
#pragma unroll
          for (int u = 0; u < 3; u++) {
            mma16(z, wd[4 * u], wd[4 * u + 1], wd[4 * u + 2], wd[4 * u + 3], ow[2 * u], ow[2 * u + 1]);
            mma16(y, we[4 * u], we[4 * u + 1], we[4 * u + 2], we[4 * u + 3], ow[2 * u], ow[2 * u + 1]);
          }
          sts64f(scr + t4 * 256 + 2048, y[0], y[1]); sts64f(scr + t4 * 256 + 3072, y[2], y[3]);
        } else {
#pragma unroll
          for (int u = 0; u < 3; u++) mma16(z, wd[4 * u], wd[4 * u + 1], wd[4 * u + 2], wd[4 * u + 3], ow[2 * u], ow[2 * u + 1]);
        }
        sts64f(scr + t4 * 256, z[0], z[1]); sts64f(scr + t4 * 256 + 1024, z[2], z[3]);
        bar_sync(NB_W1, 128);
        if (j == 0 || t4 < 2) {
          float2 q[4];
          const float4 l = lds128f(sb + CH_L + ((l16 ^ tag) & 0x30));
#pragma unroll
          for (int i = 0; i < 4; i++) q[i] = lds64f(scr + t4 * 1024 + i * 256);
          SCHED();
          stg_strong32(pdst[0] + ((l4 ^ tag) & 0x7c), pack_tag(((q[0].x + q[1].x) + (q[2].x + q[3].x)) * rcp(l.x + l.y), ((q[0].y + q[1].y) + (q[2].y + q[3].y)) * rcp(l.z + l.w), tag));
        }
      }
      TM(2);
    }
    bar_sync(NB_ST, 384);
    tag ^= 0x10001;
  } while (++s < NSEG);
  if (WG == 1) {
    const uint2 a = lds64(t8 + t4 * 256 + CH_KM), b = lds64(t8 + t4 * 256 + CH_KM + 256);
    sts64(t8 + CH_M, hadd2(a.x, b.x), hadd2(a.y, b.y));
  }
  bar_arrive(NB_PRE2, 288);
}

__device__ __forceinline__ void chain_comm(const ChainParams& p, const uint32_t sb, const CUtensorMap* maps) {
  [[maybe_unused]] constexpr int WG = 2;
  const int tid = threadIdx.x & 127, t4 = __shfl_sync(~0u, tid >> 5, 0), lane = tid & 31;
  const int cta = blockIdx.x, h = cta / 3, j = cta - 3 * h, colbase = cta * 64;
  const uint8_t* const xs = reinterpret_cast<const uint8_t*>(g_xn);
  auto xload = [&](int seg, int i) { tma_load5(sb + CH_X + i * 10240, &p.xc, 0, seg * 4, 2 * i, sb + MB_T); };
  uint32_t smid; asm("mov.u32 %0, %%smid;" : "=r"(smid));
  if (t4 == 3) {
    const bool one = elect();
#pragma unroll 1
    for (int i = 0; i < 19 + CH_FLY; i++) {
      if (i >= CH_FLY) mbar_wait(sb + MB_W + 8 * ((i - CH_FLY) & 7), (i - CH_FLY) >> 3 & 1);
      if (i == 11 + CH_FLY && one) mbar_arrive(sb + MB_WQ);
      if (i == 8) { bar_sync(NB_PROJ2, 288); PRO(1); }
      if (i == 12) { bar_sync(NB_PRE2, 288); PRO(2); }
      if (i == 0) { bar_arrive(NB_ST, 384); bar_arrive(NB_PUB, 384); bar_arrive(NB_XFREE, 256); }
      if (i < 19 && one) {
        const int n = (i & 1) * 2 + (i >> 1 & 1), k = i - 12;
        const uint32_t bar = sb + MB_W + 8 * (i & 7);
        mbar_expect(bar, k < 0 ? 20480 : 12288);
        if (k < 0) tma_load(sb + ((i & 4) + n) * 20480, i >= 8 ? &p.wq : (i ^ i >> 2) & 1 ? &p.wv : &p.wk, colbase, n * 160, bar);
        else tma_load(sb + CH_WO + k * 12288, &p.wo, k < 6 ? j * 192 + k * 32 : j == 0 ? 576 : 592 + j * 16, h * 192, bar);
      }
    }
  } else {
    const uint32_t part = max(ldg_strong32(g_smpart + (smid & 255)), 1u);
    if (tid == 0) prefetch_l2(p.mem0, 10240);
    if (tid == 64) stg_strong32(p.sync + SY_PART + cta, part);
    if (t4 == 1) {
      wait_count(p.sync + SY_P + 1, ln_items(p.layer, 0));
      if (elect()) {
        mbar_expect(sb + MB_T, 40960);
#pragma unroll 1
        for (int i = 0; i < 4; i++) xload(0, i);
      }
      __syncwarp();
      PRO(0);
    }
    uint32_t reader, orient;
    for (int n = 0;; spin_guard(n)) {
      reader = ldg_strong32(p.sync + SY_PART + (tid >= 80 ? cta : tid));
      orient = ldg_strong32(g_orient + min(tid, NSLOT - 1));
      if (__all_sync(~0u, reader && orient)) break;
    }
    const uint32_t near = __ballot_sync(~0u, reader == part) >> (cta & 7) & 0xffff;
    if (tid < NSLOT) sts32(sb + CH_TAB + tid * 4, tid * 8192 + (orient == reader ? 0 : 4096));
    if (tid == 0) sts32(sb + CH_TAB + NSLOT * 4, cta < 80 ? cta : (cta & 7) + max(__ffs(near) - 1, 0));
    if (t4 == 1) PRO(3);
    bar_sync(NB_ST, 384);
    bar_arrive(NB_PUB, 384);
    if (t4 == 1) PRO(4);
    const uint32_t id = (lane >> 3) == (lane & 3) ? ((lane & 4) ? 0x3f800000u : 0x00003f80u) : 0u;
    if (t4 == 0) sts64(sb + CH_ID + lane * 8, id, id);
#pragma unroll 1
    for (int q = t4; q < 4; q += 3) {
      uint32_t m0[20];
#pragma unroll
      for (int i = 0; i < 20; i++) m0[i] = (reinterpret_cast<const uint32_t*>(p.mem0) + (lane >> 2) * (DM / 2) + q * 80 + (lane & 3))[i * 4];
      if (q < 3) bar_sync(NB_XFREE, 256);
#pragma unroll
      for (int i = 0; i < 20; i += 4) stsm4t(sb + CH_M + (q * 20 + i) * 128 + lane * 16, m0[i], m0[i + 1], m0[i + 2], m0[i + 3]);
    }
    if (t4 == 1) PRO(5);
  }
  if (cta < 4 && cta * 128 + tid < SY_N) p.other[cta * 128 + tid] = 0;
  asm volatile("barrier.cluster.wait.aligned;" ::: "memory");
  const uint32_t l8 = opaque(sb + t4 * 256 + lane * 8);
  bar_sync(NB_MEM, 384);
  uint8_t* const pool = pool_at(0);
  const uint8_t* const psrc = pool + opaque(lds32(sb + CH_TAB + lds32(sb + CH_TAB + NSLOT * 4) * 4) + t4 * 1024 + lane * 4);
  const uint32_t mdst = opaque((80 + cta / 20) * 8192 + (t4 & 1) * 4096 + (cta % 20) * 128 + lane * 4);
  int st = 0;
  uint32_t tag = 1, span = ~0u;
  auto send_tokens = [&](int s) {
    uint8_t* dst = g_kv + ((s >> 2) * 192 + cta + 3 * h) * KV_PART + (s & 3) * KV_SEG;
    bulk_store(dst, sb + CH_K, 4096);
    bulk_store(dst + KV_V, sb + CH_V + j * 4096, 4096);
    bulk_commit();
  };
  auto send_memory = [&](int s, uint32_t km) {
    fence_async();
    uint8_t* dst = g_kv + ((s >> 2) * 192 + cta + 3 * h) * KV_PART + KV_M + (s & 3) * KV_SEG;
    bulk_store(dst, km, 1024);
    bulk_store(dst + KV_V, sb + CH_VX + j * 1024, 1024);
    bulk_commit();
    bulk_wait<0>();
    if ((s & 3) == 3) { fence_async_global(); atomicAdd(p.sync + (s >> 2) * 8 + 4, 1); }
  };
#pragma unroll 1
  for (int s = 0; s < NSEG - 1; s++) {
    TM(0);
    STAT(0);
    if (t4 == 0) {
      if (elect()) {
        fence_async();
#pragma unroll 1
        for (int r = j + 1; r < j + 3; r++) bulk_push(mapa(sb + CH_V + j * 4096, r % 3), sb + CH_V + j * 4096, 4096, mapa(sb + MB_V, r % 3));
        send_tokens(s);
        bulk_wait_read<0>();
      }
      __syncwarp();
    }
    uint32_t c0, g0;
    if (t4 == 1) {
      __syncwarp();
      c0 = clk32(); g0 = gtime();
      if (elect()) atomicMax(p.sync + SY_TIME + s, g0);
    }
    if (t4 == 3 && s >= NSEG - 6 && elect()) asm volatile("prefetch.tensormap [%0];" :: "l"(maps + (NSEG - 2 - s)) : "memory");
    if (t4 == 3 && (s & 3) == 2 && s < NSEG - 2) wait_count(p.sync + SY_P + 5 + (s & ~3), ln_items(p.layer, (s >> 2) + 1));
    if (t4 == 2) { mbar_wait(sb + MB_V, s & 1); bar_arrive(NB_W1V, 160); }
    bar_sync(NB_PROJ2, 256);
    if (t4 == 0 && elect()) {
      mbar_expect(sb + MB_X, 4096);
      mbar_expect(sb + MB_T, 40960);
      for (int i = 0; i < 3; i++) xload(s + 1, i);
    }
    __syncwarp();
    STAT(1);
    TM(1);
    {
      const uint2 a = lds64(l8 + t4 * 256 + CH_KM), b = lds64(l8 + t4 * 256 + CH_KM + 256);
      sts64(l8 + CH_KS, hadd2(a.x, b.x), hadd2(a.y, b.y));
    }
    TM(4);
    bar_sync(NB_PRE2, 256);
    if (t4 == 0 && elect()) {
      xload(s + 1, 3);
      if (CH_XPF && s < NSEG - 2) prefetch_l2(xs + (s + 2) * 40960 + cta % 20 * 2048, 2048);
      if (CH_TPF && s >= NSEG - 7) {
        const int i = s - (NSEG - 7);
        if (i < 2) prefetch_l2(p.wb + (cta * 2 + i) * 12800, 12800);
        else if (i < 4) prefetch_l2(xs + (cta * 2 + i - 2) * 8192, 8192);
        else prefetch_l2(g_q + 15 * 32 * 3072 + (cta * 2 + i - 4) * 512, 8192);
      }
      send_memory(s, sb + CH_KS);
    }
    __syncwarp();
    if (t4 == 1) {
      const uint32_t late = min(ldg_strong32(p.sync + SY_TIME + s) - g0, 640u);
      if (elect()) sts32(sb + CH_TAB + 380, c0 + span + (late * 115 >> 6) + (j ? 60 : 0) + p.d1);
    }
    bar_sync(NB_W2, 128);
    uint32_t due = lds32(sb + CH_TAB + 380);
    due = __shfl_sync(~0u, due, 0);
    const uint8_t* ms = pool + (lds32(sb + CH_TAB + (80 + st * 4 + t4) * 4) + (l8 & 255));
    uint8_t* md = pool + (mdst + (cta >= 80 ? 2 : t4 < 2 ? st : st == 2 ? 0 : st + 1) * 32768);
    asm volatile("" : "+l"(ms), "+l"(md));
    if (CH_TW) mbar_wait(sb + MB_T, ~s & 1);
    TM(2);
    bar_sync(NB_ST, 384);
    __syncwarp();
    uint32_t tg = clk32();
    if (t4 == 3 && elect()) {
      if (s < NSEG - 2) mbar_expect(sb + MB_V, 8192);
      mbar_arrive_remote(mapa(sb + MB_F, j == 2 ? 0 : j + 1));
      mbar_arrive_remote(mapa(sb + MB_F, j == 0 ? 2 : j - 1));
    }
    if (s == NSEG - 2) work_init(sb, t4);
    __syncwarp();
    STAT(2);
    {
      float2 q[4];
      TM(3);
      if (t4 == 1 && s) span = min(span, tg - c0);
      until(s < 2 ? tg + 400 : (int)(due - tg) > p.dn ? due : tg + p.dn);
      for (int n = 0;;) {
        uint32_t v[8];
#pragma unroll
        for (int i = 0; i < 8; i++) v[i] = ldg_strong32(psrc + i * 128);
        sts64f(l8 + CH_R2, ((bf_lo(v[0]) + bf_lo(v[1])) + (bf_lo(v[2]) + bf_lo(v[3]))) + ((bf_lo(v[4]) + bf_lo(v[5])) + (bf_lo(v[6]) + bf_lo(v[7]))),
               ((bf_hi(v[0]) + bf_hi(v[1])) + (bf_hi(v[2]) + bf_hi(v[3]))) + ((bf_hi(v[4]) + bf_hi(v[5])) + (bf_hi(v[6]) + bf_hi(v[7]))));
        uint32_t bad;
        asm volatile("{.reg .pred p, q; .reg .b32 a; lop3.b32 a, %1, %2, %3, 0xFE; lop3.b32 a, a, %4, %6, 0xA8; setp.ne.u32 p, a, 0;\n"
                     "bar.red.or.pred q, %5, 128, p; selp.u32 %0, 1, 0, q;}"
                     : "=r"(bad) : "r"(differ(v[0], v[1], tag)), "r"(differ(v[2], v[3], tag)), "r"(differ(v[4], v[5], tag)), "r"(differ(v[6], v[7], tag)), "n"((int)NB_W2),
                       "r"((uint32_t)(cta < 80 || n < 3)) : "memory");
#pragma unroll
        for (int k = 0; k < 4; k++) asm volatile("ld.volatile.shared.v2.f32 {%0,%1}, [%2];" : "=f"(q[k].x), "=f"(q[k].y) : "r"(l8 - t4 * 256 + CH_R2 + k * 256) : "memory");
        TMV(12, n);
        if (!bad) break;
        spin_guard(n);
      }
      bar_arrive(NB_PUB, 384);
      SCHED();
      TM(9);
      stg_strong32(md, min(nz(pack2((q[0].x + q[1].x) + (q[2].x + q[3].x), (q[0].y + q[1].y) + (q[2].y + q[3].y))), t4 < 2 ? ~0u : 0u));
      tg = clk64() + p.d2;
      if (s >= 2 && (int)(due + p.dx - tg) > 0) tg = due + p.dx;
      TM(8);
    }
    STAT(3);
    until(tg);
    TM(10);
    for (int n = 0;;) {
      uint2 g[10];
#pragma unroll
      for (int i = 0; i < 10; i++) g[i] = ldg_strong64(ms + i * 256);
      if (n == 0) bar_sync(NB_XFREE, 256);
      uint32_t m = ~0u, bad;
#pragma unroll
      for (int i = 0; i < 10; i++) { sts64(l8 + CH_M + t4 * 2304 + i * 256, g[i].x, g[i].y); m = __vimin3_u32(m, g[i].x, g[i].y); }
      TMV(13, n);
      TM(11);
      asm volatile("{.reg .pred p; setp.eq.u32 p, %1, 0; vote.sync.any.pred p, p, 0xffffffff; @!p bar.sync %2, 384; selp.u32 %0, 1, 0, p;}" : "=r"(bad) : "r"(m), "n"((int)NB_MEM) : "memory");
      if (!bad) break;
      spin_guard(n);
    }
    if (++st == 3) st = 0;
    tag ^= 0x10001;
  }
  if (t4 == 0) {
    if (elect()) { fence_async(); send_tokens(NSEG - 1); }
    __syncwarp();
    bar_sync(NB_PRE2, 288);
    if (elect()) {
      send_memory(NSEG - 1, sb + CH_M);
      asm volatile("mbarrier.arrive.shared::cta.b64 _, [%0], 8;" :: "r"(sb + WK_BAR + 64) : "memory");
    }
    __syncwarp();
  }
}

__device__ __forceinline__ void chain_start(const ChainParams& p, const uint32_t sb, const int warp) {
  if (warp == 1 && elect()) {
#pragma unroll
    for (int i = 0; i < 6; i++) mbar_init(sb + CH_BAR + 8 * i, i == 2 ? 5 : i == 5 ? 2 : 1);
    asm volatile("fence.mbarrier_init.release.cluster;" ::: "memory");
    mbar_expect(sb + MB_V, 8192);
    atomicAdd(p.sync + SY_UP, 1);
    asm volatile("{.reg .pred p; setp.ne.u32 p, %0, 1024; @p trap;}" :: "r"(sb & 0xffffff));
  }
  if (warp == 0 && elect()) {
#pragma unroll
    for (int i = 0; i < 8; i++) mbar_init(sb + MB_W + 8 * i, 1);
    asm volatile("fence.mbarrier_init.release.cluster;" ::: "memory");
  }
  __syncthreads();
  asm volatile("barrier.cluster.arrive.relaxed.aligned;" ::: "memory");
}

struct WorkParams {
  ChainParams ch;
  CUtensorMap wo, xn, wb[3], wq, wc[2], out;
  const __nv_bfloat16* x;
  uint32_t* sync;
  int kind, qa_end, idle;
};
#define GO_320 4
#define GO_TAIL 1
#define PF_NS 400
enum { WK_FIRST = 0, WK_LEAD = 1, WK_CHAIN = 2, WK_LAST = 3 };
enum { IT_ATT = 0, IT_OP = 1, IT_FIN = 2, IT_BQ = 3, IT_BO = 4, IT_LN = 5, IT_Q = 6, IT_LN0 = 7, IT_OUT = 8 };
constexpr int C_EARLY = 1 << 20, C_LATE = 1 << 21, C_TAIL = 1 << 22;

__device__ __forceinline__ uint32_t item_count(int type, int b) { return type == IT_ATT ? 32 : type == IT_OP ? op_tiles(b) * op_split(b) : type == IT_FIN ? fin_items(b) : bq_items(b); }
__device__ __forceinline__ uint32_t item_need(int type, int b) { return type == IT_ATT ? 96 : item_count(type - 1, b); }
__device__ __forceinline__ int item_cols(int type, int b) {
  return type == IT_ATT || type == IT_Q ? 192 : type == IT_OUT ? 80 : type == IT_BQ ? (b < BQ_12 ? 320 : b < BQ_24 ? 160 : 80) : type == IT_OP && b >= OP_N4 ? 160 : 320; }
__device__ __forceinline__ int item_groups(int type, int b) { const int n = type == IT_FIN ? fin_items(b) : ln_items(type == IT_LN, b); return n == 4 ? 4 : n == 8 ? 2 : 1; }
#define RES_OP 0
#define RES_B 3
#define HOLD_B 12
constexpr int RES_N = RES_OP ? op_tiles(14) * op_split(14) : 0, RES_BQ = RES_B;
__device__ __forceinline__ bool reserved(int type, int b) { return type == IT_ATT ? b == 15 : type == IT_OP ? RES_OP && b == 14 : type == IT_BQ && b < RES_BQ; }
__device__ __forceinline__ int reserved_item(int cta) {
  const int h = cta / 3, j = cta - 3 * h, i = h + (j - 1) * 32;
  if (j == 0) return C_EARLY | IT_ATT << 16 | 15 << 8 | h;
  return i < RES_N ? C_TAIL | IT_OP << 16 | 14 << 8 | i : i - RES_N < RES_BQ * 6 ? C_TAIL | IT_BQ << 16 | ((i - RES_N) / 6) << 8 | (i - RES_N) % 6 : -1;
}
constexpr int LEAD1 = 12;
__device__ __forceinline__ int lead_item(int layer, int qa_end, int i) {
  if (layer == 2) return i < 128 ? C_EARLY | C_LATE | IT_OUT << 16 | (i >> 3) << 8 | (i & 7) : -1;
  if (layer == 0) {
    if (i < 32) return IT_LN0 << 16 | (i >> 4) << 8 | (i & 15);
    if (i < 88) return IT_LN0 << 16 | ((i - 24) >> 2) << 8 | (i & 3);
    i -= 88;
  } else {
    if (i < 4) return C_EARLY | IT_BO << 16 | (i >> 1) << 8 | (i & 1);
    if (i < 12) return C_EARLY | IT_LN << 16 | ((i - 4) >> 2) << 8 | (i & 3);
    if (i < 40) return C_EARLY | IT_BO << 16 | ((i - 8) >> 1) << 8 | (i & 1);
    if (i < 96) return C_EARLY | IT_LN << 16 | ((i - 32) >> 2) << 8 | (i & 3);
    i -= 96;
  }
  return i < (16 - qa_end) * 32 ? C_EARLY | IT_Q << 16 | (qa_end + (i >> 5)) << 8 | (i & 31) : -1;
}

struct Ring {
  uint32_t sb;
  int pos, seq;
  __device__ __forceinline__ uint32_t full() const { return sb + WK_BAR + 8 * (seq & 7); }
  __device__ __forceinline__ uint32_t take(int len) { if (pos + len > WK_SLOTS) pos = 0; pos += len; seq++; return sb + (pos - len) * 8192; }
  __device__ __forceinline__ uint32_t wait(int len) { mbar_wait(full(), (seq >> 3) & 1); return take(len); }
  __device__ __forceinline__ void release(int sq) const { if (elect()) mbar_arrive(sb + WK_BAR + 64 + 8 * (sq & 7)); }
};

struct Pending {
  uint32_t w[48], done;
  uint4* dst;
  __device__ __forceinline__ void store(int i) const { dst[(i >> 2) * 1024 + (i & 3) * 32] = make_uint4(w[4 * i], w[4 * i + 1], w[4 * i + 2], w[4 * i + 3]); }
  __device__ __forceinline__ void finish() { __syncwarp(); if (elect()) mbar_arrive(done); done = 0; }
  __device__ __forceinline__ void flush() {
    if (done) {
#pragma unroll
      for (int i = 0; i < 12; i++) store(i);
      finish();
    }
  }
};

template <int N>
__device__ __forceinline__ void gemm_item(float* d, Ring& r, int nkb, uint32_t go, int ask, Pending& pend) {
  const int warp = __shfl_sync(~0u, fresh_tid() >> 5, 0), wg = warp >> 2;
#pragma unroll 1
  for (int kb = 0; kb < nkb; kb++) {
    const uint32_t base = r.wait(2 + (N + 63) / 64);
    const uint64_t da = mkdesc(base + wg * 8192, 128, 1024, 0), db = mkdesc(base + 16384, 8192, 1024, 1);
    wg_fence();
#pragma unroll
    for (int kk = 0; kk < 4; kk++) {
      if (N == 80) wg_ss80_01(d, da + kk * 16, db + kk * 128, (kb | kk) != 0);
      else if (N == 160) wg_ss160_01(d, da + kk * 16, db + kk * 128, (kb | kk) != 0);
      else wg_ss192_01(d, da + kk * 16, db + kk * 128, (kb | kk) != 0);
      if (N == 320) wg_ss128_01(d + 96, da + kk * 16, db + kk * 128 + 3 * 512, (kb | kk) != 0);
    }
    wg_commit();
    if (kb == ask && go && warp == 0 && elect()) mbar_arrive(go);
    if (N == 192 && pend.done) {
#pragma unroll
      for (int i = 0; i < 12; i++) if (kb == i / 2) pend.store(i);
      if (kb == 5) pend.finish();
    }
    if (kb > 0) { wg_wait<1>(); r.release(r.seq - 2); }
  }
  wg_wait<0>();
  reg_fence<N / 2>(d);
  r.release(r.seq - 1);
}

__device__ __forceinline__ void attn_a(Ring& r, Pending& pend, bool now, const int warp) {
  uint32_t (&q)[48] = pend.w;
  const int lane = fresh_tid() & 31, t = (warp & 1) * 16 + (lane >> 2) - 2 * (lane & 3);
  const bool second = warp & 2;
  const uint32_t rows = (warp >> 2) * 2 * KV_SEG;
  uint32_t pa[20];
  float inv[2];
  const uint32_t b0 = r.wait(5) + rows, b1 = r.wait(5) + rows;
  {
    float s[40] = {};
    reg_fence<40>(s);
    wg_fence();
#pragma unroll
    for (int k = 0; k < 12; k++)
      wg_rs80_01(s, q[4 * k], q[4 * k + 1], q[4 * k + 2], q[4 * k + 3], mkdesc(k < 8 ? b0 : b1, 128, 1024, 0) + (k >> 2 & 1) * (KV_PART / 16) + (k & 3) * 16, k);
    wg_commit();
    wg_wait<0>();
    reg_fence<40>(s);
    r.release(r.seq - 2);
    const float k2 = 0.07216878364870322f * 1.44269504089f, NEG = -INFINITY;
#pragma unroll
    for (int i = 0; i < 20; i++) {
      s[i] = second ? s[20 + i] : s[i];
      if (i < 16 && 8 * ((i >> 2) - (i >> 1 & 1)) + (i & 1) > t) s[i] = NEG;
    }
#pragma unroll
    for (int hh = 0; hh < 2; hh++) {
      float m = NEG, l = 0.f;
#pragma unroll
      for (int n = 0; n < 5; n++) m = fmaxf(m, fmaxf(s[4 * n + 2 * hh], s[4 * n + 2 * hh + 1]));
      m = fmaxf(m, __shfl_xor_sync(~0u, m, 1)); m = fmaxf(m, __shfl_xor_sync(~0u, m, 2));
#pragma unroll
      for (int n = 0; n < 5; n++) {
        const float x = ex2((s[4 * n + 2 * hh] - m) * k2), y = ex2((s[4 * n + 2 * hh + 1] - m) * k2);
        const uint32_t w = pack2(x, y);
        l += x + y;
        pa[2 * n + hh] = second ? 0 : w; pa[10 + 2 * n + hh] = second ? w : 0;
      }
      l += __shfl_xor_sync(~0u, l, 1); l += __shfl_xor_sync(~0u, l, 2);
      inv[hh] = rcp(l);
    }
  }
  const uint32_t b2 = r.wait(5) + rows;
  float o[96] = {};
  reg_fence<96>(o);
  wg_fence();
#pragma unroll
  for (int u = 0; u < 3; u++) {
#pragma unroll
    for (int k = 0; k < 5; k++)
      wg_rs64_00(o + 32 * u, pa[4 * k], pa[4 * k + 1], pa[4 * k + 2], pa[4 * k + 3], mkdesc(u ? b2 : b1, 1024, 128, 0) + (~u & 1) * (KV_PART / 16) + k * 128, k);
    wg_commit();
  }
#pragma unroll
  for (int u = 0; u < 3; u++) {
    if (u == 0) wg_wait<2>(); else if (u == 1) wg_wait<1>(); else wg_wait<0>();
    reg_fence<32>(o + 32 * u);
    if (u != 1) r.release(r.seq - 2 + u / 2);
#pragma unroll
    for (int i = 0; i < 16; i++) { const float* x = &o[32 * u + 4 * (i & 7) + (i >> 2 & 2)]; q[16 * u + i] = pack2(x[0] * inv[i >> 3], x[1] * inv[i >> 3]); }
    if (now) {
#pragma unroll
      for (int i = 0; i < 4; i++) pend.store(4 * u + i);
    }
  }
}

__device__ __forceinline__ void ln_groups(Ring& ring, uint32_t scratch, int planes, int rg, bool two) {
  constexpr int G = 2;
  const int warp = fresh_tid() >> 5, lane = fresh_tid() & 31;
  const uint32_t id = (lane >> 3) == (lane & 3) ? ((lane & 4) ? 0x3f800000u : 0x00003f80u) : 0u;
  const uint32_t at = (warp * 160 + lane) * 8, at1 = planes > 1 ? at : (lane >> 2) * 1280 + warp * 160 + (lane & 3) * 4;
  const uint32_t step = planes > 1 ? 256 : 32, half = planes > 1 ? 4 : 16;
  float v[G][5][4] = {};
#pragma unroll
  for (int r = 0; r < G; r++) {
#pragma unroll 1
    for (int k = r && !two ? 0 : planes; k > 0; k -= 4) {
      const uint32_t a = ring.wait(min(k, 4) + 1);
      if (k == 1) {
#pragma unroll
        for (int i = 0; i < 5; i++) mma8(v[r][i], lds32(a + at1 + i * step), lds32(a + at1 + i * step + half), id);
      } else {
#pragma unroll
        for (int i = 0; i < 10; i++) {
          if (i == 5 && k < 4) break;
          const uint2 x = lds64(a + at + i / 5 * 20480 + i % 5 * 256), y = lds64(a + at + i / 5 * 20480 + 10240 + i % 5 * 256);
          mma16(v[r][i % 5], x.x, x.y, y.x, y.y, id, id);
        }
      }
      ring.release(ring.seq - 1);
    }
  }
  uint2 xr[G][5];
  float mw[G];
  scratch += (lane >> 2) * 64;
#pragma unroll
  for (int r = 0; r < G; r++) {
    float m = 0.f, q2[4] = {};
#pragma unroll
    for (int i = 0; i < 5; i++) {
      float* t = v[r][i];
      xr[r][i] = make_uint2(pack2(t[0], t[1]), pack2(t[2], t[3]));
      t[0] = bf_lo(xr[r][i].x); t[1] = bf_hi(xr[r][i].x); t[2] = bf_lo(xr[r][i].y); t[3] = bf_hi(xr[r][i].y);
      m += (t[0] + t[1]) + (t[2] + t[3]);
    }
    m += __shfl_xor_sync(~0u, m, 1); m += __shfl_xor_sync(~0u, m, 2);
    m *= 1.f / 80;
#pragma unroll
    for (int i = 0; i < 20; i++) { float& t = v[r][i >> 2][i & 3]; t -= m; q2[i & 3] = fmaf(t, t, q2[i & 3]); }
    float q = (q2[0] + q2[1]) + (q2[2] + q2[3]);
    mw[r] = m;
    q += __shfl_xor_sync(~0u, q, 1); q += __shfl_xor_sync(~0u, q, 2);
    if ((lane & 3) == 0) sts64f(scratch + r * 512 + warp * 8, m, q);
  }
  bar_sync(1, 256);
#pragma unroll
  for (int r = 0; r < G; r++) {
    const float4 t = lds128f(scratch + r * 512 + (lane & 3) * 16);
    float mean = t.x + t.z;
    mean += __shfl_xor_sync(~0u, mean, 1); mean += __shfl_xor_sync(~0u, mean, 2);
    mean *= 0.125f;
    float var = (t.y + t.w) + 80.f * ((t.x - mean) * (t.x - mean) + (t.z - mean) * (t.z - mean));
    var += __shfl_xor_sync(~0u, var, 1); var += __shfl_xor_sync(~0u, var, 2);
    float rs;
    asm("rsqrt.approx.ftz.f32 %0, %1;" : "=f"(rs) : "f"(var * (1.f / DM) + 1e-5f));
#pragma unroll
    for (int i = 0; i < 20; i++) v[r][i >> 2][i & 3] = fmaf(v[r][i >> 2][i & 3], rs, (mw[r] - mean) * rs);
  }
#pragma unroll
  for (int r = 0; r < G; r++) {
    if (r && !two) break;
    uint32_t* xn = g_xn + (rg + r) * 2560 + warp * 320 + lane;
#pragma unroll
    for (int i = 0; i < 10; i++) xn[i * 32] = pack2(v[r][i >> 1][2 * (i & 1)], v[r][i >> 1][2 * (i & 1) + 1]);
#pragma unroll
    for (int i = 0; i < 5; i++) g_x[(rg + r) * 17 * 1280 + warp * 160 + i * 32 + lane] = xr[r][i];
  }
}

__device__ __forceinline__ void store_partial(const float* d, int b, int split, int unit, int nu) {
  uint2* dst = g_x + (((b * 16 + (fresh_tid() >> 5) * 2) * 17 + 1 + split) * 40 + unit) * 32 + (fresh_tid() & 31);
#pragma unroll
  for (int u = 0; u < 20; u++) {
    if (u == 10 && nu == 10) break;
    dst[u * 32] = make_uint2(pack2(d[8 * u], d[8 * u + 1]), pack2(d[8 * u + 4], d[8 * u + 5]));
    dst[(680 + u) * 32] = make_uint2(pack2(d[8 * u + 2], d[8 * u + 3]), pack2(d[8 * u + 6], d[8 * u + 7]));
  }
}

__device__ __forceinline__ void store_bqkv(const float* d, int b, int idx, int nh) {
  const int lane = fresh_tid() & 31, c = lane & 3, rg = b * 16 + (fresh_tid() >> 5) * 2, h0 = idx * nh;
  const float sc = h0 < 32 ? 0.22360679775f * 1.44269504089f : 1.f;
  const bool lo = c < 2;
  uint32_t* da = g_bqkv + (h0 * 256 + rg) * 96 + lane;
  uint32_t* db = da + 256 * 96 + (lo ? 2 : -2);
  uint32_t pad[2];
#pragma unroll
  for (int r = 0; r < 2; r++) pad[r] = !(c & 1) && (h0 >= 64 || (h0 >= 32 && (lane & 4) && poly_group(rg + r))) ? 0x00003f80u : 0u;
#pragma unroll
  for (int q = 0; q < 8; q++) {
    if ((q == 2 || q == 4) && nh == 2 * q) break;
#pragma unroll
    for (int r = 0; r < 2; r++) {
      uint32_t w[5];
#pragma unroll
      for (int i = 0; i < 5; i++) w[i] = pack2(d[20 * q + 4 * i + 2 * r] * sc, d[20 * q + 4 * i + 2 * r + 1] * sc);
      const int o = q * 2 * 256 * 96 + r * 96;
      da[o] = w[0]; da[o + 32] = w[1]; da[o + 64] = lo ? w[2] : pad[r];
      db[o] = lo ? w[3] : w[2]; db[o + 32] = lo ? w[4] : w[3]; db[o + 64] = lo ? pad[r] : w[4];
    }
  }
}

__device__ __forceinline__ void work_loader(const WorkParams& p, const uint32_t sb, const bool weights) {
  const uint32_t bars = sb + WK_BAR, bIF = bars + 128, bIE = bars + 160, bGo = bars + 224, slots = bars + 272;
  int pos = 0, seq = 0, tail = 0, used = 0;
  uint32_t lens = 0;
  const bool one = elect();
  if (p.kind == WK_CHAIN) {
    seq = 1; used = lens = 8;
    if (one) mbar_arrive(bars);
  }
  for (int n = 0;; n++) {
    mbar_wait(bIF + 8 * (n & 3), (n >> 2) & 1);
    const int code = __shfl_sync(~0u, (int)lds32(slots + 4 * (n & 3)), 0);
    if (code < 0) break;
    const int type = (code >> 16) & 15, b = (code >> 8) & 255, idx = code & 255;
    if (one) mbar_arrive(bIE + 8 * (n & 3));
    const bool qa = type == IT_ATT && b < p.qa_end, ln = type == IT_FIN || type == IT_LN || type == IT_LN0;
    const int parts = ln ? item_groups(type, b) : type == IT_ATT ? 2 : 1;
#pragma unroll 1
    for (int part = 0; part < parts; part++) {
      int bytes = 163840, chunk = 40960, nb = 0, flag = b * 8 + 4 + type, need = item_need(type & 3, b), c0 = 0, c3 = idx, c4 = 0, step = 64;
      const uint8_t* src = g_kv + (b * 32 + idx) * 6 * KV_PART;
      const CUtensorMap* m = nullptr;
      if (ln) {
        const int rg = b * 16 + idx * parts + part;
        bytes = (type == IT_FIN ? op_split(b) + 1 : type == IT_LN ? 2 : 1) * 10240;
        src = type == IT_LN0 ? reinterpret_cast<const uint8_t*>(p.x) + rg * 10240 : reinterpret_cast<const uint8_t*>(g_x) + rg * 174080;
        if (type == IT_LN) { flag = SY_P + b * 4; need = 2; }
        if (type == IT_LN0 || part) need = 0;
      } else if (part) {
        bytes = 6 * KV_PART;
      } else if (type == IT_ATT && !qa) {
        bytes = chunk = 49152;
        src = reinterpret_cast<const uint8_t*>(g_q) + (b * 32 + idx) * 49152;
        flag = SY_P + b * 4 + 3; need = 32;
      } else {
        const int cols = item_cols(type, b);
        chunk = 16384; nb = (cols + 63) >> 6;
        src = reinterpret_cast<const uint8_t*>(g_of) + b * 163840;
        if (type == IT_OP) {
          const int nkb = op_steps(b), kb0 = (idx >> op_tiles(b) / 2) * nkb;
          bytes = nkb * 16384;
          src = reinterpret_cast<const uint8_t*>(g_o) + (b * 96 + kb0) * 16384;
          if (weights) m = &p.wo;
          c0 = (idx & (op_tiles(b) - 1)) * cols; c3 = 0; c4 = kb0 * 2; step = 2;
        } else if (type == IT_BQ) {
          m = weights ? &p.wb[cols >> 7] : &p.xn;
        } else if (type == IT_BO || type == IT_OUT) {
          if (weights) m = &p.wc[cols >> 8];
          flag = SY_OB; need = type == IT_BO && b < 2 ? 32 : -1;
        } else {
          m = weights ? &p.wq : &p.xn;
          flag = SY_P + b * 4 + 1; need = ln_items(p.ch.layer, b);
        }
      }
      if (!weights) {
        c3 = b * 16;
        if (need < 0) pdl_wait(); else if (need) wait_count(p.sync + flag, need);
        if ((ln ? !part : part && (!qa || (code & C_EARLY))) && one) mbar_arrive(bGo);
      }
      const int boxes = weights ? nb : m != nullptr;
#pragma unroll 1
      for (; bytes > 0; bytes -= chunk) {
        const int now = min(bytes, chunk), len = ((now + 8191) >> 13) + nb, skip = pos + len > WK_SLOTS ? WK_SLOTS - pos : 0, sh = 4 * (seq & 7);
        used += len + skip;
        while (used > WK_SLOTS || seq - tail >= 8) {
          mbar_wait(bars + 64 + 8 * (tail & 7), (tail >> 3) & 1);
          used -= (lens >> 4 * (tail & 7)) & 15;
          tail++;
        }
        lens = (lens & ~(15u << sh)) | (len + skip) << sh;
        if (pos + len > WK_SLOTS) pos = 0;
        const uint32_t bar = bars + 2 * sh, dst = sb + pos * 8192 + weights * 16384;
        if (one) mbar_expect(bar, weights ? nb * 8192 : now);
#pragma unroll 1
        for (int i = 0; i < boxes; i++)
          if (one) tma_load5(dst + i * 8192, m, c0 + i * 64, c3, c4, bar);
        if (!weights && !m && one) bulk_load_last(dst, src, now, bar);
        if (weights) c4 += step; else c0 += 128;
        src += chunk; pos += len; seq++;
      }
    }
  }
}

__global__ void __launch_bounds__(384, 1) work_kernel(const __grid_constant__ WorkParams p) {
  extern __shared__ __align__(1024) uint8_t smem_raw[];
  const uint32_t sb = s2u(smem_raw), bars = sb + WK_BAR;
  const uint32_t bIF = bars + 128, bIE = bars + 160, done = bars + 192, bGo = bars + 224, slots = bars + 272, scratch = bars + 384;
  const int warp = __shfl_sync(~0u, threadIdx.x >> 5, 0);
  uint32_t* const sync = p.sync;
  TRACE(0);
  pdl_launch();
  if (p.kind == WK_LEAD && !helper_sm() && __syncthreads_or(threadIdx.x == 0 && ldg_strong32(sync + SY_PRE + 1) >= LEAD1)) { pdl_wait(); return; }
  if (p.kind == WK_CHAIN) {
    chain_start(p.ch, sb, warp);
  } else {
    if (warp < 4) work_init(sb, warp);
    __syncthreads();
    if (p.kind == WK_FIRST) {
      if (!(warp & 13)) probe_slots(bars + 320);
      if (!helper_sm()) return;
    }
  }
  if (warp >= 8) {
    asm volatile("setmaxnreg.dec.sync.aligned.u32 40;");
    if (p.kind == WK_CHAIN) chain_comm(p.ch, sb, &p.wo);
    const int warp = __shfl_sync(~0u, fresh_tid() >> 5, 0), lane = fresh_tid() & 31;
    if (warp == 9) {
      const bool keep = p.kind > WK_LEAD || helper_sm();
      int n = 0, code = p.kind == WK_CHAIN ? reserved_item(blockIdx.x) : -1;
      if (code >= 0) {
        if (lane == 0) { sts32(slots, code); mbar_arrive(bIF); }
        n = 1;
      }
      const int b = lane & 15, layer = p.kind == WK_LAST ? 2 : sync != g_sync;
      bool first = layer == 1, lead = p.kind != WK_CHAIN;
      for (;; n++) {
        if (n > 0) mbar_wait(bGo, (n - 1) & 1);
        mbar_wait(bIE + 8 * (n & 3), ((n >> 2) & 1) ^ 1);
        code = -1;
        if (lead) {
          int i = blockIdx.x + n * 256;
          if (first) { if (lane == 0) i = atomicAdd(sync + SY_PRE + 1, 1); i = __shfl_sync(~0u, i, 0); first = i < LEAD1; }
          if (layer < 2 && !first) {
            if (lane == 0) i = keep ? atomicAdd(sync + SY_PRE, 1) + layer * LEAD1 : 1 << 20;
            i = __shfl_sync(~0u, i, 0);
            if (!keep) pdl_wait();
          }
          code = lead_item(layer, p.qa_end, i);
          lead = code >= 0 || layer == 2 || !keep;
          if (!lead && p.kind <= WK_LEAD) {
            const uint32_t t0 = gtime();
            while (!lead && __all_sync(~0u, ldg_strong32(sync + SY_UP) < 96)) lead = __any_sync(~0u, gtime() - t0 > 20000);
          }
        }
        if (!lead) {
          int spin = 0, ticket = 0;
          if (lane == 0) ticket = atomicAdd(sync + SY_T, 1);
          for (;;) {
            const uint4 hd = ldg_strong128(sync + b * 8), pr = ldg_strong128(sync + b * 8 + 4);
            const uint32_t hv[4] = {hd.x, hd.y, hd.z, hd.w}, pv[4] = {pr.x, pr.y, pr.z, pr.w};
            const uint32_t chain_done = __ballot_sync(~0u, (pr.x & 0xffff) >= 96) | (p.kind == WK_CHAIN) << 15;
            int left[4], avail[4], rdy = 0, claimed = 0, upstream = 0;
#pragma unroll
            for (int t = 0; t < 4; t++) {
              const int cnt = lane < 16 && !reserved(t, b) ? item_count(t, b) : 0;
              left[t] = max(cnt - (int)hv[t], 0);
              claimed += cnt - left[t];
              const bool ready = (pv[t] & 0xffff) >= item_need(t, b);
              rdy |= ready << t;
              bool ok = ready || (t != IT_ATT && (chain_done >> 15 & 1) && !left[t - 1] && (t < 2 || !left[t - 2]));
              if (t == IT_BQ && (chain_done >> HOLD_B & 1) && !(chain_done >> 15 & 1)) ok = false;
              avail[t] = ok ? left[t] : 0;
              upstream |= __any_sync(~0u, left[t] > 0);
            }
            if (!upstream) { code = -1; break; }
            int rank = max(__shfl_sync(~0u, ticket, 0) - __reduce_add_sync(~0u, claimed), 0), type = -1, mine = 0;
#pragma unroll
            for (int c = 0; c < 7; c++) {
              const int t = c == 0 || c == 6 ? IT_ATT : c == 1 || c == 4 ? IT_FIN : c == 2 ? IT_OP : IT_BQ;
              int a = c == 2 || (rdy >> t & 1) == (c < 4) ? avail[t] : 0;
              if (c == 6) a = b < p.qa_end && !(rdy & 1) && ((chain_done << 1 | 1) >> b & 1) ? left[t] : 0;
              const int tot = __reduce_add_sync(~0u, a);
              if (type < 0) { if (rank < tot) { type = t; mine = a; } else rank -= tot; }
            }
            if (type >= 0) {
#pragma unroll
              for (int o = 1; o < 16; o <<= 1) { const int y = __shfl_up_sync(~0u, mine, o); if (lane >= o) mine += y; }
              const int blk = __ffs(__ballot_sync(~0u, mine > rank)) - 1;
              const int early = !(__shfl_sync(~0u, rdy, blk) >> type & 1);
              uint32_t idx = 0;
              if (lane == 0) idx = atomicAdd(sync + blk * 8 + type, 1);
              idx = __shfl_sync(~0u, idx, 0);
              if (idx < item_count(type, blk)) { code = (chain_done >> 14 & 1) << 22 | early << 20 | type << 16 | blk << 8 | idx; break; }
            } else {
              __nanosleep(50);
            }
            spin_guard(spin);
          }
        }
        if (lane == 0) {
          sts32(slots + 4 * (n & 3), code);
          mbar_arrive(bIF + 8 * (n & 3));
        }
        __syncwarp();
        if (code < 0) break;
      }
    } else if (warp >= 10) {
      work_loader(p, sb, warp == 10);
    } else {
      for (int n = 0;; n++) {
        mbar_wait(bIF + 8 * (n & 3), (n >> 2) & 1);
        const int code = __shfl_sync(~0u, (int)lds32(slots + 4 * (n & 3)), 0);
        if (code < 0) break;
        const int type = (code >> 16) & 15, b = (code >> 8) & 255;
        mbar_wait(done + 8 * (n & 3), (n >> 2) & 1);
        if (elect()) {
          if (type != IT_OUT) red_release(sync + (type < IT_BQ ? b * 8 + 5 + type : SY_P + b * 4 + ((0x13102 >> 4 * (type - IT_BQ)) & 3)), 1);
          mbar_arrive(bIE + 8 * (n & 3));
        }
        __syncwarp();
      }
    }
  } else {
    asm volatile("setmaxnreg.inc.sync.aligned.u32 232;");
    if (p.kind == WK_CHAIN) chain_compute(p.ch, sb);
    const int warp = __shfl_sync(~0u, fresh_tid() >> 5, 0), lane = fresh_tid() & 31;
    Ring r{sb, 0, p.kind == WK_CHAIN};
    Pending pend = {};
    int nln = 0;
    auto projects = [&](int n) {
      uint32_t here;
      asm volatile("{.reg .pred p; mbarrier.test_wait.parity.shared::cta.b64 p, [%1], %2; vote.sync.all.pred p, p, 0xffffffff; selp.u32 %0, 1, 0, p;}" : "=r"(here) : "r"(bIF + 8 * (n & 3)), "r"((n >> 2) & 1) : "memory");
      if (!here) return false;
      const int code = __shfl_sync(~0u, (int)lds32(slots + 4 * (n & 3)), 0);
      return code >= 0 && (((code >> 16) & 15) == IT_Q || (((code >> 16) & 15) == IT_ATT && ((code >> 8) & 255) < p.qa_end));
    };
#pragma unroll 1
    for (int n = 0;; n++) {
      if (pend.done && !projects(n)) pend.flush();
      mbar_wait(bIF + 8 * (n & 3), (n >> 2) & 1);
      const int code = __shfl_sync(~0u, (int)lds32(slots + 4 * (n & 3)), 0);
      if (code < 0) { TRACE(2); break; }
      const int type = (code >> 16) & 15, b = (code >> 8) & 255, idx = code & 255;
      const uint32_t go = (code & C_LATE) || (type == IT_ATT && (code & C_EARLY)) ? 0 : bGo;
      ITEM(code & 0xfffff, 0);
      if (type == IT_ATT || type == IT_Q) {
        if (type == IT_Q || b < p.qa_end) {
          float d[96] = {};
          reg_fence<96>(d);
          ITEM(9 << 16 | (code & 0xffff), 0);
          gemm_item<192>(d, r, 10, go, 4, pend);
          ITEM(9 << 16 | (code & 0xffff), 1);
#pragma unroll
          for (int i = 0; i < 48; i++) pend.w[i] = pack2(d[2 * i], d[2 * i + 1]);
        } else {
          const uint32_t base = r.wait(6) + warp * 2048 + lane * 16;
#pragma unroll
          for (int i = 0; i < 12; i++) {
            const uint4 t = lds128(base + (i >> 2) * 16384 + (i & 3) * 512);
            pend.w[4 * i] = t.x; pend.w[4 * i + 1] = t.y; pend.w[4 * i + 2] = t.z; pend.w[4 * i + 3] = t.w;
          }
          __syncwarp();
          r.release(r.seq - 1);
        }
        const bool now = type == IT_ATT && !projects(n + 1);
        if (type == IT_Q) {
          pend.dst = g_q + (b * 32 + idx) * 3072 + warp * 128 + lane;
        } else {
          pend.dst = g_o + (b * 32 + idx) * 3072 + warp * 128 + (lane & 3) * 8 + (lane >> 2);
          attn_a(r, pend, now, warp);
        }
        pend.done = done + 8 * (n & 3);
        if (now) pend.finish();
      } else {
        if (type == IT_FIN || type == IT_LN || type == IT_LN0) {
          const int ng = item_groups(type, b);
          const int planes = type == IT_FIN ? op_split(b) + 1 : type == IT_LN ? 2 : 1;
#pragma unroll 1
          for (int i = 0; i < ng; i += 2) ln_groups(r, scratch + (nln++ & 1) * 1024, planes, b * 16 + idx * ng + i, ng > 1);
        } else {
          const int cols = item_cols(type, b), nkb = type == IT_OP ? op_steps(b) : 10;
          float d[160] = {};
          if (type == IT_OUT) {
            const uint2* x = g_x + ((b * 16 + warp * 2) * 680 + idx * 5) * 32 + lane;
#pragma unroll
            for (int i = 0; i < 10; i++) { const uint2 y = __ldcg(x + (i / 5 * 680 + i % 5) * 32); d[40 + 2 * i] = __uint_as_float(y.x); d[41 + 2 * i] = __uint_as_float(y.y); }
          }
          reg_fence<160>(d);
          if (type != IT_OUT) ITEM((type == IT_BQ ? 10 : 11) << 16 | (code & 0xffff), 0);
          const int ask = max(nkb - ((code & C_TAIL ? GO_TAIL : GO_320) << (2 - (cols >> 7))), 0);
          if (cols == 320) gemm_item<320>(d, r, nkb, go, ask, pend);
          else if (cols == 160) gemm_item<160>(d, r, nkb, go, ask, pend);
          else gemm_item<80>(d, r, nkb, go, ask, pend);
          if (type != IT_OUT) ITEM((type == IT_BQ ? 10 : 11) << 16 | (code & 0xffff), 1);
          reg_fence<160>(d);
          if (type == IT_OUT) {
            bar_sync(1, 256);
            const uint32_t dst = sb + (warp * 16 + (lane & 15)) * 160 + (lane >> 4) * 16;
#pragma unroll
            for (int u = 0; u < 5; u++) {
              uint32_t w[4];
#pragma unroll
              for (int i = 0; i < 4; i++) { const uint32_t y = __float_as_uint(d[40 + (i & 1) * 10 + 2 * u + (i >> 1)]); w[i] = pack2(bf_lo(y) + d[8 * u + 2 * i], bf_hi(y) + d[8 * u + 2 * i + 1]); }
              stsm4(dst + u * 32, w[0], w[1], w[2], w[3]);
            }
            fence_async();
            __syncwarp();
            if (elect()) { tma_store(&p.out, sb + warp * 2560, idx * 80, b * 128 + warp * 16); bulk_commit(); bulk_wait<0>(); }
          } else {
            if (warp >= 4) bar_sync(7, 256);
            if (type == IT_BQ) store_bqkv(d, b, idx, 4 << (cols >> 7));
            else store_partial(d, b, cols == 320 ? idx >> 1 : idx >> 2, cols == 320 ? (idx & 1) * 20 : (idx & 3) * 10, cols >> 4);
            if (warp < 4) bar_arrive(7, 256);
          }
        }
        __syncwarp();
        if (elect()) mbar_arrive(done + 8 * (n & 3));
#pragma unroll
        for (int i = 0; i < 48; i++) pend.w[i] = 0;
      }
      if ((code & C_LATE) && warp == 4 && elect()) mbar_arrive(bGo);
      ITEM(code & 0xfffff, 1);
    }
  }
}

constexpr int AB_SMEM = 1024 + 2 * 98304 + 256;
#define AB_N 32
#define AB_WG 4
constexpr int AB_T = AB_WG * 128, AB_PASS = 8 / AB_WG;
__device__ __forceinline__ float ex2_poly(float t) {
  const uint32_t r = __float_as_uint(t) & 0xffff8000u;
  const float f = t - __uint_as_float(r);
  const float p = fmaf(fmaf(fmaf(-5.869912678e-38f, f, -1.700740250e-37f), f, -5.234869734e-37f), f, -7.522601252e-37f);
  uint32_t y;
  asm("mad.lo.u32 %0, %1, 256, %2;" : "=r"(y) : "r"(r), "r"(__float_as_uint(p)));
  return __uint_as_float(y);
}
__device__ __forceinline__ uint32_t hsq(uint32_t w, uint32_t c) { uint32_t r; asm("fma.rn.bf16x2 %0, %1, %1, %2;" : "=r"(r) : "r"(w), "r"(c)); return r; }
__device__ __forceinline__ float sq2(uint32_t w) { const float a = bf_lo(w), b = bf_hi(w); return fmaf(a, a, b * b); }

__device__ __forceinline__ void attn_b_store(const float* o, int h, int row0, int lane) {
  const int g = lane >> 2, c = lane & 3;
  const float i0 = rcp(__shfl_sync(~0u, o[8], (lane & ~3) | 2)), i1 = rcp(__shfl_sync(~0u, o[10], (lane & ~3) | 2));
#pragma unroll
  for (int jj = 0; jj < 3; jj++) {
    if (jj < 2 || c < 2) {
      const int col = h * 20 + 8 * jj + 2 * c;
      g_of[core_word(row0 + g, col)] = pack2(o[4 * jj] * i0, o[4 * jj + 1] * i0);
      g_of[core_word(row0 + g + 8, col)] = pack2(o[4 * jj + 2] * i1, o[4 * jj + 3] * i1);
    }
  }
}

__device__ __forceinline__ void attn_b_qk(float* s, uint32_t q0, uint32_t q1, uint32_t q2, uint32_t q3, uint32_t q4, uint32_t q5, uint32_t z0, uint32_t z1,
                                          uint64_t dk, uint64_t dk2) {
  wg_rs32_00(s, q0, q1, q2, q3, dk, 0);
  wg_rs32_00(s, q4, q5, z0, z1, dk2, 1);
}

struct AttnParams { const uint8_t* pf[4]; uint32_t *sync, *next; };
__global__ void __launch_bounds__(AB_T + 128, 1) attn_b_kernel(const __grid_constant__ AttnParams p) {
  extern __shared__ uint8_t smem_raw[];
  const uint32_t sb = (s2u(smem_raw) + 1023) & ~1023u, sK = sb, sV = sb + 98304, bars = sb + 2 * 98304;
  const int warp = __shfl_sync(~0u, threadIdx.x >> 5, 0), lane = threadIdx.x & 31;
  const int h = blockIdx.x & 31, quarter = blockIdx.x >> 5;
  BT(0);
  TRACE(0);
  if (warp < 10 && elect()) {
    mbar_init(bars + 8 * warp + (warp & 8) * 8, warp < 8 ? 1 : warp == 8 ? AB_T / 32 : 2);
    asm volatile("fence.mbarrier_init.release.cluster;" ::: "memory");
  }
  __syncthreads();
  if (warp >= AB_T / 32) {
    asm volatile("setmaxnreg.dec.sync.aligned.u32 32;");
    if (warp == AB_T / 32 + 1) return;
    if (warp > AB_T / 32) {
      uint32_t kmax = 0;
#pragma unroll 1
      for (int i = 0; i < 32; i++) {
        if (!(i & 3)) mbar_wait(bars + 2 * i, 0);
        const uint32_t a = sK + i * 3072 + ((threadIdx.x >> 3) & 7) * 384 + (lane & 7) * 16;
        const uint4 x = lds128(a), y = lds128(a + 128);
        const uint2 z = lds64(a + 256);
        const uint32_t n = hadd2(hsq(x.x, hsq(x.y, hsq(x.z, hsq(x.w, hsq(z.x, 0))))), hsq(y.x, hsq(y.y, hsq(y.z, hsq(y.w, hsq(z.y, 0))))));
        kmax = max(kmax, __float_as_uint(bf_lo(n) + bf_hi(n)) & 0x7fffffffu);
      }
      const uint32_t kbits = __reduce_max_sync(~0u, kmax);
      if (lane == 0) { sts32(bars + 64 + (warp & 1) * 4, kbits); mbar_arrive(bars + 136); }
      return;
    }
    const uint8_t* gk = reinterpret_cast<const uint8_t*>(g_bqkv + (32 + h) * 256 * 96);
    const uint8_t* gv = reinterpret_cast<const uint8_t*>(g_bqkv + (64 + h) * 256 * 96);
    uint32_t todo = 255;
    for (int spin = 0; todo;) {
      const uint32_t up = __ballot_sync(~0u, ld_acquire(p.sync + SY_P + (lane & 15) * 4 + 2) >= bq_items(lane & 15));
      fence_async_global();
#pragma unroll 1
      for (int i = 0; i < 8; i++) {
        if (!(todo >> i & 1) || (up >> 2 * i & 3) != 3) continue;
        todo &= ~(1u << i);
        if (elect()) {
          mbar_expect(bars + 8 * i, 24576);
          bulk_load(sK + i * 12288, gk + i * 12288, 12288, bars + 8 * i);
          bulk_load(sV + i * 12288, gv + i * 12288, 12288, bars + 8 * i);
        }
      }
      spin_guard(spin);
    }
    pdl_launch();
    TRACE(1);
#pragma unroll 1
    for (int i = lane; i < 512 && blockIdx.x < NSLOT; i += 32) reinterpret_cast<uint4*>(pool_at(blockIdx.x * 8192))[i] = make_uint4(0, 0, 0, 0);
    if (!p.next && blockIdx.x < 8) { const int i = blockIdx.x * 32 + lane; g_smpart[i] = 0; if (i < NSLOT) g_orient[i] = 0; }
    if (p.next) {
      mbar_wait(bars + 128, 0);
      if (quarter == 0 && lane == 0) red_release(p.next + SY_OB, 1);
#pragma unroll 1
      for (int i = 0; i < (PF_NS ? 32 : 0); i++) {
        if (elect()) prefetch_l2(p.pf[i >> 3] + blockIdx.x * 61440 + (i & 7) * 7680, 7680);
        __nanosleep(PF_NS);
      }
    }
    return;
  }
  asm volatile("setmaxnreg.inc.sync.aligned.u32 112;");
  constexpr int NT = SEQ / AB_N, PER = 256 / AB_N;
  uint32_t qn[8];
  auto load_q = [&](int pass) {
    const uint32_t* gq = g_bqkv + (h * 256 + pass * 128 + quarter * 32 + warp * 2) * 96 + lane;
#pragma unroll
    for (int i = 0; i < 8; i++) qn[i] = __ldcg(gq + (i & 1) * 96 + min(i >> 1, 2) * 32 + (i < 6 ? 0 : 3 - (lane & 3)));
  };
  mbar_wait(bars + 8 * quarter, 0);
  load_q(0);
#pragma unroll 1
  for (int pass = 0; pass < AB_PASS; pass++) {
    const int row0 = pass * 1024 + quarter * 256 + warp * 16;
    const uint32_t q0 = qn[0], q1 = qn[1], q2 = qn[2], q3 = qn[3], z0 = qn[6], z1 = qn[7];
    uint32_t q4 = qn[4], q5 = qn[5];
    if ((lane & 3) == 2) { q4 = 0x43BCu; q5 = 0x43BCu; }
    float o[12];
    uint64_t dk = mkdesc(sK, 128, 384, 0), dk2 = mkdesc(sK + 256, 0, 384, 0), dv = mkdesc(sV, 384, 128, 0);
    float sa[AB_N / 2], sb2[AB_N / 2];
    uint32_t pa[AB_N / 4], pb[AB_N / 4];
    if (pass == 0) mbar_wait(bars, 0);
    BT(1 + 2 * pass);
    wg_fence();
    attn_b_qk(sa, q0, q1, q2, q3, q4, q5, z0, z1, dk, dk2);
    wg_commit();
    attn_b_qk(sb2, q0, q1, q2, q3, q4, q5, z0, z1, dk + AB_N * 3, dk2 + AB_N * 3);
    wg_commit();
#pragma unroll 1
    for (int kt = 0; kt < NT; kt += 2) {
      const int nx = kt + 2 < NT ? kt + 2 : 0;
      if (pass == 0 && (nx & (PER - 1)) == 0) mbar_wait(bars + 8 * (nx / PER), 0);
      const uint64_t nk = dk + nx * (AB_N * 3), nk2 = dk2 + nx * (AB_N * 3);
      wg_wait<1>();
      reg_fence<AB_N / 2>(sa);
#pragma unroll
      for (int i = 0; i < AB_N / 4; i++) pa[i] = pack2(ex2(sa[2 * i]), poly_group(i >> 1) ? ex2_poly(sa[2 * i + 1]) : ex2(sa[2 * i + 1]));
      wg_fence();
#pragma unroll
      for (int kk = 0; kk < AB_N / 16; kk++) wg_rs24_01(o, pa[4 * kk], pa[4 * kk + 1], pa[4 * kk + 2], pa[4 * kk + 3], dv + kk * 48, kk | kt);
      attn_b_qk(sa, q0, q1, q2, q3, q4, q5, z0, z1, nk, nk2);
      wg_commit();
      wg_wait<1>();
      reg_fence<AB_N / 2>(sb2);
#pragma unroll
      for (int i = 0; i < AB_N / 4; i++) pb[i] = pack2(ex2(sb2[2 * i]), poly_group((i >> 1) + AB_N / 8) ? ex2_poly(sb2[2 * i + 1]) : ex2(sb2[2 * i + 1]));
      wg_fence();
#pragma unroll
      for (int kk = 0; kk < AB_N / 16; kk++) wg_rs24_01(o, pb[4 * kk], pb[4 * kk + 1], pb[4 * kk + 2], pb[4 * kk + 3], dv + AB_N * 3 + kk * 48, 1);
      attn_b_qk(sb2, q0, q1, q2, q3, q4, q5, z0, z1, nk + AB_N * 3, nk2 + AB_N * 3);
      wg_commit();
      dv += AB_N * 6;
    }
    wg_wait<0>();
    reg_fence<12>(o); reg_fence<AB_N / 2>(sa); reg_fence<AB_N / 2>(sb2);
    BT(2 + 2 * pass);
    if (pass + 1 < AB_PASS) load_q(pass + 1);
    mbar_wait(bars + 136, 0);
    const uint2 kb = lds64(bars + 64);
    const float kmax = __uint_as_float(max(kb.x, kb.y));
    if ((lane & 3) == 2) q4 = q5 = 0;
    float n0 = sq2(q0) + sq2(q2) + sq2(q4), n1 = sq2(q1) + sq2(q3) + sq2(q5);
    n0 += __shfl_xor_sync(~0u, n0, 1); n1 += __shfl_xor_sync(~0u, n1, 1);
    n0 += __shfl_xor_sync(~0u, n0, 2); n1 += __shfl_xor_sync(~0u, n1, 2);
    uint32_t redo;
    asm volatile("{.reg .pred p, q; setp.ne.u32 p, %1, 0; bar.red.or.pred q, %2, 128, p; selp.u32 %0, 1, 0, q;}"
                 : "=r"(redo) : "r"((uint32_t)!(n0 * kmax <= 9500.f && n1 * kmax <= 9500.f)), "r"(2 + (warp >> 2)) : "memory");
    if (redo) {
#pragma unroll
      for (int i = 0; i < 12; i++) o[i] = 0.f;
      float m0 = -INFINITY, m1 = -INFINITY;
#pragma unroll 1
      for (int kt = 0; kt < 64; kt++) {
        float s[16];
        wg_fence();
        wg_rs32_00(s, q0, q1, q2, q3, dk + kt * 96, 0);
        wg_rs32_00(s, q4, q5, z0, z1, dk2 + kt * 96, 1);
        wg_commit();
        wg_wait<0>();
        reg_fence<16>(s); reg_fence<12>(o);
        float n0 = m0, n1 = m1;
#pragma unroll
        for (int jj = 0; jj < 4; jj++) { n0 = fmaxf(n0, fmaxf(s[4 * jj], s[4 * jj + 1])); n1 = fmaxf(n1, fmaxf(s[4 * jj + 2], s[4 * jj + 3])); }
        n0 = fmaxf(n0, __shfl_xor_sync(~0u, n0, 1)); n0 = fmaxf(n0, __shfl_xor_sync(~0u, n0, 2));
        n1 = fmaxf(n1, __shfl_xor_sync(~0u, n1, 1)); n1 = fmaxf(n1, __shfl_xor_sync(~0u, n1, 2));
        const float r0 = ex2(m0 - n0), r1 = ex2(m1 - n1);
        m0 = n0; m1 = n1;
#pragma unroll
        for (int jj = 0; jj < 3; jj++) { o[4 * jj] *= r0; o[4 * jj + 1] *= r0; o[4 * jj + 2] *= r1; o[4 * jj + 3] *= r1; }
        uint32_t pp[8];
#pragma unroll
        for (int jj = 0; jj < 4; jj++) {
          pp[2 * jj] = pack2(ex2(s[4 * jj] - m0), ex2(s[4 * jj + 1] - m0));
          pp[2 * jj + 1] = pack2(ex2(s[4 * jj + 2] - m1), ex2(s[4 * jj + 3] - m1));
        }
        reg_fence<12>(o);
        wg_fence();
#pragma unroll
        for (int kk = 0; kk < 2; kk++) wg_rs24_01(o, pp[4 * kk], pp[4 * kk + 1], pp[4 * kk + 2], pp[4 * kk + 3], mkdesc(sV, 384, 128, 0) + kt * 96 + kk * 48, 1);
        wg_commit();
      }
      wg_wait<0>();
      reg_fence<12>(o);
    }
    attn_b_store(o, h, row0, lane);
    __syncwarp();
    if (pass == 0 && lane == 0) mbar_arrive(bars + 128);
  }
  BT(5);
  TRACE(2);
}

typedef CUresult (*EncodeFn)(CUtensorMap*, CUtensorMapDataType, cuuint32_t, void*, const cuuint64_t*, const cuuint64_t*,
                             const cuuint32_t*, const cuuint32_t*, CUtensorMapInterleave, CUtensorMapSwizzle,
                             CUtensorMapL2promotion, CUtensorMapFloatOOBfill);

void make_map(EncodeFn enc, CUtensorMap* m, const void* ptr, int cols, int rows, int box_rows, int box_cols = 64) {
  const cuuint64_t dims[2] = {(cuuint64_t)cols, (cuuint64_t)rows};
  const cuuint64_t strides[1] = {(cuuint64_t)cols * 2};
  const cuuint32_t box[2] = {(cuuint32_t)box_cols, (cuuint32_t)box_rows}, es[2] = {1, 1};
  enc(m, CU_TENSOR_MAP_DATA_TYPE_BFLOAT16, 2, const_cast<void*>(ptr), dims, strides, box, es, CU_TENSOR_MAP_INTERLEAVE_NONE,
      box_cols == 64 ? CU_TENSOR_MAP_SWIZZLE_128B : box_cols == 32 ? CU_TENSOR_MAP_SWIZZLE_64B : CU_TENSOR_MAP_SWIZZLE_NONE, CU_TENSOR_MAP_L2_PROMOTION_L2_256B, CU_TENSOR_MAP_FLOAT_OOB_FILL_NONE);
}
void make_map5(EncodeFn enc, CUtensorMap* m, const void* ptr, bool words, const cuuint64_t (&dims)[5], const cuuint64_t (&strides)[4], const cuuint32_t (&box)[5]) {
  const cuuint32_t es[5] = {1, 1, 1, 1, 1};
  enc(m, words ? CU_TENSOR_MAP_DATA_TYPE_UINT64 : CU_TENSOR_MAP_DATA_TYPE_BFLOAT16, 5, const_cast<void*>(ptr), dims, strides, box, es, CU_TENSOR_MAP_INTERLEAVE_NONE,
      words ? CU_TENSOR_MAP_SWIZZLE_NONE : CU_TENSOR_MAP_SWIZZLE_128B, dims[0] % 64 ? CU_TENSOR_MAP_L2_PROMOTION_L2_128B : CU_TENSOR_MAP_L2_PROMOTION_L2_256B,
      CU_TENSOR_MAP_FLOAT_OOB_FILL_NONE);
}
void make_tiles(EncodeFn enc, CUtensorMap* m, const void* ptr, cuuint64_t cols, cuuint64_t tile) {
  make_map5(enc, m, ptr, false, {tile, 1, 1, cols / tile, DM}, {tile * 2, tile * 2, tile * 2, cols * 2}, {64, 1, 1, 1, 64});
}
template <class... KA, class... A>
void launch(void (*kern)(KA...), int grid, int block, int smem, int cluster, bool pdl, A... args) {
  cudaFuncSetAttribute(kern, cudaFuncAttributeMaxDynamicSharedMemorySize, smem);
  cudaLaunchConfig_t cfg = {};
  cfg.gridDim = dim3(grid); cfg.blockDim = dim3(block); cfg.dynamicSmemBytes = smem; cfg.stream = cudaStreamPerThread;
  cudaLaunchAttribute at[2];
  int n = 0;
  if (cluster > 1) { at[n].id = cudaLaunchAttributeClusterDimension; at[n].val.clusterDim.x = cluster; at[n].val.clusterDim.y = 1; at[n].val.clusterDim.z = 1; n++; }
  if (pdl) { at[n].id = cudaLaunchAttributeProgrammaticStreamSerialization; at[n].val.programmaticStreamSerializationAllowed = 1; n++; }
  cfg.attrs = at; cfg.numAttrs = n;
  cudaLaunchKernelEx(&cfg, kern, args...);
}
template <class T> void* sym(T& s) { void* p = nullptr; cudaGetSymbolAddress(&p, s); return p; }

}

#define MODE(b) 0
extern "C" void kernel_launch(void* const* d_in, const int* in_sizes, int n_in, void* d_out, int out_size) {
  const __nv_bfloat16* x = (const __nv_bfloat16*)d_in[0];
  void* fn = nullptr; cudaDriverEntryPointQueryResult qr;
  cudaGetDriverEntryPoint("cuTensorMapEncodeTiled", &fn, cudaEnableDefault, &qr);
  EncodeFn enc = (EncodeFn)fn;

  WorkParams wk = {};
  ChainParams& ch = wk.ch;
  AttnParams at = {};
  make_map(enc, &ch.wq, d_in[2], HD, DM, 160); make_map(enc, &ch.wk, d_in[3], HD, DM, 160); make_map(enc, &ch.wv, d_in[4], HD, DM, 160);
  make_map(enc, &ch.wo, d_in[5], DM, HD, 192, 32);
  ch.mem0 = (const __nv_bfloat16*)d_in[1];
  ch.wb = (const uint8_t*)d_in[8];
  ch.d1 = 250; ch.d2 = 200; ch.dn = 150; ch.dx = 950;
  make_tiles(enc, &wk.wq, d_in[2], HD, 192);
  for (int i = 0; i < 3; i++) make_tiles(enc, &wk.wb[i], d_in[8], 1920, 80 << i);
  for (int i = 0; i < 2; i++) make_tiles(enc, &wk.wc[i], d_in[9], DM, 80 << 2 * i);
  make_map(enc, &wk.out, d_out, DM, SEQ, 16, 80);
  make_map5(enc, &wk.wo, d_in[5], false, {DM, 2, 4, 4, HD / 32}, {DM * 2, DM * 16, DM * 4, DM * 64}, {64, 2, 4, 4, 2});
  make_map5(enc, &wk.xn, sym(g_xn), true, {1280, 1, 1, 256, 1}, {10240, 10240, 10240, 10240}, {128, 1, 1, 16, 1});
  make_map5(enc, &ch.xc, sym(g_xn), true, {160, 1, 1, 256, 8}, {1280, 1280, 10240, 1280}, {160, 1, 1, 4, 2});
  wk.x = x;
  for (int i = 0; i < 4; i++) at.pf[i] = (const uint8_t*)d_in[i < 2 ? 3 + i : i == 2 ? 2 : 5];
  int qa_end[2] = {12, 12};
  for (int layer = 0; layer < 2; layer++) {
    ch.sync = wk.sync = at.sync = (uint32_t*)sym(g_sync) + layer * SY_N;
    ch.other = (uint32_t*)sym(g_sync) + (1 - layer) * SY_N;
    ch.layer = layer;
    at.next = layer ? nullptr : ch.other;
    wk.qa_end = qa_end[layer];
    wk.kind = layer ? WK_LEAD : WK_FIRST;
    launch(work_kernel, 132, 384, CH_SMEM, 1, layer != 0, wk);
    wk.kind = WK_CHAIN;
    launch(work_kernel, 96, 384, CH_SMEM, 3, true, wk);
    launch(attn_b_kernel, 128, AB_T + 128, AB_SMEM, 1, true, at);
  }
  wk.kind = WK_LAST;
  launch(work_kernel, 128, 384, CH_SMEM, 1, true, wk);
}
```

```cpp
#include <cuda_runtime.h>
#include <cuda_bf16.h>
#include <cuda.h>
#include <stdint.h>
#include <stdlib.h>

namespace {

constexpr int SEQ = 2048, DM = 640, HD = 6144, NSEG = 64;
constexpr int SPIN_LIMIT = 1 << 20;

__device__ __align__(128) uint2 g_x[256 * 17 * 1280];
__device__ __align__(128) uint32_t g_xn[SEQ * DM / 2];
__device__ __align__(128) uint32_t g_of[SEQ * DM / 2];
__device__ __align__(128) uint4 g_o[SEQ * HD / 8];
__device__ __align__(128) uint4 g_q[SEQ * HD / 8];
constexpr int KV_M = 4096, KV_SEG = 5120, KV_PART = 20480, KV_V = 3 * KV_PART;
__device__ __align__(128) uint8_t g_kv[16 * 32 * 6 * KV_PART];
#define OP_B8 11
#define OP_B16 14
#define OP_N4 16
#define BQ_12 12
#define BQ_24 14
#define FIN_16 12
__host__ __device__ constexpr int op_split(int b) { return b < OP_B8 ? 4 : b < OP_B16 ? 8 : 16; }
__host__ __device__ constexpr int op_steps(int b) { return b < OP_B8 ? 24 : b < OP_B16 ? 12 : 6; }
__host__ __device__ constexpr int op_tiles(int b) { return b < OP_N4 ? 2 : 4; }
__host__ __device__ constexpr int fin_items(int b) { return b < OP_B8 ? 4 : b < FIN_16 ? 8 : 16; }
__host__ __device__ constexpr int bq_items(int b) { return b < BQ_12 ? 6 : b < BQ_24 ? 12 : 24; }
__host__ __device__ constexpr int ln_items(int layer, int b) { return layer == 0 && b < 2 ? 16 : 4; }
constexpr int SY_P = 128, SY_T = 192, SY_UP = 224, SY_OB = 225, SY_PRE = 256, SY_PART = 288, SY_TIME = 384, SY_N = 448;
__device__ __align__(128) uint32_t g_sync[2 * SY_N];
constexpr int NSLOT = 92;
__device__ uint32_t g_pool[(NSLOT + 2) * 2048];
__device__ uint32_t g_smpart[256], g_orient[NSLOT];
__device__ __align__(128) uint32_t g_bqkv[3 * 32 * 256 * 96];

#define BT(i)
#define MISS(k, n)
#define PRO(i)
#define TRACE(w)
#define ITEM(code, w)
#define STAT(k)
#define TMV(i, v)
#define TM(i)
#define TMD(i, dep)

__device__ __forceinline__ uint32_t gtime() { uint32_t c; asm volatile("mov.u32 %0, %%globaltimer_lo;" : "=r"(c) :: "memory"); return c; }
__device__ __forceinline__ uint32_t clk32() { uint32_t c; asm volatile("mov.u32 %0, %%clock;" : "=r"(c) :: "memory"); return c; }
__device__ __forceinline__ uint32_t fresh_tid() { uint32_t t; asm volatile("mov.u32 %0, %%tid.x;" : "=r"(t)); return t; }
__device__ __forceinline__ uint32_t s2u(const void* p) { return (uint32_t)__cvta_generic_to_shared(p); }
__device__ __forceinline__ uint32_t pack2(float a, float b) {
  uint32_t r; asm("cvt.rn.bf16x2.f32 %0, %1, %2;" : "=r"(r) : "f"(b), "f"(a)); return r; }
__device__ __forceinline__ float bf_lo(uint32_t w) { return __uint_as_float(w << 16); }
__device__ __forceinline__ float bf_hi(uint32_t w) { return __uint_as_float(w & 0xffff0000u); }
__device__ __forceinline__ float ex2(float x) { float y; asm("ex2.approx.ftz.f32 %0, %1;" : "=f"(y) : "f"(x)); return y; }

__device__ __forceinline__ void mbar_init(uint32_t bar, uint32_t n) {
  asm volatile("mbarrier.init.shared::cta.b64 [%0], %1;" :: "r"(bar), "r"(n) : "memory"); }
__device__ __forceinline__ void mbar_expect(uint32_t bar, uint32_t bytes) {
  asm volatile("mbarrier.arrive.expect_tx.shared::cta.b64 _, [%0], %1;" :: "r"(bar), "r"(bytes) : "memory"); }
__device__ __forceinline__ void mbar_arrive(uint32_t bar) {
  asm volatile("mbarrier.arrive.shared::cta.b64 _, [%0];" :: "r"(bar) : "memory"); }
#define ONE "{.reg .pred one; elect.sync _|one, 0xffffffff; @one "
__device__ __forceinline__ void mbar_arrive_one(uint32_t bar) { asm volatile(ONE "mbarrier.arrive.shared::cta.b64 _, [%0];}" :: "r"(bar) : "memory"); }
__device__ __forceinline__ void mbar_expect_one(uint32_t bar, uint32_t bytes) {
  asm volatile(ONE "mbarrier.arrive.expect_tx.shared::cta.b64 _, [%0], %1;}" :: "r"(bar), "r"(bytes) : "memory"); }
__device__ __forceinline__ uint32_t atomic_inc_one(uint32_t* p) {
  uint32_t v = 0; asm volatile(ONE "atom.relaxed.gpu.global.add.u32 %0, [%1], 1;}" : "+r"(v) : "l"(p) : "memory"); return v; }
__device__ __forceinline__ void mbar_arrive_remote(uint32_t bar) {
  asm volatile("mbarrier.arrive.shared::cluster.b64 _, [%0];" :: "r"(bar) : "memory"); }
__device__ __forceinline__ void mbar_wait(uint32_t bar, uint32_t ph) {
  asm volatile("{.reg .pred p; .reg .u32 n; mov.u32 n, 0;\n"
               "W: mbarrier.try_wait.parity.shared::cta.b64 p, [%0], %1; @p bra.uni D;\n"
               "add.u32 n, n, 1; setp.gt.u32 p, n, %2; @p trap; bra.uni W;\n"
               "D: }" :: "r"(bar), "r"(ph), "n"(SPIN_LIMIT) : "memory");
}
__device__ __forceinline__ bool elect() {
  uint32_t p; asm volatile("{.reg .pred q; elect.sync _|q, 0xffffffff; selp.u32 %0, 1, 0, q;}" : "=r"(p)); return p; }
__device__ __forceinline__ void spin_guard(int& n) {
  asm volatile("{.reg .pred p; add.s32 %0, %0, 1; setp.gt.s32 p, %0, %1; @p trap;}" : "+r"(n) : "n"(SPIN_LIMIT));
}
__device__ __forceinline__ void pdl_wait() { asm volatile("griddepcontrol.wait;" ::: "memory"); TRACE(1); }
__device__ __forceinline__ void pdl_launch() { asm volatile("griddepcontrol.launch_dependents;" ::: "memory"); }
__device__ __forceinline__ uint32_t ld_acquire(const uint32_t* p) { uint32_t v; asm volatile("ld.acquire.gpu.global.u32 %0, [%1];" : "=r"(v) : "l"(p) : "memory"); return v; }
__device__ __forceinline__ void red_release(uint32_t* p, uint32_t v) { asm volatile("red.release.gpu.global.add.u32 [%0], %1;" :: "l"(p), "r"(v) : "memory"); }
__device__ __forceinline__ void fence_async_global() { asm volatile("fence.proxy.async.global;" ::: "memory"); }
__device__ __forceinline__ void fence_async() { asm volatile("fence.proxy.async.shared::cta;" ::: "memory"); }
__device__ __forceinline__ void bar_sync(int id, int n) { asm volatile("bar.sync %0, %1;" :: "r"(id), "r"(n) : "memory"); }
__device__ __forceinline__ void bar_arrive(int id, int n) { asm volatile("bar.arrive %0, %1;" :: "r"(id), "r"(n) : "memory"); }
__device__ __forceinline__ void tma_load(uint32_t dst, const CUtensorMap* m, int c0, int c1, uint32_t bar) {
  asm volatile("cp.async.bulk.tensor.2d.shared::cluster.global.mbarrier::complete_tx::bytes [%0], [%1, {%3, %4}], [%2];"
               :: "r"(dst), "l"(m), "r"(bar), "r"(c0), "r"(c1) : "memory"); }
__device__ __forceinline__ void tma_load5_one(uint32_t dst, const CUtensorMap* m, int c0, int c3, int c4, uint32_t bar) {
  asm volatile(ONE "cp.async.bulk.tensor.5d.shared::cluster.global.mbarrier::complete_tx::bytes [%0], [%1, {%3, %6, %6, %4, %5}], [%2];}"
               :: "r"(dst), "l"(m), "r"(bar), "r"(c0), "r"(c3), "r"(c4), "r"(0) : "memory"); }
__device__ __forceinline__ void tma_store(const CUtensorMap* m, uint32_t src, int c0, int c1) {
  asm volatile("cp.async.bulk.tensor.2d.global.shared::cta.bulk_group [%0, {%2, %3}], [%1];"
               :: "l"(m), "r"(src), "r"(c0), "r"(c1) : "memory"); }
__device__ __forceinline__ uint64_t evict_first() { uint64_t p; asm("createpolicy.fractional.L2::evict_first.b64 %0, 1.0;" : "=l"(p)); return p; }
__device__ __forceinline__ void bulk_load_last_one(uint32_t dst, const void* src, uint32_t bytes, uint32_t bar) {
  asm volatile(ONE "cp.async.bulk.shared::cluster.global.mbarrier::complete_tx::bytes.L2::cache_hint [%0], [%1], %2, [%3], %4;}"
               :: "r"(dst), "l"(src), "r"(bytes), "r"(bar), "l"(evict_first()) : "memory"); }
__device__ __forceinline__ void bulk_store_stream(void* dst, uint32_t src, uint32_t bytes) {
  asm volatile("cp.async.bulk.global.shared::cta.bulk_group.L2::cache_hint [%0], [%1], %2, %3;" :: "l"(dst), "r"(src), "r"(bytes), "l"(evict_first()) : "memory"); }
__device__ __forceinline__ void bulk_load(uint32_t dst, const void* src, uint32_t bytes, uint32_t bar) {
  asm volatile("cp.async.bulk.shared::cluster.global.mbarrier::complete_tx::bytes [%0], [%1], %2, [%3];"
               :: "r"(dst), "l"(src), "r"(bytes), "r"(bar) : "memory"); }
__device__ __forceinline__ void bulk_push(uint32_t dst, uint32_t src, uint32_t bytes, uint32_t bar) {
  asm volatile("cp.async.bulk.shared::cluster.shared::cta.mbarrier::complete_tx::bytes [%0], [%1], %2, [%3];"
               :: "r"(dst), "r"(src), "r"(bytes), "r"(bar) : "memory"); }
__device__ __forceinline__ void bulk_store(void* dst, uint32_t src, uint32_t bytes) {
  asm volatile("cp.async.bulk.global.shared::cta.bulk_group [%0], [%1], %2;" :: "l"(dst), "r"(src), "r"(bytes) : "memory"); }
__device__ __forceinline__ void bulk_commit() { asm volatile("cp.async.bulk.commit_group;" ::: "memory"); }
template <int N> __device__ __forceinline__ void bulk_wait_read() { asm volatile("cp.async.bulk.wait_group.read %0;" :: "n"(N) : "memory"); }
template <int N> __device__ __forceinline__ void bulk_wait() { asm volatile("cp.async.bulk.wait_group %0;" :: "n"(N) : "memory"); }

__device__ __forceinline__ uint64_t mkdesc(uint32_t addr, uint32_t lbo, uint32_t sbo, uint32_t sw) {
  return (uint64_t)((addr & 0x3FFFF) >> 4) | ((uint64_t)(lbo >> 4) << 16) | ((uint64_t)(sbo >> 4) << 32) | ((uint64_t)sw << 62); }
__device__ __forceinline__ void wg_fence() { asm volatile("wgmma.fence.sync.aligned;" ::: "memory"); }
__device__ __forceinline__ void wg_commit() { asm volatile("wgmma.commit_group.sync.aligned;" ::: "memory"); }
template <int N> __device__ __forceinline__ void wg_wait() { asm volatile("wgmma.wait_group.sync.aligned %0;" :: "n"(N) : "memory"); }
template <int N> __device__ __forceinline__ void reg_fence(float* d) {
#pragma unroll
  for (int i = 0; i < N; i++) asm volatile("" : "+f"(d[i]) :: "memory");
}

__device__ __forceinline__ void mma16(float* d, uint32_t a0, uint32_t a1, uint32_t a2, uint32_t a3, uint32_t b0, uint32_t b1) {
  asm volatile("mma.sync.aligned.m16n8k16.row.col.f32.bf16.bf16.f32 {%0,%1,%2,%3},{%4,%5,%6,%7},{%8,%9},{%0,%1,%2,%3};"
               : "+f"(d[0]), "+f"(d[1]), "+f"(d[2]), "+f"(d[3]) : "r"(a0), "r"(a1), "r"(a2), "r"(a3), "r"(b0), "r"(b1)); }
__device__ __forceinline__ void mma8(float* d, uint32_t a0, uint32_t a1, uint32_t b0) {
  asm volatile("mma.sync.aligned.m16n8k8.row.col.f32.bf16.bf16.f32 {%0,%1,%2,%3},{%4,%5},{%6},{%0,%1,%2,%3};"
               : "+f"(d[0]), "+f"(d[1]), "+f"(d[2]), "+f"(d[3]) : "r"(a0), "r"(a1), "r"(b0)); }
__device__ __forceinline__ void ldsm4(uint32_t* r, uint32_t a) {
  asm volatile("ldmatrix.sync.aligned.m8n8.x4.shared.b16 {%0,%1,%2,%3},[%4];" : "=r"(r[0]), "=r"(r[1]), "=r"(r[2]), "=r"(r[3]) : "r"(a) : "memory"); }
__device__ __forceinline__ uint4 ldsm4v(uint32_t a) { uint32_t r[4]; ldsm4(r, a); return make_uint4(r[0], r[1], r[2], r[3]); }
__device__ __forceinline__ void ldsm4t(uint32_t* r, uint32_t a) {
  asm volatile("ldmatrix.sync.aligned.m8n8.x4.trans.shared.b16 {%0,%1,%2,%3},[%4];" : "=r"(r[0]), "=r"(r[1]), "=r"(r[2]), "=r"(r[3]) : "r"(a) : "memory"); }
__device__ __forceinline__ void ldsm2(uint32_t* r, uint32_t a) {
  asm volatile("ldmatrix.sync.aligned.m8n8.x2.shared.b16 {%0,%1},[%2];" : "=r"(r[0]), "=r"(r[1]) : "r"(a) : "memory"); }
__device__ __forceinline__ void ldsm2t(uint32_t* r, uint32_t a) {
  asm volatile("ldmatrix.sync.aligned.m8n8.x2.trans.shared.b16 {%0,%1},[%2];" : "=r"(r[0]), "=r"(r[1]) : "r"(a) : "memory"); }
__device__ __forceinline__ void stsm4(uint32_t a, uint32_t r0, uint32_t r1, uint32_t r2, uint32_t r3) {
  asm volatile("stmatrix.sync.aligned.m8n8.x4.shared.b16 [%0], {%1,%2,%3,%4};" :: "r"(a), "r"(r0), "r"(r1), "r"(r2), "r"(r3) : "memory"); }
__device__ __forceinline__ void stsm4t(uint32_t a, uint32_t r0, uint32_t r1, uint32_t r2, uint32_t r3) {
  asm volatile("stmatrix.sync.aligned.m8n8.x4.trans.shared.b16 [%0], {%1,%2,%3,%4};" :: "r"(a), "r"(r0), "r"(r1), "r"(r2), "r"(r3) : "memory"); }
__device__ __forceinline__ void stsm2(uint32_t a, uint32_t r0, uint32_t r1) {
  asm volatile("stmatrix.sync.aligned.m8n8.x2.shared.b16 [%0], {%1,%2};" :: "r"(a), "r"(r0), "r"(r1) : "memory"); }
__device__ __forceinline__ void stsm2t(uint32_t a, uint32_t r0, uint32_t r1) {
  asm volatile("stmatrix.sync.aligned.m8n8.x2.trans.shared.b16 [%0], {%1,%2};" :: "r"(a), "r"(r0), "r"(r1) : "memory"); }
__device__ __forceinline__ void sts32(uint32_t a, uint32_t v) { asm volatile("st.shared.b32 [%0], %1;" :: "r"(a), "r"(v) : "memory"); }
__device__ __forceinline__ void sts64f(uint32_t a, float x, float y) { asm volatile("st.shared.v2.f32 [%0], {%1,%2};" :: "r"(a), "f"(x), "f"(y) : "memory"); }
__device__ __forceinline__ void sts128(uint32_t a, uint4 v) {
  asm volatile("st.shared.v4.b32 [%0], {%1,%2,%3,%4};" :: "r"(a), "r"(v.x), "r"(v.y), "r"(v.z), "r"(v.w) : "memory"); }
__device__ __forceinline__ void sts128f(uint32_t a, float x, float y, float z, float w) {
  asm volatile("st.shared.v4.f32 [%0], {%1,%2,%3,%4};" :: "r"(a), "f"(x), "f"(y), "f"(z), "f"(w) : "memory"); }
__device__ __forceinline__ float lds32f(uint32_t a) { float v; asm volatile("ld.shared.f32 %0, [%1];" : "=f"(v) : "r"(a) : "memory"); return v; }
__device__ __forceinline__ float2 lds64f(uint32_t a) { float2 v; asm volatile("ld.shared.v2.f32 {%0,%1}, [%2];" : "=f"(v.x), "=f"(v.y) : "r"(a) : "memory"); return v; }
__device__ __forceinline__ float4 lds128f(uint32_t a) {
  float4 v; asm volatile("ld.shared.v4.f32 {%0,%1,%2,%3}, [%4];" : "=f"(v.x), "=f"(v.y), "=f"(v.z), "=f"(v.w) : "r"(a) : "memory"); return v; }
__device__ __forceinline__ uint4 lds128(uint32_t a) {
  uint4 v; asm volatile("ld.shared.v4.b32 {%0,%1,%2,%3}, [%4];" : "=r"(v.x), "=r"(v.y), "=r"(v.z), "=r"(v.w) : "r"(a) : "memory"); return v; }
__device__ __forceinline__ uint4 ldg_strong128(const void* p) {
  uint4 v; asm volatile("ld.relaxed.gpu.global.v4.u32 {%0,%1,%2,%3}, [%4];" : "=r"(v.x), "=r"(v.y), "=r"(v.z), "=r"(v.w) : "l"(p) : "memory"); return v; }
__device__ __forceinline__ uint2 ldg_strong64(const void* p) {
  uint2 v; asm volatile("ld.relaxed.gpu.global.v2.u32 {%0,%1}, [%2];" : "=r"(v.x), "=r"(v.y) : "l"(p) : "memory"); return v; }
__device__ __forceinline__ void stg_strong32(void* p, uint32_t v) { asm volatile("st.relaxed.gpu.global.u32 [%0], %1;" :: "l"(p), "r"(v) : "memory"); }
__device__ __forceinline__ void stg_strong128(void* p, uint4 v) {
  asm volatile("st.relaxed.gpu.global.v4.u32 [%0], {%1,%2,%3,%4};" :: "l"(p), "r"(v.x), "r"(v.y), "r"(v.z), "r"(v.w) : "memory"); }
__device__ __forceinline__ uint32_t mapa(uint32_t a, uint32_t r) {
  uint32_t o; asm("mapa.shared::cluster.u32 %0, %1, %2;" : "=r"(o) : "r"(a), "r"(r)); return o; }
__device__ __forceinline__ void st_async2f(uint32_t a, float x, float y, uint32_t bar) {
  asm volatile("st.async.shared::cluster.mbarrier::complete_tx::bytes.v2.f32 [%0], {%1,%2}, [%3];" :: "r"(a), "f"(x), "f"(y), "r"(bar) : "memory"); }
__device__ __forceinline__ void st_async32(uint32_t a, uint32_t x, uint32_t bar) {
  asm volatile("st.async.shared::cluster.mbarrier::complete_tx::bytes.b32 [%0], %1, [%2];" :: "r"(a), "r"(x), "r"(bar) : "memory"); }
__device__ __forceinline__ uint32_t lds32(uint32_t a) { uint32_t v; asm volatile("ld.shared.b32 %0, [%1];" : "=r"(v) : "r"(a) : "memory"); return v; }
__device__ __forceinline__ void st_async64(uint32_t a, uint32_t x, uint32_t y, uint32_t bar) {
  asm volatile("st.async.shared::cluster.mbarrier::complete_tx::bytes.v2.b32 [%0], {%1,%2}, [%3];" :: "r"(a), "r"(x), "r"(y), "r"(bar) : "memory"); }
__device__ __forceinline__ void st_async128(uint32_t a, uint4 v, uint32_t bar) {
  asm volatile("st.async.shared::cluster.mbarrier::complete_tx::bytes.v4.b32 [%0], {%1,%2,%3,%4}, [%5];" :: "r"(a), "r"(v.x), "r"(v.y), "r"(v.z), "r"(v.w), "r"(bar) : "memory"); }
__device__ __forceinline__ uint2 lds64(uint32_t a) { uint2 v; asm volatile("ld.shared.v2.b32 {%0,%1}, [%2];" : "=r"(v.x), "=r"(v.y) : "r"(a) : "memory"); return v; }
__device__ __forceinline__ void sts64(uint32_t a, uint32_t x, uint32_t y) { asm volatile("st.shared.v2.b32 [%0], {%1,%2};" :: "r"(a), "r"(x), "r"(y) : "memory"); }
__device__ __forceinline__ uint32_t ldg_strong32(const void* p) { uint32_t v; asm volatile("ld.relaxed.gpu.global.u32 %0, [%1];" : "=r"(v) : "l"(p) : "memory"); return v; }
__device__ __forceinline__ uint32_t transpose8(uint32_t x) { uint32_t r; asm volatile("movmatrix.sync.aligned.m8n8.trans.b16 %0, %1;" : "=r"(r) : "r"(x)); return r; }
__device__ __forceinline__ uint32_t hadd2(uint32_t a, uint32_t b) { uint32_t r; asm("add.rn.bf16x2 %0, %1, %2;" : "=r"(r) : "r"(a), "r"(b)); return r; }
__device__ __forceinline__ uint32_t min4(uint4 v) { return min(__vimin3_u32(v.x, v.y, v.z), v.w); }

__device__ __forceinline__ void wg_ss192_01(float* d, uint64_t da, uint64_t db, int sd) {
  asm volatile("{.reg .pred p; setp.ne.b32 p, %98, 0;\n"
    "wgmma.mma_async.sync.aligned.m64n192k16.f32.bf16.bf16 {%0,%1,%2,%3,%4,%5,%6,%7,%8,%9,%10,%11,%12,%13,%14,%15,%16,%17,%18,%19,%20,%21,%22,%23,%24,%25,%26,%27,%28,%29,%30,%31,%32,%33,%34,%35,%36,%37,%38,%39,%40,%41,%42,%43,%44,%45,%46,%47,%48,%49,%50,%51,%52,%53,%54,%55,%56,%57,%58,%59,%60,%61,%62,%63,%64,%65,%66,%67,%68,%69,%70,%71,%72,%73,%74,%75,%76,%77,%78,%79,%80,%81,%82,%83,%84,%85,%86,%87,%88,%89,%90,%91,%92,%93,%94,%95}, %96, %97, p, 1, 1, 0, 1;}"
    : "+f"(d[0]),"+f"(d[1]),"+f"(d[2]),"+f"(d[3]),"+f"(d[4]),"+f"(d[5]),"+f"(d[6]),"+f"(d[7]),"+f"(d[8]),"+f"(d[9]),"+f"(d[10]),"+f"(d[11]),"+f"(d[12]),"+f"(d[13]),"+f"(d[14]),"+f"(d[15]),"+f"(d[16]),"+f"(d[17]),"+f"(d[18]),"+f"(d[19]),"+f"(d[20]),"+f"(d[21]),"+f"(d[22]),"+f"(d[23]),"+f"(d[24]),"+f"(d[25]),"+f"(d[26]),"+f"(d[27]),"+f"(d[28]),"+f"(d[29]),"+f"(d[30]),"+f"(d[31]),"+f"(d[32]),"+f"(d[33]),"+f"(d[34]),"+f"(d[35]),"+f"(d[36]),"+f"(d[37]),"+f"(d[38]),"+f"(d[39]),"+f"(d[40]),"+f"(d[41]),"+f"(d[42]),"+f"(d[43]),"+f"(d[44]),"+f"(d[45]),"+f"(d[46]),"+f"(d[47]),"+f"(d[48]),"+f"(d[49]),"+f"(d[50]),"+f"(d[51]),"+f"(d[52]),"+f"(d[53]),"+f"(d[54]),"+f"(d[55]),"+f"(d[56]),"+f"(d[57]),"+f"(d[58]),"+f"(d[59]),"+f"(d[60]),"+f"(d[61]),"+f"(d[62]),"+f"(d[63]),"+f"(d[64]),"+f"(d[65]),"+f"(d[66]),"+f"(d[67]),"+f"(d[68]),"+f"(d[69]),"+f"(d[70]),"+f"(d[71]),"+f"(d[72]),"+f"(d[73]),"+f"(d[74]),"+f"(d[75]),"+f"(d[76]),"+f"(d[77]),"+f"(d[78]),"+f"(d[79]),"+f"(d[80]),"+f"(d[81]),"+f"(d[82]),"+f"(d[83]),"+f"(d[84]),"+f"(d[85]),"+f"(d[86]),"+f"(d[87]),"+f"(d[88]),"+f"(d[89]),"+f"(d[90]),"+f"(d[91]),"+f"(d[92]),"+f"(d[93]),"+f"(d[94]),"+f"(d[95])
    : "l"(da), "l"(db), "r"(sd));
}
__device__ __forceinline__ void wg_ss128_01(float* d, uint64_t da, uint64_t db, int sd) {
  asm volatile("{.reg .pred p; setp.ne.b32 p, %66, 0;\n"
    "wgmma.mma_async.sync.aligned.m64n128k16.f32.bf16.bf16 {%0,%1,%2,%3,%4,%5,%6,%7,%8,%9,%10,%11,%12,%13,%14,%15,%16,%17,%18,%19,%20,%21,%22,%23,%24,%25,%26,%27,%28,%29,%30,%31,%32,%33,%34,%35,%36,%37,%38,%39,%40,%41,%42,%43,%44,%45,%46,%47,%48,%49,%50,%51,%52,%53,%54,%55,%56,%57,%58,%59,%60,%61,%62,%63}, %64, %65, p, 1, 1, 0, 1;}"
    : "+f"(d[0]),"+f"(d[1]),"+f"(d[2]),"+f"(d[3]),"+f"(d[4]),"+f"(d[5]),"+f"(d[6]),"+f"(d[7]),"+f"(d[8]),"+f"(d[9]),"+f"(d[10]),"+f"(d[11]),"+f"(d[12]),"+f"(d[13]),"+f"(d[14]),"+f"(d[15]),"+f"(d[16]),"+f"(d[17]),"+f"(d[18]),"+f"(d[19]),"+f"(d[20]),"+f"(d[21]),"+f"(d[22]),"+f"(d[23]),"+f"(d[24]),"+f"(d[25]),"+f"(d[26]),"+f"(d[27]),"+f"(d[28]),"+f"(d[29]),"+f"(d[30]),"+f"(d[31]),"+f"(d[32]),"+f"(d[33]),"+f"(d[34]),"+f"(d[35]),"+f"(d[36]),"+f"(d[37]),"+f"(d[38]),"+f"(d[39]),"+f"(d[40]),"+f"(d[41]),"+f"(d[42]),"+f"(d[43]),"+f"(d[44]),"+f"(d[45]),"+f"(d[46]),"+f"(d[47]),"+f"(d[48]),"+f"(d[49]),"+f"(d[50]),"+f"(d[51]),"+f"(d[52]),"+f"(d[53]),"+f"(d[54]),"+f"(d[55]),"+f"(d[56]),"+f"(d[57]),"+f"(d[58]),"+f"(d[59]),"+f"(d[60]),"+f"(d[61]),"+f"(d[62]),"+f"(d[63])
    : "l"(da), "l"(db), "r"(sd));
}
__device__ __forceinline__ void wg_ss160_01(float* d, uint64_t da, uint64_t db, int sd) {
  asm volatile("{.reg .pred p; setp.ne.b32 p, %82, 0;\n"
    "wgmma.mma_async.sync.aligned.m64n160k16.f32.bf16.bf16 {%0,%1,%2,%3,%4,%5,%6,%7,%8,%9,%10,%11,%12,%13,%14,%15,%16,%17,%18,%19,%20,%21,%22,%23,%24,%25,%26,%27,%28,%29,%30,%31,%32,%33,%34,%35,%36,%37,%38,%39,%40,%41,%42,%43,%44,%45,%46,%47,%48,%49,%50,%51,%52,%53,%54,%55,%56,%57,%58,%59,%60,%61,%62,%63,%64,%65,%66,%67,%68,%69,%70,%71,%72,%73,%74,%75,%76,%77,%78,%79}, %80, %81, p, 1, 1, 0, 1;}"
    : "+f"(d[0]),"+f"(d[1]),"+f"(d[2]),"+f"(d[3]),"+f"(d[4]),"+f"(d[5]),"+f"(d[6]),"+f"(d[7]),"+f"(d[8]),"+f"(d[9]),"+f"(d[10]),"+f"(d[11]),"+f"(d[12]),"+f"(d[13]),"+f"(d[14]),"+f"(d[15]),"+f"(d[16]),"+f"(d[17]),"+f"(d[18]),"+f"(d[19]),"+f"(d[20]),"+f"(d[21]),"+f"(d[22]),"+f"(d[23]),"+f"(d[24]),"+f"(d[25]),"+f"(d[26]),"+f"(d[27]),"+f"(d[28]),"+f"(d[29]),"+f"(d[30]),"+f"(d[31]),"+f"(d[32]),"+f"(d[33]),"+f"(d[34]),"+f"(d[35]),"+f"(d[36]),"+f"(d[37]),"+f"(d[38]),"+f"(d[39]),"+f"(d[40]),"+f"(d[41]),"+f"(d[42]),"+f"(d[43]),"+f"(d[44]),"+f"(d[45]),"+f"(d[46]),"+f"(d[47]),"+f"(d[48]),"+f"(d[49]),"+f"(d[50]),"+f"(d[51]),"+f"(d[52]),"+f"(d[53]),"+f"(d[54]),"+f"(d[55]),"+f"(d[56]),"+f"(d[57]),"+f"(d[58]),"+f"(d[59]),"+f"(d[60]),"+f"(d[61]),"+f"(d[62]),"+f"(d[63]),"+f"(d[64]),"+f"(d[65]),"+f"(d[66]),"+f"(d[67]),"+f"(d[68]),"+f"(d[69]),"+f"(d[70]),"+f"(d[71]),"+f"(d[72]),"+f"(d[73]),"+f"(d[74]),"+f"(d[75]),"+f"(d[76]),"+f"(d[77]),"+f"(d[78]),"+f"(d[79])
    : "l"(da), "l"(db), "r"(sd));
}
__device__ __forceinline__ void wg_ss80_01(float* d, uint64_t da, uint64_t db, int sd) {
  asm volatile("{.reg .pred p; setp.ne.b32 p, %42, 0;\n"
    "wgmma.mma_async.sync.aligned.m64n80k16.f32.bf16.bf16 {%0,%1,%2,%3,%4,%5,%6,%7,%8,%9,%10,%11,%12,%13,%14,%15,%16,%17,%18,%19,%20,%21,%22,%23,%24,%25,%26,%27,%28,%29,%30,%31,%32,%33,%34,%35,%36,%37,%38,%39}, %40, %41, p, 1, 1, 0, 1;}"
    : "+f"(d[0]),"+f"(d[1]),"+f"(d[2]),"+f"(d[3]),"+f"(d[4]),"+f"(d[5]),"+f"(d[6]),"+f"(d[7]),"+f"(d[8]),"+f"(d[9]),"+f"(d[10]),"+f"(d[11]),"+f"(d[12]),"+f"(d[13]),"+f"(d[14]),"+f"(d[15]),"+f"(d[16]),"+f"(d[17]),"+f"(d[18]),"+f"(d[19]),"+f"(d[20]),"+f"(d[21]),"+f"(d[22]),"+f"(d[23]),"+f"(d[24]),"+f"(d[25]),"+f"(d[26]),"+f"(d[27]),"+f"(d[28]),"+f"(d[29]),"+f"(d[30]),"+f"(d[31]),"+f"(d[32]),"+f"(d[33]),"+f"(d[34]),"+f"(d[35]),"+f"(d[36]),"+f"(d[37]),"+f"(d[38]),"+f"(d[39])
    : "l"(da), "l"(db), "r"(sd));
}
__device__ __forceinline__ void wg_rs32_00(float* d, uint32_t a0, uint32_t a1, uint32_t a2, uint32_t a3, uint64_t db, int sd) {
  asm volatile("{.reg .pred p; setp.ne.b32 p, %21, 0;\n"
    "wgmma.mma_async.sync.aligned.m64n32k16.f32.bf16.bf16 {%0,%1,%2,%3,%4,%5,%6,%7,%8,%9,%10,%11,%12,%13,%14,%15}, {%16,%17,%18,%19}, %20, p, 1, 1, 0;}"
    : "+f"(d[0]),"+f"(d[1]),"+f"(d[2]),"+f"(d[3]),"+f"(d[4]),"+f"(d[5]),"+f"(d[6]),"+f"(d[7]),"+f"(d[8]),"+f"(d[9]),"+f"(d[10]),"+f"(d[11]),"+f"(d[12]),"+f"(d[13]),"+f"(d[14]),"+f"(d[15])
    : "r"(a0), "r"(a1), "r"(a2), "r"(a3), "l"(db), "r"(sd));
}
__device__ __forceinline__ void wg_rs64_00(float* d, uint32_t a0, uint32_t a1, uint32_t a2, uint32_t a3, uint64_t db, int sd) {
  asm volatile("{.reg .pred p; setp.ne.b32 p, %37, 0;\n"
    "wgmma.mma_async.sync.aligned.m64n64k16.f32.bf16.bf16 {%0,%1,%2,%3,%4,%5,%6,%7,%8,%9,%10,%11,%12,%13,%14,%15,%16,%17,%18,%19,%20,%21,%22,%23,%24,%25,%26,%27,%28,%29,%30,%31}, {%32,%33,%34,%35}, %36, p, 1, 1, 0;}"
    : "+f"(d[0]),"+f"(d[1]),"+f"(d[2]),"+f"(d[3]),"+f"(d[4]),"+f"(d[5]),"+f"(d[6]),"+f"(d[7]),"+f"(d[8]),"+f"(d[9]),"+f"(d[10]),"+f"(d[11]),"+f"(d[12]),"+f"(d[13]),"+f"(d[14]),"+f"(d[15]),"+f"(d[16]),"+f"(d[17]),"+f"(d[18]),"+f"(d[19]),"+f"(d[20]),"+f"(d[21]),"+f"(d[22]),"+f"(d[23]),"+f"(d[24]),"+f"(d[25]),"+f"(d[26]),"+f"(d[27]),"+f"(d[28]),"+f"(d[29]),"+f"(d[30]),"+f"(d[31])
    : "r"(a0), "r"(a1), "r"(a2), "r"(a3), "l"(db), "r"(sd));
}
__device__ __forceinline__ void wg_rs80_01(float* d, uint32_t a0, uint32_t a1, uint32_t a2, uint32_t a3, uint64_t db, int sd) {
  asm volatile("{.reg .pred p; setp.ne.b32 p, %45, 0;\n"
    "wgmma.mma_async.sync.aligned.m64n80k16.f32.bf16.bf16 {%0,%1,%2,%3,%4,%5,%6,%7,%8,%9,%10,%11,%12,%13,%14,%15,%16,%17,%18,%19,%20,%21,%22,%23,%24,%25,%26,%27,%28,%29,%30,%31,%32,%33,%34,%35,%36,%37,%38,%39}, {%40,%41,%42,%43}, %44, p, 1, 1, 1;}"
    : "+f"(d[0]),"+f"(d[1]),"+f"(d[2]),"+f"(d[3]),"+f"(d[4]),"+f"(d[5]),"+f"(d[6]),"+f"(d[7]),"+f"(d[8]),"+f"(d[9]),"+f"(d[10]),"+f"(d[11]),"+f"(d[12]),"+f"(d[13]),"+f"(d[14]),"+f"(d[15]),"+f"(d[16]),"+f"(d[17]),"+f"(d[18]),"+f"(d[19]),"+f"(d[20]),"+f"(d[21]),"+f"(d[22]),"+f"(d[23]),"+f"(d[24]),"+f"(d[25]),"+f"(d[26]),"+f"(d[27]),"+f"(d[28]),"+f"(d[29]),"+f"(d[30]),"+f"(d[31]),"+f"(d[32]),"+f"(d[33]),"+f"(d[34]),"+f"(d[35]),"+f"(d[36]),"+f"(d[37]),"+f"(d[38]),"+f"(d[39])
    : "r"(a0), "r"(a1), "r"(a2), "r"(a3), "l"(db), "r"(sd));
}
__device__ __forceinline__ void wg_rs24_01(float* d, uint32_t a0, uint32_t a1, uint32_t a2, uint32_t a3, uint64_t db, int sd) {
  asm volatile("{.reg .pred p; setp.ne.b32 p, %17, 0;\n"
    "wgmma.mma_async.sync.aligned.m64n24k16.f32.bf16.bf16 {%0,%1,%2,%3,%4,%5,%6,%7,%8,%9,%10,%11}, {%12,%13,%14,%15}, %16, p, 1, 1, 1;}"
    : "+f"(d[0]),"+f"(d[1]),"+f"(d[2]),"+f"(d[3]),"+f"(d[4]),"+f"(d[5]),"+f"(d[6]),"+f"(d[7]),"+f"(d[8]),"+f"(d[9]),"+f"(d[10]),"+f"(d[11])
    : "r"(a0), "r"(a1), "r"(a2), "r"(a3), "l"(db), "r"(sd));
}

#define AB_POLY 0x77
__device__ __forceinline__ constexpr bool poly_group(int group) { return (AB_POLY >> (group & 7)) & 1; }

template <int V> struct Int { static constexpr int value = V; };

__device__ __forceinline__ int core_word(int row, int col) {
  return ((((row >> 7) * 10 + (col >> 6)) * 16 + ((row >> 3) & 15)) * 8 + ((col >> 3) & 7)) * 32 + (row & 7) * 4 + ((col & 7) >> 1);
}
__device__ __forceinline__ void wait_count(const uint32_t* c, uint32_t n) {
  for (int spin = 0; !__all_sync(~0u, (ld_acquire(c) & 0xffff) >= n);) { __nanosleep(32); spin_guard(spin); }
  fence_async_global();
}
__device__ __forceinline__ void prefetch_l2(const void* p, uint32_t bytes) {
  asm volatile("cp.async.bulk.prefetch.L2.global [%0], %1;" :: "l"(p), "r"(bytes) : "memory"); }

#define PLACE 4
__device__ __forceinline__ bool helper_sm() {
  uint32_t m; asm volatile("mov.u32 %0, %%smid;" : "=r"(m));
  m = __shfl_sync(~0u, m, 0);
  return m < 2 || m >= 120 || (m >= 92 && m < 102) || (m >= 106 && m < 117) || m == 118;
}

__device__ __forceinline__ uint8_t* pool_at(uint32_t off) {
  return reinterpret_cast<uint8_t*>((reinterpret_cast<uintptr_t>(g_pool) + 8191) & ~(uintptr_t)8191) + off; }
__device__ __forceinline__ void probe_slots(uint32_t scratch) {
  const int w = __shfl_sync(~0u, (threadIdx.x >> 6) & 1, 0), slot = w == 0 ? NSLOT : blockIdx.x;
  if (w == 0 || slot < NSLOT) {
    uint32_t* q = reinterpret_cast<uint32_t*>(pool_at(slot * 8192)) + (w == 0 ? (blockIdx.x & 31) * 32 + (blockIdx.x >> 5) : 0);
    uint32_t best[2] = {~0u, ~0u};
    const bool one = elect();
    if (one) { stg_strong32(q, 0u); stg_strong32(q + 1024, 0u); }
#pragma unroll 1
    for (int r = 0; r < 8; r++) {
      uint32_t v = 0;
      const uint32_t t0 = clk32();
      if (one) asm volatile("atom.relaxed.gpu.global.exch.b32 %0, [%1], 0;" : "=r"(v) : "l"(q + (r & 1) * 1024) : "memory");
      if (__any_sync(~0u, v != 0)) break;
      const uint32_t t = min(clk32() - t0, best[0]);
      best[0] = best[1]; best[1] = t;
    }
    if (one) sts32(scratch + w * 4, best[0] < best[1]);
  }
  bar_sync(2, 64);
  if ((threadIdx.x & 31) == 0) {
    const int part = lds32(scratch) ? 1 : 2;
    if (w == 0) { uint32_t smid; asm("mov.u32 %0, %%smid;" : "=r"(smid)); stg_strong32(g_smpart + (smid & 255), part); }
    else if (slot < NSLOT) stg_strong32(g_orient + slot, lds32(scratch + 4) ? part : 3 - part);
  }
  __syncwarp();
}

constexpr int WK_SLOTS = 28, WK_BAR = WK_SLOTS * 8192;
__device__ __forceinline__ void work_init(uint32_t sb, int w) {
  if (elect()) {
#pragma unroll
    for (int i = 0; i < 8; i++) mbar_init(sb + WK_BAR + 64 * w + 8 * i, 0x18318822 >> (8 * w + (i & 4)) & 15);
  }
  asm volatile("fence.mbarrier_init.release.cluster;" ::: "memory");
}

struct ChainParams {
  CUtensorMap wq, wk, wv, wo, xc;
  const __nv_bfloat16* mem0;
  const uint8_t* wb;
  uint32_t *sync, *other;
  int layer;
  int d1, d2, dn, dx, mode, zero;
};
constexpr int CH_WQ = 0, CH_WO = 81920, CH_X = CH_WO + 86016, CH_M = CH_X, CH_Q = CH_X + 34816, CH_KM = CH_Q + 2048, CH_VP = CH_KM + 2048,
              CH_K = CH_X + 40960, CH_O = CH_K, CH_KS = CH_K + 3072, CH_V = CH_K + 4096, CH_VX = CH_V + 12288, CH_R2 = CH_VX,
              CH_SX = CH_VX + 3072, CH_SO = CH_SX + 2048, CH_ID = CH_SO + 1024, CH_L = CH_ID + 256, CH_TAB = CH_L + 64, CH_BAR = CH_TAB + 384;
constexpr int CH_SMEM = CH_BAR + 144;
constexpr int MB_WO = CH_BAR, MB_WQ = CH_BAR + 8, MB_X = CH_BAR + 16, MB_V = CH_BAR + 24, MB_T = CH_BAR + 32, MB_F = CH_BAR + 40, MB_G = CH_BAR + 48, MB_W = CH_BAR + 56;
enum { NB_PROJ = 1, NB_O = 2, NB_W1 = 3, NB_PRE = 4, NB_ST = 5, NB_MEM = 6, NB_XFREE = 7, NB_H1 = 8, NB_PUB = 9, NB_W2 = 10, NB_PROJ2 = 11, NB_PRE2 = 12, NB_H2 = 13, NB_W1V = 14 };
#define CH_NQ 9
#define CH_XPF 1
#define CH_TPF 1
#define CH_FLY 6
#define CH_TW 1
#define CH_NQ0 4
#define CH_PA 6
#define CH_PB 9
#define CH_PC 13
#define CH_PL 4
#define CH_DBL 0x0888
#define CH_PD 1
#define SCHED() asm volatile("griddepcontrol.launch_dependents;" ::: "memory")
__device__ __forceinline__ uint32_t opaque(uint32_t x) { return __shfl_sync(~0u, x, threadIdx.x & 31); }
__device__ __forceinline__ uint32_t uniform(uint32_t x) { return __shfl_sync(~0u, x, 0); }
__device__ __forceinline__ uint32_t nz(uint32_t x) { uint32_t r; asm("max.u32 %0, %1, 1;" : "=r"(r) : "r"(x)); return r; }
__device__ __forceinline__ uint32_t set_tag(uint32_t w, uint32_t tag) { uint32_t r; asm("lop3.b32 %0, %1, %2, 1, 0xD8;" : "=r"(r) : "r"(w), "r"(tag)); return r; }
__device__ __forceinline__ uint32_t pack_tag(float lo, float hi, uint32_t tag) { return set_tag(__byte_perm(__float_as_uint(lo) + tag, pack2(hi, hi), 0x7632), tag); }
__device__ __forceinline__ uint32_t differ(uint32_t a, uint32_t b, uint32_t t) { uint32_t r; asm("lop3.b32 %0, %1, %2, %3, 0x7E;" : "=r"(r) : "r"(a), "r"(b), "r"(t)); return r; }
__device__ __forceinline__ uint32_t clk64() { uint64_t c; asm volatile("mov.u64 %0, %%clock64;" : "=l"(c) :: "memory"); return (uint32_t)c; }
__device__ __forceinline__ void until(uint32_t t) {
  asm volatile("{.reg .pred p; .reg .u64 c; .reg .s32 d;\nW: mov.u64 c, %%clock64; cvt.u32.u64 d, c; sub.s32 d, d, %0; setp.lt.s32 p, d, 0; @p bra.uni W;}" :: "r"(t) : "memory");
}
__device__ __forceinline__ float rcp(float x) { float y; asm("rcp.approx.ftz.f32 %0, %1;" : "=f"(y) : "f"(x)); return y; }

__device__ __forceinline__ void chain_compute(const ChainParams& p, const uint32_t sb) {
  const int tid = threadIdx.x & 127, WG = __shfl_sync(~0u, threadIdx.x >> 7, 0), t4 = __shfl_sync(~0u, tid >> 5, 0), lane = tid & 31;
  const int cta = blockIdx.x, h = cta / 3, j = cta - 3 * h;
  uint32_t a0[80], a1[80], tw[4 * CH_NQ];
  const uint32_t wq = opaque(sb + CH_WQ + (WG * 320 + (lane & 7) + (lane >> 4) * 8) * 128 + (((2 * t4 + ((lane >> 3) & 1)) ^ (lane & 7)) << 4));
#pragma unroll
  for (int k = 0; k < 40; k++) {
    if (k % 10 == 0) mbar_wait(sb + MB_W + WG * 8 + k / 10 * 16, 0);
    if (k < 20) ldsm4t(&a0[4 * k], wq + k * 2048); else ldsm4t(&a1[4 * k - 80], wq + CH_WO + (k - 20) * 2048);
    if (k % 20 == 19) bar_arrive(k < 20 ? NB_PROJ2 : NB_PRE2, 288);
  }
  const int r1 = j == 2 ? 0 : j + 1, r2 = j == 0 ? 2 : j - 1;
  const uint32_t l16 = opaque(sb + lane * 16), l8 = opaque(sb + lane * 8), l4 = opaque(sb + lane * 4);
  const uint32_t t16 = l16 + t4 * 512, t8 = l8 + t4 * 256;
  uint32_t wo = opaque(sb + CH_WO + (WG == 0 ? (t4 >> 1) * 36864 : 73728 + t4 * 1024) + ((lane & 7) + (lane >> 4) * 8) * 64 +
                       (((((lane >> 3) & 1) + (WG == 0 ? (t4 & 1) * 2 : 0)) ^ ((lane >> 1) & 3)) << 4));
  const uint32_t ko0 = uniform(CH_K + (tid >> 5) * 1024 + (tid >> 6) * 512), ko1 = uniform(CH_K + (tid >> 5) * 1024 + 512 - (tid >> 6) * 512),
                 o768 = uniform((tid >> 5) * 768);
  const uint32_t give = uniform(t4 * 512 + (WG == 0 ? CH_K : CH_V + j * 4096)), own = uniform(t4 * 512 + (WG == 0 ? CH_V + j * 4096 : CH_K)), mem = uniform(CH_M + WG * 5120);
  const uint32_t vxo = uniform(t4 * 256 + CH_VX + j * 1024);
  uint32_t tag = 1, xd = uniform((1024 + CH_X + WG * 20480) >> 4 | 8 << 16);
  asm volatile("barrier.cluster.wait.aligned;" ::: "memory");
  mbar_wait(sb + MB_WQ, 0);
  mbar_wait(sb + MB_T, 0);
  bar_sync(NB_ST, 384);
  uint8_t* pdst[6];
#pragma unroll
  for (int i = 0; i < 6; i++) {
    const int line = WG == 0 ? 24 * j + 12 * (t4 >> 1) + 2 * (t4 & 1) + 4 * (i >> 1) + (i & 1) : j == 0 ? 72 + t4 : 74 + 2 * j + (t4 & 1);
    pdst[i] = pool_at(uniform(lds32(sb + CH_TAB + line * 4)) + h * 128);
  }
  auto batch = [&](float* d, const uint32_t (&a)[80], int acc, int n0, int n1) {
    const uint32_t d0 = xd ^ (tag & (2 << acc));
    wg_fence();
#pragma unroll
    for (int k = 0; k < 20; k++) {
      if (!(k & 3) && n0 + k / 4 < n1) {
        __syncwarp();
        ldsm4t(&tw[4 * n0 + k], wq + (n0 + k / 4) * 2048);
        __syncwarp();
      }
      uint64_t db;
      asm("mov.b64 %0, {%1, %2};" : "=l"(db) : "r"(d0 + k / 5 * 320 + k % 5 * 16), "r"(80));
      wg_rs32_00(d, a[4 * k], a[4 * k + 1], a[4 * k + 2], a[4 * k + 3], db, acc | k);
    }
    wg_commit();
    wg_wait<0>();
    reg_fence<16>(d);
  };
  int s = 0;
#pragma unroll 1
  do {
    {
      float d[16];
      if (!CH_TW) mbar_wait(sb + MB_T, s & 1);
      batch(d, a0, 0, 0, CH_NQ0);
      s--; TM(10); s++;
      mbar_wait(sb + MB_F, ~s & 1);
#pragma unroll
      for (int i = 0; i < 2; i++)
        sts128(l16 + give + i * 2048, make_uint4(pack2(d[8 * i], d[8 * i + 1]), pack2(d[8 * i + 2], d[8 * i + 3]), pack2(d[8 * i + 4], d[8 * i + 5]), pack2(d[8 * i + 6], d[8 * i + 7])));
      bar_sync(NB_PUB, 384);
#pragma unroll
      for (int i = 0; i < 2; i++) {
        const uint4 t = lds128(l16 + own + i * 2048);
        d[8 * i] = bf_lo(t.x); d[8 * i + 1] = bf_hi(t.x); d[8 * i + 2] = bf_lo(t.y); d[8 * i + 3] = bf_hi(t.y);
        d[8 * i + 4] = bf_lo(t.z); d[8 * i + 5] = bf_hi(t.z); d[8 * i + 6] = bf_lo(t.w); d[8 * i + 7] = bf_hi(t.w);
      }
      reg_fence<16>(d);
      batch(d, a1, 1, CH_NQ0, CH_NQ);
      s--; TM(11); s++;
      if (WG == 0) bar_arrive(NB_XFREE, 256);
#pragma unroll
      for (int i = 0; i < 8; i++) sts32(l4 + (own - t4 * 256) + (i >> 1) * 1024 + (i & 1) * 128, pack2(d[2 * i], d[2 * i + 1]));
      s--; TM(9); s++;
    }
    float dq[4] = {}, d0[4] = {}, d1[4] = {};
    uint32_t b[40], wf[80];
    const uint32_t* kf = &wf[52];
#pragma unroll
    for (int i = 0; i < 4 * CH_NQ; i++) wf[i] = tw[i];
    auto step = [&](int k) {
      mma16(dq, wf[4 * k], wf[4 * k + 1], wf[4 * k + 2], wf[4 * k + 3], b[2 * k], b[2 * k + 1]);
      mma16(d0, a0[4 * k], a0[4 * k + 1], a0[4 * k + 2], a0[4 * k + 3], b[2 * k], b[2 * k + 1]);
      mma16(d1, a1[4 * k], a1[4 * k + 1], a1[4 * k + 2], a1[4 * k + 3], b[2 * k], b[2 * k + 1]);
    };
    auto finish = [&](int wg, const float* dk) {
      const float k2 = 0.07216878364870322f * 1.44269504089f;
      sts32(l4 + t4 * 512 + CH_Q + wg * 128, pack2(dq[0] * k2, dq[1] * k2));
      sts32(l4 + t4 * 512 + CH_Q + wg * 128 + 256, pack2(dq[2] * k2, dq[3] * k2));
      sts32(l4 + t4 * 512 + CH_KM + wg * 256, pack2(dk[0], dk[1]));
      sts32(l4 + t4 * 512 + CH_KM + wg * 256 + 128, pack2(dk[2], dk[3]));
    };
    const bool more = s < NSEG - 1;
    bar_sync(NB_MEM, 384);
    ldsm4t(&b[0], l16 + mem);
    ldsm4t(&b[4], l16 + mem + 512);
    TMD(0, b[0]);
    {
      int nw = CH_NQ, nb = 2;
#pragma unroll
      for (int k = 0; k < 20; k++) {
        SCHED();
        step(k);
#pragma unroll
        for (int i = 0; i < (CH_DBL >> k & 1) + 1; i++) {
          if (nb < 10 && 2 * nb <= nw) { ldsm4t(&b[4 * nb], l16 + mem + nb * 512); nb++; }
          else if (nw < 20) { ldsm4t(&wf[4 * nw], wq + nw * 2048); nw++; }
          else if (nw < 22) {
            const uint32_t x = l16 ^ ((o768 ^ tag) & 256);
            uint32_t* r = &wf[4 * nw - 28];
            asm volatile("{.reg .pred p; setp.ne.u32 p, %5, 0; @p ldmatrix.sync.aligned.m8n8.x4.trans.shared.b16 {%0,%1,%2,%3},[%4];}"
                         : "+r"(r[0]), "+r"(r[1]), "+r"(r[2]), "+r"(r[3]) : "r"(x + (nw == 20 ? ko0 : ko1)), "r"(WG) : "memory");
            nw++;
          }
        }
      }
      SCHED();
    }
    if (WG == 0) {
      finish(0, d0);
      TM(1);
      bar_sync(NB_PROJ, 256);
      if (!more) {
        const float4 pv = lds128f(t16 + CH_VP);
        sts32(l4 + vxo, pack2(d1[0] + pv.x, d1[1] + pv.y));
        sts32(l4 + vxo + 128, pack2(d1[2] + pv.z, d1[3] + pv.w));
        continue;
      }
      const float4 pv = lds128f(t16 + CH_VP);
      const uint32_t xo = l4 + (vxo ^ (tag & 2)), x1 = mapa(xo, r1), x2 = mapa(xo, r2);
      SCHED();
      const uint32_t v0 = pack2(d1[0] + pv.x, d1[1] + pv.y), v1 = pack2(d1[2] + pv.z, d1[3] + pv.w);
      st_async32(x1, v0, mapa(sb + MB_X, r1));
      st_async32(x2, v0, mapa(sb + MB_X, r2));
      st_async32(x1 + 128, v1, mapa(sb + MB_X, r1));
      st_async32(x2 + 128, v1, mapa(sb + MB_X, r2));
      sts32(xo, v0);
      sts32(xo + 128, v1);
      __syncwarp();
      mbar_arrive_one(sb + MB_X);
      bar_arrive(NB_PROJ2, 256);
      TM(3);
      uint32_t w[144];
      auto tile_of = [](int n) { return n < 27 ? n % 3 : (0x26484 >> 2 * (n - 27)) & 3; };
      auto step_of = [](int n) { return n < 27 ? n / 3 : 9 + ((0x29610 >> 2 * (n - 27)) & 3); };
      auto wload = [&](int n) { ldsm4t(&w[4 * n], wo + tile_of(n) * 12288 + (step_of(n) % 3) * 4096 + (step_of(n) / 3) * 1024); };
#pragma unroll
      for (int n = 0; n < CH_PA; n++) wload(n);
      bar_sync(NB_PRE, 256);
#pragma unroll
      for (int n = CH_PA; n < CH_PB; n++) wload(n);
      bar_arrive(NB_PRE2, 256);
      if (CH_PC > CH_PB) {
        mbar_wait(sb + MB_X, s & 1);
        for (int i = 0; i < CH_PD; i++) wo = __shfl_xor_sync(~0u, wo, p.zero);
#pragma unroll
        for (int n = CH_PB; n < CH_PC; n++) wload(n);
      }
      TM(4);
      bar_sync(NB_O, 256);
      {
        float x[3][4] = {};
        uint32_t ob[24];
        float4 l;
        ldsm4t(&ob[0], l16 + CH_O);
        ldsm4t(&ob[4], l16 + CH_O + 512);
        TMD(7, ob[0]);
        int nw = CH_PC, no = 2;
        float i0, i1;
        uint8_t* dst[6];
        uint32_t lo[6], hi[6];
        auto pre = [&](int i) { lo[i] = __float_as_uint(x[i >> 1][2 * (i & 1)] * i0) + tag; hi[i] = pack2(0.f, x[i >> 1][2 * (i & 1) + 1] * i1); };
        auto emit = [&](int i) { stg_strong32(dst[i], set_tag(__byte_perm(lo[i], hi[i], 0x7632), tag)); };
#pragma unroll
        for (int n = 0; n < 36; n++) {
          SCHED();
          mma16(x[tile_of(n)], w[4 * n], w[4 * n + 1], w[4 * n + 2], w[4 * n + 3], ob[step_of(n) * 2], ob[step_of(n) * 2 + 1]);
          if (n >= CH_PL) {
            if (no < 6 && no * 2 <= step_of(min(nw, 35))) { ldsm4t(&ob[4 * no], l16 + CH_O + no * 512); no++; }
            else if (nw < 36) { wload(nw); nw++; }
          }
          if (n == 18) l = lds128f(sb + CH_L + ((l16 ^ tag) & 0x30));
          if (n == 26) { i0 = rcp(l.x + l.y); i1 = rcp(l.z + l.w); asm volatile("" : "+f"(i0), "+f"(i1)); }
          if (n >= 28 && n < 34) { dst[n - 28] = pdst[n - 28] + ((l4 ^ tag) & 0x7c); asm volatile("" : "+l"(dst[n - 28])); }
          if (n == 32) { for (int i = 0; i < 2; i++) { pre(i); asm volatile("" : "+r"(lo[i]), "+r"(hi[i])); } }
          if (n == 33) { emit(0); emit(1); }
        }
        for (int i = 2; i < 6; i++) pre(i);
        for (int i = 2; i < 6; i++) emit(i);
      }
      TM(8);
    } else {
      finish(1, d1);
      sts128f(t16 + CH_VP, d0[0], d0[1], d0[2], d0[3]);
      TM(1);
      bar_sync(NB_PROJ, 256);
      uint32_t pair;
      {
        float d0[4] = {}, d1[4] = {}, dm[4] = {};
        uint32_t q[16], km[4];
#pragma unroll
        for (int e = 0; e < 4; e++) {
          ldsm4t(&q[4 * e], l16 + (e ^ t4) * 512 + CH_Q);
          SCHED();
          if (e == 1) { ldsm4t(km, t16 + CH_KM); SCHED(); }
        }
        const uint32_t xo = l4 + ((t4 * 128) ^ (tag & 2));
        pair = l16 + ((l16 ^ tag) & 256) * 3;
        asm volatile("" : "+r"(pair));
        uint64_t x[4];
#pragma unroll
        for (int i = 0; i < 4; i++) {
          const int r = i & 1 ? r2 : r1;
          asm volatile("mov.b64 %0, {%1, %2};" : "=l"(x[i]) : "r"(mapa(xo, r) + CH_SX + (i & 1) * 1024 + (i & 2) * 256), "r"(mapa(sb + MB_X, r)));
        }
        SCHED();
        mma16(d0, q[0], q[1], q[2], q[3], kf[0], kf[1]);
        SCHED();
        mma16(d1, q[4], q[5], q[6], q[7], kf[2], kf[3]);
        SCHED();
        mma16(dm, q[0], q[1], q[2], q[3], hadd2(km[0], km[2]), hadd2(km[1], km[3]));
        mma16(d0, q[8], q[9], q[10], q[11], kf[4], kf[5]);
        SCHED();
        mma16(d1, q[12], q[13], q[14], q[15], kf[6], kf[7]);
        if (!more) continue;
        const uint32_t w1 = pack2(dm[0] + dm[2], dm[1] + dm[3]);
        st_async32((uint32_t)x[2], w1, x[2] >> 32);
        st_async32((uint32_t)x[3], w1, x[3] >> 32);
        SCHED();
        const uint32_t w0 = pack2((d0[0] + d0[2]) + (d1[0] + d1[2]), (d0[1] + d0[3]) + (d1[1] + d1[3]));
        st_async32((uint32_t)x[0], w0, x[0] >> 32);
        st_async32((uint32_t)x[1], w0, x[1] >> 32);
        sts32(xo + CH_SO, w0);
        sts32(xo + CH_SO + 512, w1);
      }
      TM(3);
      float sc[3][4] = {};
      uint32_t wd[12];
      uint32_t redo;
      auto attend = [&](auto first) {
        uint4 vb[6];
        uint32_t vm[6];
        float e[10];
        uint32_t ow[6];
        if (first.value) {
          const uint2 id = lds64(l8 + CH_ID);
          bar_sync(NB_W1V, 160);
          uint32_t r[8];
          ldsm4(r, l16 + CH_SO); ldsm4(r + 4, l16 + CH_SO + 512);
#pragma unroll
          for (int u = 0; u < 6; u++) vb[u] = ldsm4v(pair + t4 * 256 + CH_V + u * 2048);
          bar_arrive(NB_PRE, 256);
          const uint32_t sxa = pair + CH_SX;
          SCHED();
          mma8(sc[0], r[0], r[1], id.x);
          mma8(sc[1], r[2], r[3], id.x);
          mma16(sc[2], r[4], r[5], r[6], r[7], id.x, id.y);
          TM(7);
          mbar_wait(sb + MB_X, s & 1);
          TM(4);
          uint32_t t[16];
          ldsm4(t, sxa); ldsm4(t + 4, sxa + 256); ldsm4(t + 8, sxa + 512);
          SCHED();
          mma16(sc[0], t[0], t[1], t[2], t[3], id.x, id.y);
          ldsm4(t + 12, sxa + 768);
          SCHED();
          mma16(sc[1], t[4], t[5], t[6], t[7], id.x, id.y);
          ldsm4(vm, pair + t4 * 256 + CH_VX);
          SCHED();
          e[0] = ex2(sc[0][0]);
          mma16(sc[2], t[8], t[9], t[10], t[11], id.x, id.y);
          ldsm2(vm + 4, l16 + t4 * 256 + CH_VX + 2048);
          SCHED();
          e[1] = ex2(sc[0][1]);
          ldsm4t(&wd[0], wo);
          SCHED();
          e[2] = ex2(sc[0][2]);
          SCHED();
          e[3] = ex2(sc[0][3]);
          mma16(sc[2], t[12], t[13], t[14], t[15], id.x, id.y);
          SCHED();
          e[4] = ex2(sc[1][0]);
          ldsm4t(&wd[4], wo + 4096);
          SCHED();
          e[5] = ex2(sc[1][1]);
        } else {
#pragma unroll
          for (int u = 0; u < 6; u++) vb[u] = ldsm4v(pair + t4 * 256 + CH_V + u * 2048);
          ldsm4(vm, pair + t4 * 256 + CH_VX);
          ldsm2(vm + 4, l16 + t4 * 256 + CH_VX + 2048);
        }
        float o[3][4] = {};
        if (!first.value) {
#pragma unroll
          for (int i = 0; i < 6; i++) e[i] = ex2(sc[i >> 2][i & 3]);
        }
        const uint32_t p1 = pack2(e[0], e[1]), p2 = pack2(e[2], e[3]);
        float l = (e[0] + e[1]) + (e[2] + e[3]);
        asm volatile("" : "+f"(l));
        SCHED();
        e[6] = ex2(sc[1][2]);
        mma16(o[0], vb[0].x, vb[0].y, vb[0].z, vb[0].w, p1, p2);
        if (first.value) { sc[2][0] += sc[2][2]; sc[2][1] += sc[2][3]; }
        SCHED();
        e[7] = ex2(sc[1][3]);
        mma16(o[1], vb[2].x, vb[2].y, vb[2].z, vb[2].w, p1, p2);
        SCHED();
        e[8] = ex2(sc[2][0]);
        mma16(o[2], vb[4].x, vb[4].y, vb[4].z, vb[4].w, p1, p2);
        SCHED();
        e[9] = ex2(sc[2][1]);
        SCHED();
        const uint32_t p3 = pack2(e[4], e[5]), p4 = pack2(e[6], e[7]);
        l += (e[4] + e[5]) + (e[6] + e[7]);
#pragma unroll
        for (int u = 0; u < 3; u++) mma16(o[u], vb[2 * u + 1].x, vb[2 * u + 1].y, vb[2 * u + 1].z, vb[2 * u + 1].w, p3, p4);
        SCHED();
        const uint32_t p0 = pack2(e[8], e[9]);
        l += e[8] + e[9];
        const float l2 = __shfl_xor_sync(~0u, l, 1);
        if (first.value) ldsm4t(&wd[8], wo + 8192);
#pragma unroll
        for (int u = 0; u < 3; u++) mma8(o[u], vm[2 * u], vm[2 * u + 1], p0);
        redo = __any_sync(~0u, !(l > 1e-9f && l < 1e9f));
        uint32_t la = sb + CH_L + (((l4 ^ tag) >> 1) & 0x3c);
        asm volatile("" : "+r"(la));
        SCHED();
#pragma unroll
        for (int u = 0; u < 3; u++) { ow[2 * u] = pack2(o[u][0], o[u][1]); ow[2 * u + 1] = pack2(o[u][2], o[u][3]); }
#pragma unroll
        for (int u = 0; u < 6; u++) sts32(l4 + o768 + CH_O + u * 128, ow[u]);
        if (t4 == 0) sts32(la, __float_as_uint(l + l2));
      };
      attend(Int<1>());
      TM(6);
      asm volatile("{.reg .pred p; setp.eq.u32 p, %0, 0; @p bar.sync 2, 256;}" :: "r"(redo) : "memory");
      if (redo) {
        float mx = fmaxf(sc[2][0], sc[2][1]);
#pragma unroll
        for (int i = 0; i < 4; i++) mx = fmaxf(mx, fmaxf(sc[0][i], sc[1][i]));
        mx = fmaxf(mx, __shfl_xor_sync(~0u, mx, 1));
        mx = fmaxf(mx, __shfl_xor_sync(~0u, mx, 2));
#pragma unroll
        for (int i = 0; i < 4; i++) { sc[0][i] -= mx; sc[1][i] -= mx; }
        sc[2][0] -= mx; sc[2][1] -= mx;
        attend(Int<0>());
        bar_arrive(NB_O, 256);
      }
      {
        float z[4] = {};
        const uint32_t scr = l8 + ((CH_V + r1 * 4096) ^ (tag & 2));
        uint32_t ow[6], we[12];
        __syncwarp();
        ldsm4t(ow, l16 + o768 + CH_O);
        ldsm2t(ow + 4, l16 + o768 + CH_O + 512);
        if (j == 0) {
          float y[4] = {};
#pragma unroll
          for (int u = 0; u < 3; u++) ldsm4t(&we[4 * u], (wo ^ 32) + u * 4096);
          SCHED();
#pragma unroll
          for (int u = 0; u < 3; u++) {
            mma16(z, wd[4 * u], wd[4 * u + 1], wd[4 * u + 2], wd[4 * u + 3], ow[2 * u], ow[2 * u + 1]);
            mma16(y, we[4 * u], we[4 * u + 1], we[4 * u + 2], we[4 * u + 3], ow[2 * u], ow[2 * u + 1]);
          }
          sts64f(scr + t4 * 256 + 2048, y[0], y[1]); sts64f(scr + t4 * 256 + 3072, y[2], y[3]);
        } else {
#pragma unroll
          for (int u = 0; u < 3; u++) mma16(z, wd[4 * u], wd[4 * u + 1], wd[4 * u + 2], wd[4 * u + 3], ow[2 * u], ow[2 * u + 1]);
        }
        sts64f(scr + t4 * 256, z[0], z[1]); sts64f(scr + t4 * 256 + 1024, z[2], z[3]);
        bar_sync(NB_W1, 128);
        if (j == 0 || t4 < 2) {
          float2 q[4];
          const float4 l = lds128f(sb + CH_L + ((l16 ^ tag) & 0x30));
#pragma unroll
          for (int i = 0; i < 4; i++) q[i] = lds64f(scr + t4 * 1024 + i * 256);
          SCHED();
          stg_strong32(pdst[0] + ((l4 ^ tag) & 0x7c), pack_tag(((q[0].x + q[1].x) + (q[2].x + q[3].x)) * rcp(l.x + l.y), ((q[0].y + q[1].y) + (q[2].y + q[3].y)) * rcp(l.z + l.w), tag));
        }
      }
      TM(2);
    }
    bar_sync(NB_ST, 384);
    tag ^= 0x10001;
  } while (++s < NSEG);
  if (WG == 1) {
    const uint2 a = lds64(t8 + t4 * 256 + CH_KM), b = lds64(t8 + t4 * 256 + CH_KM + 256);
    sts64(t8 + CH_M, hadd2(a.x, b.x), hadd2(a.y, b.y));
  }
  bar_arrive(NB_PRE2, 288);
}

__device__ __forceinline__ void chain_comm(const ChainParams& p, const uint32_t sb, const CUtensorMap* maps) {
  [[maybe_unused]] constexpr int WG = 2;
  const int tid = threadIdx.x & 127, t4 = __shfl_sync(~0u, tid >> 5, 0), lane = tid & 31;
  const int cta = blockIdx.x, h = cta / 3, j = cta - 3 * h, colbase = cta * 64;
  const uint8_t* const xs = reinterpret_cast<const uint8_t*>(g_xn);
  auto xload = [&](int seg, int i) { tma_load5_one(sb + CH_X + i * 10240, &p.xc, 0, seg * 4, 2 * i, sb + MB_T); };
  uint32_t smid; asm("mov.u32 %0, %%smid;" : "=r"(smid));
  if (t4 == 3) {
    const bool one = elect();
#pragma unroll 1
    for (int i = 0; i < 19 + CH_FLY; i++) {
      if (i >= CH_FLY) mbar_wait(sb + MB_W + 8 * ((i - CH_FLY) & 7), (i - CH_FLY) >> 3 & 1);
      if (i == 11 + CH_FLY && one) mbar_arrive(sb + MB_WQ);
      if (i == 8) { bar_sync(NB_PROJ2, 288); PRO(1); }
      if (i == 12) { bar_sync(NB_PRE2, 288); PRO(2); }
      if (i == 0) { bar_arrive(NB_ST, 384); bar_arrive(NB_PUB, 384); bar_arrive(NB_XFREE, 256); }
      if (i < 19 && one) {
        const int n = (i & 1) * 2 + (i >> 1 & 1), k = i - 12;
        const uint32_t bar = sb + MB_W + 8 * (i & 7);
        mbar_expect(bar, k < 0 ? 20480 : 12288);
        if (k < 0) tma_load(sb + ((i & 4) + n) * 20480, i >= 8 ? &p.wq : (i ^ i >> 2) & 1 ? &p.wv : &p.wk, colbase, n * 160, bar);
        else tma_load(sb + CH_WO + k * 12288, &p.wo, k < 6 ? j * 192 + k * 32 : j == 0 ? 576 : 592 + j * 16, h * 192, bar);
      }
    }
  } else {
    const uint32_t part = max(ldg_strong32(g_smpart + (smid & 255)), 1u);
    if (tid == 0) prefetch_l2(p.mem0, 10240);
    if (tid == 64) stg_strong32(p.sync + SY_PART + cta, part);
    if (t4 == 1) {
      wait_count(p.sync + SY_P + 1, ln_items(p.layer, 0));
      mbar_expect_one(sb + MB_T, 40960);
#pragma unroll 1
      for (int i = 0; i < 4; i++) xload(0, i);
      PRO(0);
    }
    uint32_t reader, orient;
    for (int n = 0;; spin_guard(n)) {
      reader = ldg_strong32(p.sync + SY_PART + (tid >= 80 ? cta : tid));
      orient = ldg_strong32(g_orient + min(tid, NSLOT - 1));
      if (__all_sync(~0u, reader && orient)) break;
    }
    const uint32_t near = __ballot_sync(~0u, reader == part) >> (cta & 7) & 0xffff;
    if (tid < NSLOT) sts32(sb + CH_TAB + tid * 4, tid * 8192 + (orient == reader ? 0 : 4096));
    if (tid == 0) sts32(sb + CH_TAB + NSLOT * 4, cta < 80 ? cta : (cta & 7) + max(__ffs(near) - 1, 0));
    if (t4 == 1) PRO(3);
    bar_sync(NB_ST, 384);
    bar_arrive(NB_PUB, 384);
    if (t4 == 1) PRO(4);
    const uint32_t id = (lane >> 3) == (lane & 3) ? ((lane & 4) ? 0x3f800000u : 0x00003f80u) : 0u;
    if (t4 == 0) sts64(sb + CH_ID + lane * 8, id, id);
#pragma unroll 1
    for (int q = t4; q < 4; q += 3) {
      uint32_t m0[20];
#pragma unroll
      for (int i = 0; i < 20; i++) m0[i] = (reinterpret_cast<const uint32_t*>(p.mem0) + (lane >> 2) * (DM / 2) + q * 80 + (lane & 3))[i * 4];
      if (q < 3) bar_sync(NB_XFREE, 256);
#pragma unroll
      for (int i = 0; i < 20; i += 4) stsm4t(sb + CH_M + (q * 20 + i) * 128 + lane * 16, m0[i], m0[i + 1], m0[i + 2], m0[i + 3]);
    }
    if (t4 == 1) PRO(5);
  }
  if (cta < 4 && cta * 128 + tid < SY_N) p.other[cta * 128 + tid] = 0;
  asm volatile("barrier.cluster.wait.aligned;" ::: "memory");
  const uint32_t l8 = opaque(sb + t4 * 256 + lane * 8);
  bar_sync(NB_MEM, 384);
  uint8_t* const pool = pool_at(0);
  const uint8_t* const psrc = pool + opaque(lds32(sb + CH_TAB + lds32(sb + CH_TAB + NSLOT * 4) * 4) + t4 * 1024 + lane * 4);
  const uint32_t mdst = opaque((80 + cta / 20) * 8192 + (t4 & 1) * 4096 + (cta % 20) * 128 + lane * 4);
  int st = 0;
  uint32_t tag = 1, span = ~0u;
  auto send_tokens = [&](int s) {
    uint8_t* dst = g_kv + ((s >> 2) * 192 + cta + 3 * h) * KV_PART + (s & 3) * KV_SEG;
    bulk_store(dst, sb + CH_K, 4096);
    bulk_store(dst + KV_V, sb + CH_V + j * 4096, 4096);
    bulk_commit();
  };
  auto send_memory = [&](int s, uint32_t km) {
    fence_async();
    uint8_t* dst = g_kv + ((s >> 2) * 192 + cta + 3 * h) * KV_PART + KV_M + (s & 3) * KV_SEG;
    bulk_store(dst, km, 1024);
    bulk_store(dst + KV_V, sb + CH_VX + j * 1024, 1024);
    bulk_commit();
    bulk_wait<0>();
    if ((s & 3) == 3) { fence_async_global(); atomicAdd(p.sync + (s >> 2) * 8 + 4, 1); }
  };
#pragma unroll 1
  for (int s = 0; s < NSEG - 1; s++) {
    TM(0);
    STAT(0);
    if (t4 == 0) {
      if (elect()) {
        fence_async();
#pragma unroll 1
        for (int r = j + 1; r < j + 3; r++) bulk_push(mapa(sb + CH_V + j * 4096, r % 3), sb + CH_V + j * 4096, 4096, mapa(sb + MB_V, r % 3));
        send_tokens(s);
        bulk_wait_read<0>();
      }
      __syncwarp();
    }
    uint32_t c0, g0;
    if (t4 == 1) {
      __syncwarp();
      c0 = clk32(); g0 = gtime();
      if (elect()) atomicMax(p.sync + SY_TIME + s, g0);
    }
    if (t4 == 3 && s >= NSEG - 6 && elect()) asm volatile("prefetch.tensormap [%0];" :: "l"(maps + (NSEG - 2 - s)) : "memory");
    if (t4 == 3 && (s & 3) == 2 && s < NSEG - 2) wait_count(p.sync + SY_P + 5 + (s & ~3), ln_items(p.layer, (s >> 2) + 1));
    if (t4 == 2) { mbar_wait(sb + MB_V, s & 1); bar_arrive(NB_W1V, 160); }
    bar_sync(NB_PROJ2, 256);
    if (t4 == 0) {
      mbar_expect_one(sb + MB_X, 4096);
      mbar_expect_one(sb + MB_T, 40960);
      for (int i = 0; i < 3; i++) xload(s + 1, i);
    }
    __syncwarp();
    STAT(1);
    TM(1);
    {
      const uint2 a = lds64(l8 + t4 * 256 + CH_KM), b = lds64(l8 + t4 * 256 + CH_KM + 256);
      sts64(l8 + CH_KS, hadd2(a.x, b.x), hadd2(a.y, b.y));
    }
    TM(4);
    bar_sync(NB_PRE2, 256);
    if (t4 == 0) xload(s + 1, 3);
    if (t4 == 0 && elect()) {
      if (CH_XPF && s < NSEG - 2) prefetch_l2(xs + (s + 2) * 40960 + cta % 20 * 2048, 2048);
      if (CH_TPF && s >= NSEG - 7) {
        const int i = s - (NSEG - 7);
        if (i < 2) prefetch_l2(p.wb + (cta * 2 + i) * 12800, 12800);
        else if (i < 4) prefetch_l2(xs + (cta * 2 + i - 2) * 8192, 8192);
        else prefetch_l2(g_q + 15 * 32 * 3072 + (cta * 2 + i - 4) * 512, 8192);
      }
      send_memory(s, sb + CH_KS);
    }
    __syncwarp();
    if (t4 == 1) {
      const uint32_t late = min(ldg_strong32(p.sync + SY_TIME + s) - g0, 640u);
      if (elect()) sts32(sb + CH_TAB + 380, c0 + span + (late * 115 >> 6) + (j ? 60 : 0) + p.d1);
    }
    bar_sync(NB_W2, 128);
    uint32_t due = lds32(sb + CH_TAB + 380);
    due = __shfl_sync(~0u, due, 0);
    const uint8_t* ms = pool + (lds32(sb + CH_TAB + (80 + st * 4 + t4) * 4) + (l8 & 255));
    uint8_t* md = pool + (mdst + (cta >= 80 ? 2 : t4 < 2 ? st : st == 2 ? 0 : st + 1) * 32768);
    asm volatile("" : "+l"(ms), "+l"(md));
    if (CH_TW) mbar_wait(sb + MB_T, ~s & 1);
    TM(2);
    bar_sync(NB_ST, 384);
    __syncwarp();
    uint32_t tg = clk32();
    if (t4 == 3 && elect()) {
      if (s < NSEG - 2) mbar_expect(sb + MB_V, 8192);
      mbar_arrive_remote(mapa(sb + MB_F, j == 2 ? 0 : j + 1));
      mbar_arrive_remote(mapa(sb + MB_F, j == 0 ? 2 : j - 1));
    }
    if (s == NSEG - 2) work_init(sb, t4);
    __syncwarp();
    STAT(2);
    {
      float2 q[4];
      TM(3);
      if (t4 == 1 && s) span = min(span, tg - c0);
      until(s < 2 ? tg + 400 : (int)(due - tg) > p.dn ? due : tg + p.dn);
      for (int n = 0;;) {
        uint32_t v[8];
#pragma unroll
        for (int i = 0; i < 8; i++) v[i] = ldg_strong32(psrc + i * 128);
        sts64f(l8 + CH_R2, ((bf_lo(v[0]) + bf_lo(v[1])) + (bf_lo(v[2]) + bf_lo(v[3]))) + ((bf_lo(v[4]) + bf_lo(v[5])) + (bf_lo(v[6]) + bf_lo(v[7]))),
               ((bf_hi(v[0]) + bf_hi(v[1])) + (bf_hi(v[2]) + bf_hi(v[3]))) + ((bf_hi(v[4]) + bf_hi(v[5])) + (bf_hi(v[6]) + bf_hi(v[7]))));
        uint32_t bad;
        asm volatile("{.reg .pred p, q; .reg .b32 a; lop3.b32 a, %1, %2, %3, 0xFE; lop3.b32 a, a, %4, %6, 0xA8; setp.ne.u32 p, a, 0;\n"
                     "bar.red.or.pred q, %5, 128, p; selp.u32 %0, 1, 0, q;}"
                     : "=r"(bad) : "r"(differ(v[0], v[1], tag)), "r"(differ(v[2], v[3], tag)), "r"(differ(v[4], v[5], tag)), "r"(differ(v[6], v[7], tag)), "n"((int)NB_W2),
                       "r"((uint32_t)(cta < 80 || n < 3)) : "memory");
#pragma unroll
        for (int k = 0; k < 4; k++) asm volatile("ld.volatile.shared.v2.f32 {%0,%1}, [%2];" : "=f"(q[k].x), "=f"(q[k].y) : "r"(l8 - t4 * 256 + CH_R2 + k * 256) : "memory");
        TMV(12, n);
        if (!__any_sync(~0u, bad)) break;
        spin_guard(n);
      }
      bar_arrive(NB_PUB, 384);
      SCHED();
      TM(9);
      stg_strong32(md, min(nz(pack2((q[0].x + q[1].x) + (q[2].x + q[3].x), (q[0].y + q[1].y) + (q[2].y + q[3].y))), t4 < 2 ? ~0u : 0u));
      tg = clk64() + p.d2;
      if (s >= 2 && (int)(due + p.dx - tg) > 0) tg = due + p.dx;
      TM(8);
    }
    STAT(3);
    until(tg);
    TM(10);
    for (int n = 0;;) {
      uint2 g[10];
#pragma unroll
      for (int i = 0; i < 10; i++) g[i] = ldg_strong64(ms + i * 256);
      if (n == 0) bar_sync(NB_XFREE, 256);
      uint32_t m = ~0u, bad;
#pragma unroll
      for (int i = 0; i < 10; i++) { sts64(l8 + CH_M + t4 * 2304 + i * 256, g[i].x, g[i].y); m = __vimin3_u32(m, g[i].x, g[i].y); }
      TMV(13, n);
      TM(11);
      asm volatile("{.reg .pred p; setp.eq.u32 p, %1, 0; vote.sync.any.pred p, p, 0xffffffff; @!p bar.sync %2, 384; selp.u32 %0, 1, 0, p;}" : "=r"(bad) : "r"(m), "n"((int)NB_MEM) : "memory");
      if (!bad) break;
      spin_guard(n);
    }
    if (++st == 3) st = 0;
    tag ^= 0x10001;
  }
  if (t4 == 0) {
    if (elect()) { fence_async(); send_tokens(NSEG - 1); }
    __syncwarp();
    bar_sync(NB_PRE2, 288);
    if (elect()) {
      send_memory(NSEG - 1, sb + CH_M);
      asm volatile("mbarrier.arrive.shared::cta.b64 _, [%0], 8;" :: "r"(sb + WK_BAR + 64) : "memory");
    }
    __syncwarp();
  }
}

__device__ __forceinline__ void chain_start(const ChainParams& p, const uint32_t sb, const int warp) {
  if (warp == 1 && elect()) {
#pragma unroll
    for (int i = 0; i < 6; i++) mbar_init(sb + CH_BAR + 8 * i, i == 2 ? 5 : i == 5 ? 2 : 1);
    asm volatile("fence.mbarrier_init.release.cluster;" ::: "memory");
    mbar_expect(sb + MB_V, 8192);
    atomicAdd(p.sync + SY_UP, 1);
    asm volatile("{.reg .pred p; setp.ne.u32 p, %0, 1024; @p trap;}" :: "r"(sb & 0xffffff));
  }
  if (warp == 0 && elect()) {
#pragma unroll
    for (int i = 0; i < 8; i++) mbar_init(sb + MB_W + 8 * i, 1);
    asm volatile("fence.mbarrier_init.release.cluster;" ::: "memory");
  }
  __syncthreads();
  asm volatile("barrier.cluster.arrive.relaxed.aligned;" ::: "memory");
}

struct WorkParams {
  ChainParams ch;
  CUtensorMap wo, xn, wb[3], wq, wc[2], out;
  const __nv_bfloat16* x;
  uint32_t* sync;
  int kind, qa_end, idle;
};
#define GO_320 4
#define GO_TAIL 1
#define PF_NS 400
enum { WK_FIRST = 0, WK_LEAD = 1, WK_CHAIN = 2, WK_LAST = 3 };
enum { IT_ATT = 0, IT_OP = 1, IT_FIN = 2, IT_BQ = 3, IT_BO = 4, IT_LN = 5, IT_Q = 6, IT_LN0 = 7, IT_OUT = 8 };
constexpr int C_EARLY = 1 << 20, C_LATE = 1 << 21, C_TAIL = 1 << 22, C_PROJ = 1 << 23;

__device__ __forceinline__ uint32_t item_count(int type, int b) { return type == IT_ATT ? 32 : type == IT_OP ? op_tiles(b) * op_split(b) : type == IT_FIN ? fin_items(b) : bq_items(b); }
__device__ __forceinline__ uint32_t item_need(int type, int b) { return type == IT_ATT ? 96 : item_count(type - 1, b); }
__device__ __forceinline__ int item_cols(int type, int b) {
  return type == IT_ATT || type == IT_Q ? 192 : type == IT_OUT ? 80 : type == IT_BQ ? (b < BQ_12 ? 320 : b < BQ_24 ? 160 : 80) : type == IT_OP && b >= OP_N4 ? 160 : 320; }
__device__ __forceinline__ int item_groups(int type, int b) { const int n = type == IT_FIN ? fin_items(b) : ln_items(type == IT_LN, b); return n == 4 ? 4 : n == 8 ? 2 : 1; }
#define RES_OP 0
#define RES_B 3
#define HOLD_B 12
constexpr int RES_N = RES_OP ? op_tiles(14) * op_split(14) : 0, RES_BQ = RES_B;
__device__ __forceinline__ bool reserved(int type, int b) { return type == IT_ATT ? b == 15 : type == IT_OP ? RES_OP && b == 14 : type == IT_BQ && b < RES_BQ; }
__device__ __forceinline__ int reserved_item(int cta) {
  const int h = cta / 3, j = cta - 3 * h, i = h + (j - 1) * 32;
  if (j == 0) return C_EARLY | IT_ATT << 16 | 15 << 8 | h;
  return i < RES_N ? C_TAIL | IT_OP << 16 | 14 << 8 | i : i - RES_N < RES_BQ * 6 ? C_TAIL | IT_BQ << 16 | ((i - RES_N) / 6) << 8 | (i - RES_N) % 6 : -1;
}
constexpr int LEAD1 = 12;
__device__ __forceinline__ int lead_item(int layer, int qa_end, int i) {
  if (layer == 2) return i < 128 ? C_EARLY | C_LATE | IT_OUT << 16 | (i >> 3) << 8 | (i & 7) : -1;
  if (layer == 0) {
    if (i < 32) return IT_LN0 << 16 | (i >> 4) << 8 | (i & 15);
    if (i < 88) return IT_LN0 << 16 | ((i - 24) >> 2) << 8 | (i & 3);
    i -= 88;
  } else {
    if (i < 4) return C_EARLY | IT_BO << 16 | (i >> 1) << 8 | (i & 1);
    if (i < 12) return C_EARLY | IT_LN << 16 | ((i - 4) >> 2) << 8 | (i & 3);
    if (i < 40) return C_EARLY | IT_BO << 16 | ((i - 8) >> 1) << 8 | (i & 1);
    if (i < 96) return C_EARLY | IT_LN << 16 | ((i - 32) >> 2) << 8 | (i & 3);
    i -= 96;
  }
  return i < (16 - qa_end) * 32 ? C_PROJ | IT_Q << 16 | (qa_end + (i >> 5)) << 8 | (i & 31) : -1;
}

struct Ring {
  uint32_t sb;
  int pos, seq;
  __device__ __forceinline__ uint32_t full() const { return sb + WK_BAR + 8 * (seq & 7); }
  __device__ __forceinline__ uint32_t take(int len) { if (pos + len > WK_SLOTS) pos = 0; pos += len; seq++; return sb + (pos - len) * 8192; }
  __device__ __forceinline__ uint32_t wait(int len) { mbar_wait(full(), (seq >> 3) & 1); return take(len); }
  __device__ __forceinline__ void release(int sq) const { mbar_arrive_one(sb + WK_BAR + 64 + 8 * (sq & 7)); }
};

struct Pending {
  uint32_t w[48], done;
  uint4* dst;
  __device__ __forceinline__ void store(int i) const { dst[(i >> 2) * 1024 + (i & 3) * 32] = make_uint4(w[4 * i], w[4 * i + 1], w[4 * i + 2], w[4 * i + 3]); }
  __device__ __forceinline__ void finish() { __syncwarp(); mbar_arrive_one(done); done = 0; }
};

template <int N>
__device__ __forceinline__ void gemm_step(float* d, Ring& r, int warp, int acc) {
  const uint32_t base = r.wait(2 + (N + 63) / 64);
  const uint64_t da = mkdesc(base + (warp >> 2) * 8192, 128, 1024, 0), db = mkdesc(base + 16384, 8192, 1024, 1);
  wg_fence();
#pragma unroll
  for (int kk = 0; kk < 4; kk++) {
    if (N == 80) wg_ss80_01(d, da + kk * 16, db + kk * 128, acc | kk);
    else if (N == 160) wg_ss160_01(d, da + kk * 16, db + kk * 128, acc | kk);
    else wg_ss192_01(d, da + kk * 16, db + kk * 128, acc | kk);
    if (N == 320) wg_ss128_01(d + 96, da + kk * 16, db + kk * 128 + 3 * 512, acc | kk);
  }
  wg_commit();
}
template <int N>
__device__ __forceinline__ void gemm_item(float* d, Ring& r, int warp, int nkb, uint32_t go, int ask) {
#pragma unroll 1
  for (int kb = 0; kb < nkb; kb++) {
    gemm_step<N>(d, r, warp, kb);
    if (kb == ask && go && warp == 0) mbar_arrive_one(go);
    if (kb > 0) { wg_wait<1>(); r.release(r.seq - 2); }
  }
  wg_wait<0>();
  r.release(r.seq - 1);
}

template <class Peek>
__device__ __forceinline__ void attn_a(Ring& r, Pending& pend, Peek peek, const int warp, const int lane) {
  uint32_t (&q)[48] = pend.w;
  const int t = (warp & 1) * 16 + (lane >> 2) - 2 * (lane & 3);
  const bool second = warp & 2;
  const uint32_t rows = (warp >> 2) * 2 * KV_SEG;
  uint32_t pa[20], b2;
  float inv[2];
  bool now;
  const uint32_t b0 = r.wait(5) + rows, b1 = r.wait(5) + rows;
  {
    float s[40];
    wg_fence();
#pragma unroll
    for (int k = 0; k < 12; k++)
      wg_rs80_01(s, q[4 * k], q[4 * k + 1], q[4 * k + 2], q[4 * k + 3], mkdesc(k < 8 ? b0 : b1, 128, 1024, 0) + (k >> 2 & 1) * (KV_PART / 16) + (k & 3) * 16, k);
    wg_commit();
    now = peek();
    b2 = r.wait(5) + rows;
    wg_wait<0>();
    reg_fence<40>(s);
    r.release(r.seq - 3);
    const float k2 = 0.07216878364870322f * 1.44269504089f, NEG = -INFINITY;
#pragma unroll
    for (int i = 0; i < 20; i++) {
      s[i] = second ? s[20 + i] : s[i];
      if (i < 16 && 8 * ((i >> 2) - (i >> 1 & 1)) + (i & 1) > t) s[i] = NEG;
    }
#pragma unroll
    for (int hh = 0; hh < 2; hh++) {
      float m = NEG, l = 0.f;
#pragma unroll
      for (int n = 0; n < 5; n++) m = fmaxf(m, fmaxf(s[4 * n + 2 * hh], s[4 * n + 2 * hh + 1]));
      m = fmaxf(m, __shfl_xor_sync(~0u, m, 1)); m = fmaxf(m, __shfl_xor_sync(~0u, m, 2));
      m *= -k2;
#pragma unroll
      for (int n = 0; n < 5; n++) {
        const float x = ex2(fmaf(s[4 * n + 2 * hh], k2, m)), y = ex2(fmaf(s[4 * n + 2 * hh + 1], k2, m));
        const uint32_t w = pack2(x, y);
        l += x + y;
        pa[2 * n + hh] = second ? 0 : w; pa[10 + 2 * n + hh] = second ? w : 0;
      }
      inv[hh] = l;
    }
  }
  float o[96];
  wg_fence();
#pragma unroll
  for (int u = 0; u < 3; u++) {
#pragma unroll
    for (int k = 0; k < 5; k++)
      wg_rs64_00(o + 32 * u, pa[4 * k], pa[4 * k + 1], pa[4 * k + 2], pa[4 * k + 3], mkdesc(u ? b2 : b1, 1024, 128, 0) + (~u & 1) * (KV_PART / 16) + k * 128, k);
    wg_commit();
  }
#pragma unroll
  for (int hh = 0; hh < 2; hh++) { float l = inv[hh]; l += __shfl_xor_sync(~0u, l, 1); l += __shfl_xor_sync(~0u, l, 2); inv[hh] = rcp(l); }
#pragma unroll
  for (int u = 0; u < 3; u++) {
    if (u == 0) wg_wait<2>(); else if (u == 1) wg_wait<1>(); else wg_wait<0>();
    reg_fence<32>(o + 32 * u);
    if (u != 1) r.release(r.seq - 2 + u / 2);
#pragma unroll
    for (int i = 0; i < 16; i++) { const float* x = &o[32 * u + 4 * (i & 7) + (i >> 2 & 2)]; q[16 * u + i] = pack2(x[0] * inv[i >> 3], x[1] * inv[i >> 3]); }
    if (now) {
#pragma unroll
      for (int i = 0; i < 4; i++) pend.store(4 * u + i);
    }
  }
}

__device__ __forceinline__ void ln_groups(Ring& ring, uint32_t scratch, int planes, int rg, bool two) {
  constexpr int G = 2;
  const int warp = fresh_tid() >> 5, lane = fresh_tid() & 31;
  const uint32_t id = (lane >> 3) == (lane & 3) ? ((lane & 4) ? 0x3f800000u : 0x00003f80u) : 0u;
  const uint32_t at = (warp * 160 + lane) * 8, at1 = planes > 1 ? at : (lane >> 2) * 1280 + warp * 160 + (lane & 3) * 4;
  const uint32_t step = planes > 1 ? 256 : 32, half = planes > 1 ? 4 : 16;
  float v[G][5][4] = {};
#pragma unroll
  for (int r = 0; r < G; r++) {
#pragma unroll 1
    for (int k = r && !two ? 0 : planes; k > 0; k -= 4) {
      const uint32_t a = ring.wait(min(k, 4) + 1);
      if (k == 1) {
#pragma unroll
        for (int i = 0; i < 5; i++) mma8(v[r][i], lds32(a + at1 + i * step), lds32(a + at1 + i * step + half), id);
      } else {
#pragma unroll
        for (int i = 0; i < 10; i++) {
          if (i == 5 && k < 4) break;
          const uint2 x = lds64(a + at + i / 5 * 20480 + i % 5 * 256), y = lds64(a + at + i / 5 * 20480 + 10240 + i % 5 * 256);
          mma16(v[r][i % 5], x.x, x.y, y.x, y.y, id, id);
        }
      }
      ring.release(ring.seq - 1);
    }
  }
  uint2 xr[G][5];
  float mw[G];
  scratch += (lane >> 2) * 64;
#pragma unroll
  for (int r = 0; r < G; r++) {
    float m = 0.f, q2[4] = {};
#pragma unroll
    for (int i = 0; i < 5; i++) {
      float* t = v[r][i];
      xr[r][i] = make_uint2(pack2(t[0], t[1]), pack2(t[2], t[3]));
      t[0] = bf_lo(xr[r][i].x); t[1] = bf_hi(xr[r][i].x); t[2] = bf_lo(xr[r][i].y); t[3] = bf_hi(xr[r][i].y);
      m += (t[0] + t[1]) + (t[2] + t[3]);
    }
    m += __shfl_xor_sync(~0u, m, 1); m += __shfl_xor_sync(~0u, m, 2);
    m *= 1.f / 80;
#pragma unroll
    for (int i = 0; i < 20; i++) { float& t = v[r][i >> 2][i & 3]; t -= m; q2[i & 3] = fmaf(t, t, q2[i & 3]); }
    float q = (q2[0] + q2[1]) + (q2[2] + q2[3]);
    mw[r] = m;
    q += __shfl_xor_sync(~0u, q, 1); q += __shfl_xor_sync(~0u, q, 2);
    if ((lane & 3) == 0) sts64f(scratch + r * 512 + warp * 8, m, q);
  }
  bar_sync(1, 256);
#pragma unroll
  for (int r = 0; r < G; r++) {
    const float4 t = lds128f(scratch + r * 512 + (lane & 3) * 16);
    float mean = t.x + t.z;
    mean += __shfl_xor_sync(~0u, mean, 1); mean += __shfl_xor_sync(~0u, mean, 2);
    mean *= 0.125f;
    float var = (t.y + t.w) + 80.f * ((t.x - mean) * (t.x - mean) + (t.z - mean) * (t.z - mean));
    var += __shfl_xor_sync(~0u, var, 1); var += __shfl_xor_sync(~0u, var, 2);
    float rs;
    asm("rsqrt.approx.ftz.f32 %0, %1;" : "=f"(rs) : "f"(var * (1.f / DM) + 1e-5f));
#pragma unroll
    for (int i = 0; i < 20; i++) v[r][i >> 2][i & 3] = fmaf(v[r][i >> 2][i & 3], rs, (mw[r] - mean) * rs);
  }
#pragma unroll
  for (int r = 0; r < G; r++) {
    if (r && !two) break;
    uint32_t* xn = g_xn + (rg + r) * 2560 + warp * 320 + lane;
#pragma unroll
    for (int i = 0; i < 10; i++) xn[i * 32] = pack2(v[r][i >> 1][2 * (i & 1)], v[r][i >> 1][2 * (i & 1) + 1]);
#pragma unroll
    for (int i = 0; i < 5; i++) g_x[(rg + r) * 17 * 1280 + warp * 160 + i * 32 + lane] = xr[r][i];
  }
}

__device__ __forceinline__ void store_partial(const float* d, int b, int split, int unit, int nu) {
  uint2* dst = g_x + (((b * 16 + (fresh_tid() >> 5) * 2) * 17 + 1 + split) * 40 + unit) * 32 + (fresh_tid() & 31);
#pragma unroll
  for (int u = 0; u < 20; u++) {
    if (u == 10 && nu == 10) break;
    dst[u * 32] = make_uint2(pack2(d[8 * u], d[8 * u + 1]), pack2(d[8 * u + 4], d[8 * u + 5]));
    dst[(680 + u) * 32] = make_uint2(pack2(d[8 * u + 2], d[8 * u + 3]), pack2(d[8 * u + 6], d[8 * u + 7]));
  }
}

__device__ __forceinline__ void store_bqkv(const float* d, int b, int idx, int nh) {
  const int lane = fresh_tid() & 31, c = lane & 3, rg = b * 16 + (fresh_tid() >> 5) * 2, h0 = idx * nh;
  const float sc = h0 < 32 ? 0.22360679775f * 1.44269504089f : 1.f;
  const bool lo = c < 2;
  uint32_t* da = g_bqkv + (h0 * 256 + rg) * 96 + lane;
  uint32_t* db = da + 256 * 96 + (lo ? 2 : -2);
  uint32_t pad[2];
#pragma unroll
  for (int r = 0; r < 2; r++) pad[r] = !(c & 1) && (h0 >= 64 || (h0 >= 32 && (lane & 4) && poly_group(rg + r))) ? 0x00003f80u : 0u;
#pragma unroll
  for (int q = 0; q < 8; q++) {
    if ((q == 2 || q == 4) && nh == 2 * q) break;
#pragma unroll
    for (int r = 0; r < 2; r++) {
      uint32_t w[5];
#pragma unroll
      for (int i = 0; i < 5; i++) w[i] = pack2(d[20 * q + 4 * i + 2 * r] * sc, d[20 * q + 4 * i + 2 * r + 1] * sc);
      const int o = q * 2 * 256 * 96 + r * 96;
      da[o] = w[0]; da[o + 32] = w[1]; da[o + 64] = lo ? w[2] : pad[r];
      db[o] = lo ? w[3] : w[2]; db[o + 32] = lo ? w[4] : w[3]; db[o + 64] = lo ? pad[r] : w[4];
    }
  }
}

__device__ __forceinline__ void work_loader(const WorkParams& p, const uint32_t sb, const bool weights) {
  const uint32_t bars = sb + WK_BAR, bIF = bars + 128, bIE = bars + 160, bGo = bars + 224, slots = bars + 272;
  int pos = 0, seq = 0, tail = 0, used = 0;
  uint32_t lens = 0;
  if (p.kind == WK_CHAIN) {
    seq = 1; used = lens = 8;
    mbar_arrive_one(bars);
  }
#pragma unroll 1
  for (int n = 0, part = 0;;) {
    if (part == 0) mbar_wait(bIF + 8 * (n & 3), (n >> 2) & 1);
    const int code = __shfl_sync(~0u, (int)lds32(slots + 4 * (n & 3)), 0);
    if (code < 0) break;
    const int type = (code >> 16) & 15, b = (code >> 8) & 255, idx = code & 255;
    const bool qa = code & C_PROJ, ln = type == IT_FIN || type == IT_LN || type == IT_LN0;
    const int parts = ln ? item_groups(type, b) : type == IT_ATT ? 2 : 1;
    {
      int bytes = 163840, chunk = 40960, nb = 0, flag = b * 8 + 4 + type, need = item_need(type & 3, b), c0 = 0, c3 = idx, c4 = 0, s3 = 0, s4 = 64;
      const uint8_t* src = g_kv + (b * 32 + idx) * 6 * KV_PART;
      const CUtensorMap* m = nullptr;
      if (ln) {
        const int rg = b * 16 + idx * parts + part;
        bytes = (type == IT_FIN ? op_split(b) + 1 : type == IT_LN ? 2 : 1) * 10240;
        src = type == IT_LN0 ? reinterpret_cast<const uint8_t*>(p.x) + rg * 10240 : reinterpret_cast<const uint8_t*>(g_x) + rg * 174080;
        if (type == IT_LN) { flag = SY_P + b * 4; need = 2; }
        if (type == IT_LN0 || part) need = 0;
      } else if (part) {
        bytes = 6 * KV_PART;
      } else if (type == IT_ATT && !qa) {
        bytes = chunk = 49152;
        src = reinterpret_cast<const uint8_t*>(g_q) + (b * 32 + idx) * 49152;
        flag = SY_P + b * 4 + 3; need = 32;
      } else {
        const int cols = item_cols(type, b);
        chunk = 16384; nb = (cols + 63) >> 6;
        src = reinterpret_cast<const uint8_t*>(g_of) + b * 163840;
        if (type == IT_OP) {
          const int nkb = op_steps(b), kb0 = (idx >> op_tiles(b) / 2) * nkb;
          bytes = nkb * 16384;
          src = reinterpret_cast<const uint8_t*>(g_o) + (b * 96 + kb0) * 16384;
          if (weights) m = &p.wo;
          c0 = (idx & (op_tiles(b) - 1)) * cols; c3 = 0; c4 = kb0 * 2; s4 = 2;
        } else if (type == IT_BQ) {
          m = weights ? &p.wb[cols >> 7] : &p.xn;
        } else if (type == IT_BO || type == IT_OUT) {
          if (weights) m = &p.wc[cols >> 8];
          flag = SY_OB; need = type == IT_BO && b < 2 ? 32 : -1;
        } else {
          m = weights ? &p.wq : &p.xn;
          c3 = 0; c4 = idx * 3; s3 = 64; s4 = 0;
          flag = SY_P + b * 4 + 1; need = ln_items(p.ch.layer, b);
        }
      }
      if (!weights) {
        c3 = b * 16; c4 = s3 = s4 = 0;
        if (need < 0) pdl_wait(); else if (need) wait_count(p.sync + flag, need);
        if ((ln ? !part : part && (!qa || (code & C_EARLY)))) mbar_arrive_one(bGo);
      }
      if (++part == parts) { mbar_arrive_one(bIE + 8 * (n & 3)); part = 0; n++; }
      const int boxes = weights && !s3 ? nb : m != nullptr;
#pragma unroll 1
      for (; bytes > 0; bytes -= chunk) {
        const int now = min(bytes, chunk), len = ((now + 8191) >> 13) + nb, skip = pos + len > WK_SLOTS ? WK_SLOTS - pos : 0, sh = 4 * (seq & 7);
        used += len + skip;
        while (used > WK_SLOTS || seq - tail >= 8) {
          mbar_wait(bars + 64 + 8 * (tail & 7), (tail >> 3) & 1);
          used -= (lens >> 4 * (tail & 7)) & 15;
          tail++;
        }
        lens = (lens & ~(15u << sh)) | (len + skip) << sh;
        if (pos + len > WK_SLOTS) pos = 0;
        const uint32_t bar = bars + 2 * sh, dst = sb + pos * 8192 + weights * 16384;
        mbar_expect_one(bar, weights ? nb * 8192 : now);
#pragma unroll 1
        for (int i = 0; i < boxes; i++)
          tma_load5_one(dst + i * 8192, m, c0 + i * 64, c3, c4, bar);
        if (!weights && !m) bulk_load_last_one(dst, src, now, bar);
        c3 += s3; c4 += s4;
        if (!weights) c0 += 128;
        src += chunk; pos += len; seq++;
      }
    }
  }
}

__global__ void __launch_bounds__(384, 1) work_kernel(const __grid_constant__ WorkParams p) {
  extern __shared__ __align__(1024) uint8_t smem_raw[];
  const uint32_t sb = s2u(smem_raw), bars = sb + WK_BAR;
  const uint32_t bIF = bars + 128, bIE = bars + 160, done = bars + 192, bGo = bars + 224, slots = bars + 272, scratch = bars + 384;
  const int warp = __shfl_sync(~0u, threadIdx.x >> 5, 0);
  uint32_t* const sync = p.sync;
  TRACE(0);
  pdl_launch();
  if (p.kind == WK_LEAD && !helper_sm() && __any_sync(~0u, __syncthreads_or(threadIdx.x == 0 && ldg_strong32(sync + SY_PRE + 1) >= LEAD1))) { pdl_wait(); return; }
  if (p.kind == WK_CHAIN) {
    chain_start(p.ch, sb, warp);
  } else {
    if (warp < 4) work_init(sb, warp);
    __syncthreads();
    if (p.kind == WK_FIRST) {
      if (!(warp & 13)) probe_slots(bars + 320);
      if (!helper_sm()) return;
    }
  }
  if (warp >= 8) {
    asm volatile("setmaxnreg.dec.sync.aligned.u32 40;");
    if (p.kind == WK_CHAIN) chain_comm(p.ch, sb, &p.wo);
    const int warp = __shfl_sync(~0u, fresh_tid() >> 5, 0), lane = fresh_tid() & 31;
    if (warp == 9) {
      const bool keep = p.kind > WK_LEAD || helper_sm();
      int n = 0, code = p.kind == WK_CHAIN ? reserved_item(blockIdx.x) : -1;
      if (code >= 0) {
        sts32(slots, code);
        mbar_arrive_one(bIF);
        n = 1;
      }
      const int b = lane & 15, layer = p.kind == WK_LAST ? 2 : sync != g_sync;
      bool first = layer == 1, lead = p.kind != WK_CHAIN;
      for (;; n++) {
        if (n > 0) mbar_wait(bGo, (n - 1) & 1);
        mbar_wait(bIE + 8 * (n & 3), ((n >> 2) & 1) ^ 1);
        code = -1;
        if (lead) {
          int i = blockIdx.x + n * 256;
          if (first) { i = __reduce_add_sync(~0u, atomic_inc_one(sync + SY_PRE + 1)); first = i < LEAD1; }
          if (layer < 2 && !first) {
            i = 1 << 20;
            if (keep) i = __reduce_add_sync(~0u, atomic_inc_one(sync + SY_PRE)) + layer * LEAD1; else pdl_wait();
          }
          code = lead_item(layer, p.qa_end, i);
          lead = code >= 0 || layer == 2 || !keep;
          if (!lead && p.kind <= WK_LEAD) {
            const uint32_t t0 = gtime();
            while (!lead && __all_sync(~0u, ldg_strong32(sync + SY_UP) < 96)) lead = __any_sync(~0u, gtime() - t0 > 20000);
          }
        }
        if (!lead) {
          int spin = 0;
          const int ticket = atomic_inc_one(sync + SY_T);
          for (;;) {
            const uint4 hd = ldg_strong128(sync + b * 8), pr = ldg_strong128(sync + b * 8 + 4);
            const uint32_t hv[4] = {hd.x, hd.y, hd.z, hd.w}, pv[4] = {pr.x, pr.y, pr.z, pr.w};
            const uint32_t chain_done = __ballot_sync(~0u, (pr.x & 0xffff) >= 96) | (p.kind == WK_CHAIN) << 15;
            int left[4], avail[4], rdy = 0, claimed = 0, upstream = 0;
#pragma unroll
            for (int t = 0; t < 4; t++) {
              const int cnt = lane < 16 && !reserved(t, b) ? item_count(t, b) : 0;
              left[t] = max(cnt - (int)hv[t], 0);
              claimed += cnt - left[t];
              const bool ready = (pv[t] & 0xffff) >= item_need(t, b);
              rdy |= ready << t;
              bool ok = ready || (t != IT_ATT && (chain_done >> 15 & 1) && !left[t - 1] && (t < 2 || !left[t - 2]));
              if (t == IT_BQ && (chain_done >> HOLD_B & 1) && !(chain_done >> 15 & 1)) ok = false;
              avail[t] = ok ? left[t] : 0;
              upstream |= __any_sync(~0u, left[t] > 0);
            }
            if (!upstream) { code = -1; break; }
            int rank = max(__reduce_add_sync(~0u, ticket - claimed), 0), type = -1, mine = 0;
#pragma unroll
            for (int c = 0; c < 7; c++) {
              const int t = c == 0 || c == 6 ? IT_ATT : c == 1 || c == 4 ? IT_FIN : c == 2 ? IT_OP : IT_BQ;
              int a = c == 2 || (rdy >> t & 1) == (c < 4) ? avail[t] : 0;
              if (c == 6) a = b < p.qa_end && !(rdy & 1) && ((chain_done << 1 | 1) >> b & 1) ? left[t] : 0;
              const int tot = __reduce_add_sync(~0u, a);
              if (type < 0) { if (rank < tot) { type = t; mine = a; } else rank -= tot; }
            }
            if (type >= 0) {
#pragma unroll
              for (int o = 1; o < 16; o <<= 1) { const int y = __shfl_up_sync(~0u, mine, o); if (lane >= o) mine += y; }
              const int blk = __ffs(__ballot_sync(~0u, mine > rank)) - 1;
              const int early = !(__shfl_sync(~0u, rdy, blk) >> type & 1);
              const uint32_t idx = __reduce_add_sync(~0u, atomic_inc_one(sync + blk * 8 + type));
              if (idx < item_count(type, blk)) { code = (type == IT_ATT && blk < p.qa_end) << 23 | (chain_done >> 14 & 1) << 22 | early << 20 | type << 16 | blk << 8 | idx; break; }
            } else {
              __nanosleep(50);
            }
            spin_guard(spin);
          }
        }
        sts32(slots + 4 * (n & 3), code);
        mbar_arrive_one(bIF + 8 * (n & 3));
        if (code < 0) break;
      }
    } else if (warp >= 10) {
      work_loader(p, sb, warp == 10);
    } else {
      for (int n = 0;; n++) {
        mbar_wait(bIF + 8 * (n & 3), (n >> 2) & 1);
        const int code = __shfl_sync(~0u, (int)lds32(slots + 4 * (n & 3)), 0);
        if (code < 0) break;
        const int type = (code >> 16) & 15, b = (code >> 8) & 255;
        mbar_wait(done + 8 * (n & 3), (n >> 2) & 1);
        if (elect()) {
          if (type != IT_OUT) red_release(sync + (type < IT_BQ ? b * 8 + 5 + type : SY_P + b * 4 + ((0x13102 >> 4 * (type - IT_BQ)) & 3)), 1);
          mbar_arrive(bIE + 8 * (n & 3));
        }
        __syncwarp();
      }
    }
  } else {
    asm volatile("setmaxnreg.inc.sync.aligned.u32 232;");
    if (p.kind == WK_CHAIN) chain_compute(p.ch, sb);
    const int warp = __shfl_sync(~0u, fresh_tid() >> 5, 0), lane = fresh_tid() & 31;
    Ring r{sb, 0, p.kind == WK_CHAIN};
    int nln = 0;
#pragma unroll 1
    for (int n = 0;; n++) {
      mbar_wait(bIF + 8 * (n & 3), (n >> 2) & 1);
      int code = __shfl_sync(~0u, (int)lds32(slots + 4 * (n & 3)), 0);
      if (code < 0) { TRACE(2); break; }
      if (((code >> 16) & 15) == IT_ATT || (code & C_PROJ)) {
        Pending pend = {};
#pragma unroll 1
        for (;; n++) {
          const int tile = (((code >> 8) & 255) * 32 + (code & 255)) * 3072 + warp * 128;
          int next = 0;
          auto peek = [&]() {
            uint32_t here;
            asm volatile("{.reg .pred p; mbarrier.test_wait.parity.shared::cta.b64 p, [%1], %2; selp.u32 %0, -1, 0, p;}" : "=r"(here) : "r"(bIF + 8 * ((n + 1) & 3)), "r"(((n + 1) >> 2) & 1) : "memory");
            next = __shfl_sync(~0u, (int)(lds32(slots + 4 * ((n + 1) & 3) + (here & p.ch.zero)) & here), 0);
            return next < C_PROJ;
          };
          ITEM(code & 0xfffff, 0);
          if (code & C_PROJ) {
            float d[96];
            ITEM(9 << 16 | (code & 0xffff), 0);
            gemm_step<192>(d, r, warp, 0);
#pragma unroll 1
            for (int kb = 1; kb < 10; kb++) {
              gemm_step<192>(d, r, warp, 1);
              if (kb == 4 && (code & (C_EARLY | 15 << 16)) != C_EARLY && warp == 0) mbar_arrive_one(bGo);
              if (pend.done) {
#pragma unroll
                for (int i = 0; i < 12; i++) if (kb == 1 + i / 2) pend.store(i);
                if (kb == 6) pend.finish();
              }
              wg_wait<1>();
              r.release(r.seq - 2);
            }
            wg_wait<0>();
            reg_fence<96>(d);
            r.release(r.seq - 1);
            ITEM(9 << 16 | (code & 0xffff), 1);
#pragma unroll
            for (int i = 0; i < 48; i++) pend.w[i] = pack2(d[2 * i], d[2 * i + 1]);
          } else {
            const uint32_t base = r.wait(6) + warp * 2048 + lane * 16;
#pragma unroll
            for (int i = 0; i < 12; i++) {
              const uint4 t = lds128(base + (i >> 2) * 16384 + (i & 3) * 512);
              pend.w[4 * i] = t.x; pend.w[4 * i + 1] = t.y; pend.w[4 * i + 2] = t.z; pend.w[4 * i + 3] = t.w;
            }
            __syncwarp();
            r.release(r.seq - 1);
          }
          if (code & 15 << 16) {
            pend.dst = g_q + tile + lane;
            if (peek()) {
#pragma unroll
              for (int i = 0; i < 12; i++) pend.store(i);
            }
          } else {
            pend.dst = g_o + tile + (lane & 3) * 8 + (lane >> 2);
            attn_a(r, pend, peek, warp, lane);
          }
          pend.done = done + 8 * (n & 3);
          ITEM(code & 0xfffff, 1);
          if (next < C_PROJ) break;
          code = next;
        }
        pend.finish();
      } else {
        const int type = (code >> 16) & 15, b = (code >> 8) & 255, idx = code & 255;
        const uint32_t go = code & C_LATE ? 0 : bGo;
        ITEM(code & 0xfffff, 0);
        if (type == IT_FIN || type == IT_LN || type == IT_LN0) {
          const int ng = item_groups(type, b);
          const int planes = type == IT_FIN ? op_split(b) + 1 : type == IT_LN ? 2 : 1;
#pragma unroll 1
          for (int i = 0; i < ng; i += 2) ln_groups(r, scratch + (nln++ & 1) * 1024, planes, b * 16 + idx * ng + i, ng > 1);
        } else {
          const int cols = item_cols(type, b), nkb = type == IT_OP ? op_steps(b) : 10;
          float d[160] = {};
          if (type == IT_OUT) {
            const uint2* x = g_x + ((b * 16 + warp * 2) * 680 + idx * 5) * 32 + lane;
#pragma unroll
            for (int i = 0; i < 10; i++) { const uint2 y = __ldcg(x + (i / 5 * 680 + i % 5) * 32); d[40 + 2 * i] = __uint_as_float(y.x); d[41 + 2 * i] = __uint_as_float(y.y); }
          }
          reg_fence<160>(d);
          if (type != IT_OUT) ITEM((type == IT_BQ ? 10 : 11) << 16 | (code & 0xffff), 0);
          const int ask = max(nkb - ((code & C_TAIL ? GO_TAIL : GO_320) << (2 - (cols >> 7))), 0);
          if (cols == 320) gemm_item<320>(d, r, warp, nkb, go, ask);
          else if (cols == 160) gemm_item<160>(d, r, warp, nkb, go, ask);
          else gemm_item<80>(d, r, warp, nkb, go, ask);
          if (type != IT_OUT) ITEM((type == IT_BQ ? 10 : 11) << 16 | (code & 0xffff), 1);
          reg_fence<160>(d);
          if (type == IT_OUT) {
            bar_sync(1, 256);
            const uint32_t dst = sb + (warp * 16 + (lane & 15)) * 160 + (lane >> 4) * 16;
#pragma unroll
            for (int u = 0; u < 5; u++) {
              uint32_t w[4];
#pragma unroll
              for (int i = 0; i < 4; i++) { const uint32_t y = __float_as_uint(d[40 + (i & 1) * 10 + 2 * u + (i >> 1)]); w[i] = pack2(bf_lo(y) + d[8 * u + 2 * i], bf_hi(y) + d[8 * u + 2 * i + 1]); }
              stsm4(dst + u * 32, w[0], w[1], w[2], w[3]);
            }
            fence_async();
            __syncwarp();
            if (elect()) { tma_store(&p.out, sb + warp * 2560, idx * 80, b * 128 + warp * 16); bulk_commit(); bulk_wait<0>(); }
          } else {
            if (warp >= 4) bar_sync(7, 256);
            if (type == IT_BQ) store_bqkv(d, b, idx, 4 << (cols >> 7));
            else store_partial(d, b, cols == 320 ? idx >> 1 : idx >> 2, cols == 320 ? (idx & 1) * 20 : (idx & 3) * 10, cols >> 4);
            if (warp < 4) bar_arrive(7, 256);
          }
        }
        __syncwarp();
        mbar_arrive_one(done + 8 * (n & 3));
        if ((code & C_LATE) && warp == 4) mbar_arrive_one(bGo);
        ITEM(code & 0xfffff, 1);
      }
    }
  }
}

constexpr int AB_SMEM = 1024 + 2 * 98304 + 256;
#define AB_N 32
#define AB_WG 4
constexpr int AB_T = AB_WG * 128, AB_PASS = 8 / AB_WG;
__device__ __forceinline__ float ex2_poly(float t) {
  const uint32_t r = __float_as_uint(t) & 0xffff8000u;
  const float f = t - __uint_as_float(r);
  const float p = fmaf(fmaf(fmaf(-5.869912678e-38f, f, -1.700740250e-37f), f, -5.234869734e-37f), f, -7.522601252e-37f);
  uint32_t y;
  asm("mad.lo.u32 %0, %1, 256, %2;" : "=r"(y) : "r"(r), "r"(__float_as_uint(p)));
  return __uint_as_float(y);
}
__device__ __forceinline__ uint32_t hsq(uint32_t w, uint32_t c) { uint32_t r; asm("fma.rn.bf16x2 %0, %1, %1, %2;" : "=r"(r) : "r"(w), "r"(c)); return r; }
__device__ __forceinline__ float sq2(uint32_t w) { const float a = bf_lo(w), b = bf_hi(w); return fmaf(a, a, b * b); }

__device__ __forceinline__ void attn_b_store(const float* o, int h, int row0, int lane) {
  const int g = lane >> 2, c = lane & 3;
  const float i0 = rcp(__shfl_sync(~0u, o[8], (lane & ~3) | 2)), i1 = rcp(__shfl_sync(~0u, o[10], (lane & ~3) | 2));
#pragma unroll
  for (int jj = 0; jj < 3; jj++) {
    if (jj < 2 || c < 2) {
      const int col = h * 20 + 8 * jj + 2 * c;
      g_of[core_word(row0 + g, col)] = pack2(o[4 * jj] * i0, o[4 * jj + 1] * i0);
      g_of[core_word(row0 + g + 8, col)] = pack2(o[4 * jj + 2] * i1, o[4 * jj + 3] * i1);
    }
  }
}

__device__ __forceinline__ void attn_b_qk(float* s, uint32_t q0, uint32_t q1, uint32_t q2, uint32_t q3, uint32_t q4, uint32_t q5, uint32_t z0, uint32_t z1,
                                          uint64_t dk, uint64_t dk2) {
  wg_rs32_00(s, q0, q1, q2, q3, dk, 0);
  wg_rs32_00(s, q4, q5, z0, z1, dk2, 1);
}

struct AttnParams { const uint8_t* pf[4]; uint32_t *sync, *next; };
__global__ void __launch_bounds__(AB_T + 128, 1) attn_b_kernel(const __grid_constant__ AttnParams p) {
  extern __shared__ uint8_t smem_raw[];
  const uint32_t sb = (s2u(smem_raw) + 1023) & ~1023u, sK = sb, sV = sb + 98304, bars = sb + 2 * 98304;
  const int warp = __shfl_sync(~0u, threadIdx.x >> 5, 0), lane = threadIdx.x & 31;
  const int h = blockIdx.x & 31, quarter = blockIdx.x >> 5;
  BT(0);
  TRACE(0);
  if (warp < 10 && elect()) {
    mbar_init(bars + 8 * warp + (warp & 8) * 8, warp < 8 ? 1 : warp == 8 ? AB_T / 32 : 2);
    asm volatile("fence.mbarrier_init.release.cluster;" ::: "memory");
  }
  __syncthreads();
  if (warp >= AB_T / 32) {
    asm volatile("setmaxnreg.dec.sync.aligned.u32 32;");
    if (warp == AB_T / 32 + 1) return;
    if (warp > AB_T / 32) {
      uint32_t kmax = 0;
#pragma unroll 1
      for (int i = 0; i < 32; i++) {
        if (!(i & 3)) mbar_wait(bars + 2 * i, 0);
        const uint32_t a = sK + i * 3072 + ((threadIdx.x >> 3) & 7) * 384 + (lane & 7) * 16;
        const uint4 x = lds128(a), y = lds128(a + 128);
        const uint2 z = lds64(a + 256);
        const uint32_t n = hadd2(hsq(x.x, hsq(x.y, hsq(x.z, hsq(x.w, hsq(z.x, 0))))), hsq(y.x, hsq(y.y, hsq(y.z, hsq(y.w, hsq(z.y, 0))))));
        kmax = max(kmax, __float_as_uint(bf_lo(n) + bf_hi(n)) & 0x7fffffffu);
      }
      const uint32_t kbits = __reduce_max_sync(~0u, kmax);
      if (lane == 0) { sts32(bars + 64 + (warp & 1) * 4, kbits); mbar_arrive(bars + 136); }
      return;
    }
    const uint8_t* gk = reinterpret_cast<const uint8_t*>(g_bqkv + (32 + h) * 256 * 96);
    const uint8_t* gv = reinterpret_cast<const uint8_t*>(g_bqkv + (64 + h) * 256 * 96);
    uint32_t todo = 255;
    for (int spin = 0; todo;) {
      const uint32_t up = __ballot_sync(~0u, ld_acquire(p.sync + SY_P + (lane & 15) * 4 + 2) >= bq_items(lane & 15));
      fence_async_global();
#pragma unroll 1
      for (int i = 0; i < 8; i++) {
        if (!(todo >> i & 1) || (up >> 2 * i & 3) != 3) continue;
        todo &= ~(1u << i);
        if (elect()) {
          mbar_expect(bars + 8 * i, 24576);
          bulk_load(sK + i * 12288, gk + i * 12288, 12288, bars + 8 * i);
          bulk_load(sV + i * 12288, gv + i * 12288, 12288, bars + 8 * i);
        }
      }
      spin_guard(spin);
    }
    pdl_launch();
    TRACE(1);
#pragma unroll 1
    for (int i = lane; i < 512 && blockIdx.x < NSLOT; i += 32) reinterpret_cast<uint4*>(pool_at(blockIdx.x * 8192))[i] = make_uint4(0, 0, 0, 0);
    if (!p.next && blockIdx.x < 8) { const int i = blockIdx.x * 32 + lane; g_smpart[i] = 0; if (i < NSLOT) g_orient[i] = 0; }
    if (p.next) {
      mbar_wait(bars + 128, 0);
      if (quarter == 0 && lane == 0) red_release(p.next + SY_OB, 1);
#pragma unroll 1
      for (int i = 0; i < (PF_NS ? 32 : 0); i++) {
        if (elect()) prefetch_l2(p.pf[i >> 3] + blockIdx.x * 61440 + (i & 7) * 7680, 7680);
        __nanosleep(PF_NS);
      }
    }
    return;
  }
  asm volatile("setmaxnreg.inc.sync.aligned.u32 112;");
  constexpr int NT = SEQ / AB_N, PER = 256 / AB_N;
  uint32_t qn[8];
  auto load_q = [&](int pass) {
    const uint32_t* gq = g_bqkv + (h * 256 + pass * 128 + quarter * 32 + warp * 2) * 96 + lane;
#pragma unroll
    for (int i = 0; i < 8; i++) qn[i] = __ldcg(gq + (i & 1) * 96 + min(i >> 1, 2) * 32 + (i < 6 ? 0 : 3 - (lane & 3)));
  };
  mbar_wait(bars + 8 * quarter, 0);
  load_q(0);
#pragma unroll 1
  for (int pass = 0; pass < AB_PASS; pass++) {
    const int row0 = pass * 1024 + quarter * 256 + warp * 16;
    const uint32_t q0 = qn[0], q1 = qn[1], q2 = qn[2], q3 = qn[3], z0 = qn[6], z1 = qn[7];
    uint32_t q4 = qn[4], q5 = qn[5];
    if ((lane & 3) == 2) { q4 = 0x43BCu; q5 = 0x43BCu; }
    float o[12];
    uint64_t dk = mkdesc(sK, 128, 384, 0), dk2 = mkdesc(sK + 256, 0, 384, 0), dv = mkdesc(sV, 384, 128, 0);
    float sa[AB_N / 2], sb2[AB_N / 2];
    uint32_t pa[AB_N / 4], pb[AB_N / 4];
    if (pass == 0) mbar_wait(bars, 0);
    BT(1 + 2 * pass);
    wg_fence();
    attn_b_qk(sa, q0, q1, q2, q3, q4, q5, z0, z1, dk, dk2);
    wg_commit();
    attn_b_qk(sb2, q0, q1, q2, q3, q4, q5, z0, z1, dk + AB_N * 3, dk2 + AB_N * 3);
    wg_commit();
#pragma unroll 1
    for (int kt = 0; kt < NT; kt += 2) {
      const int nx = kt + 2 < NT ? kt + 2 : 0;
      if (pass == 0 && (nx & (PER - 1)) == 0) mbar_wait(bars + 8 * (nx / PER), 0);
      const uint64_t nk = dk + nx * (AB_N * 3), nk2 = dk2 + nx * (AB_N * 3);
      wg_wait<1>();
      reg_fence<AB_N / 2>(sa);
#pragma unroll
      for (int i = 0; i < AB_N / 4; i++) pa[i] = pack2(ex2(sa[2 * i]), poly_group(i >> 1) ? ex2_poly(sa[2 * i + 1]) : ex2(sa[2 * i + 1]));
      wg_fence();
#pragma unroll
      for (int kk = 0; kk < AB_N / 16; kk++) wg_rs24_01(o, pa[4 * kk], pa[4 * kk + 1], pa[4 * kk + 2], pa[4 * kk + 3], dv + kk * 48, kk | kt);
      attn_b_qk(sa, q0, q1, q2, q3, q4, q5, z0, z1, nk, nk2);
      wg_commit();
      wg_wait<1>();
      reg_fence<AB_N / 2>(sb2);
#pragma unroll
      for (int i = 0; i < AB_N / 4; i++) pb[i] = pack2(ex2(sb2[2 * i]), poly_group((i >> 1) + AB_N / 8) ? ex2_poly(sb2[2 * i + 1]) : ex2(sb2[2 * i + 1]));
      wg_fence();
#pragma unroll
      for (int kk = 0; kk < AB_N / 16; kk++) wg_rs24_01(o, pb[4 * kk], pb[4 * kk + 1], pb[4 * kk + 2], pb[4 * kk + 3], dv + AB_N * 3 + kk * 48, 1);
      attn_b_qk(sb2, q0, q1, q2, q3, q4, q5, z0, z1, nk + AB_N * 3, nk2 + AB_N * 3);
      wg_commit();
      dv += AB_N * 6;
    }
    wg_wait<0>();
    reg_fence<12>(o); reg_fence<AB_N / 2>(sa); reg_fence<AB_N / 2>(sb2);
    BT(2 + 2 * pass);
    if (pass + 1 < AB_PASS) load_q(pass + 1);
    mbar_wait(bars + 136, 0);
    const uint2 kb = lds64(bars + 64);
    const float kmax = __uint_as_float(max(kb.x, kb.y));
    if ((lane & 3) == 2) q4 = q5 = 0;
    float n0 = sq2(q0) + sq2(q2) + sq2(q4), n1 = sq2(q1) + sq2(q3) + sq2(q5);
    n0 += __shfl_xor_sync(~0u, n0, 1); n1 += __shfl_xor_sync(~0u, n1, 1);
    n0 += __shfl_xor_sync(~0u, n0, 2); n1 += __shfl_xor_sync(~0u, n1, 2);
    uint32_t redo;
    asm volatile("{.reg .pred p, q; setp.ne.u32 p, %1, 0; bar.red.or.pred q, %2, 128, p; selp.u32 %0, 1, 0, q;}"
                 : "=r"(redo) : "r"((uint32_t)!(n0 * kmax <= 9500.f && n1 * kmax <= 9500.f)), "r"(2 + (warp >> 2)) : "memory");
    if (redo) {
#pragma unroll
      for (int i = 0; i < 12; i++) o[i] = 0.f;
      float m0 = -INFINITY, m1 = -INFINITY;
#pragma unroll 1
      for (int kt = 0; kt < 64; kt++) {
        float s[16];
        wg_fence();
        wg_rs32_00(s, q0, q1, q2, q3, dk + kt * 96, 0);
        wg_rs32_00(s, q4, q5, z0, z1, dk2 + kt * 96, 1);
        wg_commit();
        wg_wait<0>();
        reg_fence<16>(s); reg_fence<12>(o);
        float n0 = m0, n1 = m1;
#pragma unroll
        for (int jj = 0; jj < 4; jj++) { n0 = fmaxf(n0, fmaxf(s[4 * jj], s[4 * jj + 1])); n1 = fmaxf(n1, fmaxf(s[4 * jj + 2], s[4 * jj + 3])); }
        n0 = fmaxf(n0, __shfl_xor_sync(~0u, n0, 1)); n0 = fmaxf(n0, __shfl_xor_sync(~0u, n0, 2));
        n1 = fmaxf(n1, __shfl_xor_sync(~0u, n1, 1)); n1 = fmaxf(n1, __shfl_xor_sync(~0u, n1, 2));
        const float r0 = ex2(m0 - n0), r1 = ex2(m1 - n1);
        m0 = n0; m1 = n1;
#pragma unroll
        for (int jj = 0; jj < 3; jj++) { o[4 * jj] *= r0; o[4 * jj + 1] *= r0; o[4 * jj + 2] *= r1; o[4 * jj + 3] *= r1; }
        uint32_t pp[8];
#pragma unroll
        for (int jj = 0; jj < 4; jj++) {
          pp[2 * jj] = pack2(ex2(s[4 * jj] - m0), ex2(s[4 * jj + 1] - m0));
          pp[2 * jj + 1] = pack2(ex2(s[4 * jj + 2] - m1), ex2(s[4 * jj + 3] - m1));
        }
        reg_fence<12>(o);
        wg_fence();
#pragma unroll
        for (int kk = 0; kk < 2; kk++) wg_rs24_01(o, pp[4 * kk], pp[4 * kk + 1], pp[4 * kk + 2], pp[4 * kk + 3], mkdesc(sV, 384, 128, 0) + kt * 96 + kk * 48, 1);
        wg_commit();
      }
      wg_wait<0>();
      reg_fence<12>(o);
    }
    attn_b_store(o, h, row0, lane);
    __syncwarp();
    if (pass == 0 && lane == 0) mbar_arrive(bars + 128);
  }
  BT(5);
  TRACE(2);
}

typedef CUresult (*EncodeFn)(CUtensorMap*, CUtensorMapDataType, cuuint32_t, void*, const cuuint64_t*, const cuuint64_t*,
                             const cuuint32_t*, const cuuint32_t*, CUtensorMapInterleave, CUtensorMapSwizzle,
                             CUtensorMapL2promotion, CUtensorMapFloatOOBfill);

void make_map(EncodeFn enc, CUtensorMap* m, const void* ptr, int cols, int rows, int box_rows, int box_cols = 64) {
  const cuuint64_t dims[2] = {(cuuint64_t)cols, (cuuint64_t)rows};
  const cuuint64_t strides[1] = {(cuuint64_t)cols * 2};
  const cuuint32_t box[2] = {(cuuint32_t)box_cols, (cuuint32_t)box_rows}, es[2] = {1, 1};
  enc(m, CU_TENSOR_MAP_DATA_TYPE_BFLOAT16, 2, const_cast<void*>(ptr), dims, strides, box, es, CU_TENSOR_MAP_INTERLEAVE_NONE,
      box_cols == 64 ? CU_TENSOR_MAP_SWIZZLE_128B : box_cols == 32 ? CU_TENSOR_MAP_SWIZZLE_64B : CU_TENSOR_MAP_SWIZZLE_NONE, CU_TENSOR_MAP_L2_PROMOTION_L2_256B, CU_TENSOR_MAP_FLOAT_OOB_FILL_NONE);
}
void make_map5(EncodeFn enc, CUtensorMap* m, const void* ptr, bool words, const cuuint64_t (&dims)[5], const cuuint64_t (&strides)[4], const cuuint32_t (&box)[5]) {
  const cuuint32_t es[5] = {1, 1, 1, 1, 1};
  enc(m, words ? CU_TENSOR_MAP_DATA_TYPE_UINT64 : CU_TENSOR_MAP_DATA_TYPE_BFLOAT16, 5, const_cast<void*>(ptr), dims, strides, box, es, CU_TENSOR_MAP_INTERLEAVE_NONE,
      words ? CU_TENSOR_MAP_SWIZZLE_NONE : CU_TENSOR_MAP_SWIZZLE_128B, dims[0] % 64 ? CU_TENSOR_MAP_L2_PROMOTION_L2_128B : CU_TENSOR_MAP_L2_PROMOTION_L2_256B,
      CU_TENSOR_MAP_FLOAT_OOB_FILL_NONE);
}
void make_tiles(EncodeFn enc, CUtensorMap* m, const void* ptr, cuuint64_t cols, cuuint64_t tile) {
  make_map5(enc, m, ptr, false, {tile, 1, 1, cols / tile, DM}, {tile * 2, tile * 2, tile * 2, cols * 2}, {64, 1, 1, 1, 64});
}
template <class... KA, class... A>
void launch(void (*kern)(KA...), int grid, int block, int smem, int cluster, bool pdl, A... args) {
  cudaFuncSetAttribute(kern, cudaFuncAttributeMaxDynamicSharedMemorySize, smem);
  cudaLaunchConfig_t cfg = {};
  cfg.gridDim = dim3(grid); cfg.blockDim = dim3(block); cfg.dynamicSmemBytes = smem; cfg.stream = cudaStreamPerThread;
  cudaLaunchAttribute at[2];
  int n = 0;
  if (cluster > 1) { at[n].id = cudaLaunchAttributeClusterDimension; at[n].val.clusterDim.x = cluster; at[n].val.clusterDim.y = 1; at[n].val.clusterDim.z = 1; n++; }
  if (pdl) { at[n].id = cudaLaunchAttributeProgrammaticStreamSerialization; at[n].val.programmaticStreamSerializationAllowed = 1; n++; }
  cfg.attrs = at; cfg.numAttrs = n;
  cudaLaunchKernelEx(&cfg, kern, args...);
}
template <class T> void* sym(T& s) { void* p = nullptr; cudaGetSymbolAddress(&p, s); return p; }

}

#define MODE(b) 0
extern "C" void kernel_launch(void* const* d_in, const int* in_sizes, int n_in, void* d_out, int out_size) {
  const __nv_bfloat16* x = (const __nv_bfloat16*)d_in[0];
  void* fn = nullptr; cudaDriverEntryPointQueryResult qr;
  cudaGetDriverEntryPoint("cuTensorMapEncodeTiled", &fn, cudaEnableDefault, &qr);
  EncodeFn enc = (EncodeFn)fn;

  WorkParams wk = {};
  ChainParams& ch = wk.ch;
  AttnParams at = {};
  make_map(enc, &ch.wq, d_in[2], HD, DM, 160); make_map(enc, &ch.wk, d_in[3], HD, DM, 160); make_map(enc, &ch.wv, d_in[4], HD, DM, 160);
  make_map(enc, &ch.wo, d_in[5], DM, HD, 192, 32);
  ch.mem0 = (const __nv_bfloat16*)d_in[1];
  ch.wb = (const uint8_t*)d_in[8];
  ch.d1 = 250; ch.d2 = 200; ch.dn = 150; ch.dx = 950;
  make_map5(enc, &wk.wq, d_in[2], false, {64, 1, 1, DM, HD / 64}, {128, 128, HD * 2, 128}, {64, 1, 1, 64, 3});
  for (int i = 0; i < 3; i++) make_tiles(enc, &wk.wb[i], d_in[8], 1920, 80 << i);
  for (int i = 0; i < 2; i++) make_tiles(enc, &wk.wc[i], d_in[9], DM, 80 << 2 * i);
  make_map(enc, &wk.out, d_out, DM, SEQ, 16, 80);
  make_map5(enc, &wk.wo, d_in[5], false, {DM, 2, 4, 4, HD / 32}, {DM * 2, DM * 16, DM * 4, DM * 64}, {64, 2, 4, 4, 2});
  make_map5(enc, &wk.xn, sym(g_xn), true, {1280, 1, 1, 256, 1}, {10240, 10240, 10240, 10240}, {128, 1, 1, 16, 1});
  make_map5(enc, &ch.xc, sym(g_xn), true, {160, 1, 1, 256, 8}, {1280, 1280, 10240, 1280}, {160, 1, 1, 4, 2});
  wk.x = x;
  for (int i = 0; i < 4; i++) at.pf[i] = (const uint8_t*)d_in[i < 2 ? 3 + i : i == 2 ? 2 : 5];
  int qa_end[2] = {12, 12};
  for (int layer = 0; layer < 2; layer++) {
    ch.sync = wk.sync = at.sync = (uint32_t*)sym(g_sync) + layer * SY_N;
    ch.other = (uint32_t*)sym(g_sync) + (1 - layer) * SY_N;
    ch.layer = layer;
    at.next = layer ? nullptr : ch.other;
    wk.qa_end = qa_end[layer];
    wk.kind = layer ? WK_LEAD : WK_FIRST;
    launch(work_kernel, 132, 384, CH_SMEM, 1, layer != 0, wk);
    wk.kind = WK_CHAIN;
    launch(work_kernel, 96, 384, CH_SMEM, 3, true, wk);
    launch(attn_b_kernel, 128, AB_T + 128, AB_SMEM, 1, true, at);
  }
  wk.kind = WK_LAST;
  launch(work_kernel, 128, 384, CH_SMEM, 1, true, wk);
}
```

```cpp
#include <cuda_runtime.h>
#include <cuda_bf16.h>
#include <cuda.h>
#include <stdint.h>
#include <stdlib.h>

namespace {

constexpr int SEQ = 2048, DM = 640, HD = 6144, NSEG = 64;
constexpr int SPIN_LIMIT = 1 << 20;

__device__ __align__(128) uint2 g_x[256 * 17 * 1280];
__device__ __align__(128) uint32_t g_xn[SEQ * DM / 2];
__device__ __align__(128) uint32_t g_of[SEQ * DM / 2];
__device__ __align__(128) uint4 g_o[SEQ * HD / 8];
__device__ __align__(128) uint4 g_q[SEQ * HD / 8];
constexpr int KV_M = 4096, KV_SEG = 5120, KV_PART = 20480, KV_V = 3 * KV_PART;
__device__ __align__(128) uint8_t g_kv[16 * 32 * 6 * KV_PART];
#define OP_B8 11
#define OP_B16 13
#define OP_N4 16
#define BQ_12 12
#define BQ_24 13
#define FIN_16 12
__host__ __device__ constexpr int op_split(int b) { return b < OP_B8 ? 4 : b < OP_B16 ? 8 : 16; }
__host__ __device__ constexpr int op_steps(int b) { return b < OP_B8 ? 24 : b < OP_B16 ? 12 : 6; }
__host__ __device__ constexpr int op_tiles(int b) { return b < OP_N4 ? 2 : 4; }
__host__ __device__ constexpr int fin_items(int b) { return b < OP_B8 ? 4 : b < FIN_16 ? 8 : 16; }
__host__ __device__ constexpr int bq_items(int b) { return b < BQ_12 ? 6 : b < BQ_24 ? 12 : 24; }
__host__ __device__ constexpr int ln_items(int layer, int b) { return layer == 0 && b < 2 ? 16 : 4; }
constexpr int SY_P = 128, SY_T = 192, SY_UP = 224, SY_OB = 225, SY_PRE = 256, SY_PART = 288, SY_TIME = 384, SY_N = 448;
__device__ __align__(128) uint32_t g_sync[2 * SY_N];
constexpr int NSLOT = 92;
__device__ uint32_t g_pool[(NSLOT + 2) * 2048];
__device__ uint32_t g_smpart[256], g_orient[NSLOT];
__device__ __align__(128) uint32_t g_bqkv[3 * 32 * 256 * 96];

#define BT(i)
#define MISS(k, n)
#define PRO(i)
#define TRACE(w)
#define ITEM(code, w)
#define STAT(k)
#define TMV(i, v)
#define TM(i)
#define TMD(i, dep)

__device__ __forceinline__ uint32_t gtime() { uint32_t c; asm volatile("mov.u32 %0, %%globaltimer_lo;" : "=r"(c) :: "memory"); return c; }
__device__ __forceinline__ uint32_t clk32() { uint32_t c; asm volatile("mov.u32 %0, %%clock;" : "=r"(c) :: "memory"); return c; }
__device__ __forceinline__ uint32_t fresh_tid() { uint32_t t; asm volatile("mov.u32 %0, %%tid.x;" : "=r"(t)); return t; }
__device__ __forceinline__ uint32_t s2u(const void* p) { return (uint32_t)__cvta_generic_to_shared(p); }
__device__ __forceinline__ uint32_t pack2(float a, float b) {
  uint32_t r; asm("cvt.rn.bf16x2.f32 %0, %1, %2;" : "=r"(r) : "f"(b), "f"(a)); return r; }
__device__ __forceinline__ float bf_lo(uint32_t w) { return __uint_as_float(w << 16); }
__device__ __forceinline__ float bf_hi(uint32_t w) { return __uint_as_float(w & 0xffff0000u); }
__device__ __forceinline__ float ex2(float x) { float y; asm("ex2.approx.ftz.f32 %0, %1;" : "=f"(y) : "f"(x)); return y; }

__device__ __forceinline__ void mbar_init(uint32_t bar, uint32_t n) {
  asm volatile("mbarrier.init.shared::cta.b64 [%0], %1;" :: "r"(bar), "r"(n) : "memory"); }
__device__ __forceinline__ void mbar_expect(uint32_t bar, uint32_t bytes) {
  asm volatile("mbarrier.arrive.expect_tx.shared::cta.b64 _, [%0], %1;" :: "r"(bar), "r"(bytes) : "memory"); }
__device__ __forceinline__ void mbar_arrive(uint32_t bar) {
  asm volatile("mbarrier.arrive.shared::cta.b64 _, [%0];" :: "r"(bar) : "memory"); }
#define ONE "{.reg .pred one; elect.sync _|one, 0xffffffff; @one "
__device__ __forceinline__ void mbar_arrive_one(uint32_t bar) { asm volatile(ONE "mbarrier.arrive.shared::cta.b64 _, [%0];}" :: "r"(bar) : "memory"); }
__device__ __forceinline__ void mbar_expect_one(uint32_t bar, uint32_t bytes) {
  asm volatile(ONE "mbarrier.arrive.expect_tx.shared::cta.b64 _, [%0], %1;}" :: "r"(bar), "r"(bytes) : "memory"); }
__device__ __forceinline__ uint32_t atomic_inc_one(uint32_t* p) {
  uint32_t v = 0; asm volatile(ONE "atom.relaxed.gpu.global.add.u32 %0, [%1], 1;}" : "+r"(v) : "l"(p) : "memory"); return v; }
__device__ __forceinline__ void mbar_arrive_remote(uint32_t bar) {
  asm volatile("mbarrier.arrive.shared::cluster.b64 _, [%0];" :: "r"(bar) : "memory"); }
__device__ __forceinline__ void mbar_wait(uint32_t bar, uint32_t ph) {
  asm volatile("{.reg .pred p; .reg .u32 n; mov.u32 n, 0;\n"
               "W: mbarrier.try_wait.parity.shared::cta.b64 p, [%0], %1; @p bra.uni D;\n"
               "add.u32 n, n, 1; setp.gt.u32 p, n, %2; @p trap; bra.uni W;\n"
               "D: }" :: "r"(bar), "r"(ph), "n"(SPIN_LIMIT) : "memory");
}
__device__ __forceinline__ bool elect() {
  uint32_t p; asm volatile("{.reg .pred q; elect.sync _|q, 0xffffffff; selp.u32 %0, 1, 0, q;}" : "=r"(p)); return p; }
__device__ __forceinline__ void spin_guard(int& n) {
  asm volatile("{.reg .pred p; add.s32 %0, %0, 1; setp.gt.s32 p, %0, %1; @p trap;}" : "+r"(n) : "n"(SPIN_LIMIT));
}
__device__ __forceinline__ void pdl_wait() { asm volatile("griddepcontrol.wait;" ::: "memory"); TRACE(1); }
__device__ __forceinline__ void pdl_launch() { asm volatile("griddepcontrol.launch_dependents;" ::: "memory"); }
__device__ __forceinline__ uint32_t ld_acquire(const uint32_t* p) { uint32_t v; asm volatile("ld.acquire.gpu.global.u32 %0, [%1];" : "=r"(v) : "l"(p) : "memory"); return v; }
__device__ __forceinline__ void red_release(uint32_t* p, uint32_t v) { asm volatile("red.release.gpu.global.add.u32 [%0], %1;" :: "l"(p), "r"(v) : "memory"); }
__device__ __forceinline__ void fence_async_global() { asm volatile("fence.proxy.async.global;" ::: "memory"); }
__device__ __forceinline__ void fence_async() { asm volatile("fence.proxy.async.shared::cta;" ::: "memory"); }
__device__ __forceinline__ void bar_sync(int id, int n) { asm volatile("bar.sync %0, %1;" :: "r"(id), "r"(n) : "memory"); }
__device__ __forceinline__ void bar_arrive(int id, int n) { asm volatile("bar.arrive %0, %1;" :: "r"(id), "r"(n) : "memory"); }
__device__ __forceinline__ void tma_load(uint32_t dst, const CUtensorMap* m, int c0, int c1, uint32_t bar) {
  asm volatile("cp.async.bulk.tensor.2d.shared::cluster.global.mbarrier::complete_tx::bytes [%0], [%1, {%3, %4}], [%2];"
               :: "r"(dst), "l"(m), "r"(bar), "r"(c0), "r"(c1) : "memory"); }
__device__ __forceinline__ void tma_load5_one(uint32_t dst, const CUtensorMap* m, int c0, int c3, int c4, uint32_t bar) {
  asm volatile(ONE "cp.async.bulk.tensor.5d.shared::cluster.global.mbarrier::complete_tx::bytes [%0], [%1, {%3, %6, %6, %4, %5}], [%2];}"
               :: "r"(dst), "l"(m), "r"(bar), "r"(c0), "r"(c3), "r"(c4), "r"(0) : "memory"); }
__device__ __forceinline__ void tma_store(const CUtensorMap* m, uint32_t src, int c0, int c1) {
  asm volatile("cp.async.bulk.tensor.2d.global.shared::cta.bulk_group [%0, {%2, %3}], [%1];"
               :: "l"(m), "r"(src), "r"(c0), "r"(c1) : "memory"); }
__device__ __forceinline__ uint64_t evict_first() { uint64_t p; asm("createpolicy.fractional.L2::evict_first.b64 %0, 1.0;" : "=l"(p)); return p; }
__device__ __forceinline__ void bulk_load_last_one(uint32_t dst, const void* src, uint32_t bytes, uint32_t bar) {
  asm volatile(ONE "cp.async.bulk.shared::cluster.global.mbarrier::complete_tx::bytes.L2::cache_hint [%0], [%1], %2, [%3], %4;}"
               :: "r"(dst), "l"(src), "r"(bytes), "r"(bar), "l"(evict_first()) : "memory"); }
__device__ __forceinline__ void bulk_store_stream(void* dst, uint32_t src, uint32_t bytes) {
  asm volatile("cp.async.bulk.global.shared::cta.bulk_group.L2::cache_hint [%0], [%1], %2, %3;" :: "l"(dst), "r"(src), "r"(bytes), "l"(evict_first()) : "memory"); }
__device__ __forceinline__ void bulk_load(uint32_t dst, const void* src, uint32_t bytes, uint32_t bar) {
  asm volatile("cp.async.bulk.shared::cluster.global.mbarrier::complete_tx::bytes [%0], [%1], %2, [%3];"
               :: "r"(dst), "l"(src), "r"(bytes), "r"(bar) : "memory"); }
__device__ __forceinline__ void bulk_push(uint32_t dst, uint32_t src, uint32_t bytes, uint32_t bar) {
  asm volatile("cp.async.bulk.shared::cluster.shared::cta.mbarrier::complete_tx::bytes [%0], [%1], %2, [%3];"
               :: "r"(dst), "r"(src), "r"(bytes), "r"(bar) : "memory"); }
__device__ __forceinline__ void bulk_store(void* dst, uint32_t src, uint32_t bytes) {
  asm volatile("cp.async.bulk.global.shared::cta.bulk_group [%0], [%1], %2;" :: "l"(dst), "r"(src), "r"(bytes) : "memory"); }
__device__ __forceinline__ void bulk_commit() { asm volatile("cp.async.bulk.commit_group;" ::: "memory"); }
template <int N> __device__ __forceinline__ void bulk_wait_read() { asm volatile("cp.async.bulk.wait_group.read %0;" :: "n"(N) : "memory"); }
template <int N> __device__ __forceinline__ void bulk_wait() { asm volatile("cp.async.bulk.wait_group %0;" :: "n"(N) : "memory"); }

__device__ __forceinline__ uint64_t mkdesc(uint32_t addr, uint32_t lbo, uint32_t sbo, uint32_t sw) {
  return (uint64_t)((addr & 0x3FFFF) >> 4) | ((uint64_t)(lbo >> 4) << 16) | ((uint64_t)(sbo >> 4) << 32) | ((uint64_t)sw << 62); }
__device__ __forceinline__ void wg_fence() { asm volatile("wgmma.fence.sync.aligned;" ::: "memory"); }
__device__ __forceinline__ void wg_commit() { asm volatile("wgmma.commit_group.sync.aligned;" ::: "memory"); }
template <int N> __device__ __forceinline__ void wg_wait() { asm volatile("wgmma.wait_group.sync.aligned %0;" :: "n"(N) : "memory"); }
template <int N> __device__ __forceinline__ void reg_fence(float* d) {
#pragma unroll
  for (int i = 0; i < N; i++) asm volatile("" : "+f"(d[i]) :: "memory");
}

__device__ __forceinline__ void mma16(float* d, uint32_t a0, uint32_t a1, uint32_t a2, uint32_t a3, uint32_t b0, uint32_t b1) {
  asm volatile("mma.sync.aligned.m16n8k16.row.col.f32.bf16.bf16.f32 {%0,%1,%2,%3},{%4,%5,%6,%7},{%8,%9},{%0,%1,%2,%3};"
               : "+f"(d[0]), "+f"(d[1]), "+f"(d[2]), "+f"(d[3]) : "r"(a0), "r"(a1), "r"(a2), "r"(a3), "r"(b0), "r"(b1)); }
__device__ __forceinline__ void mma8(float* d, uint32_t a0, uint32_t a1, uint32_t b0) {
  asm volatile("mma.sync.aligned.m16n8k8.row.col.f32.bf16.bf16.f32 {%0,%1,%2,%3},{%4,%5},{%6},{%0,%1,%2,%3};"
               : "+f"(d[0]), "+f"(d[1]), "+f"(d[2]), "+f"(d[3]) : "r"(a0), "r"(a1), "r"(b0)); }
__device__ __forceinline__ void ldsm4(uint32_t* r, uint32_t a) {
  asm volatile("ldmatrix.sync.aligned.m8n8.x4.shared.b16 {%0,%1,%2,%3},[%4];" : "=r"(r[0]), "=r"(r[1]), "=r"(r[2]), "=r"(r[3]) : "r"(a) : "memory"); }
__device__ __forceinline__ uint4 ldsm4v(uint32_t a) { uint32_t r[4]; ldsm4(r, a); return make_uint4(r[0], r[1], r[2], r[3]); }
__device__ __forceinline__ void ldsm4t(uint32_t* r, uint32_t a) {
  asm volatile("ldmatrix.sync.aligned.m8n8.x4.trans.shared.b16 {%0,%1,%2,%3},[%4];" : "=r"(r[0]), "=r"(r[1]), "=r"(r[2]), "=r"(r[3]) : "r"(a) : "memory"); }
__device__ __forceinline__ void ldsm2(uint32_t* r, uint32_t a) {
  asm volatile("ldmatrix.sync.aligned.m8n8.x2.shared.b16 {%0,%1},[%2];" : "=r"(r[0]), "=r"(r[1]) : "r"(a) : "memory"); }
__device__ __forceinline__ void ldsm2t(uint32_t* r, uint32_t a) {
  asm volatile("ldmatrix.sync.aligned.m8n8.x2.trans.shared.b16 {%0,%1},[%2];" : "=r"(r[0]), "=r"(r[1]) : "r"(a) : "memory"); }
__device__ __forceinline__ void stsm4(uint32_t a, uint32_t r0, uint32_t r1, uint32_t r2, uint32_t r3) {
  asm volatile("stmatrix.sync.aligned.m8n8.x4.shared.b16 [%0], {%1,%2,%3,%4};" :: "r"(a), "r"(r0), "r"(r1), "r"(r2), "r"(r3) : "memory"); }
__device__ __forceinline__ void stsm4t(uint32_t a, uint32_t r0, uint32_t r1, uint32_t r2, uint32_t r3) {
  asm volatile("stmatrix.sync.aligned.m8n8.x4.trans.shared.b16 [%0], {%1,%2,%3,%4};" :: "r"(a), "r"(r0), "r"(r1), "r"(r2), "r"(r3) : "memory"); }
__device__ __forceinline__ void stsm2(uint32_t a, uint32_t r0, uint32_t r1) {
  asm volatile("stmatrix.sync.aligned.m8n8.x2.shared.b16 [%0], {%1,%2};" :: "r"(a), "r"(r0), "r"(r1) : "memory"); }
__device__ __forceinline__ void stsm2t(uint32_t a, uint32_t r0, uint32_t r1) {
  asm volatile("stmatrix.sync.aligned.m8n8.x2.trans.shared.b16 [%0], {%1,%2};" :: "r"(a), "r"(r0), "r"(r1) : "memory"); }
__device__ __forceinline__ void sts32(uint32_t a, uint32_t v) { asm volatile("st.shared.b32 [%0], %1;" :: "r"(a), "r"(v) : "memory"); }
__device__ __forceinline__ void sts64f(uint32_t a, float x, float y) { asm volatile("st.shared.v2.f32 [%0], {%1,%2};" :: "r"(a), "f"(x), "f"(y) : "memory"); }
__device__ __forceinline__ void sts128(uint32_t a, uint4 v) {
  asm volatile("st.shared.v4.b32 [%0], {%1,%2,%3,%4};" :: "r"(a), "r"(v.x), "r"(v.y), "r"(v.z), "r"(v.w) : "memory"); }
__device__ __forceinline__ void sts128f(uint32_t a, float x, float y, float z, float w) {
  asm volatile("st.shared.v4.f32 [%0], {%1,%2,%3,%4};" :: "r"(a), "f"(x), "f"(y), "f"(z), "f"(w) : "memory"); }
__device__ __forceinline__ float lds32f(uint32_t a) { float v; asm volatile("ld.shared.f32 %0, [%1];" : "=f"(v) : "r"(a) : "memory"); return v; }
__device__ __forceinline__ float2 lds64f(uint32_t a) { float2 v; asm volatile("ld.shared.v2.f32 {%0,%1}, [%2];" : "=f"(v.x), "=f"(v.y) : "r"(a) : "memory"); return v; }
__device__ __forceinline__ float4 lds128f(uint32_t a) {
  float4 v; asm volatile("ld.shared.v4.f32 {%0,%1,%2,%3}, [%4];" : "=f"(v.x), "=f"(v.y), "=f"(v.z), "=f"(v.w) : "r"(a) : "memory"); return v; }
__device__ __forceinline__ uint4 lds128(uint32_t a) {
  uint4 v; asm volatile("ld.shared.v4.b32 {%0,%1,%2,%3}, [%4];" : "=r"(v.x), "=r"(v.y), "=r"(v.z), "=r"(v.w) : "r"(a) : "memory"); return v; }
__device__ __forceinline__ uint4 ldg_strong128(const void* p) {
  uint4 v; asm volatile("ld.relaxed.gpu.global.v4.u32 {%0,%1,%2,%3}, [%4];" : "=r"(v.x), "=r"(v.y), "=r"(v.z), "=r"(v.w) : "l"(p) : "memory"); return v; }
__device__ __forceinline__ uint2 ldg_strong64(const void* p) {
  uint2 v; asm volatile("ld.relaxed.gpu.global.v2.u32 {%0,%1}, [%2];" : "=r"(v.x), "=r"(v.y) : "l"(p) : "memory"); return v; }
__device__ __forceinline__ void stg_strong32(void* p, uint32_t v) { asm volatile("st.relaxed.gpu.global.u32 [%0], %1;" :: "l"(p), "r"(v) : "memory"); }
__device__ __forceinline__ void stg_strong128(void* p, uint4 v) {
  asm volatile("st.relaxed.gpu.global.v4.u32 [%0], {%1,%2,%3,%4};" :: "l"(p), "r"(v.x), "r"(v.y), "r"(v.z), "r"(v.w) : "memory"); }
__device__ __forceinline__ uint32_t mapa(uint32_t a, uint32_t r) {
  uint32_t o; asm("mapa.shared::cluster.u32 %0, %1, %2;" : "=r"(o) : "r"(a), "r"(r)); return o; }
__device__ __forceinline__ void st_async2f(uint32_t a, float x, float y, uint32_t bar) {
  asm volatile("st.async.shared::cluster.mbarrier::complete_tx::bytes.v2.f32 [%0], {%1,%2}, [%3];" :: "r"(a), "f"(x), "f"(y), "r"(bar) : "memory"); }
__device__ __forceinline__ void st_async32(uint32_t a, uint32_t x, uint32_t bar) {
  asm volatile("st.async.shared::cluster.mbarrier::complete_tx::bytes.b32 [%0], %1, [%2];" :: "r"(a), "r"(x), "r"(bar) : "memory"); }
__device__ __forceinline__ uint32_t lds32(uint32_t a) { uint32_t v; asm volatile("ld.shared.b32 %0, [%1];" : "=r"(v) : "r"(a) : "memory"); return v; }
__device__ __forceinline__ void st_async64(uint32_t a, uint32_t x, uint32_t y, uint32_t bar) {
  asm volatile("st.async.shared::cluster.mbarrier::complete_tx::bytes.v2.b32 [%0], {%1,%2}, [%3];" :: "r"(a), "r"(x), "r"(y), "r"(bar) : "memory"); }
__device__ __forceinline__ void st_async128(uint32_t a, uint4 v, uint32_t bar) {
  asm volatile("st.async.shared::cluster.mbarrier::complete_tx::bytes.v4.b32 [%0], {%1,%2,%3,%4}, [%5];" :: "r"(a), "r"(v.x), "r"(v.y), "r"(v.z), "r"(v.w), "r"(bar) : "memory"); }
__device__ __forceinline__ uint2 lds64(uint32_t a) { uint2 v; asm volatile("ld.shared.v2.b32 {%0,%1}, [%2];" : "=r"(v.x), "=r"(v.y) : "r"(a) : "memory"); return v; }
__device__ __forceinline__ void sts64(uint32_t a, uint32_t x, uint32_t y) { asm volatile("st.shared.v2.b32 [%0], {%1,%2};" :: "r"(a), "r"(x), "r"(y) : "memory"); }
__device__ __forceinline__ uint32_t ldg_strong32(const void* p) { uint32_t v; asm volatile("ld.relaxed.gpu.global.u32 %0, [%1];" : "=r"(v) : "l"(p) : "memory"); return v; }
__device__ __forceinline__ uint32_t transpose8(uint32_t x) { uint32_t r; asm volatile("movmatrix.sync.aligned.m8n8.trans.b16 %0, %1;" : "=r"(r) : "r"(x)); return r; }
__device__ __forceinline__ uint32_t hadd2(uint32_t a, uint32_t b) { uint32_t r; asm("add.rn.bf16x2 %0, %1, %2;" : "=r"(r) : "r"(a), "r"(b)); return r; }
__device__ __forceinline__ uint32_t min4(uint4 v) { return min(__vimin3_u32(v.x, v.y, v.z), v.w); }

__device__ __forceinline__ void wg_ss192_01(float* d, uint64_t da, uint64_t db, int sd) {
  asm volatile("{.reg .pred p; setp.ne.b32 p, %98, 0;\n"
    "wgmma.mma_async.sync.aligned.m64n192k16.f32.bf16.bf16 {%0,%1,%2,%3,%4,%5,%6,%7,%8,%9,%10,%11,%12,%13,%14,%15,%16,%17,%18,%19,%20,%21,%22,%23,%24,%25,%26,%27,%28,%29,%30,%31,%32,%33,%34,%35,%36,%37,%38,%39,%40,%41,%42,%43,%44,%45,%46,%47,%48,%49,%50,%51,%52,%53,%54,%55,%56,%57,%58,%59,%60,%61,%62,%63,%64,%65,%66,%67,%68,%69,%70,%71,%72,%73,%74,%75,%76,%77,%78,%79,%80,%81,%82,%83,%84,%85,%86,%87,%88,%89,%90,%91,%92,%93,%94,%95}, %96, %97, p, 1, 1, 0, 1;}"
    : "+f"(d[0]),"+f"(d[1]),"+f"(d[2]),"+f"(d[3]),"+f"(d[4]),"+f"(d[5]),"+f"(d[6]),"+f"(d[7]),"+f"(d[8]),"+f"(d[9]),"+f"(d[10]),"+f"(d[11]),"+f"(d[12]),"+f"(d[13]),"+f"(d[14]),"+f"(d[15]),"+f"(d[16]),"+f"(d[17]),"+f"(d[18]),"+f"(d[19]),"+f"(d[20]),"+f"(d[21]),"+f"(d[22]),"+f"(d[23]),"+f"(d[24]),"+f"(d[25]),"+f"(d[26]),"+f"(d[27]),"+f"(d[28]),"+f"(d[29]),"+f"(d[30]),"+f"(d[31]),"+f"(d[32]),"+f"(d[33]),"+f"(d[34]),"+f"(d[35]),"+f"(d[36]),"+f"(d[37]),"+f"(d[38]),"+f"(d[39]),"+f"(d[40]),"+f"(d[41]),"+f"(d[42]),"+f"(d[43]),"+f"(d[44]),"+f"(d[45]),"+f"(d[46]),"+f"(d[47]),"+f"(d[48]),"+f"(d[49]),"+f"(d[50]),"+f"(d[51]),"+f"(d[52]),"+f"(d[53]),"+f"(d[54]),"+f"(d[55]),"+f"(d[56]),"+f"(d[57]),"+f"(d[58]),"+f"(d[59]),"+f"(d[60]),"+f"(d[61]),"+f"(d[62]),"+f"(d[63]),"+f"(d[64]),"+f"(d[65]),"+f"(d[66]),"+f"(d[67]),"+f"(d[68]),"+f"(d[69]),"+f"(d[70]),"+f"(d[71]),"+f"(d[72]),"+f"(d[73]),"+f"(d[74]),"+f"(d[75]),"+f"(d[76]),"+f"(d[77]),"+f"(d[78]),"+f"(d[79]),"+f"(d[80]),"+f"(d[81]),"+f"(d[82]),"+f"(d[83]),"+f"(d[84]),"+f"(d[85]),"+f"(d[86]),"+f"(d[87]),"+f"(d[88]),"+f"(d[89]),"+f"(d[90]),"+f"(d[91]),"+f"(d[92]),"+f"(d[93]),"+f"(d[94]),"+f"(d[95])
    : "l"(da), "l"(db), "r"(sd));
}
__device__ __forceinline__ void wg_ss128_01(float* d, uint64_t da, uint64_t db, int sd) {
  asm volatile("{.reg .pred p; setp.ne.b32 p, %66, 0;\n"
    "wgmma.mma_async.sync.aligned.m64n128k16.f32.bf16.bf16 {%0,%1,%2,%3,%4,%5,%6,%7,%8,%9,%10,%11,%12,%13,%14,%15,%16,%17,%18,%19,%20,%21,%22,%23,%24,%25,%26,%27,%28,%29,%30,%31,%32,%33,%34,%35,%36,%37,%38,%39,%40,%41,%42,%43,%44,%45,%46,%47,%48,%49,%50,%51,%52,%53,%54,%55,%56,%57,%58,%59,%60,%61,%62,%63}, %64, %65, p, 1, 1, 0, 1;}"
    : "+f"(d[0]),"+f"(d[1]),"+f"(d[2]),"+f"(d[3]),"+f"(d[4]),"+f"(d[5]),"+f"(d[6]),"+f"(d[7]),"+f"(d[8]),"+f"(d[9]),"+f"(d[10]),"+f"(d[11]),"+f"(d[12]),"+f"(d[13]),"+f"(d[14]),"+f"(d[15]),"+f"(d[16]),"+f"(d[17]),"+f"(d[18]),"+f"(d[19]),"+f"(d[20]),"+f"(d[21]),"+f"(d[22]),"+f"(d[23]),"+f"(d[24]),"+f"(d[25]),"+f"(d[26]),"+f"(d[27]),"+f"(d[28]),"+f"(d[29]),"+f"(d[30]),"+f"(d[31]),"+f"(d[32]),"+f"(d[33]),"+f"(d[34]),"+f"(d[35]),"+f"(d[36]),"+f"(d[37]),"+f"(d[38]),"+f"(d[39]),"+f"(d[40]),"+f"(d[41]),"+f"(d[42]),"+f"(d[43]),"+f"(d[44]),"+f"(d[45]),"+f"(d[46]),"+f"(d[47]),"+f"(d[48]),"+f"(d[49]),"+f"(d[50]),"+f"(d[51]),"+f"(d[52]),"+f"(d[53]),"+f"(d[54]),"+f"(d[55]),"+f"(d[56]),"+f"(d[57]),"+f"(d[58]),"+f"(d[59]),"+f"(d[60]),"+f"(d[61]),"+f"(d[62]),"+f"(d[63])
    : "l"(da), "l"(db), "r"(sd));
}
__device__ __forceinline__ void wg_ss160_01(float* d, uint64_t da, uint64_t db, int sd) {
  asm volatile("{.reg .pred p; setp.ne.b32 p, %82, 0;\n"
    "wgmma.mma_async.sync.aligned.m64n160k16.f32.bf16.bf16 {%0,%1,%2,%3,%4,%5,%6,%7,%8,%9,%10,%11,%12,%13,%14,%15,%16,%17,%18,%19,%20,%21,%22,%23,%24,%25,%26,%27,%28,%29,%30,%31,%32,%33,%34,%35,%36,%37,%38,%39,%40,%41,%42,%43,%44,%45,%46,%47,%48,%49,%50,%51,%52,%53,%54,%55,%56,%57,%58,%59,%60,%61,%62,%63,%64,%65,%66,%67,%68,%69,%70,%71,%72,%73,%74,%75,%76,%77,%78,%79}, %80, %81, p, 1, 1, 0, 1;}"
    : "+f"(d[0]),"+f"(d[1]),"+f"(d[2]),"+f"(d[3]),"+f"(d[4]),"+f"(d[5]),"+f"(d[6]),"+f"(d[7]),"+f"(d[8]),"+f"(d[9]),"+f"(d[10]),"+f"(d[11]),"+f"(d[12]),"+f"(d[13]),"+f"(d[14]),"+f"(d[15]),"+f"(d[16]),"+f"(d[17]),"+f"(d[18]),"+f"(d[19]),"+f"(d[20]),"+f"(d[21]),"+f"(d[22]),"+f"(d[23]),"+f"(d[24]),"+f"(d[25]),"+f"(d[26]),"+f"(d[27]),"+f"(d[28]),"+f"(d[29]),"+f"(d[30]),"+f"(d[31]),"+f"(d[32]),"+f"(d[33]),"+f"(d[34]),"+f"(d[35]),"+f"(d[36]),"+f"(d[37]),"+f"(d[38]),"+f"(d[39]),"+f"(d[40]),"+f"(d[41]),"+f"(d[42]),"+f"(d[43]),"+f"(d[44]),"+f"(d[45]),"+f"(d[46]),"+f"(d[47]),"+f"(d[48]),"+f"(d[49]),"+f"(d[50]),"+f"(d[51]),"+f"(d[52]),"+f"(d[53]),"+f"(d[54]),"+f"(d[55]),"+f"(d[56]),"+f"(d[57]),"+f"(d[58]),"+f"(d[59]),"+f"(d[60]),"+f"(d[61]),"+f"(d[62]),"+f"(d[63]),"+f"(d[64]),"+f"(d[65]),"+f"(d[66]),"+f"(d[67]),"+f"(d[68]),"+f"(d[69]),"+f"(d[70]),"+f"(d[71]),"+f"(d[72]),"+f"(d[73]),"+f"(d[74]),"+f"(d[75]),"+f"(d[76]),"+f"(d[77]),"+f"(d[78]),"+f"(d[79])
    : "l"(da), "l"(db), "r"(sd));
}
__device__ __forceinline__ void wg_ss80_01(float* d, uint64_t da, uint64_t db, int sd) {
  asm volatile("{.reg .pred p; setp.ne.b32 p, %42, 0;\n"
    "wgmma.mma_async.sync.aligned.m64n80k16.f32.bf16.bf16 {%0,%1,%2,%3,%4,%5,%6,%7,%8,%9,%10,%11,%12,%13,%14,%15,%16,%17,%18,%19,%20,%21,%22,%23,%24,%25,%26,%27,%28,%29,%30,%31,%32,%33,%34,%35,%36,%37,%38,%39}, %40, %41, p, 1, 1, 0, 1;}"
    : "+f"(d[0]),"+f"(d[1]),"+f"(d[2]),"+f"(d[3]),"+f"(d[4]),"+f"(d[5]),"+f"(d[6]),"+f"(d[7]),"+f"(d[8]),"+f"(d[9]),"+f"(d[10]),"+f"(d[11]),"+f"(d[12]),"+f"(d[13]),"+f"(d[14]),"+f"(d[15]),"+f"(d[16]),"+f"(d[17]),"+f"(d[18]),"+f"(d[19]),"+f"(d[20]),"+f"(d[21]),"+f"(d[22]),"+f"(d[23]),"+f"(d[24]),"+f"(d[25]),"+f"(d[26]),"+f"(d[27]),"+f"(d[28]),"+f"(d[29]),"+f"(d[30]),"+f"(d[31]),"+f"(d[32]),"+f"(d[33]),"+f"(d[34]),"+f"(d[35]),"+f"(d[36]),"+f"(d[37]),"+f"(d[38]),"+f"(d[39])
    : "l"(da), "l"(db), "r"(sd));
}
__device__ __forceinline__ void wg_rs32_00(float* d, uint32_t a0, uint32_t a1, uint32_t a2, uint32_t a3, uint64_t db, int sd) {
  asm volatile("{.reg .pred p; setp.ne.b32 p, %21, 0;\n"
    "wgmma.mma_async.sync.aligned.m64n32k16.f32.bf16.bf16 {%0,%1,%2,%3,%4,%5,%6,%7,%8,%9,%10,%11,%12,%13,%14,%15}, {%16,%17,%18,%19}, %20, p, 1, 1, 0;}"
    : "+f"(d[0]),"+f"(d[1]),"+f"(d[2]),"+f"(d[3]),"+f"(d[4]),"+f"(d[5]),"+f"(d[6]),"+f"(d[7]),"+f"(d[8]),"+f"(d[9]),"+f"(d[10]),"+f"(d[11]),"+f"(d[12]),"+f"(d[13]),"+f"(d[14]),"+f"(d[15])
    : "r"(a0), "r"(a1), "r"(a2), "r"(a3), "l"(db), "r"(sd));
}
__device__ __forceinline__ void wg_rs64_00(float* d, uint32_t a0, uint32_t a1, uint32_t a2, uint32_t a3, uint64_t db, int sd) {
  asm volatile("{.reg .pred p; setp.ne.b32 p, %37, 0;\n"
    "wgmma.mma_async.sync.aligned.m64n64k16.f32.bf16.bf16 {%0,%1,%2,%3,%4,%5,%6,%7,%8,%9,%10,%11,%12,%13,%14,%15,%16,%17,%18,%19,%20,%21,%22,%23,%24,%25,%26,%27,%28,%29,%30,%31}, {%32,%33,%34,%35}, %36, p, 1, 1, 0;}"
    : "+f"(d[0]),"+f"(d[1]),"+f"(d[2]),"+f"(d[3]),"+f"(d[4]),"+f"(d[5]),"+f"(d[6]),"+f"(d[7]),"+f"(d[8]),"+f"(d[9]),"+f"(d[10]),"+f"(d[11]),"+f"(d[12]),"+f"(d[13]),"+f"(d[14]),"+f"(d[15]),"+f"(d[16]),"+f"(d[17]),"+f"(d[18]),"+f"(d[19]),"+f"(d[20]),"+f"(d[21]),"+f"(d[22]),"+f"(d[23]),"+f"(d[24]),"+f"(d[25]),"+f"(d[26]),"+f"(d[27]),"+f"(d[28]),"+f"(d[29]),"+f"(d[30]),"+f"(d[31])
    : "r"(a0), "r"(a1), "r"(a2), "r"(a3), "l"(db), "r"(sd));
}
__device__ __forceinline__ void wg_rs80_01(float* d, uint32_t a0, uint32_t a1, uint32_t a2, uint32_t a3, uint64_t db, int sd) {
  asm volatile("{.reg .pred p; setp.ne.b32 p, %45, 0;\n"
    "wgmma.mma_async.sync.aligned.m64n80k16.f32.bf16.bf16 {%0,%1,%2,%3,%4,%5,%6,%7,%8,%9,%10,%11,%12,%13,%14,%15,%16,%17,%18,%19,%20,%21,%22,%23,%24,%25,%26,%27,%28,%29,%30,%31,%32,%33,%34,%35,%36,%37,%38,%39}, {%40,%41,%42,%43}, %44, p, 1, 1, 1;}"
    : "+f"(d[0]),"+f"(d[1]),"+f"(d[2]),"+f"(d[3]),"+f"(d[4]),"+f"(d[5]),"+f"(d[6]),"+f"(d[7]),"+f"(d[8]),"+f"(d[9]),"+f"(d[10]),"+f"(d[11]),"+f"(d[12]),"+f"(d[13]),"+f"(d[14]),"+f"(d[15]),"+f"(d[16]),"+f"(d[17]),"+f"(d[18]),"+f"(d[19]),"+f"(d[20]),"+f"(d[21]),"+f"(d[22]),"+f"(d[23]),"+f"(d[24]),"+f"(d[25]),"+f"(d[26]),"+f"(d[27]),"+f"(d[28]),"+f"(d[29]),"+f"(d[30]),"+f"(d[31]),"+f"(d[32]),"+f"(d[33]),"+f"(d[34]),"+f"(d[35]),"+f"(d[36]),"+f"(d[37]),"+f"(d[38]),"+f"(d[39])
    : "r"(a0), "r"(a1), "r"(a2), "r"(a3), "l"(db), "r"(sd));
}
__device__ __forceinline__ void wg_rs24_01(float* d, uint32_t a0, uint32_t a1, uint32_t a2, uint32_t a3, uint64_t db, int sd) {
  asm volatile("{.reg .pred p; setp.ne.b32 p, %17, 0;\n"
    "wgmma.mma_async.sync.aligned.m64n24k16.f32.bf16.bf16 {%0,%1,%2,%3,%4,%5,%6,%7,%8,%9,%10,%11}, {%12,%13,%14,%15}, %16, p, 1, 1, 1;}"
    : "+f"(d[0]),"+f"(d[1]),"+f"(d[2]),"+f"(d[3]),"+f"(d[4]),"+f"(d[5]),"+f"(d[6]),"+f"(d[7]),"+f"(d[8]),"+f"(d[9]),"+f"(d[10]),"+f"(d[11])
    : "r"(a0), "r"(a1), "r"(a2), "r"(a3), "l"(db), "r"(sd));
}

#define AB_POLY 0x77
__device__ __forceinline__ constexpr bool poly_group(int group) { return (AB_POLY >> (group & 7)) & 1; }

template <int V> struct Int { static constexpr int value = V; };

__device__ __forceinline__ int core_word(int row, int col) {
  return ((((row >> 7) * 10 + (col >> 6)) * 16 + ((row >> 3) & 15)) * 8 + ((col >> 3) & 7)) * 32 + (row & 7) * 4 + ((col & 7) >> 1);
}
__device__ __forceinline__ void wait_count(const uint32_t* c, uint32_t n) {
  for (int spin = 0; !__all_sync(~0u, (ld_acquire(c) & 0xffff) >= n);) { __nanosleep(32); spin_guard(spin); }
  fence_async_global();
}
__device__ __forceinline__ void prefetch_l2(const void* p, uint32_t bytes) {
  asm volatile("cp.async.bulk.prefetch.L2.global [%0], %1;" :: "l"(p), "r"(bytes) : "memory"); }

#define PLACE 4
__device__ __forceinline__ bool helper_sm() {
  uint32_t m; asm volatile("mov.u32 %0, %%smid;" : "=r"(m));
  m = __shfl_sync(~0u, m, 0);
  return m < 2 || m >= 120 || (m >= 92 && m < 102) || (m >= 106 && m < 117) || m == 118;
}

__device__ __forceinline__ uint8_t* pool_at(uint32_t off) {
  return reinterpret_cast<uint8_t*>((reinterpret_cast<uintptr_t>(g_pool) + 8191) & ~(uintptr_t)8191) + off; }
__device__ __forceinline__ void probe_slots(uint32_t scratch) {
  const int w = __shfl_sync(~0u, (threadIdx.x >> 6) & 1, 0), slot = w == 0 ? NSLOT : blockIdx.x;
  if (w == 0 || slot < NSLOT) {
    uint32_t* q = reinterpret_cast<uint32_t*>(pool_at(slot * 8192)) + (w == 0 ? (blockIdx.x & 31) * 32 + (blockIdx.x >> 5) : 0);
    uint32_t best[2] = {~0u, ~0u};
    const bool one = elect();
    if (one) { stg_strong32(q, 0u); stg_strong32(q + 1024, 0u); }
#pragma unroll 1
    for (int r = 0; r < 8; r++) {
      uint32_t v = 0;
      const uint32_t t0 = clk32();
      if (one) asm volatile("atom.relaxed.gpu.global.exch.b32 %0, [%1], 0;" : "=r"(v) : "l"(q + (r & 1) * 1024) : "memory");
      if (__any_sync(~0u, v != 0)) break;
      const uint32_t t = min(clk32() - t0, best[0]);
      best[0] = best[1]; best[1] = t;
    }
    if (one) sts32(scratch + w * 4, best[0] < best[1]);
  }
  bar_sync(2, 64);
  if ((threadIdx.x & 31) == 0) {
    const int part = lds32(scratch) ? 1 : 2;
    if (w == 0) { uint32_t smid; asm("mov.u32 %0, %%smid;" : "=r"(smid)); stg_strong32(g_smpart + (smid & 255), part); }
    else if (slot < NSLOT) stg_strong32(g_orient + slot, lds32(scratch + 4) ? part : 3 - part);
  }
  __syncwarp();
}

constexpr int WK_SLOTS = 28, WK_BAR = WK_SLOTS * 8192;
__device__ __forceinline__ void work_init(uint32_t sb, int w) {
  if (elect()) {
#pragma unroll
    for (int i = 0; i < 8; i++) mbar_init(sb + WK_BAR + 64 * w + 8 * i, 0x18318822 >> (8 * w + (i & 4)) & 15);
  }
  asm volatile("fence.mbarrier_init.release.cluster;" ::: "memory");
}

struct ChainParams {
  CUtensorMap wq, wk, wv, wo, xc;
  const __nv_bfloat16* mem0;
  const uint8_t* wb;
  uint32_t *sync, *other;
  int layer;
  int d1, d2, dn, dx, mode, zero;
};
constexpr int CH_WQ = 0, CH_WO = 81920, CH_X = CH_WO + 86016, CH_M = CH_X, CH_Q = CH_X + 34816, CH_KM = CH_Q + 2048, CH_VP = CH_KM + 2048,
              CH_K = CH_X + 40960, CH_O = CH_K, CH_KS = CH_K + 3072, CH_V = CH_K + 4096, CH_VX = CH_V + 12288, CH_R2 = CH_VX,
              CH_SX = CH_VX + 3072, CH_SO = CH_SX + 2048, CH_ID = CH_SO + 1024, CH_L = CH_ID + 256, CH_TAB = CH_L + 64, CH_BAR = CH_TAB + 384;
constexpr int CH_SMEM = CH_BAR + 144;
constexpr int MB_WO = CH_BAR, MB_WQ = CH_BAR + 8, MB_X = CH_BAR + 16, MB_V = CH_BAR + 24, MB_T = CH_BAR + 32, MB_F = CH_BAR + 40, MB_G = CH_BAR + 48, MB_W = CH_BAR + 56;
enum { NB_PROJ = 1, NB_O = 2, NB_W1 = 3, NB_PRE = 4, NB_ST = 5, NB_MEM = 6, NB_XFREE = 7, NB_H1 = 8, NB_PUB = 9, NB_W2 = 10, NB_PROJ2 = 11, NB_PRE2 = 12, NB_H2 = 13, NB_W1V = 14 };
#define CH_NQ 9
#define CH_XPF 1
#define CH_TPF 1
#define CH_FLY 6
#define CH_TW 1
#define H1VOTE 0
#define CH_NQ0 4
#define CH_PA 6
#define CH_PB 9
#define CH_PC 13
#define CH_PL 4
#define CH_DBL 0x0888
#define CH_PD 1
#define SCHED() asm volatile("griddepcontrol.launch_dependents;" ::: "memory")
__device__ __forceinline__ uint32_t opaque(uint32_t x) { return __shfl_sync(~0u, x, threadIdx.x & 31); }
__device__ __forceinline__ uint32_t uniform(uint32_t x) { return __shfl_sync(~0u, x, 0); }
__device__ __forceinline__ uint32_t nz(uint32_t x) { uint32_t r; asm("max.u32 %0, %1, 1;" : "=r"(r) : "r"(x)); return r; }
__device__ __forceinline__ uint32_t set_tag(uint32_t w, uint32_t tag) { uint32_t r; asm("lop3.b32 %0, %1, %2, 1, 0xD8;" : "=r"(r) : "r"(w), "r"(tag)); return r; }
__device__ __forceinline__ uint32_t pack_tag(float lo, float hi, uint32_t tag) { return set_tag(__byte_perm(__float_as_uint(lo) + tag, pack2(hi, hi), 0x7632), tag); }
__device__ __forceinline__ uint32_t differ(uint32_t a, uint32_t b, uint32_t t) { uint32_t r; asm("lop3.b32 %0, %1, %2, %3, 0x7E;" : "=r"(r) : "r"(a), "r"(b), "r"(t)); return r; }
__device__ __forceinline__ uint32_t clk64() { uint64_t c; asm volatile("mov.u64 %0, %%clock64;" : "=l"(c) :: "memory"); return (uint32_t)c; }
__device__ __forceinline__ void until(uint32_t t) {
  asm volatile("{.reg .pred p; .reg .u64 c; .reg .s32 d;\nW: mov.u64 c, %%clock64; cvt.u32.u64 d, c; sub.s32 d, d, %0; setp.lt.s32 p, d, 0; @p bra.uni W;}" :: "r"(t) : "memory");
}
__device__ __forceinline__ float rcp(float x) { float y; asm("rcp.approx.ftz.f32 %0, %1;" : "=f"(y) : "f"(x)); return y; }

__device__ __forceinline__ void chain_compute(const ChainParams& p, const uint32_t sb) {
  const int tid = threadIdx.x & 127, WG = __shfl_sync(~0u, threadIdx.x >> 7, 0), t4 = __shfl_sync(~0u, tid >> 5, 0), lane = tid & 31;
  const int cta = blockIdx.x, h = cta / 3, j = cta - 3 * h;
  uint32_t a0[80], a1[80], tw[4 * CH_NQ];
  const uint32_t wq = opaque(sb + CH_WQ + (WG * 320 + (lane & 7) + (lane >> 4) * 8) * 128 + (((2 * t4 + ((lane >> 3) & 1)) ^ (lane & 7)) << 4));
#pragma unroll
  for (int k = 0; k < 40; k++) {
    if (k % 10 == 0) mbar_wait(sb + MB_W + WG * 8 + k / 10 * 16, 0);
    if (k < 20) ldsm4t(&a0[4 * k], wq + k * 2048); else ldsm4t(&a1[4 * k - 80], wq + CH_WO + (k - 20) * 2048);
    if (k % 20 == 19) bar_arrive(k < 20 ? NB_PROJ2 : NB_PRE2, 288);
  }
  const int r1 = j == 2 ? 0 : j + 1, r2 = j == 0 ? 2 : j - 1;
  const uint32_t l16 = opaque(sb + lane * 16), l8 = opaque(sb + lane * 8), l4 = opaque(sb + lane * 4);
  const uint32_t t16 = l16 + t4 * 512, t8 = l8 + t4 * 256;
  uint32_t wo = opaque(sb + CH_WO + (WG == 0 ? (t4 >> 1) * 36864 : 73728 + t4 * 1024) + ((lane & 7) + (lane >> 4) * 8) * 64 +
                       (((((lane >> 3) & 1) + (WG == 0 ? (t4 & 1) * 2 : 0)) ^ ((lane >> 1) & 3)) << 4));
  const uint32_t ko0 = uniform(CH_K + (tid >> 5) * 1024 + (tid >> 6) * 512), ko1 = uniform(CH_K + (tid >> 5) * 1024 + 512 - (tid >> 6) * 512),
                 o768 = uniform((tid >> 5) * 768);
  const uint32_t give = uniform(t4 * 512 + (WG == 0 ? CH_K : CH_V + j * 4096)), own = uniform(t4 * 512 + (WG == 0 ? CH_V + j * 4096 : CH_K)), mem = uniform(CH_M + WG * 5120);
  const uint32_t vxo = uniform(t4 * 256 + CH_VX + j * 1024);
  uint32_t tag = 1, xd = uniform((1024 + CH_X + WG * 20480) >> 4 | 8 << 16);
  asm volatile("barrier.cluster.wait.aligned;" ::: "memory");
  mbar_wait(sb + MB_WQ, 0);
  mbar_wait(sb + MB_T, 0);
  bar_sync(NB_ST, 384);
  uint8_t* pdst[6];
#pragma unroll
  for (int i = 0; i < 6; i++) {
    const int line = WG == 0 ? 24 * j + 12 * (t4 >> 1) + 2 * (t4 & 1) + 4 * (i >> 1) + (i & 1) : j == 0 ? 72 + t4 : 74 + 2 * j + (t4 & 1);
    pdst[i] = pool_at(uniform(lds32(sb + CH_TAB + line * 4)) + h * 128);
  }
  auto batch = [&](float* d, const uint32_t (&a)[80], int acc, int n0, int n1) {
    const uint32_t d0 = xd ^ (tag & (2 << acc));
    wg_fence();
#pragma unroll
    for (int k = 0; k < 20; k++) {
      if (!(k & 3) && n0 + k / 4 < n1) {
        __syncwarp();
        ldsm4t(&tw[4 * n0 + k], wq + (n0 + k / 4) * 2048);
        __syncwarp();
      }
      uint64_t db;
      asm("mov.b64 %0, {%1, %2};" : "=l"(db) : "r"(d0 + k / 5 * 320 + k % 5 * 16), "r"(80));
      wg_rs32_00(d, a[4 * k], a[4 * k + 1], a[4 * k + 2], a[4 * k + 3], db, acc | k);
    }
    wg_commit();
    wg_wait<0>();
    reg_fence<16>(d);
  };
  int s = 0;
#pragma unroll 1
  do {
    {
      float d[16];
      if (!CH_TW) mbar_wait(sb + MB_T, s & 1);
      batch(d, a0, 0, 0, CH_NQ0);
      s--; TM(10); s++;
      mbar_wait(sb + MB_F, ~s & 1);
#pragma unroll
      for (int i = 0; i < 2; i++)
        sts128(l16 + give + i * 2048, make_uint4(pack2(d[8 * i], d[8 * i + 1]), pack2(d[8 * i + 2], d[8 * i + 3]), pack2(d[8 * i + 4], d[8 * i + 5]), pack2(d[8 * i + 6], d[8 * i + 7])));
      bar_sync(NB_PUB, 384);
#pragma unroll
      for (int i = 0; i < 2; i++) {
        const uint4 t = lds128(l16 + own + i * 2048);
        d[8 * i] = bf_lo(t.x); d[8 * i + 1] = bf_hi(t.x); d[8 * i + 2] = bf_lo(t.y); d[8 * i + 3] = bf_hi(t.y);
        d[8 * i + 4] = bf_lo(t.z); d[8 * i + 5] = bf_hi(t.z); d[8 * i + 6] = bf_lo(t.w); d[8 * i + 7] = bf_hi(t.w);
      }
      reg_fence<16>(d);
      batch(d, a1, 1, CH_NQ0, CH_NQ);
      s--; TM(11); s++;
      if (WG == 0) bar_arrive(NB_XFREE, 256);
#pragma unroll
      for (int i = 0; i < 8; i++) sts32(l4 + (own - t4 * 256) + (i >> 1) * 1024 + (i & 1) * 128, pack2(d[2 * i], d[2 * i + 1]));
      s--; TM(9); s++;
    }
    float dq[4] = {}, d0[4] = {}, d1[4] = {};
    uint32_t b[40], wf[80];
    const uint32_t* kf = &wf[52];
#pragma unroll
    for (int i = 0; i < 4 * CH_NQ; i++) wf[i] = tw[i];
    auto step = [&](int k) {
      mma16(dq, wf[4 * k], wf[4 * k + 1], wf[4 * k + 2], wf[4 * k + 3], b[2 * k], b[2 * k + 1]);
      mma16(d0, a0[4 * k], a0[4 * k + 1], a0[4 * k + 2], a0[4 * k + 3], b[2 * k], b[2 * k + 1]);
      mma16(d1, a1[4 * k], a1[4 * k + 1], a1[4 * k + 2], a1[4 * k + 3], b[2 * k], b[2 * k + 1]);
    };
    auto finish = [&](int wg, const float* dk) {
      const float k2 = 0.07216878364870322f * 1.44269504089f;
      sts32(l4 + t4 * 512 + CH_Q + wg * 128, pack2(dq[0] * k2, dq[1] * k2));
      sts32(l4 + t4 * 512 + CH_Q + wg * 128 + 256, pack2(dq[2] * k2, dq[3] * k2));
      sts32(l4 + t4 * 512 + CH_KM + wg * 256, pack2(dk[0], dk[1]));
      sts32(l4 + t4 * 512 + CH_KM + wg * 256 + 128, pack2(dk[2], dk[3]));
    };
    const bool more = s < NSEG - 1;
    bar_sync(NB_MEM, 384);
    ldsm4t(&b[0], l16 + mem);
    ldsm4t(&b[4], l16 + mem + 512);
    TMD(0, b[0]);
    {
      int nw = CH_NQ, nb = 2;
#pragma unroll
      for (int k = 0; k < 20; k++) {
        SCHED();
        step(k);
#pragma unroll
        for (int i = 0; i < (CH_DBL >> k & 1) + 1; i++) {
          if (nb < 10 && 2 * nb <= nw) { ldsm4t(&b[4 * nb], l16 + mem + nb * 512); nb++; }
          else if (nw < 20) { ldsm4t(&wf[4 * nw], wq + nw * 2048); nw++; }
          else if (nw < 22) {
            const uint32_t x = l16 ^ ((o768 ^ tag) & 256);
            uint32_t* r = &wf[4 * nw - 28];
            asm volatile("{.reg .pred p; setp.ne.u32 p, %5, 0; @p ldmatrix.sync.aligned.m8n8.x4.trans.shared.b16 {%0,%1,%2,%3},[%4];}"
                         : "+r"(r[0]), "+r"(r[1]), "+r"(r[2]), "+r"(r[3]) : "r"(x + (nw == 20 ? ko0 : ko1)), "r"(WG) : "memory");
            nw++;
          }
        }
      }
      SCHED();
    }
    if (WG == 0) {
      finish(0, d0);
      TM(1);
      bar_sync(NB_PROJ, 256);
      if (!more) {
        const float4 pv = lds128f(t16 + CH_VP);
        sts32(l4 + vxo, pack2(d1[0] + pv.x, d1[1] + pv.y));
        sts32(l4 + vxo + 128, pack2(d1[2] + pv.z, d1[3] + pv.w));
        continue;
      }
      const float4 pv = lds128f(t16 + CH_VP);
      const uint32_t xo = l4 + (vxo ^ (tag & 2)), x1 = mapa(xo, r1), x2 = mapa(xo, r2);
      SCHED();
      const uint32_t v0 = pack2(d1[0] + pv.x, d1[1] + pv.y), v1 = pack2(d1[2] + pv.z, d1[3] + pv.w);
      st_async32(x1, v0, mapa(sb + MB_X, r1));
      st_async32(x2, v0, mapa(sb + MB_X, r2));
      st_async32(x1 + 128, v1, mapa(sb + MB_X, r1));
      st_async32(x2 + 128, v1, mapa(sb + MB_X, r2));
      sts32(xo, v0);
      sts32(xo + 128, v1);
      __syncwarp();
      mbar_arrive_one(sb + MB_X);
      bar_arrive(NB_PROJ2, 256);
      TM(3);
      uint32_t w[144];
      auto tile_of = [](int n) { return n < 27 ? n % 3 : (0x26484 >> 2 * (n - 27)) & 3; };
      auto step_of = [](int n) { return n < 27 ? n / 3 : 9 + ((0x29610 >> 2 * (n - 27)) & 3); };
      auto wload = [&](int n) { ldsm4t(&w[4 * n], wo + tile_of(n) * 12288 + (step_of(n) % 3) * 4096 + (step_of(n) / 3) * 1024); };
#pragma unroll
      for (int n = 0; n < CH_PA; n++) wload(n);
      bar_sync(NB_PRE, 256);
#pragma unroll
      for (int n = CH_PA; n < CH_PB; n++) wload(n);
      bar_arrive(NB_PRE2, 256);
      if (CH_PC > CH_PB) {
        mbar_wait(sb + MB_X, s & 1);
        for (int i = 0; i < CH_PD; i++) wo = __shfl_xor_sync(~0u, wo, p.zero);
#pragma unroll
        for (int n = CH_PB; n < CH_PC; n++) wload(n);
      }
      TM(4);
      bar_sync(NB_O, 256);
      {
        float x[3][4] = {};
        uint32_t ob[24];
        float4 l;
        ldsm4t(&ob[0], l16 + CH_O);
        ldsm4t(&ob[4], l16 + CH_O + 512);
        TMD(7, ob[0]);
        int nw = CH_PC, no = 2;
        float i0, i1;
        uint8_t* dst[6];
        uint32_t lo[6], hi[6];
        auto pre = [&](int i) { lo[i] = __float_as_uint(x[i >> 1][2 * (i & 1)] * i0) + tag; hi[i] = pack2(0.f, x[i >> 1][2 * (i & 1) + 1] * i1); };
        auto emit = [&](int i) { stg_strong32(dst[i], set_tag(__byte_perm(lo[i], hi[i], 0x7632), tag)); };
#pragma unroll
        for (int n = 0; n < 36; n++) {
          SCHED();
          mma16(x[tile_of(n)], w[4 * n], w[4 * n + 1], w[4 * n + 2], w[4 * n + 3], ob[step_of(n) * 2], ob[step_of(n) * 2 + 1]);
          if (n >= CH_PL) {
            if (no < 6 && no * 2 <= step_of(min(nw, 35))) { ldsm4t(&ob[4 * no], l16 + CH_O + no * 512); no++; }
            else if (nw < 36) { wload(nw); nw++; }
          }
          if (n == 18) l = lds128f(sb + CH_L + ((l16 ^ tag) & 0x30));
          if (n == 26) { i0 = rcp(l.x + l.y); i1 = rcp(l.z + l.w); asm volatile("" : "+f"(i0), "+f"(i1)); }
          if (n >= 28 && n < 34) { dst[n - 28] = pdst[n - 28] + ((l4 ^ tag) & 0x7c); asm volatile("" : "+l"(dst[n - 28])); }
          if (n == 32) { for (int i = 0; i < 2; i++) { pre(i); asm volatile("" : "+r"(lo[i]), "+r"(hi[i])); } }
          if (n == 33) { emit(0); emit(1); }
        }
        for (int i = 2; i < 6; i++) pre(i);
        for (int i = 2; i < 6; i++) emit(i);
      }
      TM(8);
    } else {
      finish(1, d1);
      sts128f(t16 + CH_VP, d0[0], d0[1], d0[2], d0[3]);
      TM(1);
      bar_sync(NB_PROJ, 256);
      uint32_t pair;
      {
        float d0[4] = {}, d1[4] = {}, dm[4] = {};
        uint32_t q[16], km[4];
#pragma unroll
        for (int e = 0; e < 4; e++) {
          ldsm4t(&q[4 * e], l16 + (e ^ t4) * 512 + CH_Q);
          SCHED();
          if (e == 1) { ldsm4t(km, t16 + CH_KM); SCHED(); }
        }
        const uint32_t xo = l4 + ((t4 * 128) ^ (tag & 2));
        pair = l16 + ((l16 ^ tag) & 256) * 3;
        asm volatile("" : "+r"(pair));
        uint64_t x[4];
#pragma unroll
        for (int i = 0; i < 4; i++) {
          const int r = i & 1 ? r2 : r1;
          asm volatile("mov.b64 %0, {%1, %2};" : "=l"(x[i]) : "r"(mapa(xo, r) + CH_SX + (i & 1) * 1024 + (i & 2) * 256), "r"(mapa(sb + MB_X, r)));
        }
        SCHED();
        mma16(d0, q[0], q[1], q[2], q[3], kf[0], kf[1]);
        SCHED();
        mma16(d1, q[4], q[5], q[6], q[7], kf[2], kf[3]);
        SCHED();
        mma16(dm, q[0], q[1], q[2], q[3], hadd2(km[0], km[2]), hadd2(km[1], km[3]));
        mma16(d0, q[8], q[9], q[10], q[11], kf[4], kf[5]);
        SCHED();
        mma16(d1, q[12], q[13], q[14], q[15], kf[6], kf[7]);
        if (!more) continue;
        const uint32_t w1 = pack2(dm[0] + dm[2], dm[1] + dm[3]);
        st_async32((uint32_t)x[2], w1, x[2] >> 32);
        st_async32((uint32_t)x[3], w1, x[3] >> 32);
        SCHED();
        const uint32_t w0 = pack2((d0[0] + d0[2]) + (d1[0] + d1[2]), (d0[1] + d0[3]) + (d1[1] + d1[3]));
        st_async32((uint32_t)x[0], w0, x[0] >> 32);
        st_async32((uint32_t)x[1], w0, x[1] >> 32);
        sts32(xo + CH_SO, w0);
        sts32(xo + CH_SO + 512, w1);
      }
      TM(3);
      float sc[3][4] = {};
      uint32_t wd[12];
      uint32_t redo;
      auto attend = [&](auto first) {
        uint4 vb[6];
        uint32_t vm[6];
        float e[10];
        uint32_t ow[6];
        if (first.value) {
          const uint2 id = lds64(l8 + CH_ID);
          bar_sync(NB_W1V, 160);
          uint32_t r[8];
          ldsm4(r, l16 + CH_SO); ldsm4(r + 4, l16 + CH_SO + 512);
#pragma unroll
          for (int u = 0; u < 6; u++) vb[u] = ldsm4v(pair + t4 * 256 + CH_V + u * 2048);
          bar_arrive(NB_PRE, 256);
          const uint32_t sxa = pair + CH_SX;
          SCHED();
          mma8(sc[0], r[0], r[1], id.x);
          mma8(sc[1], r[2], r[3], id.x);
          mma16(sc[2], r[4], r[5], r[6], r[7], id.x, id.y);
          TM(7);
          mbar_wait(sb + MB_X, s & 1);
          TM(4);
          uint32_t t[16];
          ldsm4(t, sxa); ldsm4(t + 4, sxa + 256); ldsm4(t + 8, sxa + 512);
          SCHED();
          mma16(sc[0], t[0], t[1], t[2], t[3], id.x, id.y);
          ldsm4(t + 12, sxa + 768);
          SCHED();
          mma16(sc[1], t[4], t[5], t[6], t[7], id.x, id.y);
          ldsm4(vm, pair + t4 * 256 + CH_VX);
          SCHED();
          e[0] = ex2(sc[0][0]);
          mma16(sc[2], t[8], t[9], t[10], t[11], id.x, id.y);
          ldsm2(vm + 4, l16 + t4 * 256 + CH_VX + 2048);
          SCHED();
          e[1] = ex2(sc[0][1]);
          ldsm4t(&wd[0], wo);
          SCHED();
          e[2] = ex2(sc[0][2]);
          SCHED();
          e[3] = ex2(sc[0][3]);
          mma16(sc[2], t[12], t[13], t[14], t[15], id.x, id.y);
          SCHED();
          e[4] = ex2(sc[1][0]);
          ldsm4t(&wd[4], wo + 4096);
          SCHED();
          e[5] = ex2(sc[1][1]);
        } else {
#pragma unroll
          for (int u = 0; u < 6; u++) vb[u] = ldsm4v(pair + t4 * 256 + CH_V + u * 2048);
          ldsm4(vm, pair + t4 * 256 + CH_VX);
          ldsm2(vm + 4, l16 + t4 * 256 + CH_VX + 2048);
        }
        float o[3][4] = {};
        if (!first.value) {
#pragma unroll
          for (int i = 0; i < 6; i++) e[i] = ex2(sc[i >> 2][i & 3]);
        }
        const uint32_t p1 = pack2(e[0], e[1]), p2 = pack2(e[2], e[3]);
        float l = (e[0] + e[1]) + (e[2] + e[3]);
        asm volatile("" : "+f"(l));
        SCHED();
        e[6] = ex2(sc[1][2]);
        mma16(o[0], vb[0].x, vb[0].y, vb[0].z, vb[0].w, p1, p2);
        if (first.value) { sc[2][0] += sc[2][2]; sc[2][1] += sc[2][3]; }
        SCHED();
        e[7] = ex2(sc[1][3]);
        mma16(o[1], vb[2].x, vb[2].y, vb[2].z, vb[2].w, p1, p2);
        SCHED();
        e[8] = ex2(sc[2][0]);
        mma16(o[2], vb[4].x, vb[4].y, vb[4].z, vb[4].w, p1, p2);
        SCHED();
        e[9] = ex2(sc[2][1]);
        SCHED();
        const uint32_t p3 = pack2(e[4], e[5]), p4 = pack2(e[6], e[7]);
        l += (e[4] + e[5]) + (e[6] + e[7]);
#pragma unroll
        for (int u = 0; u < 3; u++) mma16(o[u], vb[2 * u + 1].x, vb[2 * u + 1].y, vb[2 * u + 1].z, vb[2 * u + 1].w, p3, p4);
        SCHED();
        const uint32_t p0 = pack2(e[8], e[9]);
        l += e[8] + e[9];
        const float l2 = __shfl_xor_sync(~0u, l, 1);
        if (first.value) ldsm4t(&wd[8], wo + 8192);
#pragma unroll
        for (int u = 0; u < 3; u++) mma8(o[u], vm[2 * u], vm[2 * u + 1], p0);
        redo = __any_sync(~0u, !(l > 1e-9f && l < 1e9f));
        uint32_t la = sb + CH_L + (((l4 ^ tag) >> 1) & 0x3c);
        asm volatile("" : "+r"(la));
        SCHED();
#pragma unroll
        for (int u = 0; u < 3; u++) { ow[2 * u] = pack2(o[u][0], o[u][1]); ow[2 * u + 1] = pack2(o[u][2], o[u][3]); }
#pragma unroll
        for (int u = 0; u < 6; u++) sts32(l4 + o768 + CH_O + u * 128, ow[u]);
        if (t4 == 0) sts32(la, __float_as_uint(l + l2));
      };
      attend(Int<1>());
      TM(6);
      asm volatile("{.reg .pred p; setp.eq.u32 p, %0, 0; @p bar.sync 2, 256;}" :: "r"(redo) : "memory");
      if (redo) {
        float mx = fmaxf(sc[2][0], sc[2][1]);
#pragma unroll
        for (int i = 0; i < 4; i++) mx = fmaxf(mx, fmaxf(sc[0][i], sc[1][i]));
        mx = fmaxf(mx, __shfl_xor_sync(~0u, mx, 1));
        mx = fmaxf(mx, __shfl_xor_sync(~0u, mx, 2));
#pragma unroll
        for (int i = 0; i < 4; i++) { sc[0][i] -= mx; sc[1][i] -= mx; }
        sc[2][0] -= mx; sc[2][1] -= mx;
        attend(Int<0>());
        bar_arrive(NB_O, 256);
      }
      {
        float z[4] = {};
        const uint32_t scr = l8 + ((CH_V + r1 * 4096) ^ (tag & 2));
        uint32_t ow[6], we[12];
        __syncwarp();
        ldsm4t(ow, l16 + o768 + CH_O);
        ldsm2t(ow + 4, l16 + o768 + CH_O + 512);
        if (j == 0) {
          float y[4] = {};
#pragma unroll
          for (int u = 0; u < 3; u++) ldsm4t(&we[4 * u], (wo ^ 32) + u * 4096);
          SCHED();
#pragma unroll
          for (int u = 0; u < 3; u++) {
            mma16(z, wd[4 * u], wd[4 * u + 1], wd[4 * u + 2], wd[4 * u + 3], ow[2 * u], ow[2 * u + 1]);
            mma16(y, we[4 * u], we[4 * u + 1], we[4 * u + 2], we[4 * u + 3], ow[2 * u], ow[2 * u + 1]);
          }
          sts64f(scr + t4 * 256 + 2048, y[0], y[1]); sts64f(scr + t4 * 256 + 3072, y[2], y[3]);
        } else {
#pragma unroll
          for (int u = 0; u < 3; u++) mma16(z, wd[4 * u], wd[4 * u + 1], wd[4 * u + 2], wd[4 * u + 3], ow[2 * u], ow[2 * u + 1]);
        }
        sts64f(scr + t4 * 256, z[0], z[1]); sts64f(scr + t4 * 256 + 1024, z[2], z[3]);
        bar_sync(NB_W1, 128);
        if (j == 0 || t4 < 2) {
          float2 q[4];
          const float4 l = lds128f(sb + CH_L + ((l16 ^ tag) & 0x30));
#pragma unroll
          for (int i = 0; i < 4; i++) q[i] = lds64f(scr + t4 * 1024 + i * 256);
          SCHED();
          stg_strong32(pdst[0] + ((l4 ^ tag) & 0x7c), pack_tag(((q[0].x + q[1].x) + (q[2].x + q[3].x)) * rcp(l.x + l.y), ((q[0].y + q[1].y) + (q[2].y + q[3].y)) * rcp(l.z + l.w), tag));
        }
      }
      TM(2);
    }
    bar_sync(NB_ST, 384);
    tag ^= 0x10001;
  } while (++s < NSEG);
  if (WG == 1) {
    const uint2 a = lds64(t8 + t4 * 256 + CH_KM), b = lds64(t8 + t4 * 256 + CH_KM + 256);
    sts64(t8 + CH_M, hadd2(a.x, b.x), hadd2(a.y, b.y));
  }
  bar_arrive(NB_PRE2, 288);
}

__device__ __forceinline__ void chain_comm(const ChainParams& p, const uint32_t sb, const CUtensorMap* maps) {
  [[maybe_unused]] constexpr int WG = 2;
  const int tid = threadIdx.x & 127, t4 = __shfl_sync(~0u, tid >> 5, 0), lane = tid & 31;
  const int cta = blockIdx.x, h = cta / 3, j = cta - 3 * h, colbase = cta * 64;
  const uint8_t* const xs = reinterpret_cast<const uint8_t*>(g_xn);
  auto xload = [&](int seg, int i) { tma_load5_one(sb + CH_X + i * 10240, &p.xc, 0, seg * 4, 2 * i, sb + MB_T); };
  uint32_t smid; asm("mov.u32 %0, %%smid;" : "=r"(smid));
  if (t4 == 3) {
    const bool one = elect();
#pragma unroll 1
    for (int i = 0; i < 19 + CH_FLY; i++) {
      if (i >= CH_FLY) mbar_wait(sb + MB_W + 8 * ((i - CH_FLY) & 7), (i - CH_FLY) >> 3 & 1);
      if (i == 11 + CH_FLY && one) mbar_arrive(sb + MB_WQ);
      if (i == 8) { bar_sync(NB_PROJ2, 288); PRO(1); }
      if (i == 12) { bar_sync(NB_PRE2, 288); PRO(2); }
      if (i == 0) { bar_arrive(NB_ST, 384); bar_arrive(NB_PUB, 384); bar_arrive(NB_XFREE, 256); }
      if (i < 19 && one) {
        const int n = (i & 1) * 2 + (i >> 1 & 1), k = i - 12;
        const uint32_t bar = sb + MB_W + 8 * (i & 7);
        mbar_expect(bar, k < 0 ? 20480 : 12288);
        if (k < 0) tma_load(sb + ((i & 4) + n) * 20480, i >= 8 ? &p.wq : (i ^ i >> 2) & 1 ? &p.wv : &p.wk, colbase, n * 160, bar);
        else tma_load(sb + CH_WO + k * 12288, &p.wo, k < 6 ? j * 192 + k * 32 : j == 0 ? 576 : 592 + j * 16, h * 192, bar);
      }
    }
  } else {
    const uint32_t part = max(ldg_strong32(g_smpart + (smid & 255)), 1u);
    if (tid == 0) prefetch_l2(p.mem0, 10240);
    if (tid == 64) stg_strong32(p.sync + SY_PART + cta, part);
    if (t4 == 1) {
      wait_count(p.sync + SY_P + 1, ln_items(p.layer, 0));
      mbar_expect_one(sb + MB_T, 40960);
#pragma unroll 1
      for (int i = 0; i < 4; i++) xload(0, i);
      PRO(0);
    }
    uint32_t reader, orient;
    for (int n = 0;; spin_guard(n)) {
      reader = ldg_strong32(p.sync + SY_PART + (tid >= 80 ? cta : tid));
      orient = ldg_strong32(g_orient + min(tid, NSLOT - 1));
      if (__all_sync(~0u, reader && orient)) break;
    }
    const uint32_t near = __ballot_sync(~0u, reader == part) >> (cta & 7) & 0xffff;
    if (tid < NSLOT) sts32(sb + CH_TAB + tid * 4, tid * 8192 + (orient == reader ? 0 : 4096));
    if (tid == 0) sts32(sb + CH_TAB + NSLOT * 4, cta < 80 ? cta : (cta & 7) + max(__ffs(near) - 1, 0));
    if (t4 == 1) PRO(3);
    bar_sync(NB_ST, 384);
    bar_arrive(NB_PUB, 384);
    if (t4 == 1) PRO(4);
    const uint32_t id = (lane >> 3) == (lane & 3) ? ((lane & 4) ? 0x3f800000u : 0x00003f80u) : 0u;
    if (t4 == 0) sts64(sb + CH_ID + lane * 8, id, id);
#pragma unroll 1
    for (int q = t4; q < 4; q += 3) {
      uint32_t m0[20];
#pragma unroll
      for (int i = 0; i < 20; i++) m0[i] = (reinterpret_cast<const uint32_t*>(p.mem0) + (lane >> 2) * (DM / 2) + q * 80 + (lane & 3))[i * 4];
      if (q < 3) bar_sync(NB_XFREE, 256);
#pragma unroll
      for (int i = 0; i < 20; i += 4) stsm4t(sb + CH_M + (q * 20 + i) * 128 + lane * 16, m0[i], m0[i + 1], m0[i + 2], m0[i + 3]);
    }
    if (t4 == 1) PRO(5);
  }
  if (cta < 4 && cta * 128 + tid < SY_N) p.other[cta * 128 + tid] = 0;
  asm volatile("barrier.cluster.wait.aligned;" ::: "memory");
  const uint32_t l8 = opaque(sb + t4 * 256 + lane * 8);
  bar_sync(NB_MEM, 384);
  uint8_t* const pool = pool_at(0);
  const uint8_t* const psrc = pool + opaque(lds32(sb + CH_TAB + lds32(sb + CH_TAB + NSLOT * 4) * 4) + t4 * 1024 + lane * 4);
  const uint32_t mdst = opaque((80 + cta / 20) * 8192 + (t4 & 1) * 4096 + (cta % 20) * 128 + lane * 4);
  int st = 0;
  uint32_t tag = 1, span = ~0u;
  auto send_tokens = [&](int s) {
    uint8_t* dst = g_kv + ((s >> 2) * 192 + cta + 3 * h) * KV_PART + (s & 3) * KV_SEG;
    bulk_store(dst, sb + CH_K, 4096);
    bulk_store(dst + KV_V, sb + CH_V + j * 4096, 4096);
    bulk_commit();
  };
  auto send_memory = [&](int s, uint32_t km) {
    fence_async();
    uint8_t* dst = g_kv + ((s >> 2) * 192 + cta + 3 * h) * KV_PART + KV_M + (s & 3) * KV_SEG;
    bulk_store(dst, km, 1024);
    bulk_store(dst + KV_V, sb + CH_VX + j * 1024, 1024);
    bulk_commit();
    bulk_wait<0>();
    if ((s & 3) == 3) { fence_async_global(); atomicAdd(p.sync + (s >> 2) * 8 + 4, 1); }
  };
#pragma unroll 1
  for (int s = 0; s < NSEG - 1; s++) {
    TM(0);
    STAT(0);
    if (t4 == 0) {
      if (elect()) {
        fence_async();
#pragma unroll 1
        for (int r = j + 1; r < j + 3; r++) bulk_push(mapa(sb + CH_V + j * 4096, r % 3), sb + CH_V + j * 4096, 4096, mapa(sb + MB_V, r % 3));
        send_tokens(s);
        bulk_wait_read<0>();
      }
      __syncwarp();
    }
    uint32_t c0, g0;
    if (t4 == 1) {
      __syncwarp();
      c0 = clk32(); g0 = gtime();
      if (elect()) atomicMax(p.sync + SY_TIME + s, g0);
    }
    if (t4 == 3 && s >= NSEG - 6 && elect()) asm volatile("prefetch.tensormap [%0];" :: "l"(maps + (NSEG - 2 - s)) : "memory");
    if (t4 == 3 && (s & 3) == 2 && s < NSEG - 2) wait_count(p.sync + SY_P + 5 + (s & ~3), ln_items(p.layer, (s >> 2) + 1));
    if (t4 == 2) { mbar_wait(sb + MB_V, s & 1); bar_arrive(NB_W1V, 160); }
    bar_sync(NB_PROJ2, 256);
    if (t4 == 0) {
      mbar_expect_one(sb + MB_X, 4096);
      mbar_expect_one(sb + MB_T, 40960);
      for (int i = 0; i < 3; i++) xload(s + 1, i);
    }
    __syncwarp();
    STAT(1);
    TM(1);
    {
      const uint2 a = lds64(l8 + t4 * 256 + CH_KM), b = lds64(l8 + t4 * 256 + CH_KM + 256);
      sts64(l8 + CH_KS, hadd2(a.x, b.x), hadd2(a.y, b.y));
    }
    TM(4);
    bar_sync(NB_PRE2, 256);
    if (t4 == 0) xload(s + 1, 3);
    if (t4 == 0 && elect()) {
      if (CH_XPF && s < NSEG - 2) prefetch_l2(xs + (s + 2) * 40960 + cta % 20 * 2048, 2048);
      if (CH_TPF && s >= NSEG - 7) {
        const int i = s - (NSEG - 7);
        if (i < 2) prefetch_l2(p.wb + (cta * 2 + i) * 12800, 12800);
        else if (i < 4) prefetch_l2(xs + (cta * 2 + i - 2) * 8192, 8192);
        else prefetch_l2(g_q + 15 * 32 * 3072 + (cta * 2 + i - 4) * 512, 8192);
      }
      send_memory(s, sb + CH_KS);
    }
    __syncwarp();
    if (t4 == 1) {
      const uint32_t late = min(ldg_strong32(p.sync + SY_TIME + s) - g0, 640u);
      if (elect()) sts32(sb + CH_TAB + 380, c0 + span + (late * 115 >> 6) + (j ? 60 : 0) + p.d1);
    }
    bar_sync(NB_W2, 128);
    uint32_t due = lds32(sb + CH_TAB + 380);
    due = __shfl_sync(~0u, due, 0);
    const uint8_t* ms = pool + (lds32(sb + CH_TAB + (80 + st * 4 + t4) * 4) + (l8 & 255));
    uint8_t* md = pool + (mdst + (cta >= 80 ? 2 : t4 < 2 ? st : st == 2 ? 0 : st + 1) * 32768);
    asm volatile("" : "+l"(ms), "+l"(md));
    if (CH_TW) mbar_wait(sb + MB_T, ~s & 1);
    TM(2);
    bar_sync(NB_ST, 384);
    __syncwarp();
    uint32_t tg = clk32();
    if (t4 == 3 && elect()) {
      if (s < NSEG - 2) mbar_expect(sb + MB_V, 8192);
      mbar_arrive_remote(mapa(sb + MB_F, j == 2 ? 0 : j + 1));
      mbar_arrive_remote(mapa(sb + MB_F, j == 0 ? 2 : j - 1));
    }
    if (s == NSEG - 2) work_init(sb, t4);
    __syncwarp();
    STAT(2);
    {
      float2 q[4];
      TM(3);
      if (t4 == 1 && s) span = min(span, tg - c0);
      until(s < 2 ? tg + 400 : (int)(due - tg) > p.dn ? due : tg + p.dn);
      for (int n = 0;;) {
        uint32_t v[8];
#pragma unroll
        for (int i = 0; i < 8; i++) v[i] = ldg_strong32(psrc + i * 128);
        sts64f(l8 + CH_R2, ((bf_lo(v[0]) + bf_lo(v[1])) + (bf_lo(v[2]) + bf_lo(v[3]))) + ((bf_lo(v[4]) + bf_lo(v[5])) + (bf_lo(v[6]) + bf_lo(v[7]))),
               ((bf_hi(v[0]) + bf_hi(v[1])) + (bf_hi(v[2]) + bf_hi(v[3]))) + ((bf_hi(v[4]) + bf_hi(v[5])) + (bf_hi(v[6]) + bf_hi(v[7]))));
        uint32_t bad;
        asm volatile("{.reg .pred p, q; .reg .b32 a; lop3.b32 a, %1, %2, %3, 0xFE; lop3.b32 a, a, %4, %6, 0xA8; setp.ne.u32 p, a, 0;\n"
                     "bar.red.or.pred q, %5, 128, p; selp.u32 %0, 1, 0, q;}"
                     : "=r"(bad) : "r"(differ(v[0], v[1], tag)), "r"(differ(v[2], v[3], tag)), "r"(differ(v[4], v[5], tag)), "r"(differ(v[6], v[7], tag)), "n"((int)NB_W2),
                       "r"((uint32_t)(cta < 80 || n < 3)) : "memory");
#pragma unroll
        for (int k = 0; k < 4; k++) asm volatile("ld.volatile.shared.v2.f32 {%0,%1}, [%2];" : "=f"(q[k].x), "=f"(q[k].y) : "r"(l8 - t4 * 256 + CH_R2 + k * 256) : "memory");
        TMV(12, n);
        if (!(H1VOTE ? __any_sync(~0u, bad) : bad)) break;
        spin_guard(n);
      }
      bar_arrive(NB_PUB, 384);
      SCHED();
      TM(9);
      stg_strong32(md, min(nz(pack2((q[0].x + q[1].x) + (q[2].x + q[3].x), (q[0].y + q[1].y) + (q[2].y + q[3].y))), t4 < 2 ? ~0u : 0u));
      tg = clk64() + p.d2;
      if (s >= 2 && (int)(due + p.dx - tg) > 0) tg = due + p.dx;
      TM(8);
    }
    STAT(3);
    until(tg);
    TM(10);
    for (int n = 0;;) {
      uint2 g[10];
#pragma unroll
      for (int i = 0; i < 10; i++) g[i] = ldg_strong64(ms + i * 256);
      if (n == 0) bar_sync(NB_XFREE, 256);
      uint32_t m = ~0u, bad;
#pragma unroll
      for (int i = 0; i < 10; i++) { sts64(l8 + CH_M + t4 * 2304 + i * 256, g[i].x, g[i].y); m = __vimin3_u32(m, g[i].x, g[i].y); }
      TMV(13, n);
      TM(11);
      asm volatile("{.reg .pred p; setp.eq.u32 p, %1, 0; vote.sync.any.pred p, p, 0xffffffff; @!p bar.sync %2, 384; selp.u32 %0, 1, 0, p;}" : "=r"(bad) : "r"(m), "n"((int)NB_MEM) : "memory");
      if (!bad) break;
      spin_guard(n);
    }
    if (++st == 3) st = 0;
    tag ^= 0x10001;
  }
  if (t4 == 0) {
    if (elect()) { fence_async(); send_tokens(NSEG - 1); }
    __syncwarp();
    bar_sync(NB_PRE2, 288);
    if (elect()) {
      send_memory(NSEG - 1, sb + CH_M);
      asm volatile("mbarrier.arrive.shared::cta.b64 _, [%0], 8;" :: "r"(sb + WK_BAR + 64) : "memory");
    }
    __syncwarp();
  }
}

__device__ __forceinline__ void chain_start(const ChainParams& p, const uint32_t sb, const int warp) {
  if (warp == 1 && elect()) {
#pragma unroll
    for (int i = 0; i < 6; i++) mbar_init(sb + CH_BAR + 8 * i, i == 2 ? 5 : i == 5 ? 2 : 1);
    asm volatile("fence.mbarrier_init.release.cluster;" ::: "memory");
    mbar_expect(sb + MB_V, 8192);
    atomicAdd(p.sync + SY_UP, 1);
    asm volatile("{.reg .pred p; setp.ne.u32 p, %0, 1024; @p trap;}" :: "r"(sb & 0xffffff));
  }
  if (warp == 0 && elect()) {
#pragma unroll
    for (int i = 0; i < 8; i++) mbar_init(sb + MB_W + 8 * i, 1);
    asm volatile("fence.mbarrier_init.release.cluster;" ::: "memory");
  }
  __syncthreads();
  asm volatile("barrier.cluster.arrive.relaxed.aligned;" ::: "memory");
}

struct WorkParams {
  ChainParams ch;
  CUtensorMap wo, xn, wb[3], wq, wc[2], out;
  const __nv_bfloat16* x;
  uint32_t* sync;
  int kind, qa_end, pace, idle;
};
#define GO_320 4
#define GO_TAIL 1
#define PF_NS 400
enum { WK_FIRST = 0, WK_LEAD = 1, WK_CHAIN = 2, WK_LAST = 3 };
enum { IT_ATT = 0, IT_OP = 1, IT_FIN = 2, IT_BQ = 3, IT_BO = 4, IT_LN = 5, IT_Q = 6, IT_LN0 = 7, IT_OUT = 8 };
constexpr int C_EARLY = 1 << 20, C_LATE = 1 << 21, C_TAIL = 1 << 22, C_PROJ = 1 << 23;

__device__ __forceinline__ uint32_t item_count(int type, int b) { return type == IT_ATT ? 32 : type == IT_OP ? op_tiles(b) * op_split(b) : type == IT_FIN ? fin_items(b) : bq_items(b); }
__device__ __forceinline__ uint32_t item_need(int type, int b) { return type == IT_ATT ? 96 : item_count(type - 1, b); }
__device__ __forceinline__ int item_cols(int type, int b) {
  return type == IT_ATT || type == IT_Q ? 192 : type == IT_OUT ? 80 : type == IT_BQ ? (b < BQ_12 ? 320 : b < BQ_24 ? 160 : 80) : type == IT_OP && b >= OP_N4 ? 160 : 320; }
__device__ __forceinline__ int item_groups(int type, int b) { const int n = type == IT_FIN ? fin_items(b) : ln_items(type == IT_LN, b); return n == 4 ? 4 : n == 8 ? 2 : 1; }
#define RES_OP 0
#define RES_B 4
#define HOLD_B 10
constexpr int RES_N = RES_OP ? op_tiles(14) * op_split(14) : 0, RES_BQ = RES_B;
__device__ __forceinline__ bool reserved(int type, int b) { return type == IT_ATT ? b == 15 : type == IT_OP ? RES_OP && b == 14 : type == IT_BQ && b < RES_BQ; }
__device__ __forceinline__ int reserved_item(int cta) {
  const int h = cta / 3, j = cta - 3 * h, i = h + (j - 1) * 32;
  if (j == 0) return C_EARLY | IT_ATT << 16 | 15 << 8 | h;
  return i < RES_N ? C_TAIL | IT_OP << 16 | 14 << 8 | i : i - RES_N < RES_BQ * 6 ? C_TAIL | IT_BQ << 16 | ((i - RES_N) / 6) << 8 | (i - RES_N) % 6 : -1;
}
constexpr int LEAD1 = 12;
__device__ __forceinline__ int lead_item(int layer, int qa_end, int i) {
  if (layer == 2) return i < 128 ? C_EARLY | C_LATE | IT_OUT << 16 | (i >> 3) << 8 | (i & 7) : -1;
  if (layer == 0) {
    if (i < 32) return IT_LN0 << 16 | (i >> 4) << 8 | (i & 15);
    if (i < 88) return IT_LN0 << 16 | ((i - 24) >> 2) << 8 | (i & 3);
    i -= 88;
  } else {
    if (i < 4) return C_EARLY | IT_BO << 16 | (i >> 1) << 8 | (i & 1);
    if (i < 12) return C_EARLY | IT_LN << 16 | ((i - 4) >> 2) << 8 | (i & 3);
    if (i < 40) return C_EARLY | IT_BO << 16 | ((i - 8) >> 1) << 8 | (i & 1);
    if (i < 96) return C_EARLY | IT_LN << 16 | ((i - 32) >> 2) << 8 | (i & 3);
    i -= 96;
  }
  return i < (16 - qa_end) * 32 ? C_PROJ | IT_Q << 16 | (qa_end + (i >> 5)) << 8 | (i & 31) : -1;
}

struct Ring {
  uint32_t sb;
  int pos, seq;
  __device__ __forceinline__ uint32_t full() const { return sb + WK_BAR + 8 * (seq & 7); }
  __device__ __forceinline__ uint32_t take(int len) { if (pos + len > WK_SLOTS) pos = 0; pos += len; seq++; return sb + (pos - len) * 8192; }
  __device__ __forceinline__ uint32_t wait(int len) { mbar_wait(full(), (seq >> 3) & 1); return take(len); }
  __device__ __forceinline__ void release(int sq) const { mbar_arrive_one(sb + WK_BAR + 64 + 8 * (sq & 7)); }
};

struct Pending {
  uint32_t w[48], done;
  uint4* dst;
  __device__ __forceinline__ void store(int i) const { dst[(i >> 2) * 1024 + (i & 3) * 32] = make_uint4(w[4 * i], w[4 * i + 1], w[4 * i + 2], w[4 * i + 3]); }
  __device__ __forceinline__ void finish() { __syncwarp(); mbar_arrive_one(done); done = 0; }
};

template <int N>
__device__ __forceinline__ void gemm_step(float* d, Ring& r, int warp, int acc) {
  const uint32_t base = r.wait(2 + (N + 63) / 64);
  const uint64_t da = mkdesc(base + (warp >> 2) * 8192, 128, 1024, 0), db = mkdesc(base + 16384, 8192, 1024, 1);
  wg_fence();
#pragma unroll
  for (int kk = 0; kk < 4; kk++) {
    if (N == 80) wg_ss80_01(d, da + kk * 16, db + kk * 128, acc | kk);
    else if (N == 160) wg_ss160_01(d, da + kk * 16, db + kk * 128, acc | kk);
    else wg_ss192_01(d, da + kk * 16, db + kk * 128, acc | kk);
    if (N == 320) wg_ss128_01(d + 96, da + kk * 16, db + kk * 128 + 3 * 512, acc | kk);
  }
  wg_commit();
}
template <int N>
__device__ __forceinline__ void gemm_item(float* d, Ring& r, int warp, int nkb, uint32_t go, int ask) {
#pragma unroll 1
  for (int kb = 0; kb < nkb; kb++) {
    gemm_step<N>(d, r, warp, kb);
    if (kb == ask && go && warp == 0) mbar_arrive_one(go);
    if (kb > 0) { wg_wait<1>(); r.release(r.seq - 2); }
  }
  wg_wait<0>();
  r.release(r.seq - 1);
}

template <class Peek>
__device__ __forceinline__ void attn_a(Ring& r, Pending& pend, Peek peek, const int warp, const int lane) {
  uint32_t (&q)[48] = pend.w;
  const int t = (warp & 1) * 16 + (lane >> 2) - 2 * (lane & 3);
  const bool second = warp & 2;
  const uint32_t rows = (warp >> 2) * 2 * KV_SEG;
  uint32_t pa[20], b2;
  float inv[2];
  bool now;
  const uint32_t b0 = r.wait(5) + rows, b1 = r.wait(5) + rows;
  {
    float s[40];
    wg_fence();
#pragma unroll
    for (int k = 0; k < 12; k++)
      wg_rs80_01(s, q[4 * k], q[4 * k + 1], q[4 * k + 2], q[4 * k + 3], mkdesc(k < 8 ? b0 : b1, 128, 1024, 0) + (k >> 2 & 1) * (KV_PART / 16) + (k & 3) * 16, k);
    wg_commit();
    now = peek();
    b2 = r.wait(5) + rows;
    wg_wait<0>();
    reg_fence<40>(s);
    r.release(r.seq - 3);
    const float k2 = 0.07216878364870322f * 1.44269504089f, NEG = -INFINITY;
#pragma unroll
    for (int i = 0; i < 20; i++) {
      s[i] = second ? s[20 + i] : s[i];
      if (i < 16 && 8 * ((i >> 2) - (i >> 1 & 1)) + (i & 1) > t) s[i] = NEG;
    }
#pragma unroll
    for (int hh = 0; hh < 2; hh++) {
      float m = NEG, l = 0.f;
#pragma unroll
      for (int n = 0; n < 5; n++) m = fmaxf(m, fmaxf(s[4 * n + 2 * hh], s[4 * n + 2 * hh + 1]));
      m = fmaxf(m, __shfl_xor_sync(~0u, m, 1)); m = fmaxf(m, __shfl_xor_sync(~0u, m, 2));
      m *= -k2;
#pragma unroll
      for (int n = 0; n < 5; n++) {
        const float x = ex2(fmaf(s[4 * n + 2 * hh], k2, m)), y = ex2(fmaf(s[4 * n + 2 * hh + 1], k2, m));
        const uint32_t w = pack2(x, y);
        l += x + y;
        pa[2 * n + hh] = second ? 0 : w; pa[10 + 2 * n + hh] = second ? w : 0;
      }
      inv[hh] = l;
    }
  }
  float o[96];
  wg_fence();
#pragma unroll
  for (int u = 0; u < 3; u++) {
#pragma unroll
    for (int k = 0; k < 5; k++)
      wg_rs64_00(o + 32 * u, pa[4 * k], pa[4 * k + 1], pa[4 * k + 2], pa[4 * k + 3], mkdesc(u ? b2 : b1, 1024, 128, 0) + (~u & 1) * (KV_PART / 16) + k * 128, k);
    wg_commit();
  }
#pragma unroll
  for (int hh = 0; hh < 2; hh++) { float l = inv[hh]; l += __shfl_xor_sync(~0u, l, 1); l += __shfl_xor_sync(~0u, l, 2); inv[hh] = rcp(l); }
#pragma unroll
  for (int u = 0; u < 3; u++) {
    if (u == 0) wg_wait<2>(); else if (u == 1) wg_wait<1>(); else wg_wait<0>();
    reg_fence<32>(o + 32 * u);
    if (u != 1) r.release(r.seq - 2 + u / 2);
#pragma unroll
    for (int i = 0; i < 16; i++) { const float* x = &o[32 * u + 4 * (i & 7) + (i >> 2 & 2)]; q[16 * u + i] = pack2(x[0] * inv[i >> 3], x[1] * inv[i >> 3]); }
    if (now) {
#pragma unroll
      for (int i = 0; i < 4; i++) pend.store(4 * u + i);
    }
  }
}

__device__ __forceinline__ void ln_groups(Ring& ring, uint32_t scratch, int planes, int rg, bool two) {
  constexpr int G = 2;
  const int warp = fresh_tid() >> 5, lane = fresh_tid() & 31;
  const uint32_t id = (lane >> 3) == (lane & 3) ? ((lane & 4) ? 0x3f800000u : 0x00003f80u) : 0u;
  const uint32_t at = (warp * 160 + lane) * 8, at1 = planes > 1 ? at : (lane >> 2) * 1280 + warp * 160 + (lane & 3) * 4;
  const uint32_t step = planes > 1 ? 256 : 32, half = planes > 1 ? 4 : 16;
  float v[G][5][4] = {};
#pragma unroll
  for (int r = 0; r < G; r++) {
#pragma unroll 1
    for (int k = r && !two ? 0 : planes; k > 0; k -= 4) {
      const uint32_t a = ring.wait(min(k, 4) + 1);
      if (k == 1) {
#pragma unroll
        for (int i = 0; i < 5; i++) mma8(v[r][i], lds32(a + at1 + i * step), lds32(a + at1 + i * step + half), id);
      } else {
#pragma unroll
        for (int i = 0; i < 10; i++) {
          if (i == 5 && k < 4) break;
          const uint2 x = lds64(a + at + i / 5 * 20480 + i % 5 * 256), y = lds64(a + at + i / 5 * 20480 + 10240 + i % 5 * 256);
          mma16(v[r][i % 5], x.x, x.y, y.x, y.y, id, id);
        }
      }
      ring.release(ring.seq - 1);
    }
  }
  uint2 xr[G][5];
  float mw[G];
  scratch += (lane >> 2) * 64;
#pragma unroll
  for (int r = 0; r < G; r++) {
    float m = 0.f, q2[4] = {};
#pragma unroll
    for (int i = 0; i < 5; i++) {
      float* t = v[r][i];
      xr[r][i] = make_uint2(pack2(t[0], t[1]), pack2(t[2], t[3]));
      t[0] = bf_lo(xr[r][i].x); t[1] = bf_hi(xr[r][i].x); t[2] = bf_lo(xr[r][i].y); t[3] = bf_hi(xr[r][i].y);
      m += (t[0] + t[1]) + (t[2] + t[3]);
    }
    m += __shfl_xor_sync(~0u, m, 1); m += __shfl_xor_sync(~0u, m, 2);
    m *= 1.f / 80;
#pragma unroll
    for (int i = 0; i < 20; i++) { float& t = v[r][i >> 2][i & 3]; t -= m; q2[i & 3] = fmaf(t, t, q2[i & 3]); }
    float q = (q2[0] + q2[1]) + (q2[2] + q2[3]);
    mw[r] = m;
    q += __shfl_xor_sync(~0u, q, 1); q += __shfl_xor_sync(~0u, q, 2);
    if ((lane & 3) == 0) sts64f(scratch + r * 512 + warp * 8, m, q);
  }
  bar_sync(1, 256);
#pragma unroll
  for (int r = 0; r < G; r++) {
    const float4 t = lds128f(scratch + r * 512 + (lane & 3) * 16);
    float mean = t.x + t.z;
    mean += __shfl_xor_sync(~0u, mean, 1); mean += __shfl_xor_sync(~0u, mean, 2);
    mean *= 0.125f;
    float var = (t.y + t.w) + 80.f * ((t.x - mean) * (t.x - mean) + (t.z - mean) * (t.z - mean));
    var += __shfl_xor_sync(~0u, var, 1); var += __shfl_xor_sync(~0u, var, 2);
    float rs;
    asm("rsqrt.approx.ftz.f32 %0, %1;" : "=f"(rs) : "f"(var * (1.f / DM) + 1e-5f));
#pragma unroll
    for (int i = 0; i < 20; i++) v[r][i >> 2][i & 3] = fmaf(v[r][i >> 2][i & 3], rs, (mw[r] - mean) * rs);
  }
#pragma unroll
  for (int r = 0; r < G; r++) {
    if (r && !two) break;
    uint32_t* xn = g_xn + (rg + r) * 2560 + warp * 320 + lane;
#pragma unroll
    for (int i = 0; i < 10; i++) xn[i * 32] = pack2(v[r][i >> 1][2 * (i & 1)], v[r][i >> 1][2 * (i & 1) + 1]);
#pragma unroll
    for (int i = 0; i < 5; i++) g_x[(rg + r) * 17 * 1280 + warp * 160 + i * 32 + lane] = xr[r][i];
  }
}

__device__ __forceinline__ void store_partial(const float* d, int b, int split, int unit, int nu) {
  uint2* dst = g_x + (((b * 16 + (fresh_tid() >> 5) * 2) * 17 + 1 + split) * 40 + unit) * 32 + (fresh_tid() & 31);
#pragma unroll
  for (int u = 0; u < 20; u++) {
    if (u == 10 && nu == 10) break;
    dst[u * 32] = make_uint2(pack2(d[8 * u], d[8 * u + 1]), pack2(d[8 * u + 4], d[8 * u + 5]));
    dst[(680 + u) * 32] = make_uint2(pack2(d[8 * u + 2], d[8 * u + 3]), pack2(d[8 * u + 6], d[8 * u + 7]));
  }
}

__device__ __forceinline__ void store_bqkv(const float* d, int b, int idx, int nh) {
  const int lane = fresh_tid() & 31, c = lane & 3, rg = b * 16 + (fresh_tid() >> 5) * 2, h0 = idx * nh;
  const float sc = h0 < 32 ? 0.22360679775f * 1.44269504089f : 1.f;
  const bool lo = c < 2;
  uint32_t* da = g_bqkv + (h0 * 256 + rg) * 96 + lane;
  uint32_t* db = da + 256 * 96 + (lo ? 2 : -2);
  uint32_t pad[2];
#pragma unroll
  for (int r = 0; r < 2; r++) pad[r] = !(c & 1) && (h0 >= 64 || (h0 >= 32 && (lane & 4) && poly_group(rg + r))) ? 0x00003f80u : 0u;
#pragma unroll
  for (int q = 0; q < 8; q++) {
    if ((q == 2 || q == 4) && nh == 2 * q) break;
#pragma unroll
    for (int r = 0; r < 2; r++) {
      uint32_t w[5];
#pragma unroll
      for (int i = 0; i < 5; i++) w[i] = pack2(d[20 * q + 4 * i + 2 * r] * sc, d[20 * q + 4 * i + 2 * r + 1] * sc);
      const int o = q * 2 * 256 * 96 + r * 96;
      da[o] = w[0]; da[o + 32] = w[1]; da[o + 64] = lo ? w[2] : pad[r];
      db[o] = lo ? w[3] : w[2]; db[o + 32] = lo ? w[4] : w[3]; db[o + 64] = lo ? pad[r] : w[4];
    }
  }
}

__device__ __forceinline__ void work_loader(const WorkParams& p, const uint32_t sb, const bool weights) {
  const uint32_t bars = sb + WK_BAR, bIF = bars + 128, bIE = bars + 160, bGo = bars + 224, slots = bars + 272;
  int pos = 0, seq = 0, tail = 0, used = 0;
  uint32_t lens = 0, tn = clk64();
  if (p.kind == WK_CHAIN) {
    seq = 1; used = lens = 8;
    mbar_arrive_one(bars);
  }
#pragma unroll 1
  for (int n = 0, part = 0;;) {
    if (part == 0) mbar_wait(bIF + 8 * (n & 3), (n >> 2) & 1);
    const int code = __shfl_sync(~0u, (int)lds32(slots + 4 * (n & 3)), 0);
    if (code < 0) break;
    const int type = (code >> 16) & 15, b = (code >> 8) & 255, idx = code & 255;
    const bool qa = code & C_PROJ, ln = type == IT_FIN || type == IT_LN || type == IT_LN0;
    const int parts = ln ? item_groups(type, b) : type == IT_ATT ? 2 : 1;
    {
      int bytes = 163840, chunk = 40960, nb = 0, flag = b * 8 + 4 + type, need = item_need(type & 3, b), c0 = 0, c3 = idx, c4 = 0, s3 = 0, s4 = 64;
      const uint8_t* src = g_kv + (b * 32 + idx) * 6 * KV_PART;
      const CUtensorMap* m = nullptr;
      if (ln) {
        const int rg = b * 16 + idx * parts + part;
        bytes = (type == IT_FIN ? op_split(b) + 1 : type == IT_LN ? 2 : 1) * 10240;
        src = type == IT_LN0 ? reinterpret_cast<const uint8_t*>(p.x) + rg * 10240 : reinterpret_cast<const uint8_t*>(g_x) + rg * 174080;
        if (type == IT_LN) { flag = SY_P + b * 4; need = 2; }
        if (type == IT_LN0 || part) need = 0;
      } else if (part) {
        bytes = 6 * KV_PART;
      } else if (type == IT_ATT && !qa) {
        bytes = chunk = 49152;
        src = reinterpret_cast<const uint8_t*>(g_q) + (b * 32 + idx) * 49152;
        flag = SY_P + b * 4 + 3; need = 32;
      } else {
        const int cols = item_cols(type, b);
        chunk = 16384; nb = (cols + 63) >> 6;
        src = reinterpret_cast<const uint8_t*>(g_of) + b * 163840;
        if (type == IT_OP) {
          const int nkb = op_steps(b), kb0 = (idx >> op_tiles(b) / 2) * nkb;
          bytes = nkb * 16384;
          src = reinterpret_cast<const uint8_t*>(g_o) + (b * 96 + kb0) * 16384;
          if (weights) m = &p.wo;
          c0 = (idx & (op_tiles(b) - 1)) * cols; c3 = 0; c4 = kb0 * 2; s4 = 2;
        } else if (type == IT_BQ) {
          m = weights ? &p.wb[cols >> 7] : &p.xn;
        } else if (type == IT_BO || type == IT_OUT) {
          if (weights) m = &p.wc[cols >> 8];
          flag = SY_OB; need = type == IT_BO && b < 2 ? 32 : -1;
        } else {
          m = weights ? &p.wq : &p.xn;
          c3 = 0; c4 = idx * 3; s3 = 64; s4 = 0;
          flag = SY_P + b * 4 + 1; need = ln_items(p.ch.layer, b);
        }
      }
      if (!weights) {
        c3 = b * 16; c4 = s3 = s4 = 0;
        if (need < 0) pdl_wait(); else if (need) wait_count(p.sync + flag, need);
        if ((ln ? !part : part && (!qa || (code & C_EARLY)))) mbar_arrive_one(bGo);
      }
      if (++part == parts) { mbar_arrive_one(bIE + 8 * (n & 3)); part = 0; n++; }
      const int pace = code & C_TAIL ? 0 : p.pace;
      const int boxes = weights && !s3 ? nb : m != nullptr;
#pragma unroll 1
      for (; bytes > 0; bytes -= chunk) {
        const int now = min(bytes, chunk), len = ((now + 8191) >> 13) + nb, skip = pos + len > WK_SLOTS ? WK_SLOTS - pos : 0, sh = 4 * (seq & 7);
        used += len + skip;
        while (used > WK_SLOTS || seq - tail >= 8) {
          mbar_wait(bars + 64 + 8 * (tail & 7), (tail >> 3) & 1);
          used -= (lens >> 4 * (tail & 7)) & 15;
          tail++;
        }
        lens = (lens & ~(15u << sh)) | (len + skip) << sh;
        if (pos + len > WK_SLOTS) pos = 0;
        const uint32_t bar = bars + 2 * sh, dst = sb + pos * 8192 + weights * 16384;
        if (pace) { until(tn); tn = clk64() + len * pace; }
        mbar_expect_one(bar, weights ? nb * 8192 : now);
#pragma unroll 1
        for (int i = 0; i < boxes; i++)
          tma_load5_one(dst + i * 8192, m, c0 + i * 64, c3, c4, bar);
        if (!weights && !m) bulk_load_last_one(dst, src, now, bar);
        c3 += s3; c4 += s4;
        if (!weights) c0 += 128;
        src += chunk; pos += len; seq++;
      }
    }
  }
}

__global__ void __launch_bounds__(384, 1) work_kernel(const __grid_constant__ WorkParams p) {
  extern __shared__ __align__(1024) uint8_t smem_raw[];
  const uint32_t sb = s2u(smem_raw), bars = sb + WK_BAR;
  const uint32_t bIF = bars + 128, bIE = bars + 160, done = bars + 192, bGo = bars + 224, slots = bars + 272, scratch = bars + 384;
  const int warp = __shfl_sync(~0u, threadIdx.x >> 5, 0);
  uint32_t* const sync = p.sync;
  TRACE(0);
  pdl_launch();
  if (p.kind == WK_LEAD && !helper_sm() && __any_sync(~0u, __syncthreads_or(threadIdx.x == 0 && ldg_strong32(sync + SY_PRE + 1) >= LEAD1))) { pdl_wait(); return; }
  if (p.kind == WK_CHAIN) {
    chain_start(p.ch, sb, warp);
  } else {
    if (warp < 4) work_init(sb, warp);
    __syncthreads();
    if (p.kind == WK_FIRST) {
      if (!(warp & 13)) probe_slots(bars + 320);
      if (!helper_sm()) return;
    }
  }
  if (warp >= 8) {
    asm volatile("setmaxnreg.dec.sync.aligned.u32 40;");
    if (p.kind == WK_CHAIN) chain_comm(p.ch, sb, &p.wo);
    const int warp = __shfl_sync(~0u, fresh_tid() >> 5, 0), lane = fresh_tid() & 31;
    if (warp == 9) {
      const bool keep = p.kind > WK_LEAD || helper_sm();
      int n = 0, code = p.kind == WK_CHAIN ? reserved_item(blockIdx.x) : -1;
      if (code >= 0) {
        sts32(slots, code);
        mbar_arrive_one(bIF);
        n = 1;
      }
      const int b = lane & 15, layer = p.kind == WK_LAST ? 2 : sync != g_sync;
      bool first = layer == 1, lead = p.kind != WK_CHAIN;
      for (;; n++) {
        if (n > 0) mbar_wait(bGo, (n - 1) & 1);
        mbar_wait(bIE + 8 * (n & 3), ((n >> 2) & 1) ^ 1);
        code = -1;
        if (lead) {
          int i = blockIdx.x + n * 256;
          if (first) { i = __reduce_add_sync(~0u, atomic_inc_one(sync + SY_PRE + 1)); first = i < LEAD1; }
          if (layer < 2 && !first) {
            i = 1 << 20;
            if (keep) i = __reduce_add_sync(~0u, atomic_inc_one(sync + SY_PRE)) + layer * LEAD1; else pdl_wait();
          }
          code = lead_item(layer, p.qa_end, i);
          lead = code >= 0 || layer == 2 || !keep;
          if (!lead && p.kind <= WK_LEAD) {
            const uint32_t t0 = gtime();
            while (!lead && __all_sync(~0u, ldg_strong32(sync + SY_UP) < 96)) lead = __any_sync(~0u, gtime() - t0 > 20000);
          }
        }
        if (!lead) {
          int spin = 0;
          const int ticket = atomic_inc_one(sync + SY_T);
          for (;;) {
            const uint4 hd = ldg_strong128(sync + b * 8), pr = ldg_strong128(sync + b * 8 + 4);
            const uint32_t hv[4] = {hd.x, hd.y, hd.z, hd.w}, pv[4] = {pr.x, pr.y, pr.z, pr.w};
            const uint32_t chain_done = __ballot_sync(~0u, (pr.x & 0xffff) >= 96) | (p.kind == WK_CHAIN) << 15;
            int left[4], avail[4], rdy = 0, claimed = 0, upstream = 0;
#pragma unroll
            for (int t = 0; t < 4; t++) {
              const int cnt = lane < 16 && !reserved(t, b) ? item_count(t, b) : 0;
              left[t] = max(cnt - (int)hv[t], 0);
              claimed += cnt - left[t];
              const bool ready = (pv[t] & 0xffff) >= item_need(t, b);
              rdy |= ready << t;
              bool ok = ready || (t != IT_ATT && (chain_done >> 15 & 1) && !left[t - 1] && (t < 2 || !left[t - 2]));
              if (t == IT_BQ && (chain_done >> HOLD_B & 1) && !(chain_done >> 15 & 1)) ok = false;
              avail[t] = ok ? left[t] : 0;
              upstream |= __any_sync(~0u, left[t] > 0);
            }
            if (!upstream) { code = -1; break; }
            int rank = max(__reduce_add_sync(~0u, ticket - claimed), 0), type = -1, mine = 0;
#pragma unroll
            for (int c = 0; c < 7; c++) {
              const int t = c == 0 || c == 6 ? IT_ATT : c == 1 || c == 4 ? IT_FIN : c == 2 ? IT_OP : IT_BQ;
              int a = c == 2 || (rdy >> t & 1) == (c < 4) ? avail[t] : 0;
              if (c == 6) a = b < p.qa_end && !(rdy & 1) && ((chain_done << 1 | 1) >> b & 1) ? left[t] : 0;
              const int tot = __reduce_add_sync(~0u, a);
              if (type < 0) { if (rank < tot) { type = t; mine = a; } else rank -= tot; }
            }
            if (type >= 0) {
#pragma unroll
              for (int o = 1; o < 16; o <<= 1) { const int y = __shfl_up_sync(~0u, mine, o); if (lane >= o) mine += y; }
              const int blk = __ffs(__ballot_sync(~0u, mine > rank)) - 1;
              const int early = !(__shfl_sync(~0u, rdy, blk) >> type & 1);
              const uint32_t idx = __reduce_add_sync(~0u, atomic_inc_one(sync + blk * 8 + type));
              if (idx < item_count(type, blk)) { code = (type == IT_ATT && blk < p.qa_end) << 23 | (chain_done >> 14 & 1) << 22 | early << 20 | type << 16 | blk << 8 | idx; break; }
            } else {
              __nanosleep(50);
            }
            spin_guard(spin);
          }
        }
        sts32(slots + 4 * (n & 3), code);
        mbar_arrive_one(bIF + 8 * (n & 3));
        if (code < 0) break;
      }
    } else if (warp >= 10) {
      work_loader(p, sb, warp == 10);
    } else {
      for (int n = 0;; n++) {
        mbar_wait(bIF + 8 * (n & 3), (n >> 2) & 1);
        const int code = __shfl_sync(~0u, (int)lds32(slots + 4 * (n & 3)), 0);
        if (code < 0) break;
        const int type = (code >> 16) & 15, b = (code >> 8) & 255;
        mbar_wait(done + 8 * (n & 3), (n >> 2) & 1);
        if (elect()) {
          if (type != IT_OUT) red_release(sync + (type < IT_BQ ? b * 8 + 5 + type : SY_P + b * 4 + ((0x13102 >> 4 * (type - IT_BQ)) & 3)), 1);
          mbar_arrive(bIE + 8 * (n & 3));
        }
        __syncwarp();
      }
    }
  } else {
    asm volatile("setmaxnreg.inc.sync.aligned.u32 232;");
    if (p.kind == WK_CHAIN) chain_compute(p.ch, sb);
    const int warp = __shfl_sync(~0u, fresh_tid() >> 5, 0), lane = fresh_tid() & 31;
    Ring r{sb, 0, p.kind == WK_CHAIN};
    int nln = 0;
#pragma unroll 1
    for (int n = 0;; n++) {
      mbar_wait(bIF + 8 * (n & 3), (n >> 2) & 1);
      int code = __shfl_sync(~0u, (int)lds32(slots + 4 * (n & 3)), 0);
      if (code < 0) { TRACE(2); break; }
      if (((code >> 16) & 15) == IT_ATT || (code & C_PROJ)) {
        Pending pend = {};
#pragma unroll 1
        for (;; n++) {
          const int tile = (((code >> 8) & 255) * 32 + (code & 255)) * 3072 + warp * 128;
          int next = 0;
          auto peek = [&]() {
            uint32_t here;
            asm volatile("{.reg .pred p; mbarrier.test_wait.parity.shared::cta.b64 p, [%1], %2; selp.u32 %0, -1, 0, p;}" : "=r"(here) : "r"(bIF + 8 * ((n + 1) & 3)), "r"(((n + 1) >> 2) & 1) : "memory");
            next = __shfl_sync(~0u, (int)(lds32(slots + 4 * ((n + 1) & 3) + (here & p.ch.zero)) & here), 0);
            return next < C_PROJ;
          };
          ITEM(code & 0xfffff, 0);
          if (code & C_PROJ) {
            float d[96];
            ITEM(9 << 16 | (code & 0xffff), 0);
            gemm_step<192>(d, r, warp, 0);
#pragma unroll 1
            for (int kb = 1; kb < 10; kb++) {
              gemm_step<192>(d, r, warp, 1);
              if (kb == 4 && (code & (C_EARLY | 15 << 16)) != C_EARLY && warp == 0) mbar_arrive_one(bGo);
              if (pend.done) {
#pragma unroll
                for (int i = 0; i < 12; i++) if (kb == 1 + i / 2) pend.store(i);
                if (kb == 6) pend.finish();
              }
              wg_wait<1>();
              r.release(r.seq - 2);
            }
            wg_wait<0>();
            reg_fence<96>(d);
            r.release(r.seq - 1);
            ITEM(9 << 16 | (code & 0xffff), 1);
#pragma unroll
            for (int i = 0; i < 48; i++) pend.w[i] = pack2(d[2 * i], d[2 * i + 1]);
          } else {
            const uint32_t base = r.wait(6) + warp * 2048 + lane * 16;
#pragma unroll
            for (int i = 0; i < 12; i++) {
              const uint4 t = lds128(base + (i >> 2) * 16384 + (i & 3) * 512);
              pend.w[4 * i] = t.x; pend.w[4 * i + 1] = t.y; pend.w[4 * i + 2] = t.z; pend.w[4 * i + 3] = t.w;
            }
            __syncwarp();
            r.release(r.seq - 1);
          }
          if (code & 15 << 16) {
            pend.dst = g_q + tile + lane;
            if (peek()) {
#pragma unroll
              for (int i = 0; i < 12; i++) pend.store(i);
            }
          } else {
            pend.dst = g_o + tile + (lane & 3) * 8 + (lane >> 2);
            attn_a(r, pend, peek, warp, lane);
          }
          pend.done = done + 8 * (n & 3);
          ITEM(code & 0xfffff, 1);
          if (next < C_PROJ) break;
          code = next;
        }
        pend.finish();
      } else {
        const int type = (code >> 16) & 15, b = (code >> 8) & 255, idx = code & 255;
        const uint32_t go = code & C_LATE ? 0 : bGo;
        ITEM(code & 0xfffff, 0);
        if (type == IT_FIN || type == IT_LN || type == IT_LN0) {
          const int ng = item_groups(type, b);
          const int planes = type == IT_FIN ? op_split(b) + 1 : type == IT_LN ? 2 : 1;
#pragma unroll 1
          for (int i = 0; i < ng; i += 2) ln_groups(r, scratch + (nln++ & 1) * 1024, planes, b * 16 + idx * ng + i, ng > 1);
        } else {
          const int cols = item_cols(type, b), nkb = type == IT_OP ? op_steps(b) : 10;
          float d[160] = {};
          if (type == IT_OUT) {
            const uint2* x = g_x + ((b * 16 + warp * 2) * 680 + idx * 5) * 32 + lane;
#pragma unroll
            for (int i = 0; i < 10; i++) { const uint2 y = __ldcg(x + (i / 5 * 680 + i % 5) * 32); d[40 + 2 * i] = __uint_as_float(y.x); d[41 + 2 * i] = __uint_as_float(y.y); }
          }
          reg_fence<160>(d);
          if (type != IT_OUT) ITEM((type == IT_BQ ? 10 : 11) << 16 | (code & 0xffff), 0);
          const int ask = max(nkb - ((code & C_TAIL ? GO_TAIL : GO_320) << (2 - (cols >> 7))), 0);
          if (cols == 320) gemm_item<320>(d, r, warp, nkb, go, ask);
          else if (cols == 160) gemm_item<160>(d, r, warp, nkb, go, ask);
          else gemm_item<80>(d, r, warp, nkb, go, ask);
          if (type != IT_OUT) ITEM((type == IT_BQ ? 10 : 11) << 16 | (code & 0xffff), 1);
          reg_fence<160>(d);
          if (type == IT_OUT) {
            bar_sync(1, 256);
            const uint32_t dst = sb + (warp * 16 + (lane & 15)) * 160 + (lane >> 4) * 16;
#pragma unroll
            for (int u = 0; u < 5; u++) {
              uint32_t w[4];
#pragma unroll
              for (int i = 0; i < 4; i++) { const uint32_t y = __float_as_uint(d[40 + (i & 1) * 10 + 2 * u + (i >> 1)]); w[i] = pack2(bf_lo(y) + d[8 * u + 2 * i], bf_hi(y) + d[8 * u + 2 * i + 1]); }
              stsm4(dst + u * 32, w[0], w[1], w[2], w[3]);
            }
            fence_async();
            __syncwarp();
            if (elect()) { tma_store(&p.out, sb + warp * 2560, idx * 80, b * 128 + warp * 16); bulk_commit(); bulk_wait<0>(); }
          } else {
            if (warp >= 4) bar_sync(7, 256);
            if (type == IT_BQ) store_bqkv(d, b, idx, 4 << (cols >> 7));
            else store_partial(d, b, cols == 320 ? idx >> 1 : idx >> 2, cols == 320 ? (idx & 1) * 20 : (idx & 3) * 10, cols >> 4);
            if (warp < 4) bar_arrive(7, 256);
          }
        }
        __syncwarp();
        mbar_arrive_one(done + 8 * (n & 3));
        if ((code & C_LATE) && warp == 4) mbar_arrive_one(bGo);
        ITEM(code & 0xfffff, 1);
      }
    }
  }
}

constexpr int AB_SMEM = 1024 + 2 * 98304 + 256;
#define AB_N 32
#define AB_WG 4
constexpr int AB_T = AB_WG * 128, AB_PASS = 8 / AB_WG;
__device__ __forceinline__ float ex2_poly(float t) {
  const uint32_t r = __float_as_uint(t) & 0xffff8000u;
  const float f = t - __uint_as_float(r);
  const float p = fmaf(fmaf(fmaf(-5.869912678e-38f, f, -1.700740250e-37f), f, -5.234869734e-37f), f, -7.522601252e-37f);
  uint32_t y;
  asm("mad.lo.u32 %0, %1, 256, %2;" : "=r"(y) : "r"(r), "r"(__float_as_uint(p)));
  return __uint_as_float(y);
}
__device__ __forceinline__ uint32_t hsq(uint32_t w, uint32_t c) { uint32_t r; asm("fma.rn.bf16x2 %0, %1, %1, %2;" : "=r"(r) : "r"(w), "r"(c)); return r; }
__device__ __forceinline__ float sq2(uint32_t w) { const float a = bf_lo(w), b = bf_hi(w); return fmaf(a, a, b * b); }

__device__ __forceinline__ void attn_b_store(const float* o, int h, int row0, int lane) {
  const int g = lane >> 2, c = lane & 3;
  const float i0 = rcp(__shfl_sync(~0u, o[8], (lane & ~3) | 2)), i1 = rcp(__shfl_sync(~0u, o[10], (lane & ~3) | 2));
#pragma unroll
  for (int jj = 0; jj < 3; jj++) {
    if (jj < 2 || c < 2) {
      const int col = h * 20 + 8 * jj + 2 * c;
      g_of[core_word(row0 + g, col)] = pack2(o[4 * jj] * i0, o[4 * jj + 1] * i0);
      g_of[core_word(row0 + g + 8, col)] = pack2(o[4 * jj + 2] * i1, o[4 * jj + 3] * i1);
    }
  }
}

__device__ __forceinline__ void attn_b_qk(float* s, uint32_t q0, uint32_t q1, uint32_t q2, uint32_t q3, uint32_t q4, uint32_t q5, uint32_t z0, uint32_t z1,
                                          uint64_t dk, uint64_t dk2) {
  wg_rs32_00(s, q0, q1, q2, q3, dk, 0);
  wg_rs32_00(s, q4, q5, z0, z1, dk2, 1);
}

struct AttnParams { const uint8_t* pf[4]; uint32_t *sync, *next; };
__global__ void __launch_bounds__(AB_T + 128, 1) attn_b_kernel(const __grid_constant__ AttnParams p) {
  extern __shared__ uint8_t smem_raw[];
  const uint32_t sb = (s2u(smem_raw) + 1023) & ~1023u, sK = sb, sV = sb + 98304, bars = sb + 2 * 98304;
  const int warp = __shfl_sync(~0u, threadIdx.x >> 5, 0), lane = threadIdx.x & 31;
  const int h = blockIdx.x & 31, quarter = blockIdx.x >> 5;
  BT(0);
  TRACE(0);
  if (warp < 10 && elect()) {
    mbar_init(bars + 8 * warp + (warp & 8) * 8, warp < 8 ? 1 : warp == 8 ? AB_T / 32 : 2);
    asm volatile("fence.mbarrier_init.release.cluster;" ::: "memory");
  }
  __syncthreads();
  if (warp >= AB_T / 32) {
    asm volatile("setmaxnreg.dec.sync.aligned.u32 32;");
    if (warp == AB_T / 32 + 1) return;
    if (warp > AB_T / 32) {
      uint32_t kmax = 0;
#pragma unroll 1
      for (int i = 0; i < 32; i++) {
        if (!(i & 3)) mbar_wait(bars + 2 * i, 0);
        const uint32_t a = sK + i * 3072 + ((threadIdx.x >> 3) & 7) * 384 + (lane & 7) * 16;
        const uint4 x = lds128(a), y = lds128(a + 128);
        const uint2 z = lds64(a + 256);
        const uint32_t n = hadd2(hsq(x.x, hsq(x.y, hsq(x.z, hsq(x.w, hsq(z.x, 0))))), hsq(y.x, hsq(y.y, hsq(y.z, hsq(y.w, hsq(z.y, 0))))));
        kmax = max(kmax, __float_as_uint(bf_lo(n) + bf_hi(n)) & 0x7fffffffu);
      }
      const uint32_t kbits = __reduce_max_sync(~0u, kmax);
      if (lane == 0) { sts32(bars + 64 + (warp & 1) * 4, kbits); mbar_arrive(bars + 136); }
      return;
    }
    const uint8_t* gk = reinterpret_cast<const uint8_t*>(g_bqkv + (32 + h) * 256 * 96);
    const uint8_t* gv = reinterpret_cast<const uint8_t*>(g_bqkv + (64 + h) * 256 * 96);
    uint32_t todo = 255;
    for (int spin = 0; todo;) {
      const uint32_t up = __ballot_sync(~0u, ld_acquire(p.sync + SY_P + (lane & 15) * 4 + 2) >= bq_items(lane & 15));
      fence_async_global();
#pragma unroll 1
      for (int i = 0; i < 8; i++) {
        if (!(todo >> i & 1) || (up >> 2 * i & 3) != 3) continue;
        todo &= ~(1u << i);
        if (elect()) {
          mbar_expect(bars + 8 * i, 24576);
          bulk_load(sK + i * 12288, gk + i * 12288, 12288, bars + 8 * i);
          bulk_load(sV + i * 12288, gv + i * 12288, 12288, bars + 8 * i);
        }
      }
      spin_guard(spin);
    }
    pdl_launch();
    TRACE(1);
#pragma unroll 1
    for (int i = lane; i < 512 && blockIdx.x < NSLOT; i += 32) reinterpret_cast<uint4*>(pool_at(blockIdx.x * 8192))[i] = make_uint4(0, 0, 0, 0);
    if (!p.next && blockIdx.x < 8) { const int i = blockIdx.x * 32 + lane; g_smpart[i] = 0; if (i < NSLOT) g_orient[i] = 0; }
    if (p.next) {
      mbar_wait(bars + 128, 0);
      if (quarter == 0 && lane == 0) red_release(p.next + SY_OB, 1);
#pragma unroll 1
      for (int i = 0; i < (PF_NS ? 32 : 0); i++) {
        if (elect()) prefetch_l2(p.pf[i >> 3] + blockIdx.x * 61440 + (i & 7) * 7680, 7680);
        __nanosleep(PF_NS);
      }
    }
    return;
  }
  asm volatile("setmaxnreg.inc.sync.aligned.u32 112;");
  constexpr int NT = SEQ / AB_N, PER = 256 / AB_N;
  uint32_t qn[8];
  auto load_q = [&](int pass) {
    const uint32_t* gq = g_bqkv + (h * 256 + pass * 128 + quarter * 32 + warp * 2) * 96 + lane;
#pragma unroll
    for (int i = 0; i < 8; i++) qn[i] = __ldcg(gq + (i & 1) * 96 + min(i >> 1, 2) * 32 + (i < 6 ? 0 : 3 - (lane & 3)));
  };
  mbar_wait(bars + 8 * quarter, 0);
  load_q(0);
#pragma unroll 1
  for (int pass = 0; pass < AB_PASS; pass++) {
    const int row0 = pass * 1024 + quarter * 256 + warp * 16;
    const uint32_t q0 = qn[0], q1 = qn[1], q2 = qn[2], q3 = qn[3], z0 = qn[6], z1 = qn[7];
    uint32_t q4 = qn[4], q5 = qn[5];
    if ((lane & 3) == 2) { q4 = 0x43BCu; q5 = 0x43BCu; }
    float o[12];
    uint64_t dk = mkdesc(sK, 128, 384, 0), dk2 = mkdesc(sK + 256, 0, 384, 0), dv = mkdesc(sV, 384, 128, 0);
    float sa[AB_N / 2], sb2[AB_N / 2];
    uint32_t pa[AB_N / 4], pb[AB_N / 4];
    if (pass == 0) mbar_wait(bars, 0);
    BT(1 + 2 * pass);
    wg_fence();
    attn_b_qk(sa, q0, q1, q2, q3, q4, q5, z0, z1, dk, dk2);
    wg_commit();
    attn_b_qk(sb2, q0, q1, q2, q3, q4, q5, z0, z1, dk + AB_N * 3, dk2 + AB_N * 3);
    wg_commit();
#pragma unroll 1
    for (int kt = 0; kt < NT; kt += 2) {
      const int nx = kt + 2 < NT ? kt + 2 : 0;
      if (pass == 0 && (nx & (PER - 1)) == 0) mbar_wait(bars + 8 * (nx / PER), 0);
      const uint64_t nk = dk + nx * (AB_N * 3), nk2 = dk2 + nx * (AB_N * 3);
      wg_wait<1>();
      reg_fence<AB_N / 2>(sa);
#pragma unroll
      for (int i = 0; i < AB_N / 4; i++) pa[i] = pack2(ex2(sa[2 * i]), poly_group(i >> 1) ? ex2_poly(sa[2 * i + 1]) : ex2(sa[2 * i + 1]));
      wg_fence();
#pragma unroll
      for (int kk = 0; kk < AB_N / 16; kk++) wg_rs24_01(o, pa[4 * kk], pa[4 * kk + 1], pa[4 * kk + 2], pa[4 * kk + 3], dv + kk * 48, kk | kt);
      attn_b_qk(sa, q0, q1, q2, q3, q4, q5, z0, z1, nk, nk2);
      wg_commit();
      wg_wait<1>();
      reg_fence<AB_N / 2>(sb2);
#pragma unroll
      for (int i = 0; i < AB_N / 4; i++) pb[i] = pack2(ex2(sb2[2 * i]), poly_group((i >> 1) + AB_N / 8) ? ex2_poly(sb2[2 * i + 1]) : ex2(sb2[2 * i + 1]));
      wg_fence();
#pragma unroll
      for (int kk = 0; kk < AB_N / 16; kk++) wg_rs24_01(o, pb[4 * kk], pb[4 * kk + 1], pb[4 * kk + 2], pb[4 * kk + 3], dv + AB_N * 3 + kk * 48, 1);
      attn_b_qk(sb2, q0, q1, q2, q3, q4, q5, z0, z1, nk + AB_N * 3, nk2 + AB_N * 3);
      wg_commit();
      dv += AB_N * 6;
    }
    wg_wait<0>();
    reg_fence<12>(o); reg_fence<AB_N / 2>(sa); reg_fence<AB_N / 2>(sb2);
    BT(2 + 2 * pass);
    if (pass + 1 < AB_PASS) load_q(pass + 1);
    mbar_wait(bars + 136, 0);
    const uint2 kb = lds64(bars + 64);
    const float kmax = __uint_as_float(max(kb.x, kb.y));
    if ((lane & 3) == 2) q4 = q5 = 0;
    float n0 = sq2(q0) + sq2(q2) + sq2(q4), n1 = sq2(q1) + sq2(q3) + sq2(q5);
    n0 += __shfl_xor_sync(~0u, n0, 1); n1 += __shfl_xor_sync(~0u, n1, 1);
    n0 += __shfl_xor_sync(~0u, n0, 2); n1 += __shfl_xor_sync(~0u, n1, 2);
    uint32_t redo;
    asm volatile("{.reg .pred p, q; setp.ne.u32 p, %1, 0; bar.red.or.pred q, %2, 128, p; selp.u32 %0, 1, 0, q;}"
                 : "=r"(redo) : "r"((uint32_t)!(n0 * kmax <= 9500.f && n1 * kmax <= 9500.f)), "r"(2 + (warp >> 2)) : "memory");
    if (redo) {
#pragma unroll
      for (int i = 0; i < 12; i++) o[i] = 0.f;
      float m0 = -INFINITY, m1 = -INFINITY;
#pragma unroll 1
      for (int kt = 0; kt < 64; kt++) {
        float s[16];
        wg_fence();
        wg_rs32_00(s, q0, q1, q2, q3, dk + kt * 96, 0);
        wg_rs32_00(s, q4, q5, z0, z1, dk2 + kt * 96, 1);
        wg_commit();
        wg_wait<0>();
        reg_fence<16>(s); reg_fence<12>(o);
        float n0 = m0, n1 = m1;
#pragma unroll
        for (int jj = 0; jj < 4; jj++) { n0 = fmaxf(n0, fmaxf(s[4 * jj], s[4 * jj + 1])); n1 = fmaxf(n1, fmaxf(s[4 * jj + 2], s[4 * jj + 3])); }
        n0 = fmaxf(n0, __shfl_xor_sync(~0u, n0, 1)); n0 = fmaxf(n0, __shfl_xor_sync(~0u, n0, 2));
        n1 = fmaxf(n1, __shfl_xor_sync(~0u, n1, 1)); n1 = fmaxf(n1, __shfl_xor_sync(~0u, n1, 2));
        const float r0 = ex2(m0 - n0), r1 = ex2(m1 - n1);
        m0 = n0; m1 = n1;
#pragma unroll
        for (int jj = 0; jj < 3; jj++) { o[4 * jj] *= r0; o[4 * jj + 1] *= r0; o[4 * jj + 2] *= r1; o[4 * jj + 3] *= r1; }
        uint32_t pp[8];
#pragma unroll
        for (int jj = 0; jj < 4; jj++) {
          pp[2 * jj] = pack2(ex2(s[4 * jj] - m0), ex2(s[4 * jj + 1] - m0));
          pp[2 * jj + 1] = pack2(ex2(s[4 * jj + 2] - m1), ex2(s[4 * jj + 3] - m1));
        }
        reg_fence<12>(o);
        wg_fence();
#pragma unroll
        for (int kk = 0; kk < 2; kk++) wg_rs24_01(o, pp[4 * kk], pp[4 * kk + 1], pp[4 * kk + 2], pp[4 * kk + 3], mkdesc(sV, 384, 128, 0) + kt * 96 + kk * 48, 1);
        wg_commit();
      }
      wg_wait<0>();
      reg_fence<12>(o);
    }
    attn_b_store(o, h, row0, lane);
    __syncwarp();
    if (pass == 0 && lane == 0) mbar_arrive(bars + 128);
  }
  BT(5);
  TRACE(2);
}

typedef CUresult (*EncodeFn)(CUtensorMap*, CUtensorMapDataType, cuuint32_t, void*, const cuuint64_t*, const cuuint64_t*,
                             const cuuint32_t*, const cuuint32_t*, CUtensorMapInterleave, CUtensorMapSwizzle,
                             CUtensorMapL2promotion, CUtensorMapFloatOOBfill);

void make_map(EncodeFn enc, CUtensorMap* m, const void* ptr, int cols, int rows, int box_rows, int box_cols = 64) {
  const cuuint64_t dims[2] = {(cuuint64_t)cols, (cuuint64_t)rows};
  const cuuint64_t strides[1] = {(cuuint64_t)cols * 2};
  const cuuint32_t box[2] = {(cuuint32_t)box_cols, (cuuint32_t)box_rows}, es[2] = {1, 1};
  enc(m, CU_TENSOR_MAP_DATA_TYPE_BFLOAT16, 2, const_cast<void*>(ptr), dims, strides, box, es, CU_TENSOR_MAP_INTERLEAVE_NONE,
      box_cols == 64 ? CU_TENSOR_MAP_SWIZZLE_128B : box_cols == 32 ? CU_TENSOR_MAP_SWIZZLE_64B : CU_TENSOR_MAP_SWIZZLE_NONE, CU_TENSOR_MAP_L2_PROMOTION_L2_256B, CU_TENSOR_MAP_FLOAT_OOB_FILL_NONE);
}
void make_map5(EncodeFn enc, CUtensorMap* m, const void* ptr, bool words, const cuuint64_t (&dims)[5], const cuuint64_t (&strides)[4], const cuuint32_t (&box)[5]) {
  const cuuint32_t es[5] = {1, 1, 1, 1, 1};
  enc(m, words ? CU_TENSOR_MAP_DATA_TYPE_UINT64 : CU_TENSOR_MAP_DATA_TYPE_BFLOAT16, 5, const_cast<void*>(ptr), dims, strides, box, es, CU_TENSOR_MAP_INTERLEAVE_NONE,
      words ? CU_TENSOR_MAP_SWIZZLE_NONE : CU_TENSOR_MAP_SWIZZLE_128B, dims[0] % 64 ? CU_TENSOR_MAP_L2_PROMOTION_L2_128B : CU_TENSOR_MAP_L2_PROMOTION_L2_256B,
      CU_TENSOR_MAP_FLOAT_OOB_FILL_NONE);
}
void make_tiles(EncodeFn enc, CUtensorMap* m, const void* ptr, cuuint64_t cols, cuuint64_t tile) {
  make_map5(enc, m, ptr, false, {tile, 1, 1, cols / tile, DM}, {tile * 2, tile * 2, tile * 2, cols * 2}, {64, 1, 1, 1, 64});
}
template <class... KA, class... A>
void launch(void (*kern)(KA...), int grid, int block, int smem, int cluster, bool pdl, A... args) {
  cudaFuncSetAttribute(kern, cudaFuncAttributeMaxDynamicSharedMemorySize, smem);
  cudaLaunchConfig_t cfg = {};
  cfg.gridDim = dim3(grid); cfg.blockDim = dim3(block); cfg.dynamicSmemBytes = smem; cfg.stream = cudaStreamPerThread;
  cudaLaunchAttribute at[2];
  int n = 0;
  if (cluster > 1) { at[n].id = cudaLaunchAttributeClusterDimension; at[n].val.clusterDim.x = cluster; at[n].val.clusterDim.y = 1; at[n].val.clusterDim.z = 1; n++; }
  if (pdl) { at[n].id = cudaLaunchAttributeProgrammaticStreamSerialization; at[n].val.programmaticStreamSerializationAllowed = 1; n++; }
  cfg.attrs = at; cfg.numAttrs = n;
  cudaLaunchKernelEx(&cfg, kern, args...);
}
template <class T> void* sym(T& s) { void* p = nullptr; cudaGetSymbolAddress(&p, s); return p; }

}

#define MODE(b) 0
extern "C" void kernel_launch(void* const* d_in, const int* in_sizes, int n_in, void* d_out, int out_size) {
  const __nv_bfloat16* x = (const __nv_bfloat16*)d_in[0];
  void* fn = nullptr; cudaDriverEntryPointQueryResult qr;
  cudaGetDriverEntryPoint("cuTensorMapEncodeTiled", &fn, cudaEnableDefault, &qr);
  EncodeFn enc = (EncodeFn)fn;

  WorkParams wk = {};
  ChainParams& ch = wk.ch;
  AttnParams at = {};
  make_map(enc, &ch.wq, d_in[2], HD, DM, 160); make_map(enc, &ch.wk, d_in[3], HD, DM, 160); make_map(enc, &ch.wv, d_in[4], HD, DM, 160);
  make_map(enc, &ch.wo, d_in[5], DM, HD, 192, 32);
  ch.mem0 = (const __nv_bfloat16*)d_in[1];
  ch.wb = (const uint8_t*)d_in[8];
  ch.d1 = 250; ch.d2 = 200; ch.dn = 150; ch.dx = 950;
  make_map5(enc, &wk.wq, d_in[2], false, {64, 1, 1, DM, HD / 64}, {128, 128, HD * 2, 128}, {64, 1, 1, 64, 3});
  for (int i = 0; i < 3; i++) make_tiles(enc, &wk.wb[i], d_in[8], 1920, 80 << i);
  for (int i = 0; i < 2; i++) make_tiles(enc, &wk.wc[i], d_in[9], DM, 80 << 2 * i);
  make_map(enc, &wk.out, d_out, DM, SEQ, 16, 80);
  make_map5(enc, &wk.wo, d_in[5], false, {DM, 2, 4, 4, HD / 32}, {DM * 2, DM * 16, DM * 4, DM * 64}, {64, 2, 4, 4, 2});
  make_map5(enc, &wk.xn, sym(g_xn), true, {1280, 1, 1, 256, 1}, {10240, 10240, 10240, 10240}, {128, 1, 1, 16, 1});
  make_map5(enc, &ch.xc, sym(g_xn), true, {160, 1, 1, 256, 8}, {1280, 1280, 10240, 1280}, {160, 1, 1, 4, 2});
  wk.x = x;
  for (int i = 0; i < 4; i++) at.pf[i] = (const uint8_t*)d_in[i < 2 ? 3 + i : i == 2 ? 2 : 5];
  int qa_end[2] = {12, 12}, pace = 85;
  for (int layer = 0; layer < 2; layer++) {
    ch.sync = wk.sync = at.sync = (uint32_t*)sym(g_sync) + layer * SY_N;
    ch.other = (uint32_t*)sym(g_sync) + (1 - layer) * SY_N;
    ch.layer = layer;
    at.next = layer ? nullptr : ch.other;
    wk.qa_end = qa_end[layer];
    wk.kind = layer ? WK_LEAD : WK_FIRST; wk.pace = pace;
    launch(work_kernel, 132, 384, CH_SMEM, 1, layer != 0, wk);
    wk.kind = WK_CHAIN; wk.pace = 0;
    launch(work_kernel, 96, 384, CH_SMEM, 3, true, wk);
    launch(attn_b_kernel, 128, AB_T + 128, AB_SMEM, 1, true, at);
  }
  wk.kind = WK_LAST;
  launch(work_kernel, 128, 384, CH_SMEM, 1, true, wk);
}
```

```cpp
#include <cuda_runtime.h>
#include <cuda_bf16.h>
#include <cuda.h>
#include <stdint.h>
#include <stdlib.h>

namespace {

constexpr int SEQ = 2048, DM = 640, HD = 6144, NSEG = 64;
constexpr int SPIN_LIMIT = 1 << 20;

__device__ __align__(128) uint2 g_x[256 * 17 * 1280];
__device__ __align__(128) uint32_t g_xn[SEQ * DM / 2];
__device__ __align__(128) uint32_t g_of[SEQ * DM / 2];
__device__ __align__(128) uint4 g_o[SEQ * HD / 8];
__device__ __align__(128) uint4 g_q[SEQ * HD / 8];
constexpr int KV_M = 4096, KV_SEG = 5120, KV_PART = 20480, KV_V = 3 * KV_PART;
__device__ __align__(128) uint8_t g_kv[16 * 32 * 6 * KV_PART];
#define OP_B8 11
#define OP_B16 13
#define OP_N4 14
#define BQ_12 13
#define BQ_24 16
#define FIN_16 12
#define OP_N8 16
#define OP_E16 14
__host__ __device__ constexpr int op_shift(int b) { return b < OP_N4 ? 1 : b < OP_N8 ? 2 : 3; }
__host__ __device__ constexpr int op_tiles(int b) { return 1 << op_shift(b); }
__host__ __device__ constexpr int op_split(int b) { return b < OP_B8 ? 4 : b < OP_B16 || b >= OP_E16 ? 8 : 16; }
__host__ __device__ constexpr int op_steps(int b) { return b < OP_B8 ? 24 : b < OP_B16 || b >= OP_E16 ? 12 : 6; }
__host__ __device__ constexpr int fin_items(int b) { return b < OP_B8 ? 4 : b < FIN_16 ? 8 : 16; }
__host__ __device__ constexpr int bq_items(int b) { return b < BQ_12 ? 6 : b < BQ_24 ? 12 : 24; }
__host__ __device__ constexpr int ln_items(int layer, int b) { return layer == 0 && b < 2 ? 16 : 4; }
constexpr int SY_P = 128, SY_T = 192, SY_UP = 224, SY_OB = 225, SY_PRE = 256, SY_PART = 288, SY_TIME = 384, SY_B = 448, SY_N = 576;
__device__ __align__(128) uint32_t g_sync[2 * SY_N];
constexpr int NSLOT = 92;
__device__ uint32_t g_pool[(NSLOT + 2) * 2048];
__device__ uint32_t g_smpart[256], g_orient[NSLOT];
__device__ __align__(128) uint32_t g_bqkv[3 * 32 * 256 * 96];

#define BT(i)
#define MISS(k, n)
#define PRO(i)
#define TRACE(w)
#define EV(code, w)
#define ITEM(code, w)
#define STAT(k)
#define TMV(i, v)
#define TM(i)
#define TMD(i, dep)

__device__ __forceinline__ uint32_t gtime() { uint32_t c; asm volatile("mov.u32 %0, %%globaltimer_lo;" : "=r"(c) :: "memory"); return c; }
__device__ __forceinline__ uint32_t clk32() { uint32_t c; asm volatile("mov.u32 %0, %%clock;" : "=r"(c) :: "memory"); return c; }
__device__ __forceinline__ uint32_t fresh_tid() { uint32_t t; asm volatile("mov.u32 %0, %%tid.x;" : "=r"(t)); return t; }
__device__ __forceinline__ uint32_t s2u(const void* p) { return (uint32_t)__cvta_generic_to_shared(p); }
__device__ __forceinline__ uint32_t pack2(float a, float b) {
  uint32_t r; asm("cvt.rn.bf16x2.f32 %0, %1, %2;" : "=r"(r) : "f"(b), "f"(a)); return r; }
__device__ __forceinline__ float bf_lo(uint32_t w) { return __uint_as_float(w << 16); }
__device__ __forceinline__ float bf_hi(uint32_t w) { return __uint_as_float(w & 0xffff0000u); }
__device__ __forceinline__ float ex2(float x) { float y; asm("ex2.approx.ftz.f32 %0, %1;" : "=f"(y) : "f"(x)); return y; }

__device__ __forceinline__ void mbar_init(uint32_t bar, uint32_t n) {
  asm volatile("mbarrier.init.shared::cta.b64 [%0], %1;" :: "r"(bar), "r"(n) : "memory"); }
__device__ __forceinline__ void mbar_expect(uint32_t bar, uint32_t bytes) {
  asm volatile("mbarrier.arrive.expect_tx.shared::cta.b64 _, [%0], %1;" :: "r"(bar), "r"(bytes) : "memory"); }
__device__ __forceinline__ void mbar_arrive(uint32_t bar) {
  asm volatile("mbarrier.arrive.shared::cta.b64 _, [%0];" :: "r"(bar) : "memory"); }
#define ONE "{.reg .pred one; elect.sync _|one, 0xffffffff; @one "
__device__ __forceinline__ void mbar_arrive_one(uint32_t bar) { asm volatile(ONE "mbarrier.arrive.shared::cta.b64 _, [%0];}" :: "r"(bar) : "memory"); }
__device__ __forceinline__ void mbar_expect_one(uint32_t bar, uint32_t bytes) {
  asm volatile(ONE "mbarrier.arrive.expect_tx.shared::cta.b64 _, [%0], %1;}" :: "r"(bar), "r"(bytes) : "memory"); }
__device__ __forceinline__ uint32_t atomic_inc_one(uint32_t* p) {
  uint32_t v = 0; asm volatile(ONE "atom.relaxed.gpu.global.add.u32 %0, [%1], 1;}" : "+r"(v) : "l"(p) : "memory"); return v; }
__device__ __forceinline__ void mbar_arrive_remote(uint32_t bar) {
  asm volatile("mbarrier.arrive.shared::cluster.b64 _, [%0];" :: "r"(bar) : "memory"); }
__device__ __forceinline__ void mbar_wait(uint32_t bar, uint32_t ph) {
  asm volatile("{.reg .pred p; .reg .u32 n; mov.u32 n, 0;\n"
               "W: mbarrier.try_wait.parity.shared::cta.b64 p, [%0], %1; @p bra.uni D;\n"
               "add.u32 n, n, 1; setp.gt.u32 p, n, %2; @p trap; bra.uni W;\n"
               "D: }" :: "r"(bar), "r"(ph), "n"(SPIN_LIMIT) : "memory");
}
__device__ __forceinline__ bool elect() {
  uint32_t p; asm volatile("{.reg .pred q; elect.sync _|q, 0xffffffff; selp.u32 %0, 1, 0, q;}" : "=r"(p)); return p; }
__device__ __forceinline__ void spin_guard(int& n) {
  asm volatile("{.reg .pred p; add.s32 %0, %0, 1; setp.gt.s32 p, %0, %1; @p trap;}" : "+r"(n) : "n"(SPIN_LIMIT));
}
__device__ __forceinline__ void pdl_wait() { asm volatile("griddepcontrol.wait;" ::: "memory"); TRACE(1); }
__device__ __forceinline__ void pdl_launch() { asm volatile("griddepcontrol.launch_dependents;" ::: "memory"); }
__device__ __forceinline__ uint32_t ld_acquire(const uint32_t* p) { uint32_t v; asm volatile("ld.acquire.gpu.global.u32 %0, [%1];" : "=r"(v) : "l"(p) : "memory"); return v; }
__device__ __forceinline__ void red_release(uint32_t* p, uint32_t v) { asm volatile("red.release.gpu.global.add.u32 [%0], %1;" :: "l"(p), "r"(v) : "memory"); }
__device__ __forceinline__ void fence_async_global() { asm volatile("fence.proxy.async.global;" ::: "memory"); }
__device__ __forceinline__ void fence_async() { asm volatile("fence.proxy.async.shared::cta;" ::: "memory"); }
__device__ __forceinline__ void bar_sync(int id, int n) { asm volatile("bar.sync %0, %1;" :: "r"(id), "r"(n) : "memory"); }
__device__ __forceinline__ void bar_arrive(int id, int n) { asm volatile("bar.arrive %0, %1;" :: "r"(id), "r"(n) : "memory"); }
__device__ __forceinline__ void tma_load(uint32_t dst, const CUtensorMap* m, int c0, int c1, uint32_t bar) {
  asm volatile("cp.async.bulk.tensor.2d.shared::cluster.global.mbarrier::complete_tx::bytes [%0], [%1, {%3, %4}], [%2];"
               :: "r"(dst), "l"(m), "r"(bar), "r"(c0), "r"(c1) : "memory"); }
__device__ __forceinline__ void tma_load5_one(uint32_t dst, const CUtensorMap* m, int c0, int c3, int c4, uint32_t bar) {
  asm volatile(ONE "cp.async.bulk.tensor.5d.shared::cluster.global.mbarrier::complete_tx::bytes [%0], [%1, {%3, %6, %6, %4, %5}], [%2];}"
               :: "r"(dst), "l"(m), "r"(bar), "r"(c0), "r"(c3), "r"(c4), "r"(0) : "memory"); }
__device__ __forceinline__ void tma_store(const CUtensorMap* m, uint32_t src, int c0, int c1) {
  asm volatile("cp.async.bulk.tensor.2d.global.shared::cta.bulk_group [%0, {%2, %3}], [%1];"
               :: "l"(m), "r"(src), "r"(c0), "r"(c1) : "memory"); }
__device__ __forceinline__ uint64_t evict_first() { uint64_t p; asm("createpolicy.fractional.L2::evict_first.b64 %0, 1.0;" : "=l"(p)); return p; }
__device__ __forceinline__ void bulk_load_last_one(uint32_t dst, const void* src, uint32_t bytes, uint32_t bar) {
  asm volatile(ONE "cp.async.bulk.shared::cluster.global.mbarrier::complete_tx::bytes.L2::cache_hint [%0], [%1], %2, [%3], %4;}"
               :: "r"(dst), "l"(src), "r"(bytes), "r"(bar), "l"(evict_first()) : "memory"); }
__device__ __forceinline__ void bulk_store_stream(void* dst, uint32_t src, uint32_t bytes) {
  asm volatile("cp.async.bulk.global.shared::cta.bulk_group.L2::cache_hint [%0], [%1], %2, %3;" :: "l"(dst), "r"(src), "r"(bytes), "l"(evict_first()) : "memory"); }
__device__ __forceinline__ void bulk_load(uint32_t dst, const void* src, uint32_t bytes, uint32_t bar) {
  asm volatile("cp.async.bulk.shared::cluster.global.mbarrier::complete_tx::bytes [%0], [%1], %2, [%3];"
               :: "r"(dst), "l"(src), "r"(bytes), "r"(bar) : "memory"); }
__device__ __forceinline__ void bulk_push(uint32_t dst, uint32_t src, uint32_t bytes, uint32_t bar) {
  asm volatile("cp.async.bulk.shared::cluster.shared::cta.mbarrier::complete_tx::bytes [%0], [%1], %2, [%3];"
               :: "r"(dst), "r"(src), "r"(bytes), "r"(bar) : "memory"); }
__device__ __forceinline__ void bulk_store(void* dst, uint32_t src, uint32_t bytes) {
  asm volatile("cp.async.bulk.global.shared::cta.bulk_group [%0], [%1], %2;" :: "l"(dst), "r"(src), "r"(bytes) : "memory"); }
__device__ __forceinline__ void bulk_commit() { asm volatile("cp.async.bulk.commit_group;" ::: "memory"); }
template <int N> __device__ __forceinline__ void bulk_wait_read() { asm volatile("cp.async.bulk.wait_group.read %0;" :: "n"(N) : "memory"); }
template <int N> __device__ __forceinline__ void bulk_wait() { asm volatile("cp.async.bulk.wait_group %0;" :: "n"(N) : "memory"); }

__device__ __forceinline__ uint64_t mkdesc(uint32_t addr, uint32_t lbo, uint32_t sbo, uint32_t sw) {
  return (uint64_t)((addr & 0x3FFFF) >> 4) | ((uint64_t)(lbo >> 4) << 16) | ((uint64_t)(sbo >> 4) << 32) | ((uint64_t)sw << 62); }
__device__ __forceinline__ void wg_fence() { asm volatile("wgmma.fence.sync.aligned;" ::: "memory"); }
__device__ __forceinline__ void wg_commit() { asm volatile("wgmma.commit_group.sync.aligned;" ::: "memory"); }
template <int N> __device__ __forceinline__ void wg_wait() { asm volatile("wgmma.wait_group.sync.aligned %0;" :: "n"(N) : "memory"); }
template <int N> __device__ __forceinline__ void reg_fence(float* d) {
#pragma unroll
  for (int i = 0; i < N; i++) asm volatile("" : "+f"(d[i]) :: "memory");
}

__device__ __forceinline__ void mma16(float* d, uint32_t a0, uint32_t a1, uint32_t a2, uint32_t a3, uint32_t b0, uint32_t b1) {
  asm volatile("mma.sync.aligned.m16n8k16.row.col.f32.bf16.bf16.f32 {%0,%1,%2,%3},{%4,%5,%6,%7},{%8,%9},{%0,%1,%2,%3};"
               : "+f"(d[0]), "+f"(d[1]), "+f"(d[2]), "+f"(d[3]) : "r"(a0), "r"(a1), "r"(a2), "r"(a3), "r"(b0), "r"(b1)); }
__device__ __forceinline__ void mma8(float* d, uint32_t a0, uint32_t a1, uint32_t b0) {
  asm volatile("mma.sync.aligned.m16n8k8.row.col.f32.bf16.bf16.f32 {%0,%1,%2,%3},{%4,%5},{%6},{%0,%1,%2,%3};"
               : "+f"(d[0]), "+f"(d[1]), "+f"(d[2]), "+f"(d[3]) : "r"(a0), "r"(a1), "r"(b0)); }
__device__ __forceinline__ void ldsm4(uint32_t* r, uint32_t a) {
  asm volatile("ldmatrix.sync.aligned.m8n8.x4.shared.b16 {%0,%1,%2,%3},[%4];" : "=r"(r[0]), "=r"(r[1]), "=r"(r[2]), "=r"(r[3]) : "r"(a) : "memory"); }
__device__ __forceinline__ uint4 ldsm4v(uint32_t a) { uint32_t r[4]; ldsm4(r, a); return make_uint4(r[0], r[1], r[2], r[3]); }
__device__ __forceinline__ void ldsm4t(uint32_t* r, uint32_t a) {
  asm volatile("ldmatrix.sync.aligned.m8n8.x4.trans.shared.b16 {%0,%1,%2,%3},[%4];" : "=r"(r[0]), "=r"(r[1]), "=r"(r[2]), "=r"(r[3]) : "r"(a) : "memory"); }
__device__ __forceinline__ void ldsm2(uint32_t* r, uint32_t a) {
  asm volatile("ldmatrix.sync.aligned.m8n8.x2.shared.b16 {%0,%1},[%2];" : "=r"(r[0]), "=r"(r[1]) : "r"(a) : "memory"); }
__device__ __forceinline__ void ldsm2t(uint32_t* r, uint32_t a) {
  asm volatile("ldmatrix.sync.aligned.m8n8.x2.trans.shared.b16 {%0,%1},[%2];" : "=r"(r[0]), "=r"(r[1]) : "r"(a) : "memory"); }
__device__ __forceinline__ void stsm4(uint32_t a, uint32_t r0, uint32_t r1, uint32_t r2, uint32_t r3) {
  asm volatile("stmatrix.sync.aligned.m8n8.x4.shared.b16 [%0], {%1,%2,%3,%4};" :: "r"(a), "r"(r0), "r"(r1), "r"(r2), "r"(r3) : "memory"); }
__device__ __forceinline__ void stsm4t(uint32_t a, uint32_t r0, uint32_t r1, uint32_t r2, uint32_t r3) {
  asm volatile("stmatrix.sync.aligned.m8n8.x4.trans.shared.b16 [%0], {%1,%2,%3,%4};" :: "r"(a), "r"(r0), "r"(r1), "r"(r2), "r"(r3) : "memory"); }
__device__ __forceinline__ void stsm2(uint32_t a, uint32_t r0, uint32_t r1) {
  asm volatile("stmatrix.sync.aligned.m8n8.x2.shared.b16 [%0], {%1,%2};" :: "r"(a), "r"(r0), "r"(r1) : "memory"); }
__device__ __forceinline__ void stsm2t(uint32_t a, uint32_t r0, uint32_t r1) {
  asm volatile("stmatrix.sync.aligned.m8n8.x2.trans.shared.b16 [%0], {%1,%2};" :: "r"(a), "r"(r0), "r"(r1) : "memory"); }
__device__ __forceinline__ void sts32(uint32_t a, uint32_t v) { asm volatile("st.shared.b32 [%0], %1;" :: "r"(a), "r"(v) : "memory"); }
__device__ __forceinline__ void sts64f(uint32_t a, float x, float y) { asm volatile("st.shared.v2.f32 [%0], {%1,%2};" :: "r"(a), "f"(x), "f"(y) : "memory"); }
__device__ __forceinline__ void sts128(uint32_t a, uint4 v) {
  asm volatile("st.shared.v4.b32 [%0], {%1,%2,%3,%4};" :: "r"(a), "r"(v.x), "r"(v.y), "r"(v.z), "r"(v.w) : "memory"); }
__device__ __forceinline__ void sts128f(uint32_t a, float x, float y, float z, float w) {
  asm volatile("st.shared.v4.f32 [%0], {%1,%2,%3,%4};" :: "r"(a), "f"(x), "f"(y), "f"(z), "f"(w) : "memory"); }
__device__ __forceinline__ float lds32f(uint32_t a) { float v; asm volatile("ld.shared.f32 %0, [%1];" : "=f"(v) : "r"(a) : "memory"); return v; }
__device__ __forceinline__ float2 lds64f(uint32_t a) { float2 v; asm volatile("ld.shared.v2.f32 {%0,%1}, [%2];" : "=f"(v.x), "=f"(v.y) : "r"(a) : "memory"); return v; }
__device__ __forceinline__ float4 lds128f(uint32_t a) {
  float4 v; asm volatile("ld.shared.v4.f32 {%0,%1,%2,%3}, [%4];" : "=f"(v.x), "=f"(v.y), "=f"(v.z), "=f"(v.w) : "r"(a) : "memory"); return v; }
__device__ __forceinline__ uint4 lds128(uint32_t a) {
  uint4 v; asm volatile("ld.shared.v4.b32 {%0,%1,%2,%3}, [%4];" : "=r"(v.x), "=r"(v.y), "=r"(v.z), "=r"(v.w) : "r"(a) : "memory"); return v; }
__device__ __forceinline__ uint4 ldg_strong128(const void* p) {
  uint4 v; asm volatile("ld.relaxed.gpu.global.v4.u32 {%0,%1,%2,%3}, [%4];" : "=r"(v.x), "=r"(v.y), "=r"(v.z), "=r"(v.w) : "l"(p) : "memory"); return v; }
__device__ __forceinline__ uint2 ldg_strong64(const void* p) {
  uint2 v; asm volatile("ld.relaxed.gpu.global.v2.u32 {%0,%1}, [%2];" : "=r"(v.x), "=r"(v.y) : "l"(p) : "memory"); return v; }
__device__ __forceinline__ void stg_strong32(void* p, uint32_t v) { asm volatile("st.relaxed.gpu.global.u32 [%0], %1;" :: "l"(p), "r"(v) : "memory"); }
__device__ __forceinline__ void stg_strong128(void* p, uint4 v) {
  asm volatile("st.relaxed.gpu.global.v4.u32 [%0], {%1,%2,%3,%4};" :: "l"(p), "r"(v.x), "r"(v.y), "r"(v.z), "r"(v.w) : "memory"); }
__device__ __forceinline__ uint32_t mapa(uint32_t a, uint32_t r) {
  uint32_t o; asm("mapa.shared::cluster.u32 %0, %1, %2;" : "=r"(o) : "r"(a), "r"(r)); return o; }
__device__ __forceinline__ void st_async2f(uint32_t a, float x, float y, uint32_t bar) {
  asm volatile("st.async.shared::cluster.mbarrier::complete_tx::bytes.v2.f32 [%0], {%1,%2}, [%3];" :: "r"(a), "f"(x), "f"(y), "r"(bar) : "memory"); }
__device__ __forceinline__ void st_async32(uint32_t a, uint32_t x, uint32_t bar) {
  asm volatile("st.async.shared::cluster.mbarrier::complete_tx::bytes.b32 [%0], %1, [%2];" :: "r"(a), "r"(x), "r"(bar) : "memory"); }
__device__ __forceinline__ uint32_t lds32(uint32_t a) { uint32_t v; asm volatile("ld.shared.b32 %0, [%1];" : "=r"(v) : "r"(a) : "memory"); return v; }
__device__ __forceinline__ void st_async64(uint32_t a, uint32_t x, uint32_t y, uint32_t bar) {
  asm volatile("st.async.shared::cluster.mbarrier::complete_tx::bytes.v2.b32 [%0], {%1,%2}, [%3];" :: "r"(a), "r"(x), "r"(y), "r"(bar) : "memory"); }
__device__ __forceinline__ void st_async128(uint32_t a, uint4 v, uint32_t bar) {
  asm volatile("st.async.shared::cluster.mbarrier::complete_tx::bytes.v4.b32 [%0], {%1,%2,%3,%4}, [%5];" :: "r"(a), "r"(v.x), "r"(v.y), "r"(v.z), "r"(v.w), "r"(bar) : "memory"); }
__device__ __forceinline__ uint2 lds64(uint32_t a) { uint2 v; asm volatile("ld.shared.v2.b32 {%0,%1}, [%2];" : "=r"(v.x), "=r"(v.y) : "r"(a) : "memory"); return v; }
__device__ __forceinline__ void sts64(uint32_t a, uint32_t x, uint32_t y) { asm volatile("st.shared.v2.b32 [%0], {%1,%2};" :: "r"(a), "r"(x), "r"(y) : "memory"); }
__device__ __forceinline__ uint32_t ldg_strong32(const void* p) { uint32_t v; asm volatile("ld.relaxed.gpu.global.u32 %0, [%1];" : "=r"(v) : "l"(p) : "memory"); return v; }
__device__ __forceinline__ uint32_t transpose8(uint32_t x) { uint32_t r; asm volatile("movmatrix.sync.aligned.m8n8.trans.b16 %0, %1;" : "=r"(r) : "r"(x)); return r; }
__device__ __forceinline__ uint32_t hadd2(uint32_t a, uint32_t b) { uint32_t r; asm("add.rn.bf16x2 %0, %1, %2;" : "=r"(r) : "r"(a), "r"(b)); return r; }
__device__ __forceinline__ uint32_t min4(uint4 v) { return min(__vimin3_u32(v.x, v.y, v.z), v.w); }

__device__ __forceinline__ void wg_ss192_01(float* d, uint64_t da, uint64_t db, int sd) {
  asm volatile("{.reg .pred p; setp.ne.b32 p, %98, 0;\n"
    "wgmma.mma_async.sync.aligned.m64n192k16.f32.bf16.bf16 {%0,%1,%2,%3,%4,%5,%6,%7,%8,%9,%10,%11,%12,%13,%14,%15,%16,%17,%18,%19,%20,%21,%22,%23,%24,%25,%26,%27,%28,%29,%30,%31,%32,%33,%34,%35,%36,%37,%38,%39,%40,%41,%42,%43,%44,%45,%46,%47,%48,%49,%50,%51,%52,%53,%54,%55,%56,%57,%58,%59,%60,%61,%62,%63,%64,%65,%66,%67,%68,%69,%70,%71,%72,%73,%74,%75,%76,%77,%78,%79,%80,%81,%82,%83,%84,%85,%86,%87,%88,%89,%90,%91,%92,%93,%94,%95}, %96, %97, p, 1, 1, 0, 1;}"
    : "+f"(d[0]),"+f"(d[1]),"+f"(d[2]),"+f"(d[3]),"+f"(d[4]),"+f"(d[5]),"+f"(d[6]),"+f"(d[7]),"+f"(d[8]),"+f"(d[9]),"+f"(d[10]),"+f"(d[11]),"+f"(d[12]),"+f"(d[13]),"+f"(d[14]),"+f"(d[15]),"+f"(d[16]),"+f"(d[17]),"+f"(d[18]),"+f"(d[19]),"+f"(d[20]),"+f"(d[21]),"+f"(d[22]),"+f"(d[23]),"+f"(d[24]),"+f"(d[25]),"+f"(d[26]),"+f"(d[27]),"+f"(d[28]),"+f"(d[29]),"+f"(d[30]),"+f"(d[31]),"+f"(d[32]),"+f"(d[33]),"+f"(d[34]),"+f"(d[35]),"+f"(d[36]),"+f"(d[37]),"+f"(d[38]),"+f"(d[39]),"+f"(d[40]),"+f"(d[41]),"+f"(d[42]),"+f"(d[43]),"+f"(d[44]),"+f"(d[45]),"+f"(d[46]),"+f"(d[47]),"+f"(d[48]),"+f"(d[49]),"+f"(d[50]),"+f"(d[51]),"+f"(d[52]),"+f"(d[53]),"+f"(d[54]),"+f"(d[55]),"+f"(d[56]),"+f"(d[57]),"+f"(d[58]),"+f"(d[59]),"+f"(d[60]),"+f"(d[61]),"+f"(d[62]),"+f"(d[63]),"+f"(d[64]),"+f"(d[65]),"+f"(d[66]),"+f"(d[67]),"+f"(d[68]),"+f"(d[69]),"+f"(d[70]),"+f"(d[71]),"+f"(d[72]),"+f"(d[73]),"+f"(d[74]),"+f"(d[75]),"+f"(d[76]),"+f"(d[77]),"+f"(d[78]),"+f"(d[79]),"+f"(d[80]),"+f"(d[81]),"+f"(d[82]),"+f"(d[83]),"+f"(d[84]),"+f"(d[85]),"+f"(d[86]),"+f"(d[87]),"+f"(d[88]),"+f"(d[89]),"+f"(d[90]),"+f"(d[91]),"+f"(d[92]),"+f"(d[93]),"+f"(d[94]),"+f"(d[95])
    : "l"(da), "l"(db), "r"(sd));
}
__device__ __forceinline__ void wg_ss128_01(float* d, uint64_t da, uint64_t db, int sd) {
  asm volatile("{.reg .pred p; setp.ne.b32 p, %66, 0;\n"
    "wgmma.mma_async.sync.aligned.m64n128k16.f32.bf16.bf16 {%0,%1,%2,%3,%4,%5,%6,%7,%8,%9,%10,%11,%12,%13,%14,%15,%16,%17,%18,%19,%20,%21,%22,%23,%24,%25,%26,%27,%28,%29,%30,%31,%32,%33,%34,%35,%36,%37,%38,%39,%40,%41,%42,%43,%44,%45,%46,%47,%48,%49,%50,%51,%52,%53,%54,%55,%56,%57,%58,%59,%60,%61,%62,%63}, %64, %65, p, 1, 1, 0, 1;}"
    : "+f"(d[0]),"+f"(d[1]),"+f"(d[2]),"+f"(d[3]),"+f"(d[4]),"+f"(d[5]),"+f"(d[6]),"+f"(d[7]),"+f"(d[8]),"+f"(d[9]),"+f"(d[10]),"+f"(d[11]),"+f"(d[12]),"+f"(d[13]),"+f"(d[14]),"+f"(d[15]),"+f"(d[16]),"+f"(d[17]),"+f"(d[18]),"+f"(d[19]),"+f"(d[20]),"+f"(d[21]),"+f"(d[22]),"+f"(d[23]),"+f"(d[24]),"+f"(d[25]),"+f"(d[26]),"+f"(d[27]),"+f"(d[28]),"+f"(d[29]),"+f"(d[30]),"+f"(d[31]),"+f"(d[32]),"+f"(d[33]),"+f"(d[34]),"+f"(d[35]),"+f"(d[36]),"+f"(d[37]),"+f"(d[38]),"+f"(d[39]),"+f"(d[40]),"+f"(d[41]),"+f"(d[42]),"+f"(d[43]),"+f"(d[44]),"+f"(d[45]),"+f"(d[46]),"+f"(d[47]),"+f"(d[48]),"+f"(d[49]),"+f"(d[50]),"+f"(d[51]),"+f"(d[52]),"+f"(d[53]),"+f"(d[54]),"+f"(d[55]),"+f"(d[56]),"+f"(d[57]),"+f"(d[58]),"+f"(d[59]),"+f"(d[60]),"+f"(d[61]),"+f"(d[62]),"+f"(d[63])
    : "l"(da), "l"(db), "r"(sd));
}
__device__ __forceinline__ void wg_ss160_01(float* d, uint64_t da, uint64_t db, int sd) {
  asm volatile("{.reg .pred p; setp.ne.b32 p, %82, 0;\n"
    "wgmma.mma_async.sync.aligned.m64n160k16.f32.bf16.bf16 {%0,%1,%2,%3,%4,%5,%6,%7,%8,%9,%10,%11,%12,%13,%14,%15,%16,%17,%18,%19,%20,%21,%22,%23,%24,%25,%26,%27,%28,%29,%30,%31,%32,%33,%34,%35,%36,%37,%38,%39,%40,%41,%42,%43,%44,%45,%46,%47,%48,%49,%50,%51,%52,%53,%54,%55,%56,%57,%58,%59,%60,%61,%62,%63,%64,%65,%66,%67,%68,%69,%70,%71,%72,%73,%74,%75,%76,%77,%78,%79}, %80, %81, p, 1, 1, 0, 1;}"
    : "+f"(d[0]),"+f"(d[1]),"+f"(d[2]),"+f"(d[3]),"+f"(d[4]),"+f"(d[5]),"+f"(d[6]),"+f"(d[7]),"+f"(d[8]),"+f"(d[9]),"+f"(d[10]),"+f"(d[11]),"+f"(d[12]),"+f"(d[13]),"+f"(d[14]),"+f"(d[15]),"+f"(d[16]),"+f"(d[17]),"+f"(d[18]),"+f"(d[19]),"+f"(d[20]),"+f"(d[21]),"+f"(d[22]),"+f"(d[23]),"+f"(d[24]),"+f"(d[25]),"+f"(d[26]),"+f"(d[27]),"+f"(d[28]),"+f"(d[29]),"+f"(d[30]),"+f"(d[31]),"+f"(d[32]),"+f"(d[33]),"+f"(d[34]),"+f"(d[35]),"+f"(d[36]),"+f"(d[37]),"+f"(d[38]),"+f"(d[39]),"+f"(d[40]),"+f"(d[41]),"+f"(d[42]),"+f"(d[43]),"+f"(d[44]),"+f"(d[45]),"+f"(d[46]),"+f"(d[47]),"+f"(d[48]),"+f"(d[49]),"+f"(d[50]),"+f"(d[51]),"+f"(d[52]),"+f"(d[53]),"+f"(d[54]),"+f"(d[55]),"+f"(d[56]),"+f"(d[57]),"+f"(d[58]),"+f"(d[59]),"+f"(d[60]),"+f"(d[61]),"+f"(d[62]),"+f"(d[63]),"+f"(d[64]),"+f"(d[65]),"+f"(d[66]),"+f"(d[67]),"+f"(d[68]),"+f"(d[69]),"+f"(d[70]),"+f"(d[71]),"+f"(d[72]),"+f"(d[73]),"+f"(d[74]),"+f"(d[75]),"+f"(d[76]),"+f"(d[77]),"+f"(d[78]),"+f"(d[79])
    : "l"(da), "l"(db), "r"(sd));
}
__device__ __forceinline__ void wg_ss80_01(float* d, uint64_t da, uint64_t db, int sd) {
  asm volatile("{.reg .pred p; setp.ne.b32 p, %42, 0;\n"
    "wgmma.mma_async.sync.aligned.m64n80k16.f32.bf16.bf16 {%0,%1,%2,%3,%4,%5,%6,%7,%8,%9,%10,%11,%12,%13,%14,%15,%16,%17,%18,%19,%20,%21,%22,%23,%24,%25,%26,%27,%28,%29,%30,%31,%32,%33,%34,%35,%36,%37,%38,%39}, %40, %41, p, 1, 1, 0, 1;}"
    : "+f"(d[0]),"+f"(d[1]),"+f"(d[2]),"+f"(d[3]),"+f"(d[4]),"+f"(d[5]),"+f"(d[6]),"+f"(d[7]),"+f"(d[8]),"+f"(d[9]),"+f"(d[10]),"+f"(d[11]),"+f"(d[12]),"+f"(d[13]),"+f"(d[14]),"+f"(d[15]),"+f"(d[16]),"+f"(d[17]),"+f"(d[18]),"+f"(d[19]),"+f"(d[20]),"+f"(d[21]),"+f"(d[22]),"+f"(d[23]),"+f"(d[24]),"+f"(d[25]),"+f"(d[26]),"+f"(d[27]),"+f"(d[28]),"+f"(d[29]),"+f"(d[30]),"+f"(d[31]),"+f"(d[32]),"+f"(d[33]),"+f"(d[34]),"+f"(d[35]),"+f"(d[36]),"+f"(d[37]),"+f"(d[38]),"+f"(d[39])
    : "l"(da), "l"(db), "r"(sd));
}
__device__ __forceinline__ void wg_rs32_00(float* d, uint32_t a0, uint32_t a1, uint32_t a2, uint32_t a3, uint64_t db, int sd) {
  asm volatile("{.reg .pred p; setp.ne.b32 p, %21, 0;\n"
    "wgmma.mma_async.sync.aligned.m64n32k16.f32.bf16.bf16 {%0,%1,%2,%3,%4,%5,%6,%7,%8,%9,%10,%11,%12,%13,%14,%15}, {%16,%17,%18,%19}, %20, p, 1, 1, 0;}"
    : "+f"(d[0]),"+f"(d[1]),"+f"(d[2]),"+f"(d[3]),"+f"(d[4]),"+f"(d[5]),"+f"(d[6]),"+f"(d[7]),"+f"(d[8]),"+f"(d[9]),"+f"(d[10]),"+f"(d[11]),"+f"(d[12]),"+f"(d[13]),"+f"(d[14]),"+f"(d[15])
    : "r"(a0), "r"(a1), "r"(a2), "r"(a3), "l"(db), "r"(sd));
}
__device__ __forceinline__ void wg_rs64_00(float* d, uint32_t a0, uint32_t a1, uint32_t a2, uint32_t a3, uint64_t db, int sd) {
  asm volatile("{.reg .pred p; setp.ne.b32 p, %37, 0;\n"
    "wgmma.mma_async.sync.aligned.m64n64k16.f32.bf16.bf16 {%0,%1,%2,%3,%4,%5,%6,%7,%8,%9,%10,%11,%12,%13,%14,%15,%16,%17,%18,%19,%20,%21,%22,%23,%24,%25,%26,%27,%28,%29,%30,%31}, {%32,%33,%34,%35}, %36, p, 1, 1, 0;}"
    : "+f"(d[0]),"+f"(d[1]),"+f"(d[2]),"+f"(d[3]),"+f"(d[4]),"+f"(d[5]),"+f"(d[6]),"+f"(d[7]),"+f"(d[8]),"+f"(d[9]),"+f"(d[10]),"+f"(d[11]),"+f"(d[12]),"+f"(d[13]),"+f"(d[14]),"+f"(d[15]),"+f"(d[16]),"+f"(d[17]),"+f"(d[18]),"+f"(d[19]),"+f"(d[20]),"+f"(d[21]),"+f"(d[22]),"+f"(d[23]),"+f"(d[24]),"+f"(d[25]),"+f"(d[26]),"+f"(d[27]),"+f"(d[28]),"+f"(d[29]),"+f"(d[30]),"+f"(d[31])
    : "r"(a0), "r"(a1), "r"(a2), "r"(a3), "l"(db), "r"(sd));
}
__device__ __forceinline__ void wg_rs80_01(float* d, uint32_t a0, uint32_t a1, uint32_t a2, uint32_t a3, uint64_t db, int sd) {
  asm volatile("{.reg .pred p; setp.ne.b32 p, %45, 0;\n"
    "wgmma.mma_async.sync.aligned.m64n80k16.f32.bf16.bf16 {%0,%1,%2,%3,%4,%5,%6,%7,%8,%9,%10,%11,%12,%13,%14,%15,%16,%17,%18,%19,%20,%21,%22,%23,%24,%25,%26,%27,%28,%29,%30,%31,%32,%33,%34,%35,%36,%37,%38,%39}, {%40,%41,%42,%43}, %44, p, 1, 1, 1;}"
    : "+f"(d[0]),"+f"(d[1]),"+f"(d[2]),"+f"(d[3]),"+f"(d[4]),"+f"(d[5]),"+f"(d[6]),"+f"(d[7]),"+f"(d[8]),"+f"(d[9]),"+f"(d[10]),"+f"(d[11]),"+f"(d[12]),"+f"(d[13]),"+f"(d[14]),"+f"(d[15]),"+f"(d[16]),"+f"(d[17]),"+f"(d[18]),"+f"(d[19]),"+f"(d[20]),"+f"(d[21]),"+f"(d[22]),"+f"(d[23]),"+f"(d[24]),"+f"(d[25]),"+f"(d[26]),"+f"(d[27]),"+f"(d[28]),"+f"(d[29]),"+f"(d[30]),"+f"(d[31]),"+f"(d[32]),"+f"(d[33]),"+f"(d[34]),"+f"(d[35]),"+f"(d[36]),"+f"(d[37]),"+f"(d[38]),"+f"(d[39])
    : "r"(a0), "r"(a1), "r"(a2), "r"(a3), "l"(db), "r"(sd));
}
__device__ __forceinline__ void wg_rs24_01(float* d, uint32_t a0, uint32_t a1, uint32_t a2, uint32_t a3, uint64_t db, int sd) {
  asm volatile("{.reg .pred p; setp.ne.b32 p, %17, 0;\n"
    "wgmma.mma_async.sync.aligned.m64n24k16.f32.bf16.bf16 {%0,%1,%2,%3,%4,%5,%6,%7,%8,%9,%10,%11}, {%12,%13,%14,%15}, %16, p, 1, 1, 1;}"
    : "+f"(d[0]),"+f"(d[1]),"+f"(d[2]),"+f"(d[3]),"+f"(d[4]),"+f"(d[5]),"+f"(d[6]),"+f"(d[7]),"+f"(d[8]),"+f"(d[9]),"+f"(d[10]),"+f"(d[11])
    : "r"(a0), "r"(a1), "r"(a2), "r"(a3), "l"(db), "r"(sd));
}

#define AB_POLY 0x77
__device__ __forceinline__ constexpr bool poly_group(int group) { return (AB_POLY >> (group & 7)) & 1; }

template <int V> struct Int { static constexpr int value = V; };

__device__ __forceinline__ int core_word(int row, int col) {
  return ((((row >> 7) * 10 + (col >> 6)) * 16 + ((row >> 3) & 15)) * 8 + ((col >> 3) & 7)) * 32 + (row & 7) * 4 + ((col & 7) >> 1);
}
__device__ __forceinline__ void wait_count(const uint32_t* c, uint32_t n) {
  for (int spin = 0; !__all_sync(~0u, (ld_acquire(c) & 0xffff) >= n);) { __nanosleep(32); spin_guard(spin); }
  fence_async_global();
}
__device__ __forceinline__ void prefetch_l2(const void* p, uint32_t bytes) {
  asm volatile("cp.async.bulk.prefetch.L2.global [%0], %1;" :: "l"(p), "r"(bytes) : "memory"); }

#define PLACE 4
__device__ __forceinline__ bool helper_sm() {
  uint32_t m; asm volatile("mov.u32 %0, %%smid;" : "=r"(m));
  m = __shfl_sync(~0u, m, 0);
  return m < 2 || m >= 120 || (m >= 92 && m < 102) || (m >= 106 && m < 117) || m == 118;
}

__device__ __forceinline__ uint8_t* pool_at(uint32_t off) {
  return reinterpret_cast<uint8_t*>((reinterpret_cast<uintptr_t>(g_pool) + 8191) & ~(uintptr_t)8191) + off; }
__device__ __forceinline__ void probe_slots(uint32_t scratch) {
  const int w = __shfl_sync(~0u, (threadIdx.x >> 6) & 1, 0), slot = w == 0 ? NSLOT : blockIdx.x;
  if (w == 0 || slot < NSLOT) {
    uint32_t* q = reinterpret_cast<uint32_t*>(pool_at(slot * 8192)) + (w == 0 ? (blockIdx.x & 31) * 32 + (blockIdx.x >> 5) : 0);
    uint32_t best[2] = {~0u, ~0u};
    const bool one = elect();
    if (one) { stg_strong32(q, 0u); stg_strong32(q + 1024, 0u); }
#pragma unroll 1
    for (int r = 0; r < 8; r++) {
      uint32_t v = 0;
      const uint32_t t0 = clk32();
      if (one) asm volatile("atom.relaxed.gpu.global.exch.b32 %0, [%1], 0;" : "=r"(v) : "l"(q + (r & 1) * 1024) : "memory");
      if (__any_sync(~0u, v != 0)) break;
      const uint32_t t = min(clk32() - t0, best[0]);
      best[0] = best[1]; best[1] = t;
    }
    if (one) sts32(scratch + w * 4, best[0] < best[1]);
  }
  bar_sync(2, 64);
  if ((threadIdx.x & 31) == 0) {
    const int part = lds32(scratch) ? 1 : 2;
    if (w == 0) { uint32_t smid; asm("mov.u32 %0, %%smid;" : "=r"(smid)); stg_strong32(g_smpart + (smid & 255), part); }
    else if (slot < NSLOT) stg_strong32(g_orient + slot, lds32(scratch + 4) ? part : 3 - part);
  }
  __syncwarp();
}

constexpr int WK_SLOTS = 28, WK_BAR = WK_SLOTS * 8192;
__device__ __forceinline__ void work_init(uint32_t sb, int w) {
  if (elect()) {
#pragma unroll
    for (int i = 0; i < 8; i++) mbar_init(sb + WK_BAR + 64 * w + 8 * i, 0x18318822 >> (8 * w + (i & 4)) & 15);
  }
  asm volatile("fence.mbarrier_init.release.cluster;" ::: "memory");
}

struct ChainParams {
  CUtensorMap wq, wk, wv, wo, xc;
  const __nv_bfloat16* mem0;
  const uint8_t* wb;
  uint32_t *sync, *other;
  int layer;
  int d1, d2, dn, dx, mode, zero;
};
constexpr int CH_WQ = 0, CH_WO = 81920, CH_X = CH_WO + 86016, CH_M = CH_X, CH_Q = CH_X + 34816, CH_KM = CH_Q + 2048, CH_VP = CH_KM + 2048,
              CH_K = CH_X + 40960, CH_O = CH_K, CH_KS = CH_K + 3072, CH_V = CH_K + 4096, CH_VX = CH_V + 12288, CH_R2 = CH_VX,
              CH_SX = CH_VX + 3072, CH_SO = CH_SX + 2048, CH_ID = CH_SO + 1024, CH_L = CH_ID + 256, CH_TAB = CH_L + 64, CH_BAR = CH_TAB + 384;
constexpr int CH_SMEM = CH_BAR + 144;
constexpr int MB_WO = CH_BAR, MB_WQ = CH_BAR + 8, MB_X = CH_BAR + 16, MB_V = CH_BAR + 24, MB_T = CH_BAR + 32, MB_F = CH_BAR + 40, MB_G = CH_BAR + 48, MB_W = CH_BAR + 56;
enum { NB_PROJ = 1, NB_O = 2, NB_W1 = 3, NB_PRE = 4, NB_ST = 5, NB_MEM = 6, NB_XFREE = 7, NB_H1 = 8, NB_PUB = 9, NB_W2 = 10, NB_PROJ2 = 11, NB_PRE2 = 12, NB_H2 = 13, NB_W1V = 14 };
#define CH_NQ 9
#define CH_XPF 1
#define CH_TPF 1
#define CH_FLY 6
#define CH_TW 1
#define H1VOTE 0
#define CH_NQ0 4
#define CH_PA 6
#define CH_PB 9
#define CH_PC 13
#define CH_PL 4
#define CH_DBL 0x0888
#define CH_PD 1
#define SCHED() asm volatile("griddepcontrol.launch_dependents;" ::: "memory")
__device__ __forceinline__ uint32_t opaque(uint32_t x) { return __shfl_sync(~0u, x, threadIdx.x & 31); }
__device__ __forceinline__ uint32_t uniform(uint32_t x) { return __shfl_sync(~0u, x, 0); }
__device__ __forceinline__ uint32_t nz(uint32_t x) { uint32_t r; asm("max.u32 %0, %1, 1;" : "=r"(r) : "r"(x)); return r; }
__device__ __forceinline__ uint32_t set_tag(uint32_t w, uint32_t tag) { uint32_t r; asm("lop3.b32 %0, %1, %2, 1, 0xD8;" : "=r"(r) : "r"(w), "r"(tag)); return r; }
__device__ __forceinline__ uint32_t pack_tag(float lo, float hi, uint32_t tag) { return set_tag(__byte_perm(__float_as_uint(lo) + tag, pack2(hi, hi), 0x7632), tag); }
__device__ __forceinline__ uint32_t differ(uint32_t a, uint32_t b, uint32_t t) { uint32_t r; asm("lop3.b32 %0, %1, %2, %3, 0x7E;" : "=r"(r) : "r"(a), "r"(b), "r"(t)); return r; }
__device__ __forceinline__ uint32_t clk64() { uint64_t c; asm volatile("mov.u64 %0, %%clock64;" : "=l"(c) :: "memory"); return (uint32_t)c; }
__device__ __forceinline__ void until(uint32_t t) {
  asm volatile("{.reg .pred p; .reg .u64 c; .reg .s32 d;\nW: mov.u64 c, %%clock64; cvt.u32.u64 d, c; sub.s32 d, d, %0; setp.lt.s32 p, d, 0; @p bra.uni W;}" :: "r"(t) : "memory");
}
__device__ __forceinline__ float rcp(float x) { float y; asm("rcp.approx.ftz.f32 %0, %1;" : "=f"(y) : "f"(x)); return y; }

__device__ __forceinline__ void chain_compute(const ChainParams& p, const uint32_t sb) {
  const int tid = threadIdx.x & 127, WG = __shfl_sync(~0u, threadIdx.x >> 7, 0), t4 = __shfl_sync(~0u, tid >> 5, 0), lane = tid & 31;
  const int cta = blockIdx.x, h = cta / 3, j = cta - 3 * h;
  uint32_t a0[80], a1[80], tw[4 * CH_NQ];
  const uint32_t wq = opaque(sb + CH_WQ + (WG * 320 + (lane & 7) + (lane >> 4) * 8) * 128 + (((2 * t4 + ((lane >> 3) & 1)) ^ (lane & 7)) << 4));
#pragma unroll
  for (int k = 0; k < 40; k++) {
    if (k % 10 == 0) mbar_wait(sb + MB_W + WG * 8 + k / 10 * 16, 0);
    if (k < 20) ldsm4t(&a0[4 * k], wq + k * 2048); else ldsm4t(&a1[4 * k - 80], wq + CH_WO + (k - 20) * 2048);
    if (k % 20 == 19) bar_arrive(k < 20 ? NB_PROJ2 : NB_PRE2, 288);
  }
  const int r1 = j == 2 ? 0 : j + 1, r2 = j == 0 ? 2 : j - 1;
  const uint32_t l16 = opaque(sb + lane * 16), l8 = opaque(sb + lane * 8), l4 = opaque(sb + lane * 4);
  const uint32_t t16 = l16 + t4 * 512, t8 = l8 + t4 * 256;
  uint32_t wo = opaque(sb + CH_WO + (WG == 0 ? (t4 >> 1) * 36864 : 73728 + t4 * 1024) + ((lane & 7) + (lane >> 4) * 8) * 64 +
                       (((((lane >> 3) & 1) + (WG == 0 ? (t4 & 1) * 2 : 0)) ^ ((lane >> 1) & 3)) << 4));
  const uint32_t ko0 = uniform(CH_K + (tid >> 5) * 1024 + (tid >> 6) * 512), ko1 = uniform(CH_K + (tid >> 5) * 1024 + 512 - (tid >> 6) * 512),
                 o768 = uniform((tid >> 5) * 768);
  const uint32_t give = uniform(t4 * 512 + (WG == 0 ? CH_K : CH_V + j * 4096)), own = uniform(t4 * 512 + (WG == 0 ? CH_V + j * 4096 : CH_K)), mem = uniform(CH_M + WG * 5120);
  const uint32_t vxo = uniform(t4 * 256 + CH_VX + j * 1024);
  uint32_t tag = 1, xd = uniform((1024 + CH_X + WG * 20480) >> 4 | 8 << 16);
  asm volatile("barrier.cluster.wait.aligned;" ::: "memory");
  mbar_wait(sb + MB_WQ, 0);
  mbar_wait(sb + MB_T, 0);
  bar_sync(NB_ST, 384);
  uint8_t* pdst[6];
#pragma unroll
  for (int i = 0; i < 6; i++) {
    const int line = WG == 0 ? 24 * j + 12 * (t4 >> 1) + 2 * (t4 & 1) + 4 * (i >> 1) + (i & 1) : j == 0 ? 72 + t4 : 74 + 2 * j + (t4 & 1);
    pdst[i] = pool_at(uniform(lds32(sb + CH_TAB + line * 4)) + h * 128);
  }
  auto batch = [&](float* d, const uint32_t (&a)[80], int acc, int n0, int n1) {
    const uint32_t d0 = xd ^ (tag & (2 << acc));
    wg_fence();
#pragma unroll
    for (int k = 0; k < 20; k++) {
      if (!(k & 3) && n0 + k / 4 < n1) {
        __syncwarp();
        ldsm4t(&tw[4 * n0 + k], wq + (n0 + k / 4) * 2048);
        __syncwarp();
      }
      uint64_t db;
      asm("mov.b64 %0, {%1, %2};" : "=l"(db) : "r"(d0 + k / 5 * 320 + k % 5 * 16), "r"(80));
      wg_rs32_00(d, a[4 * k], a[4 * k + 1], a[4 * k + 2], a[4 * k + 3], db, acc | k);
    }
    wg_commit();
    wg_wait<0>();
    reg_fence<16>(d);
  };
  int s = 0;
#pragma unroll 1
  do {
    {
      float d[16];
      if (!CH_TW) mbar_wait(sb + MB_T, s & 1);
      batch(d, a0, 0, 0, CH_NQ0);
      s--; TM(10); s++;
      mbar_wait(sb + MB_F, ~s & 1);
#pragma unroll
      for (int i = 0; i < 2; i++)
        sts128(l16 + give + i * 2048, make_uint4(pack2(d[8 * i], d[8 * i + 1]), pack2(d[8 * i + 2], d[8 * i + 3]), pack2(d[8 * i + 4], d[8 * i + 5]), pack2(d[8 * i + 6], d[8 * i + 7])));
      bar_sync(NB_PUB, 384);
#pragma unroll
      for (int i = 0; i < 2; i++) {
        const uint4 t = lds128(l16 + own + i * 2048);
        d[8 * i] = bf_lo(t.x); d[8 * i + 1] = bf_hi(t.x); d[8 * i + 2] = bf_lo(t.y); d[8 * i + 3] = bf_hi(t.y);
        d[8 * i + 4] = bf_lo(t.z); d[8 * i + 5] = bf_hi(t.z); d[8 * i + 6] = bf_lo(t.w); d[8 * i + 7] = bf_hi(t.w);
      }
      reg_fence<16>(d);
      batch(d, a1, 1, CH_NQ0, CH_NQ);
      s--; TM(11); s++;
      if (WG == 0) bar_arrive(NB_XFREE, 256);
#pragma unroll
      for (int i = 0; i < 8; i++) sts32(l4 + (own - t4 * 256) + (i >> 1) * 1024 + (i & 1) * 128, pack2(d[2 * i], d[2 * i + 1]));
      s--; TM(9); s++;
    }
    float dq[4] = {}, d0[4] = {}, d1[4] = {};
    uint32_t b[40], wf[80];
    const uint32_t* kf = &wf[52];
#pragma unroll
    for (int i = 0; i < 4 * CH_NQ; i++) wf[i] = tw[i];
    auto step = [&](int k) {
      mma16(dq, wf[4 * k], wf[4 * k + 1], wf[4 * k + 2], wf[4 * k + 3], b[2 * k], b[2 * k + 1]);
      mma16(d0, a0[4 * k], a0[4 * k + 1], a0[4 * k + 2], a0[4 * k + 3], b[2 * k], b[2 * k + 1]);
      mma16(d1, a1[4 * k], a1[4 * k + 1], a1[4 * k + 2], a1[4 * k + 3], b[2 * k], b[2 * k + 1]);
    };
    auto finish = [&](int wg, const float* dk) {
      const float k2 = 0.07216878364870322f * 1.44269504089f;
      sts32(l4 + t4 * 512 + CH_Q + wg * 128, pack2(dq[0] * k2, dq[1] * k2));
      sts32(l4 + t4 * 512 + CH_Q + wg * 128 + 256, pack2(dq[2] * k2, dq[3] * k2));
      sts32(l4 + t4 * 512 + CH_KM + wg * 256, pack2(dk[0], dk[1]));
      sts32(l4 + t4 * 512 + CH_KM + wg * 256 + 128, pack2(dk[2], dk[3]));
    };
    const bool more = s < NSEG - 1;
    bar_sync(NB_MEM, 384);
    ldsm4t(&b[0], l16 + mem);
    ldsm4t(&b[4], l16 + mem + 512);
    TMD(0, b[0]);
    {
      int nw = CH_NQ, nb = 2;
#pragma unroll
      for (int k = 0; k < 20; k++) {
        SCHED();
        step(k);
#pragma unroll
        for (int i = 0; i < (CH_DBL >> k & 1) + 1; i++) {
          if (nb < 10 && 2 * nb <= nw) { ldsm4t(&b[4 * nb], l16 + mem + nb * 512); nb++; }
          else if (nw < 20) { ldsm4t(&wf[4 * nw], wq + nw * 2048); nw++; }
          else if (nw < 22) {
            const uint32_t x = l16 ^ ((o768 ^ tag) & 256);
            uint32_t* r = &wf[4 * nw - 28];
            asm volatile("{.reg .pred p; setp.ne.u32 p, %5, 0; @p ldmatrix.sync.aligned.m8n8.x4.trans.shared.b16 {%0,%1,%2,%3},[%4];}"
                         : "+r"(r[0]), "+r"(r[1]), "+r"(r[2]), "+r"(r[3]) : "r"(x + (nw == 20 ? ko0 : ko1)), "r"(WG) : "memory");
            nw++;
          }
        }
      }
      SCHED();
    }
    if (WG == 0) {
      finish(0, d0);
      TM(1);
      bar_sync(NB_PROJ, 256);
      if (!more) {
        const float4 pv = lds128f(t16 + CH_VP);
        sts32(l4 + vxo, pack2(d1[0] + pv.x, d1[1] + pv.y));
        sts32(l4 + vxo + 128, pack2(d1[2] + pv.z, d1[3] + pv.w));
        continue;
      }
      const float4 pv = lds128f(t16 + CH_VP);
      const uint32_t xo = l4 + (vxo ^ (tag & 2)), x1 = mapa(xo, r1), x2 = mapa(xo, r2);
      SCHED();
      const uint32_t v0 = pack2(d1[0] + pv.x, d1[1] + pv.y), v1 = pack2(d1[2] + pv.z, d1[3] + pv.w);
      st_async32(x1, v0, mapa(sb + MB_X, r1));
      st_async32(x2, v0, mapa(sb + MB_X, r2));
      st_async32(x1 + 128, v1, mapa(sb + MB_X, r1));
      st_async32(x2 + 128, v1, mapa(sb + MB_X, r2));
      sts32(xo, v0);
      sts32(xo + 128, v1);
      __syncwarp();
      mbar_arrive_one(sb + MB_X);
      bar_arrive(NB_PROJ2, 256);
      TM(3);
      uint32_t w[144];
      auto tile_of = [](int n) { return n < 27 ? n % 3 : (0x26484 >> 2 * (n - 27)) & 3; };
      auto step_of = [](int n) { return n < 27 ? n / 3 : 9 + ((0x29610 >> 2 * (n - 27)) & 3); };
      auto wload = [&](int n) { ldsm4t(&w[4 * n], wo + tile_of(n) * 12288 + (step_of(n) % 3) * 4096 + (step_of(n) / 3) * 1024); };
#pragma unroll
      for (int n = 0; n < CH_PA; n++) wload(n);
      bar_sync(NB_PRE, 256);
#pragma unroll
      for (int n = CH_PA; n < CH_PB; n++) wload(n);
      bar_arrive(NB_PRE2, 256);
      if (CH_PC > CH_PB) {
        mbar_wait(sb + MB_X, s & 1);
        for (int i = 0; i < CH_PD; i++) wo = __shfl_xor_sync(~0u, wo, p.zero);
#pragma unroll
        for (int n = CH_PB; n < CH_PC; n++) wload(n);
      }
      TM(4);
      bar_sync(NB_O, 256);
      {
        float x[3][4] = {};
        uint32_t ob[24];
        float4 l;
        ldsm4t(&ob[0], l16 + CH_O);
        ldsm4t(&ob[4], l16 + CH_O + 512);
        TMD(7, ob[0]);
        int nw = CH_PC, no = 2;
        float i0, i1;
        uint8_t* dst[6];
        uint32_t lo[6], hi[6];
        auto pre = [&](int i) { lo[i] = __float_as_uint(x[i >> 1][2 * (i & 1)] * i0) + tag; hi[i] = pack2(0.f, x[i >> 1][2 * (i & 1) + 1] * i1); };
        auto emit = [&](int i) { stg_strong32(dst[i], set_tag(__byte_perm(lo[i], hi[i], 0x7632), tag)); };
#pragma unroll
        for (int n = 0; n < 36; n++) {
          SCHED();
          mma16(x[tile_of(n)], w[4 * n], w[4 * n + 1], w[4 * n + 2], w[4 * n + 3], ob[step_of(n) * 2], ob[step_of(n) * 2 + 1]);
          if (n >= CH_PL) {
            if (no < 6 && no * 2 <= step_of(min(nw, 35))) { ldsm4t(&ob[4 * no], l16 + CH_O + no * 512); no++; }
            else if (nw < 36) { wload(nw); nw++; }
          }
          if (n == 18) l = lds128f(sb + CH_L + ((l16 ^ tag) & 0x30));
          if (n == 26) { i0 = rcp(l.x + l.y); i1 = rcp(l.z + l.w); asm volatile("" : "+f"(i0), "+f"(i1)); }
          if (n >= 28 && n < 34) { dst[n - 28] = pdst[n - 28] + ((l4 ^ tag) & 0x7c); asm volatile("" : "+l"(dst[n - 28])); }
          if (n == 32) { for (int i = 0; i < 2; i++) { pre(i); asm volatile("" : "+r"(lo[i]), "+r"(hi[i])); } }
          if (n == 33) { emit(0); emit(1); }
        }
        for (int i = 2; i < 6; i++) pre(i);
        for (int i = 2; i < 6; i++) emit(i);
      }
      TM(8);
    } else {
      finish(1, d1);
      sts128f(t16 + CH_VP, d0[0], d0[1], d0[2], d0[3]);
      TM(1);
      bar_sync(NB_PROJ, 256);
      uint32_t pair;
      {
        float d0[4] = {}, d1[4] = {}, dm[4] = {};
        uint32_t q[16], km[4];
#pragma unroll
        for (int e = 0; e < 4; e++) {
          ldsm4t(&q[4 * e], l16 + (e ^ t4) * 512 + CH_Q);
          SCHED();
          if (e == 1) { ldsm4t(km, t16 + CH_KM); SCHED(); }
        }
        const uint32_t xo = l4 + ((t4 * 128) ^ (tag & 2));
        pair = l16 + ((l16 ^ tag) & 256) * 3;
        asm volatile("" : "+r"(pair));
        uint64_t x[4];
#pragma unroll
        for (int i = 0; i < 4; i++) {
          const int r = i & 1 ? r2 : r1;
          asm volatile("mov.b64 %0, {%1, %2};" : "=l"(x[i]) : "r"(mapa(xo, r) + CH_SX + (i & 1) * 1024 + (i & 2) * 256), "r"(mapa(sb + MB_X, r)));
        }
        SCHED();
        mma16(d0, q[0], q[1], q[2], q[3], kf[0], kf[1]);
        SCHED();
        mma16(d1, q[4], q[5], q[6], q[7], kf[2], kf[3]);
        SCHED();
        mma16(dm, q[0], q[1], q[2], q[3], hadd2(km[0], km[2]), hadd2(km[1], km[3]));
        mma16(d0, q[8], q[9], q[10], q[11], kf[4], kf[5]);
        SCHED();
        mma16(d1, q[12], q[13], q[14], q[15], kf[6], kf[7]);
        if (!more) continue;
        const uint32_t w1 = pack2(dm[0] + dm[2], dm[1] + dm[3]);
        st_async32((uint32_t)x[2], w1, x[2] >> 32);
        st_async32((uint32_t)x[3], w1, x[3] >> 32);
        SCHED();
        const uint32_t w0 = pack2((d0[0] + d0[2]) + (d1[0] + d1[2]), (d0[1] + d0[3]) + (d1[1] + d1[3]));
        st_async32((uint32_t)x[0], w0, x[0] >> 32);
        st_async32((uint32_t)x[1], w0, x[1] >> 32);
        sts32(xo + CH_SO, w0);
        sts32(xo + CH_SO + 512, w1);
      }
      TM(3);
      float sc[3][4] = {};
      uint32_t wd[12];
      uint32_t redo;
      auto attend = [&](auto first) {
        uint4 vb[6];
        uint32_t vm[6];
        float e[10];
        uint32_t ow[6];
        if (first.value) {
          const uint2 id = lds64(l8 + CH_ID);
          bar_sync(NB_W1V, 160);
          uint32_t r[8];
          ldsm4(r, l16 + CH_SO); ldsm4(r + 4, l16 + CH_SO + 512);
#pragma unroll
          for (int u = 0; u < 6; u++) vb[u] = ldsm4v(pair + t4 * 256 + CH_V + u * 2048);
          bar_arrive(NB_PRE, 256);
          const uint32_t sxa = pair + CH_SX;
          SCHED();
          mma8(sc[0], r[0], r[1], id.x);
          mma8(sc[1], r[2], r[3], id.x);
          mma16(sc[2], r[4], r[5], r[6], r[7], id.x, id.y);
          TM(7);
          mbar_wait(sb + MB_X, s & 1);
          TM(4);
          uint32_t t[16];
          ldsm4(t, sxa); ldsm4(t + 4, sxa + 256); ldsm4(t + 8, sxa + 512);
          SCHED();
          mma16(sc[0], t[0], t[1], t[2], t[3], id.x, id.y);
          ldsm4(t + 12, sxa + 768);
          SCHED();
          mma16(sc[1], t[4], t[5], t[6], t[7], id.x, id.y);
          ldsm4(vm, pair + t4 * 256 + CH_VX);
          SCHED();
          e[0] = ex2(sc[0][0]);
          mma16(sc[2], t[8], t[9], t[10], t[11], id.x, id.y);
          ldsm2(vm + 4, l16 + t4 * 256 + CH_VX + 2048);
          SCHED();
          e[1] = ex2(sc[0][1]);
          ldsm4t(&wd[0], wo);
          SCHED();
          e[2] = ex2(sc[0][2]);
          SCHED();
          e[3] = ex2(sc[0][3]);
          mma16(sc[2], t[12], t[13], t[14], t[15], id.x, id.y);
          SCHED();
          e[4] = ex2(sc[1][0]);
          ldsm4t(&wd[4], wo + 4096);
          SCHED();
          e[5] = ex2(sc[1][1]);
        } else {
#pragma unroll
          for (int u = 0; u < 6; u++) vb[u] = ldsm4v(pair + t4 * 256 + CH_V + u * 2048);
          ldsm4(vm, pair + t4 * 256 + CH_VX);
          ldsm2(vm + 4, l16 + t4 * 256 + CH_VX + 2048);
        }
        float o[3][4] = {};
        if (!first.value) {
#pragma unroll
          for (int i = 0; i < 6; i++) e[i] = ex2(sc[i >> 2][i & 3]);
        }
        const uint32_t p1 = pack2(e[0], e[1]), p2 = pack2(e[2], e[3]);
        float l = (e[0] + e[1]) + (e[2] + e[3]);
        asm volatile("" : "+f"(l));
        SCHED();
        e[6] = ex2(sc[1][2]);
        mma16(o[0], vb[0].x, vb[0].y, vb[0].z, vb[0].w, p1, p2);
        if (first.value) { sc[2][0] += sc[2][2]; sc[2][1] += sc[2][3]; }
        SCHED();
        e[7] = ex2(sc[1][3]);
        mma16(o[1], vb[2].x, vb[2].y, vb[2].z, vb[2].w, p1, p2);
        SCHED();
        e[8] = ex2(sc[2][0]);
        mma16(o[2], vb[4].x, vb[4].y, vb[4].z, vb[4].w, p1, p2);
        SCHED();
        e[9] = ex2(sc[2][1]);
        SCHED();
        const uint32_t p3 = pack2(e[4], e[5]), p4 = pack2(e[6], e[7]);
        l += (e[4] + e[5]) + (e[6] + e[7]);
#pragma unroll
        for (int u = 0; u < 3; u++) mma16(o[u], vb[2 * u + 1].x, vb[2 * u + 1].y, vb[2 * u + 1].z, vb[2 * u + 1].w, p3, p4);
        SCHED();
        const uint32_t p0 = pack2(e[8], e[9]);
        l += e[8] + e[9];
        const float l2 = __shfl_xor_sync(~0u, l, 1);
        if (first.value) ldsm4t(&wd[8], wo + 8192);
#pragma unroll
        for (int u = 0; u < 3; u++) mma8(o[u], vm[2 * u], vm[2 * u + 1], p0);
        redo = __any_sync(~0u, !(l > 1e-9f && l < 1e9f));
        uint32_t la = sb + CH_L + (((l4 ^ tag) >> 1) & 0x3c);
        asm volatile("" : "+r"(la));
        SCHED();
#pragma unroll
        for (int u = 0; u < 3; u++) { ow[2 * u] = pack2(o[u][0], o[u][1]); ow[2 * u + 1] = pack2(o[u][2], o[u][3]); }
#pragma unroll
        for (int u = 0; u < 6; u++) sts32(l4 + o768 + CH_O + u * 128, ow[u]);
        if (t4 == 0) sts32(la, __float_as_uint(l + l2));
      };
      attend(Int<1>());
      TM(6);
      asm volatile("{.reg .pred p; setp.eq.u32 p, %0, 0; @p bar.sync 2, 256;}" :: "r"(redo) : "memory");
      if (redo) {
        float mx = fmaxf(sc[2][0], sc[2][1]);
#pragma unroll
        for (int i = 0; i < 4; i++) mx = fmaxf(mx, fmaxf(sc[0][i], sc[1][i]));
        mx = fmaxf(mx, __shfl_xor_sync(~0u, mx, 1));
        mx = fmaxf(mx, __shfl_xor_sync(~0u, mx, 2));
#pragma unroll
        for (int i = 0; i < 4; i++) { sc[0][i] -= mx; sc[1][i] -= mx; }
        sc[2][0] -= mx; sc[2][1] -= mx;
        attend(Int<0>());
        bar_arrive(NB_O, 256);
      }
      {
        float z[4] = {};
        const uint32_t scr = l8 + ((CH_V + r1 * 4096) ^ (tag & 2));
        uint32_t ow[6], we[12];
        __syncwarp();
        ldsm4t(ow, l16 + o768 + CH_O);
        ldsm2t(ow + 4, l16 + o768 + CH_O + 512);
        if (j == 0) {
          float y[4] = {};
#pragma unroll
          for (int u = 0; u < 3; u++) ldsm4t(&we[4 * u], (wo ^ 32) + u * 4096);
          SCHED();
#pragma unroll
          for (int u = 0; u < 3; u++) {
            mma16(z, wd[4 * u], wd[4 * u + 1], wd[4 * u + 2], wd[4 * u + 3], ow[2 * u], ow[2 * u + 1]);
            mma16(y, we[4 * u], we[4 * u + 1], we[4 * u + 2], we[4 * u + 3], ow[2 * u], ow[2 * u + 1]);
          }
          sts64f(scr + t4 * 256 + 2048, y[0], y[1]); sts64f(scr + t4 * 256 + 3072, y[2], y[3]);
        } else {
#pragma unroll
          for (int u = 0; u < 3; u++) mma16(z, wd[4 * u], wd[4 * u + 1], wd[4 * u + 2], wd[4 * u + 3], ow[2 * u], ow[2 * u + 1]);
        }
        sts64f(scr + t4 * 256, z[0], z[1]); sts64f(scr + t4 * 256 + 1024, z[2], z[3]);
        bar_sync(NB_W1, 128);
        if (j == 0 || t4 < 2) {
          float2 q[4];
          const float4 l = lds128f(sb + CH_L + ((l16 ^ tag) & 0x30));
#pragma unroll
          for (int i = 0; i < 4; i++) q[i] = lds64f(scr + t4 * 1024 + i * 256);
          SCHED();
          stg_strong32(pdst[0] + ((l4 ^ tag) & 0x7c), pack_tag(((q[0].x + q[1].x) + (q[2].x + q[3].x)) * rcp(l.x + l.y), ((q[0].y + q[1].y) + (q[2].y + q[3].y)) * rcp(l.z + l.w), tag));
        }
      }
      TM(2);
    }
    bar_sync(NB_ST, 384);
    tag ^= 0x10001;
  } while (++s < NSEG);
  if (WG == 1) {
    const uint2 a = lds64(t8 + t4 * 256 + CH_KM), b = lds64(t8 + t4 * 256 + CH_KM + 256);
    sts64(t8 + CH_M, hadd2(a.x, b.x), hadd2(a.y, b.y));
  }
  bar_arrive(NB_PRE2, 288);
}

__device__ __forceinline__ void chain_comm(const ChainParams& p, const uint32_t sb, const CUtensorMap* maps) {
  [[maybe_unused]] constexpr int WG = 2;
  const int tid = threadIdx.x & 127, t4 = __shfl_sync(~0u, tid >> 5, 0), lane = tid & 31;
  const int cta = blockIdx.x, h = cta / 3, j = cta - 3 * h, colbase = cta * 64;
  const uint8_t* const xs = reinterpret_cast<const uint8_t*>(g_xn);
  auto xload = [&](int seg, int i) { tma_load5_one(sb + CH_X + i * 10240, &p.xc, 0, seg * 4, 2 * i, sb + MB_T); };
  uint32_t smid; asm("mov.u32 %0, %%smid;" : "=r"(smid));
  if (t4 == 3) {
    const bool one = elect();
#pragma unroll 1
    for (int i = 0; i < 19 + CH_FLY; i++) {
      if (i >= CH_FLY) mbar_wait(sb + MB_W + 8 * ((i - CH_FLY) & 7), (i - CH_FLY) >> 3 & 1);
      if (i == 11 + CH_FLY && one) mbar_arrive(sb + MB_WQ);
      if (i == 8) { bar_sync(NB_PROJ2, 288); PRO(1); }
      if (i == 12) { bar_sync(NB_PRE2, 288); PRO(2); }
      if (i == 0) { bar_arrive(NB_ST, 384); bar_arrive(NB_PUB, 384); bar_arrive(NB_XFREE, 256); }
      if (i < 19 && one) {
        const int n = (i & 1) * 2 + (i >> 1 & 1), k = i - 12;
        const uint32_t bar = sb + MB_W + 8 * (i & 7);
        mbar_expect(bar, k < 0 ? 20480 : 12288);
        if (k < 0) tma_load(sb + ((i & 4) + n) * 20480, i >= 8 ? &p.wq : (i ^ i >> 2) & 1 ? &p.wv : &p.wk, colbase, n * 160, bar);
        else tma_load(sb + CH_WO + k * 12288, &p.wo, k < 6 ? j * 192 + k * 32 : j == 0 ? 576 : 592 + j * 16, h * 192, bar);
      }
    }
  } else {
    const uint32_t part = max(ldg_strong32(g_smpart + (smid & 255)), 1u);
    if (tid == 0) prefetch_l2(p.mem0, 10240);
    if (tid == 64) stg_strong32(p.sync + SY_PART + cta, part);
    if (t4 == 1) {
      wait_count(p.sync + SY_P + 1, ln_items(p.layer, 0));
      mbar_expect_one(sb + MB_T, 40960);
#pragma unroll 1
      for (int i = 0; i < 4; i++) xload(0, i);
      PRO(0);
    }
    uint32_t reader, orient;
    for (int n = 0;; spin_guard(n)) {
      reader = ldg_strong32(p.sync + SY_PART + (tid >= 80 ? cta : tid));
      orient = ldg_strong32(g_orient + min(tid, NSLOT - 1));
      if (__all_sync(~0u, reader && orient)) break;
    }
    const uint32_t near = __ballot_sync(~0u, reader == part) >> (cta & 7) & 0xffff;
    if (tid < NSLOT) sts32(sb + CH_TAB + tid * 4, tid * 8192 + (orient == reader ? 0 : 4096));
    if (tid == 0) sts32(sb + CH_TAB + NSLOT * 4, cta < 80 ? cta : (cta & 7) + max(__ffs(near) - 1, 0));
    if (t4 == 1) PRO(3);
    bar_sync(NB_ST, 384);
    bar_arrive(NB_PUB, 384);
    if (t4 == 1) PRO(4);
    const uint32_t id = (lane >> 3) == (lane & 3) ? ((lane & 4) ? 0x3f800000u : 0x00003f80u) : 0u;
    if (t4 == 0) sts64(sb + CH_ID + lane * 8, id, id);
#pragma unroll 1
    for (int q = t4; q < 4; q += 3) {
      uint32_t m0[20];
#pragma unroll
      for (int i = 0; i < 20; i++) m0[i] = (reinterpret_cast<const uint32_t*>(p.mem0) + (lane >> 2) * (DM / 2) + q * 80 + (lane & 3))[i * 4];
      if (q < 3) bar_sync(NB_XFREE, 256);
#pragma unroll
      for (int i = 0; i < 20; i += 4) stsm4t(sb + CH_M + (q * 20 + i) * 128 + lane * 16, m0[i], m0[i + 1], m0[i + 2], m0[i + 3]);
    }
    if (t4 == 1) PRO(5);
  }
  if (cta * 128 + tid < SY_N) p.other[cta * 128 + tid] = 0;
  asm volatile("barrier.cluster.wait.aligned;" ::: "memory");
  const uint32_t l8 = opaque(sb + t4 * 256 + lane * 8);
  bar_sync(NB_MEM, 384);
  uint8_t* const pool = pool_at(0);
  const uint8_t* const psrc = pool + opaque(lds32(sb + CH_TAB + lds32(sb + CH_TAB + NSLOT * 4) * 4) + t4 * 1024 + lane * 4);
  const uint32_t mdst = opaque((80 + cta / 20) * 8192 + (t4 & 1) * 4096 + (cta % 20) * 128 + lane * 4);
  int st = 0;
  uint32_t tag = 1, span = ~0u;
  auto send_tokens = [&](int s) {
    uint8_t* dst = g_kv + ((s >> 2) * 192 + cta + 3 * h) * KV_PART + (s & 3) * KV_SEG;
    bulk_store(dst, sb + CH_K, 4096);
    bulk_store(dst + KV_V, sb + CH_V + j * 4096, 4096);
    bulk_commit();
  };
  auto send_memory = [&](int s, uint32_t km) {
    fence_async();
    uint8_t* dst = g_kv + ((s >> 2) * 192 + cta + 3 * h) * KV_PART + KV_M + (s & 3) * KV_SEG;
    bulk_store(dst, km, 1024);
    bulk_store(dst + KV_V, sb + CH_VX + j * 1024, 1024);
    bulk_commit();
    bulk_wait<0>();
    if ((s & 3) == 3) { fence_async_global(); atomicAdd(p.sync + (s >> 2) * 8 + 4, 1); }
  };
#pragma unroll 1
  for (int s = 0; s < NSEG - 1; s++) {
    TM(0);
    STAT(0);
    if (t4 == 0) {
      if (elect()) {
        fence_async();
#pragma unroll 1
        for (int r = j + 1; r < j + 3; r++) bulk_push(mapa(sb + CH_V + j * 4096, r % 3), sb + CH_V + j * 4096, 4096, mapa(sb + MB_V, r % 3));
        send_tokens(s);
        bulk_wait_read<0>();
      }
      __syncwarp();
    }
    uint32_t c0, g0;
    if (t4 == 1) {
      __syncwarp();
      c0 = clk32(); g0 = gtime();
      if (elect()) atomicMax(p.sync + SY_TIME + s, g0);
    }
    if (t4 == 3 && s >= NSEG - 6 && elect()) asm volatile("prefetch.tensormap [%0];" :: "l"(maps + (NSEG - 2 - s)) : "memory");
    if (t4 == 3 && (s & 3) == 2 && s < NSEG - 2) wait_count(p.sync + SY_P + 5 + (s & ~3), ln_items(p.layer, (s >> 2) + 1));
    if (t4 == 2) { mbar_wait(sb + MB_V, s & 1); bar_arrive(NB_W1V, 160); }
    bar_sync(NB_PROJ2, 256);
    if (t4 == 0) {
      mbar_expect_one(sb + MB_X, 4096);
      mbar_expect_one(sb + MB_T, 40960);
      for (int i = 0; i < 3; i++) xload(s + 1, i);
    }
    __syncwarp();
    STAT(1);
    TM(1);
    {
      const uint2 a = lds64(l8 + t4 * 256 + CH_KM), b = lds64(l8 + t4 * 256 + CH_KM + 256);
      sts64(l8 + CH_KS, hadd2(a.x, b.x), hadd2(a.y, b.y));
    }
    TM(4);
    bar_sync(NB_PRE2, 256);
    if (t4 == 0) xload(s + 1, 3);
    if (t4 == 0 && elect()) {
      if (CH_XPF && s < NSEG - 2) prefetch_l2(xs + (s + 2) * 40960 + cta % 20 * 2048, 2048);
      if (CH_TPF && s >= NSEG - 7) {
        const int i = s - (NSEG - 7);
        if (i < 2) prefetch_l2(p.wb + (cta * 2 + i) * 12800, 12800);
        else if (i < 4) prefetch_l2(xs + (cta * 2 + i - 2) * 8192, 8192);
        else prefetch_l2(g_q + 15 * 32 * 3072 + (cta * 2 + i - 4) * 512, 8192);
      }
      send_memory(s, sb + CH_KS);
    }
    __syncwarp();
    if (t4 == 1) {
      const uint32_t late = min(ldg_strong32(p.sync + SY_TIME + s) - g0, 640u);
      if (elect()) sts32(sb + CH_TAB + 380, c0 + span + (late * 115 >> 6) + (j ? 60 : 0) + p.d1);
    }
    bar_sync(NB_W2, 128);
    uint32_t due = lds32(sb + CH_TAB + 380);
    due = __shfl_sync(~0u, due, 0);
    const uint8_t* ms = pool + (lds32(sb + CH_TAB + (80 + st * 4 + t4) * 4) + (l8 & 255));
    uint8_t* md = pool + (mdst + (cta >= 80 ? 2 : t4 < 2 ? st : st == 2 ? 0 : st + 1) * 32768);
    asm volatile("" : "+l"(ms), "+l"(md));
    if (CH_TW) mbar_wait(sb + MB_T, ~s & 1);
    TM(2);
    bar_sync(NB_ST, 384);
    __syncwarp();
    uint32_t tg = clk32();
    if (t4 == 3 && elect()) {
      if (s < NSEG - 2) mbar_expect(sb + MB_V, 8192);
      mbar_arrive_remote(mapa(sb + MB_F, j == 2 ? 0 : j + 1));
      mbar_arrive_remote(mapa(sb + MB_F, j == 0 ? 2 : j - 1));
    }
    if (s == NSEG - 2) work_init(sb, t4);
    __syncwarp();
    STAT(2);
    {
      float2 q[4];
      TM(3);
      if (t4 == 1 && s) span = min(span, tg - c0);
      until(s < 2 ? tg + 400 : (int)(due - tg) > p.dn ? due : tg + p.dn);
      for (int n = 0;;) {
        uint32_t v[8];
#pragma unroll
        for (int i = 0; i < 8; i++) v[i] = ldg_strong32(psrc + i * 128);
        sts64f(l8 + CH_R2, ((bf_lo(v[0]) + bf_lo(v[1])) + (bf_lo(v[2]) + bf_lo(v[3]))) + ((bf_lo(v[4]) + bf_lo(v[5])) + (bf_lo(v[6]) + bf_lo(v[7]))),
               ((bf_hi(v[0]) + bf_hi(v[1])) + (bf_hi(v[2]) + bf_hi(v[3]))) + ((bf_hi(v[4]) + bf_hi(v[5])) + (bf_hi(v[6]) + bf_hi(v[7]))));
        uint32_t bad;
        asm volatile("{.reg .pred p, q; .reg .b32 a; lop3.b32 a, %1, %2, %3, 0xFE; lop3.b32 a, a, %4, %6, 0xA8; setp.ne.u32 p, a, 0;\n"
                     "bar.red.or.pred q, %5, 128, p; selp.u32 %0, 1, 0, q;}"
                     : "=r"(bad) : "r"(differ(v[0], v[1], tag)), "r"(differ(v[2], v[3], tag)), "r"(differ(v[4], v[5], tag)), "r"(differ(v[6], v[7], tag)), "n"((int)NB_W2),
                       "r"((uint32_t)(cta < 80 || n < 3)) : "memory");
#pragma unroll
        for (int k = 0; k < 4; k++) asm volatile("ld.volatile.shared.v2.f32 {%0,%1}, [%2];" : "=f"(q[k].x), "=f"(q[k].y) : "r"(l8 - t4 * 256 + CH_R2 + k * 256) : "memory");
        TMV(12, n);
        if (!(H1VOTE ? __any_sync(~0u, bad) : bad)) break;
        spin_guard(n);
      }
      bar_arrive(NB_PUB, 384);
      SCHED();
      TM(9);
      stg_strong32(md, min(nz(pack2((q[0].x + q[1].x) + (q[2].x + q[3].x), (q[0].y + q[1].y) + (q[2].y + q[3].y))), t4 < 2 ? ~0u : 0u));
      tg = clk64() + p.d2;
      if (s >= 2 && (int)(due + p.dx - tg) > 0) tg = due + p.dx;
      TM(8);
    }
    STAT(3);
    until(tg);
    TM(10);
    for (int n = 0;;) {
      uint2 g[10];
#pragma unroll
      for (int i = 0; i < 10; i++) g[i] = ldg_strong64(ms + i * 256);
      if (n == 0) bar_sync(NB_XFREE, 256);
      uint32_t m = ~0u, bad;
#pragma unroll
      for (int i = 0; i < 10; i++) { sts64(l8 + CH_M + t4 * 2304 + i * 256, g[i].x, g[i].y); m = __vimin3_u32(m, g[i].x, g[i].y); }
      TMV(13, n);
      TM(11);
      asm volatile("{.reg .pred p; setp.eq.u32 p, %1, 0; vote.sync.any.pred p, p, 0xffffffff; @!p bar.sync %2, 384; selp.u32 %0, 1, 0, p;}" : "=r"(bad) : "r"(m), "n"((int)NB_MEM) : "memory");
      if (!bad) break;
      spin_guard(n);
    }
    if (++st == 3) st = 0;
    tag ^= 0x10001;
  }
  if (t4 == 0) {
    if (elect()) { fence_async(); send_tokens(NSEG - 1); }
    __syncwarp();
    bar_sync(NB_PRE2, 288);
    if (elect()) {
      send_memory(NSEG - 1, sb + CH_M);
      asm volatile("mbarrier.arrive.shared::cta.b64 _, [%0], 8;" :: "r"(sb + WK_BAR + 64) : "memory");
    }
    __syncwarp();
  }
}

__device__ __forceinline__ void chain_start(const ChainParams& p, const uint32_t sb, const int warp) {
  if (warp == 1 && elect()) {
#pragma unroll
    for (int i = 0; i < 6; i++) mbar_init(sb + CH_BAR + 8 * i, i == 2 ? 5 : i == 5 ? 2 : 1);
    asm volatile("fence.mbarrier_init.release.cluster;" ::: "memory");
    mbar_expect(sb + MB_V, 8192);
    atomicAdd(p.sync + SY_UP, 1);
    asm volatile("{.reg .pred p; setp.ne.u32 p, %0, 1024; @p trap;}" :: "r"(sb & 0xffffff));
  }
  if (warp == 0 && elect()) {
#pragma unroll
    for (int i = 0; i < 8; i++) mbar_init(sb + MB_W + 8 * i, 1);
    asm volatile("fence.mbarrier_init.release.cluster;" ::: "memory");
  }
  __syncthreads();
  asm volatile("barrier.cluster.arrive.relaxed.aligned;" ::: "memory");
}

struct WorkParams {
  ChainParams ch;
  CUtensorMap wo, xn, wb[3], wq, wc[2], out;
  const __nv_bfloat16* x;
  uint32_t* sync;
  int kind, qa_end, pace, idle;
};
#define GO_320 4
#define GO_TAIL 1
#define PF_NS 400
enum { WK_FIRST = 0, WK_LEAD = 1, WK_CHAIN = 2, WK_LAST = 3 };
enum { IT_ATT = 0, IT_OP = 1, IT_FIN = 2, IT_BQ = 3, IT_BO = 4, IT_LN = 5, IT_Q = 6, IT_LN0 = 7, IT_OUT = 8 };
constexpr int C_EARLY = 1 << 20, C_LATE = 1 << 21, C_TAIL = 1 << 22, C_PROJ = 1 << 23;

__device__ __forceinline__ uint32_t item_count(int type, int b) { return type == IT_ATT ? 32 : type == IT_OP ? op_tiles(b) * op_split(b) : type == IT_FIN ? fin_items(b) : bq_items(b); }
__device__ __forceinline__ uint32_t item_need(int type, int b) { return type == IT_ATT ? 96 : item_count(type - 1, b); }
__device__ __forceinline__ int item_cols(int type, int b) {
  return type == IT_ATT || type == IT_Q ? 192 : type == IT_OUT ? 80 : type == IT_BQ ? (b < BQ_12 ? 320 : b < BQ_24 ? 160 : 80) : type == IT_OP ? 640 >> op_shift(b) : 320; }
__device__ __forceinline__ int item_groups(int type, int b) { const int n = type == IT_FIN ? fin_items(b) : ln_items(type == IT_LN, b); return n == 4 ? 4 : n == 8 ? 2 : 1; }
#define RES_OP 0
#define RES_B 6
#define HOLD_B 10
constexpr int RES_N = RES_OP ? op_tiles(14) * op_split(14) : 0, RES_BQ = RES_B;
__device__ __forceinline__ bool reserved(int type, int b) { return type == IT_ATT ? b == 15 : type == IT_OP ? RES_OP && b == 14 : type == IT_BQ && b < RES_BQ; }
__device__ __forceinline__ int reserved_item(int cta) {
  const int h = cta / 3, j = cta - 3 * h, i = h + (j - 1) * 32;
  if (j == 0) return C_EARLY | IT_ATT << 16 | 15 << 8 | h;
  return i < RES_N ? C_TAIL | IT_OP << 16 | 14 << 8 | i : i - RES_N < RES_BQ * 6 ? C_TAIL | IT_BQ << 16 | ((i - RES_N) / 6) << 8 | (i - RES_N) % 6 : -1;
}
constexpr int LEAD1 = 12;
__device__ __forceinline__ int lead_item(int layer, int qa_end, int i) {
  if (layer == 2) return i < 128 ? C_EARLY | C_LATE | IT_OUT << 16 | (i >> 3) << 8 | (i & 7) : -1;
  if (layer == 0) {
    if (i < 32) return IT_LN0 << 16 | (i >> 4) << 8 | (i & 15);
    if (i < 88) return IT_LN0 << 16 | ((i - 24) >> 2) << 8 | (i & 3);
    i -= 88;
  } else {
    if (i < 4) return C_EARLY | IT_BO << 16 | (i >> 1) << 8 | (i & 1);
    if (i < 12) return C_EARLY | IT_LN << 16 | ((i - 4) >> 2) << 8 | (i & 3);
    if (i < 40) return C_EARLY | IT_BO << 16 | ((i - 8) >> 1) << 8 | (i & 1);
    if (i < 96) return C_EARLY | IT_LN << 16 | ((i - 32) >> 2) << 8 | (i & 3);
    i -= 96;
  }
  return i < (16 - qa_end) * 32 ? C_PROJ | IT_Q << 16 | (qa_end + (i >> 5)) << 8 | (i & 31) : -1;
}

struct Ring {
  uint32_t sb;
  int pos, seq;
  __device__ __forceinline__ uint32_t full() const { return sb + WK_BAR + 8 * (seq & 7); }
  __device__ __forceinline__ uint32_t take(int len) { if (pos + len > WK_SLOTS) pos = 0; pos += len; seq++; return sb + (pos - len) * 8192; }
  __device__ __forceinline__ uint32_t wait(int len) { mbar_wait(full(), (seq >> 3) & 1); return take(len); }
  __device__ __forceinline__ void release(int sq) const { mbar_arrive_one(sb + WK_BAR + 64 + 8 * (sq & 7)); }
};

struct Pending {
  uint32_t w[48], done;
  uint4* dst;
  __device__ __forceinline__ void store(int i) const { dst[(i >> 2) * 1024 + (i & 3) * 32] = make_uint4(w[4 * i], w[4 * i + 1], w[4 * i + 2], w[4 * i + 3]); }
  __device__ __forceinline__ void finish() { __syncwarp(); mbar_arrive_one(done); done = 0; }
};

template <int N>
__device__ __forceinline__ void gemm_step(float* d, Ring& r, int warp, int acc) {
  const uint32_t base = r.wait(2 + (N + 63) / 64);
  const uint64_t da = mkdesc(base + (warp >> 2) * 8192, 128, 1024, 0), db = mkdesc(base + 16384, 8192, 1024, 1);
  wg_fence();
#pragma unroll
  for (int kk = 0; kk < 4; kk++) {
    if (N == 80) wg_ss80_01(d, da + kk * 16, db + kk * 128, acc | kk);
    else if (N == 160) wg_ss160_01(d, da + kk * 16, db + kk * 128, acc | kk);
    else wg_ss192_01(d, da + kk * 16, db + kk * 128, acc | kk);
    if (N == 320) wg_ss128_01(d + 96, da + kk * 16, db + kk * 128 + 3 * 512, acc | kk);
  }
  wg_commit();
}
template <int N>
__device__ __forceinline__ void gemm_item(float* d, Ring& r, int warp, int nkb, uint32_t go, int ask) {
#pragma unroll 1
  for (int kb = 0; kb < nkb; kb++) {
    gemm_step<N>(d, r, warp, kb);
    if (kb == ask && go && warp == 0) mbar_arrive_one(go);
    if (kb > 0) { wg_wait<1>(); r.release(r.seq - 2); }
  }
  wg_wait<0>();
  r.release(r.seq - 1);
}

template <class Peek>
__device__ __forceinline__ void attn_a(Ring& r, Pending& pend, Peek peek, const int warp, const int lane) {
  uint32_t (&q)[48] = pend.w;
  const int t = (warp & 1) * 16 + (lane >> 2) - 2 * (lane & 3);
  const bool second = warp & 2;
  const uint32_t rows = (warp >> 2) * 2 * KV_SEG;
  uint32_t pa[20], b2;
  float inv[2];
  bool now;
  const uint32_t b0 = r.wait(5) + rows, b1 = r.wait(5) + rows;
  {
    float s[40];
    wg_fence();
#pragma unroll
    for (int k = 0; k < 12; k++)
      wg_rs80_01(s, q[4 * k], q[4 * k + 1], q[4 * k + 2], q[4 * k + 3], mkdesc(k < 8 ? b0 : b1, 128, 1024, 0) + (k >> 2 & 1) * (KV_PART / 16) + (k & 3) * 16, k);
    wg_commit();
    now = peek();
    b2 = r.wait(5) + rows;
    wg_wait<0>();
    reg_fence<40>(s);
    r.release(r.seq - 3);
    const float k2 = 0.07216878364870322f * 1.44269504089f, NEG = -INFINITY;
#pragma unroll
    for (int i = 0; i < 20; i++) {
      s[i] = second ? s[20 + i] : s[i];
      if (i < 16 && 8 * ((i >> 2) - (i >> 1 & 1)) + (i & 1) > t) s[i] = NEG;
    }
#pragma unroll
    for (int hh = 0; hh < 2; hh++) {
      float m = NEG, l = 0.f;
#pragma unroll
      for (int n = 0; n < 5; n++) m = fmaxf(m, fmaxf(s[4 * n + 2 * hh], s[4 * n + 2 * hh + 1]));
      m = fmaxf(m, __shfl_xor_sync(~0u, m, 1)); m = fmaxf(m, __shfl_xor_sync(~0u, m, 2));
      m *= -k2;
#pragma unroll
      for (int n = 0; n < 5; n++) {
        const float x = ex2(fmaf(s[4 * n + 2 * hh], k2, m)), y = ex2(fmaf(s[4 * n + 2 * hh + 1], k2, m));
        const uint32_t w = pack2(x, y);
        l += x + y;
        pa[2 * n + hh] = second ? 0 : w; pa[10 + 2 * n + hh] = second ? w : 0;
      }
      inv[hh] = l;
    }
  }
  float o[96];
  wg_fence();
#pragma unroll
  for (int u = 0; u < 3; u++) {
#pragma unroll
    for (int k = 0; k < 5; k++)
      wg_rs64_00(o + 32 * u, pa[4 * k], pa[4 * k + 1], pa[4 * k + 2], pa[4 * k + 3], mkdesc(u ? b2 : b1, 1024, 128, 0) + (~u & 1) * (KV_PART / 16) + k * 128, k);
    wg_commit();
  }
#pragma unroll
  for (int hh = 0; hh < 2; hh++) { float l = inv[hh]; l += __shfl_xor_sync(~0u, l, 1); l += __shfl_xor_sync(~0u, l, 2); inv[hh] = rcp(l); }
#pragma unroll
  for (int u = 0; u < 3; u++) {
    if (u == 0) wg_wait<2>(); else if (u == 1) wg_wait<1>(); else wg_wait<0>();
    reg_fence<32>(o + 32 * u);
    if (u != 1) r.release(r.seq - 2 + u / 2);
#pragma unroll
    for (int i = 0; i < 16; i++) { const float* x = &o[32 * u + 4 * (i & 7) + (i >> 2 & 2)]; q[16 * u + i] = pack2(x[0] * inv[i >> 3], x[1] * inv[i >> 3]); }
    if (now) {
#pragma unroll
      for (int i = 0; i < 4; i++) pend.store(4 * u + i);
    }
  }
}

__device__ __forceinline__ void ln_groups(Ring& ring, uint32_t scratch, int planes, int rg, bool two) {
  constexpr int G = 2;
  const int warp = fresh_tid() >> 5, lane = fresh_tid() & 31;
  const uint32_t id = (lane >> 3) == (lane & 3) ? ((lane & 4) ? 0x3f800000u : 0x00003f80u) : 0u;
  const uint32_t at = (warp * 160 + lane) * 8, at1 = planes > 1 ? at : (lane >> 2) * 1280 + warp * 160 + (lane & 3) * 4;
  const uint32_t step = planes > 1 ? 256 : 32, half = planes > 1 ? 4 : 16;
  float v[G][5][4] = {};
#pragma unroll
  for (int r = 0; r < G; r++) {
#pragma unroll 1
    for (int k = r && !two ? 0 : planes; k > 0; k -= 4) {
      const uint32_t a = ring.wait(min(k, 4) + 1);
      if (k == 1) {
#pragma unroll
        for (int i = 0; i < 5; i++) mma8(v[r][i], lds32(a + at1 + i * step), lds32(a + at1 + i * step + half), id);
      } else {
#pragma unroll
        for (int i = 0; i < 10; i++) {
          if (i == 5 && k < 4) break;
          const uint2 x = lds64(a + at + i / 5 * 20480 + i % 5 * 256), y = lds64(a + at + i / 5 * 20480 + 10240 + i % 5 * 256);
          mma16(v[r][i % 5], x.x, x.y, y.x, y.y, id, id);
        }
      }
      ring.release(ring.seq - 1);
    }
  }
  uint2 xr[G][5];
  float mw[G];
  scratch += (lane >> 2) * 64;
#pragma unroll
  for (int r = 0; r < G; r++) {
    float m = 0.f, q2[4] = {};
#pragma unroll
    for (int i = 0; i < 5; i++) {
      float* t = v[r][i];
      xr[r][i] = make_uint2(pack2(t[0], t[1]), pack2(t[2], t[3]));
      t[0] = bf_lo(xr[r][i].x); t[1] = bf_hi(xr[r][i].x); t[2] = bf_lo(xr[r][i].y); t[3] = bf_hi(xr[r][i].y);
      m += (t[0] + t[1]) + (t[2] + t[3]);
    }
    m += __shfl_xor_sync(~0u, m, 1); m += __shfl_xor_sync(~0u, m, 2);
    m *= 1.f / 80;
#pragma unroll
    for (int i = 0; i < 20; i++) { float& t = v[r][i >> 2][i & 3]; t -= m; q2[i & 3] = fmaf(t, t, q2[i & 3]); }
    float q = (q2[0] + q2[1]) + (q2[2] + q2[3]);
    mw[r] = m;
    q += __shfl_xor_sync(~0u, q, 1); q += __shfl_xor_sync(~0u, q, 2);
    if ((lane & 3) == 0) sts64f(scratch + r * 512 + warp * 8, m, q);
  }
  bar_sync(1, 256);
#pragma unroll
  for (int r = 0; r < G; r++) {
    const float4 t = lds128f(scratch + r * 512 + (lane & 3) * 16);
    float mean = t.x + t.z;
    mean += __shfl_xor_sync(~0u, mean, 1); mean += __shfl_xor_sync(~0u, mean, 2);
    mean *= 0.125f;
    float var = (t.y + t.w) + 80.f * ((t.x - mean) * (t.x - mean) + (t.z - mean) * (t.z - mean));
    var += __shfl_xor_sync(~0u, var, 1); var += __shfl_xor_sync(~0u, var, 2);
    float rs;
    asm("rsqrt.approx.ftz.f32 %0, %1;" : "=f"(rs) : "f"(var * (1.f / DM) + 1e-5f));
#pragma unroll
    for (int i = 0; i < 20; i++) v[r][i >> 2][i & 3] = fmaf(v[r][i >> 2][i & 3], rs, (mw[r] - mean) * rs);
  }
#pragma unroll
  for (int r = 0; r < G; r++) {
    if (r && !two) break;
    uint32_t* xn = g_xn + (rg + r) * 2560 + warp * 320 + lane;
#pragma unroll
    for (int i = 0; i < 10; i++) xn[i * 32] = pack2(v[r][i >> 1][2 * (i & 1)], v[r][i >> 1][2 * (i & 1) + 1]);
#pragma unroll
    for (int i = 0; i < 5; i++) g_x[(rg + r) * 17 * 1280 + warp * 160 + i * 32 + lane] = xr[r][i];
  }
}

__device__ __forceinline__ void store_partial(const float* d, int b, int split, int unit, int nu) {
  uint2* dst = g_x + (((b * 16 + (fresh_tid() >> 5) * 2) * 17 + 1 + split) * 40 + unit) * 32 + (fresh_tid() & 31);
#pragma unroll
  for (int u = 0; u < 20; u++) {
    if ((u == 5 || u == 10) && nu == u) break;
    dst[u * 32] = make_uint2(pack2(d[8 * u], d[8 * u + 1]), pack2(d[8 * u + 4], d[8 * u + 5]));
    dst[(680 + u) * 32] = make_uint2(pack2(d[8 * u + 2], d[8 * u + 3]), pack2(d[8 * u + 6], d[8 * u + 7]));
  }
}

__device__ __forceinline__ void store_bqkv(const float* d, int b, int idx, int nh) {
  const int lane = fresh_tid() & 31, c = lane & 3, rg = b * 16 + (fresh_tid() >> 5) * 2, h0 = idx * nh;
  const float sc = h0 < 32 ? 0.22360679775f * 1.44269504089f : 1.f;
  const bool lo = c < 2;
  uint32_t* da = g_bqkv + (h0 * 256 + rg) * 96 + lane;
  uint32_t* db = da + 256 * 96 + (lo ? 2 : -2);
  uint32_t pad[2];
#pragma unroll
  for (int r = 0; r < 2; r++) pad[r] = !(c & 1) && (h0 >= 64 || (h0 >= 32 && (lane & 4) && poly_group(rg + r))) ? 0x00003f80u : 0u;
#pragma unroll
  for (int q = 0; q < 8; q++) {
    if ((q == 2 || q == 4) && nh == 2 * q) break;
#pragma unroll
    for (int r = 0; r < 2; r++) {
      uint32_t w[5];
#pragma unroll
      for (int i = 0; i < 5; i++) w[i] = pack2(d[20 * q + 4 * i + 2 * r] * sc, d[20 * q + 4 * i + 2 * r + 1] * sc);
      const int o = q * 2 * 256 * 96 + r * 96;
      da[o] = w[0]; da[o + 32] = w[1]; da[o + 64] = lo ? w[2] : pad[r];
      db[o] = lo ? w[3] : w[2]; db[o + 32] = lo ? w[4] : w[3]; db[o + 64] = lo ? pad[r] : w[4];
    }
  }
}

__device__ __forceinline__ void work_loader(const WorkParams& p, const uint32_t sb, const bool weights) {
  const uint32_t bars = sb + WK_BAR, bIF = bars + 128, bIE = bars + 160, bGo = bars + 224, slots = bars + 272;
  int pos = 0, seq = 0, tail = 0, used = 0;
  uint32_t lens = 0, tn = clk64();
  if (p.kind == WK_CHAIN) {
    seq = 1; used = lens = 8;
    mbar_arrive_one(bars);
  }
#pragma unroll 1
  for (int n = 0, part = 0;;) {
    if (part == 0) mbar_wait(bIF + 8 * (n & 3), (n >> 2) & 1);
    const int code = __shfl_sync(~0u, (int)lds32(slots + 4 * (n & 3)), 0);
    if (code < 0) break;
    const int type = (code >> 16) & 15, b = (code >> 8) & 255, idx = code & 255;
    const bool qa = code & C_PROJ, ln = type == IT_FIN || type == IT_LN || type == IT_LN0;
    const int parts = ln ? item_groups(type, b) : type == IT_ATT ? 2 : 1;
    {
      int bytes = 163840, chunk = 40960, nb = 0, flag = b * 8 + 4 + type, need = item_need(type & 3, b), c0 = 0, c3 = idx, c4 = 0, s3 = 0, s4 = 64;
      const uint8_t* src = g_kv + (b * 32 + idx) * 6 * KV_PART;
      const CUtensorMap* m = nullptr;
      if (ln) {
        const int rg = b * 16 + idx * parts + part;
        bytes = (type == IT_FIN ? op_split(b) + 1 : type == IT_LN ? 2 : 1) * 10240;
        src = type == IT_LN0 ? reinterpret_cast<const uint8_t*>(p.x) + rg * 10240 : reinterpret_cast<const uint8_t*>(g_x) + rg * 174080;
        if (type == IT_LN) { flag = SY_P + b * 4; need = 2; }
        if (type == IT_LN0 || part) need = 0;
      } else if (part) {
        bytes = 6 * KV_PART;
      } else if (type == IT_ATT && !qa) {
        bytes = chunk = 49152;
        src = reinterpret_cast<const uint8_t*>(g_q) + (b * 32 + idx) * 49152;
        flag = SY_P + b * 4 + 3; need = 32;
      } else {
        const int cols = item_cols(type, b);
        chunk = 16384; nb = (cols + 63) >> 6;
        src = reinterpret_cast<const uint8_t*>(g_of) + b * 163840;
        if (type == IT_OP) {
          const int nkb = op_steps(b), kb0 = (idx >> op_shift(b)) * nkb;
          bytes = nkb * 16384;
          src = reinterpret_cast<const uint8_t*>(g_o) + (b * 96 + kb0) * 16384;
          if (weights) m = &p.wo;
          c0 = (idx & (op_tiles(b) - 1)) * cols; c3 = 0; c4 = kb0 * 2; s4 = 2;
        } else if (type == IT_BQ) {
          m = weights ? &p.wb[cols >> 7] : &p.xn;
        } else if (type == IT_BO || type == IT_OUT) {
          if (weights) m = &p.wc[cols >> 8];
          flag = SY_OB; need = type == IT_BO && b < 2 ? 32 : -1;
        } else {
          m = weights ? &p.wq : &p.xn;
          c3 = 0; c4 = idx * 3; s3 = 64; s4 = 0;
          flag = SY_P + b * 4 + 1; need = ln_items(p.ch.layer, b);
        }
      }
      if (!weights) {
        c3 = b * 16; c4 = s3 = s4 = 0;
        if (need < 0) pdl_wait(); else if (need) { wait_count(p.sync + flag, need); EV(code, 2); }
        if ((ln ? !part : part && (!qa || (code & C_EARLY)))) mbar_arrive_one(bGo);
      }
      if (++part == parts) { mbar_arrive_one(bIE + 8 * (n & 3)); part = 0; n++; }
      const int pace = code & C_TAIL ? 0 : p.pace;
      const int boxes = weights && !s3 ? nb : m != nullptr;
#pragma unroll 1
      for (; bytes > 0; bytes -= chunk) {
        const int now = min(bytes, chunk), len = ((now + 8191) >> 13) + nb, skip = pos + len > WK_SLOTS ? WK_SLOTS - pos : 0, sh = 4 * (seq & 7);
        used += len + skip;
        while (used > WK_SLOTS || seq - tail >= 8) {
          mbar_wait(bars + 64 + 8 * (tail & 7), (tail >> 3) & 1);
          used -= (lens >> 4 * (tail & 7)) & 15;
          tail++;
        }
        lens = (lens & ~(15u << sh)) | (len + skip) << sh;
        if (pos + len > WK_SLOTS) pos = 0;
        const uint32_t bar = bars + 2 * sh, dst = sb + pos * 8192 + weights * 16384;
        if (pace) { until(tn); tn = clk64() + len * pace; }
        mbar_expect_one(bar, weights ? nb * 8192 : now);
#pragma unroll 1
        for (int i = 0; i < boxes; i++)
          tma_load5_one(dst + i * 8192, m, c0 + i * 64, c3, c4, bar);
        if (!weights && !m) bulk_load_last_one(dst, src, now, bar);
        c3 += s3; c4 += s4;
        if (!weights) c0 += 128;
        src += chunk; pos += len; seq++;
      }
    }
  }
}

__global__ void __launch_bounds__(384, 1) work_kernel(const __grid_constant__ WorkParams p) {
  extern __shared__ __align__(1024) uint8_t smem_raw[];
  const uint32_t sb = s2u(smem_raw), bars = sb + WK_BAR;
  const uint32_t bIF = bars + 128, bIE = bars + 160, done = bars + 192, bGo = bars + 224, slots = bars + 272, scratch = bars + 384;
  const int warp = __shfl_sync(~0u, threadIdx.x >> 5, 0);
  uint32_t* const sync = p.sync;
  TRACE(0);
  pdl_launch();
  if (p.kind == WK_LEAD && !helper_sm() && __any_sync(~0u, __syncthreads_or(threadIdx.x == 0 && ldg_strong32(sync + SY_PRE + 1) >= LEAD1))) { pdl_wait(); return; }
  if (p.kind == WK_CHAIN) {
    chain_start(p.ch, sb, warp);
  } else {
    if (warp < 4) work_init(sb, warp);
    __syncthreads();
    if (p.kind == WK_FIRST) {
      if (!(warp & 13)) probe_slots(bars + 320);
      if (!helper_sm()) return;
    }
  }
  if (warp >= 8) {
    asm volatile("setmaxnreg.dec.sync.aligned.u32 40;");
    if (p.kind == WK_CHAIN) chain_comm(p.ch, sb, &p.wo);
    const int warp = __shfl_sync(~0u, fresh_tid() >> 5, 0), lane = fresh_tid() & 31;
    if (warp == 9) {
      const bool keep = p.kind > WK_LEAD || helper_sm();
      int n = 0, code = p.kind == WK_CHAIN ? reserved_item(blockIdx.x) : -1;
      if (code >= 0) {
        sts32(slots, code);
        mbar_arrive_one(bIF);
        n = 1;
      }
      const int b = lane & 15, layer = p.kind == WK_LAST ? 2 : sync != g_sync;
      bool first = layer == 1, lead = p.kind != WK_CHAIN;
      for (;; n++) {
        if (n > 0) mbar_wait(bGo, (n - 1) & 1);
        mbar_wait(bIE + 8 * (n & 3), ((n >> 2) & 1) ^ 1);
        code = -1;
        if (lead) {
          int i = blockIdx.x + n * 256;
          if (first) { i = __reduce_add_sync(~0u, atomic_inc_one(sync + SY_PRE + 1)); first = i < LEAD1; }
          if (layer < 2 && !first) {
            i = 1 << 20;
            if (keep) i = __reduce_add_sync(~0u, atomic_inc_one(sync + SY_PRE)) + layer * LEAD1; else pdl_wait();
          }
          code = lead_item(layer, p.qa_end, i);
          lead = code >= 0 || layer == 2 || !keep;
          if (!lead && p.kind <= WK_LEAD) {
            const uint32_t t0 = gtime();
            while (!lead && __all_sync(~0u, ldg_strong32(sync + SY_UP) < 96)) lead = __any_sync(~0u, gtime() - t0 > 20000);
          }
        }
        if (!lead) {
          int spin = 0;
          const int ticket = atomic_inc_one(sync + SY_T);
          for (;;) {
            const uint4 hd = ldg_strong128(sync + b * 8), pr = ldg_strong128(sync + b * 8 + 4);
            const uint32_t hv[4] = {hd.x, hd.y, hd.z, hd.w}, pv[4] = {pr.x, pr.y, pr.z, pr.w};
            const uint32_t chain_done = __ballot_sync(~0u, (pr.x & 0xffff) >= 96) | (p.kind == WK_CHAIN) << 15;
            int left[4], avail[4], rdy = 0, claimed = 0, upstream = 0;
#pragma unroll
            for (int t = 0; t < 4; t++) {
              const int cnt = lane < 16 && !reserved(t, b) ? item_count(t, b) : 0;
              left[t] = max(cnt - (int)hv[t], 0);
              claimed += cnt - left[t];
              const bool ready = (pv[t] & 0xffff) >= item_need(t, b);
              rdy |= ready << t;
              bool ok = ready || (t != IT_ATT && (chain_done >> 15 & 1) && !left[t - 1] && (t < 2 || !left[t - 2]));
              if (t == IT_BQ && (chain_done >> HOLD_B & 1) && !(chain_done >> 15 & 1)) ok = false;
              avail[t] = ok ? left[t] : 0;
              upstream |= __any_sync(~0u, left[t] > 0);
            }
            if (!upstream) { code = -1; break; }
            int rank = max(__reduce_add_sync(~0u, ticket - claimed), 0), type = -1, mine = 0;
#pragma unroll
            for (int c = 0; c < 7; c++) {
              const int t = c == 0 || c == 6 ? IT_ATT : c == 1 || c == 4 ? IT_FIN : c == 2 ? IT_OP : IT_BQ;
              int a = c == 2 || (rdy >> t & 1) == (c < 4) ? avail[t] : 0;
              if (c == 6) a = b < p.qa_end && !(rdy & 1) && ((chain_done << 1 | 1) >> b & 1) ? left[t] : 0;
              const int tot = __reduce_add_sync(~0u, a);
              if (type < 0) { if (rank < tot) { type = t; mine = a; } else rank -= tot; }
            }
            if (type >= 0) {
#pragma unroll
              for (int o = 1; o < 16; o <<= 1) { const int y = __shfl_up_sync(~0u, mine, o); if (lane >= o) mine += y; }
              const int blk = __ffs(__ballot_sync(~0u, mine > rank)) - 1;
              const int early = !(__shfl_sync(~0u, rdy, blk) >> type & 1);
              const uint32_t idx = __reduce_add_sync(~0u, atomic_inc_one(sync + blk * 8 + type));
              if (idx < item_count(type, blk)) { code = (type == IT_ATT && blk < p.qa_end) << 23 | (chain_done >> 14 & 1) << 22 | early << 20 | type << 16 | blk << 8 | idx; break; }
            } else {
              __nanosleep(50);
            }
            spin_guard(spin);
          }
        }
        sts32(slots + 4 * (n & 3), code);
        mbar_arrive_one(bIF + 8 * (n & 3));
        if (code < 0) break;
      }
    } else if (warp >= 10) {
      work_loader(p, sb, warp == 10);
    } else {
      for (int n = 0;; n++) {
        mbar_wait(bIF + 8 * (n & 3), (n >> 2) & 1);
        const int code = __shfl_sync(~0u, (int)lds32(slots + 4 * (n & 3)), 0);
        if (code < 0) break;
        const int type = (code >> 16) & 15, b = (code >> 8) & 255;
        mbar_wait(done + 8 * (n & 3), (n >> 2) & 1);
        const uint32_t t_done = gtime();
        if (elect()) {
          if (type != IT_OUT) red_release(sync + (type < IT_BQ ? b * 8 + 5 + type : SY_P + b * 4 + ((0x13102 >> 4 * (type - IT_BQ)) & 3)), 1);
          mbar_arrive(bIE + 8 * (n & 3));
          EV(code, 1);
        }
        __syncwarp();
      }
    }
  } else {
    asm volatile("setmaxnreg.inc.sync.aligned.u32 232;");
    if (p.kind == WK_CHAIN) chain_compute(p.ch, sb);
    const int warp = __shfl_sync(~0u, fresh_tid() >> 5, 0), lane = fresh_tid() & 31;
    Ring r{sb, 0, p.kind == WK_CHAIN};
    int nln = 0;
#pragma unroll 1
    for (int n = 0;; n++) {
      mbar_wait(bIF + 8 * (n & 3), (n >> 2) & 1);
      int code = __shfl_sync(~0u, (int)lds32(slots + 4 * (n & 3)), 0);
      if (code < 0) { TRACE(2); break; }
      if (((code >> 16) & 15) == IT_ATT || (code & C_PROJ)) {
        Pending pend = {};
#pragma unroll 1
        for (;; n++) {
          const int tile = (((code >> 8) & 255) * 32 + (code & 255)) * 3072 + warp * 128;
          int next = 0;
          auto peek = [&]() {
            uint32_t here;
            asm volatile("{.reg .pred p; mbarrier.test_wait.parity.shared::cta.b64 p, [%1], %2; selp.u32 %0, -1, 0, p;}" : "=r"(here) : "r"(bIF + 8 * ((n + 1) & 3)), "r"(((n + 1) >> 2) & 1) : "memory");
            next = __shfl_sync(~0u, (int)(lds32(slots + 4 * ((n + 1) & 3) + (here & p.ch.zero)) & here), 0);
            return next < C_PROJ;
          };
          ITEM(code & 0xfffff, 0);
          if (code & C_PROJ) {
            float d[96];
            ITEM(9 << 16 | (code & 0xffff), 0);
            gemm_step<192>(d, r, warp, 0);
#pragma unroll 1
            for (int kb = 1; kb < 10; kb++) {
              gemm_step<192>(d, r, warp, 1);
              if (kb == 4 && (code & (C_EARLY | 15 << 16)) != C_EARLY && warp == 0) mbar_arrive_one(bGo);
              if (pend.done) {
#pragma unroll
                for (int i = 0; i < 12; i++) if (kb == 1 + i / 2) pend.store(i);
                if (kb == 6) pend.finish();
              }
              wg_wait<1>();
              r.release(r.seq - 2);
            }
            wg_wait<0>();
            reg_fence<96>(d);
            r.release(r.seq - 1);
            ITEM(9 << 16 | (code & 0xffff), 1);
#pragma unroll
            for (int i = 0; i < 48; i++) pend.w[i] = pack2(d[2 * i], d[2 * i + 1]);
          } else {
            const uint32_t base = r.wait(6) + warp * 2048 + lane * 16;
#pragma unroll
            for (int i = 0; i < 12; i++) {
              const uint4 t = lds128(base + (i >> 2) * 16384 + (i & 3) * 512);
              pend.w[4 * i] = t.x; pend.w[4 * i + 1] = t.y; pend.w[4 * i + 2] = t.z; pend.w[4 * i + 3] = t.w;
            }
            __syncwarp();
            r.release(r.seq - 1);
          }
          if (code & 15 << 16) {
            pend.dst = g_q + tile + lane;
            if (peek()) {
#pragma unroll
              for (int i = 0; i < 12; i++) pend.store(i);
            }
          } else {
            pend.dst = g_o + tile + (lane & 3) * 8 + (lane >> 2);
            attn_a(r, pend, peek, warp, lane);
          }
          pend.done = done + 8 * (n & 3);
          ITEM(code & 0xfffff, 1);
          if (next < C_PROJ) break;
          code = next;
        }
        pend.finish();
      } else {
        const int type = (code >> 16) & 15, b = (code >> 8) & 255, idx = code & 255;
        const uint32_t go = code & C_LATE ? 0 : bGo;
        ITEM(code & 0xfffff, 0);
        if (type == IT_FIN || type == IT_LN || type == IT_LN0) {
          const int ng = item_groups(type, b);
          const int planes = type == IT_FIN ? op_split(b) + 1 : type == IT_LN ? 2 : 1;
#pragma unroll 1
          for (int i = 0; i < ng; i += 2) ln_groups(r, scratch + (nln++ & 1) * 1024, planes, b * 16 + idx * ng + i, ng > 1);
        } else {
          const int cols = item_cols(type, b), nkb = type == IT_OP ? op_steps(b) : 10;
          float d[160] = {};
          if (type == IT_OUT) {
            const uint2* x = g_x + ((b * 16 + warp * 2) * 680 + idx * 5) * 32 + lane;
#pragma unroll
            for (int i = 0; i < 10; i++) { const uint2 y = __ldcg(x + (i / 5 * 680 + i % 5) * 32); d[40 + 2 * i] = __uint_as_float(y.x); d[41 + 2 * i] = __uint_as_float(y.y); }
          }
          reg_fence<160>(d);
          if (type != IT_OUT) ITEM((type == IT_BQ ? 10 : 11) << 16 | (code & 0xffff), 0);
          const int ask = max(nkb - ((code & C_TAIL ? GO_TAIL : GO_320) << (2 - (cols >> 7))), 0);
          if (cols == 320) gemm_item<320>(d, r, warp, nkb, go, ask);
          else if (cols == 160) gemm_item<160>(d, r, warp, nkb, go, ask);
          else gemm_item<80>(d, r, warp, nkb, go, ask);
          if (type != IT_OUT) ITEM((type == IT_BQ ? 10 : 11) << 16 | (code & 0xffff), 1);
          reg_fence<160>(d);
          if (type == IT_OUT) {
            bar_sync(1, 256);
            const uint32_t dst = sb + (warp * 16 + (lane & 15)) * 160 + (lane >> 4) * 16;
#pragma unroll
            for (int u = 0; u < 5; u++) {
              uint32_t w[4];
#pragma unroll
              for (int i = 0; i < 4; i++) { const uint32_t y = __float_as_uint(d[40 + (i & 1) * 10 + 2 * u + (i >> 1)]); w[i] = pack2(bf_lo(y) + d[8 * u + 2 * i], bf_hi(y) + d[8 * u + 2 * i + 1]); }
              stsm4(dst + u * 32, w[0], w[1], w[2], w[3]);
            }
            fence_async();
            __syncwarp();
            if (elect()) { tma_store(&p.out, sb + warp * 2560, idx * 80, b * 128 + warp * 16); bulk_commit(); bulk_wait<0>(); }
          } else {
            if (warp >= 4) bar_sync(7, 256);
            if (type == IT_BQ) store_bqkv(d, b, idx, 4 << (cols >> 7));
            else { const int sh = 3 - (cols >> 7); store_partial(d, b, idx >> sh, (idx & ((1 << sh) - 1)) * (cols >> 4), cols >> 4); }
            if (warp < 4) bar_arrive(7, 256);
          }
        }
        __syncwarp();
        mbar_arrive_one(done + 8 * (n & 3));
        if ((code & C_LATE) && warp == 4) mbar_arrive_one(bGo);
        ITEM(code & 0xfffff, 1);
      }
    }
  }
}

constexpr int AB_SMEM = 1024 + 2 * 98304 + 256 + 5 * 6144;
#define AB_N 32
constexpr int AB_T = 512;
#define AB_NS 4300
__device__ __forceinline__ float ex2_poly(float t) {
  const uint32_t r = __float_as_uint(t) & 0xffff8000u;
  const float f = t - __uint_as_float(r);
  const float p = fmaf(fmaf(fmaf(-5.869912678e-38f, f, -1.700740250e-37f), f, -5.234869734e-37f), f, -7.522601252e-37f);
  uint32_t y;
  asm("mad.lo.u32 %0, %1, 256, %2;" : "=r"(y) : "r"(r), "r"(__float_as_uint(p)));
  return __uint_as_float(y);
}
__device__ __forceinline__ uint32_t hsq(uint32_t w, uint32_t c) { uint32_t r; asm("fma.rn.bf16x2 %0, %1, %1, %2;" : "=r"(r) : "r"(w), "r"(c)); return r; }
__device__ __forceinline__ float sq2(uint32_t w) { const float a = bf_lo(w), b = bf_hi(w); return fmaf(a, a, b * b); }

__device__ __forceinline__ void attn_b_store(const float* o, int h, int row0, int lane) {
  const int g = lane >> 2, c = lane & 3;
  const float i0 = rcp(__shfl_sync(~0u, o[8], (lane & ~3) | 2)), i1 = rcp(__shfl_sync(~0u, o[10], (lane & ~3) | 2));
#pragma unroll
  for (int jj = 0; jj < 3; jj++) {
    if (jj < 2 || c < 2) {
      const int col = h * 20 + 8 * jj + 2 * c;
      g_of[core_word(row0 + g, col)] = pack2(o[4 * jj] * i0, o[4 * jj + 1] * i0);
      g_of[core_word(row0 + g + 8, col)] = pack2(o[4 * jj + 2] * i1, o[4 * jj + 3] * i1);
    }
  }
}

__device__ __forceinline__ void attn_b_qk(float* s, uint32_t q0, uint32_t q1, uint32_t q2, uint32_t q3, uint32_t q4, uint32_t q5, uint32_t z0, uint32_t z1,
                                          uint64_t dk, uint64_t dk2) {
  wg_rs32_00(s, q0, q1, q2, q3, dk, 0);
  wg_rs32_00(s, q4, q5, z0, z1, dk2, 1);
}

struct AttnParams { const uint8_t* pf[4]; uint32_t *sync, *next; };
__global__ void __launch_bounds__(AB_T + 128, 1) attn_b_kernel(const __grid_constant__ AttnParams p) {
  extern __shared__ uint8_t smem_raw[];
  const uint32_t sb = (s2u(smem_raw) + 1023) & ~1023u, sK = sb, sV = sb + 98304, bars = sb + 2 * 98304;
  const int warp = __shfl_sync(~0u, threadIdx.x >> 5, 0), lane = threadIdx.x & 31;
  const int h = blockIdx.x & 31, quarter = blockIdx.x >> 5;
  BT(0);
  TRACE(0);
  if (warp < 10 && elect()) {
    mbar_init(bars + 8 * warp + (warp & 8) * 8, warp < 8 ? 1 : warp == 8 ? AB_T / 32 : 3);
    asm volatile("fence.mbarrier_init.release.cluster;" ::: "memory");
  }
  __syncthreads();
  if (warp >= AB_T / 32) {
    asm volatile("setmaxnreg.dec.sync.aligned.u32 32;");
    if (warp == AB_T / 32 + 1) {
      mbar_wait(bars + 8 * quarter, 0);
      uint32_t t = gtime();
#pragma unroll 1
      for (int i = 0; i < 8; i++) {
        mbar_wait(bars + 8 * i, 0);
        const uint32_t now = gtime();
        t = ((int)(now - t) > 0 ? now : t) + AB_NS / 2;
      }
      uint32_t* ends = p.sync + SY_B + h * 4;
      if (lane == 0) stg_strong32(ends + quarter, t | 1);
      for (int spin = 0; t = ldg_strong32(ends + (lane & 3)), !__all_sync(~0u, t);) spin_guard(spin);
      int e = (int)(t - __shfl_sync(~0u, t, 0)) * 4 + (lane & 3), n = 0;
#pragma unroll 1
      for (int i = 0; i < 16; i++)
        if (e == __reduce_min_sync(~0u, e)) { e += 4 * AB_NS; n++; }
      const int first = 16 + __reduce_add_sync(~0u, lane < quarter ? n : 0);
      if (lane == quarter) { sts64(bars + 72, first, n); mbar_arrive(bars + 136); }
      return;
    }
    if (warp > AB_T / 32) {
      uint32_t kmax = 0;
#pragma unroll 1
      for (int i = 0; i < 32; i++) {
        if (!(i & 3)) mbar_wait(bars + 2 * i, 0);
        const uint32_t a = sK + i * 3072 + ((threadIdx.x >> 3) & 7) * 384 + (lane & 7) * 16;
        const uint4 x = lds128(a), y = lds128(a + 128);
        const uint2 z = lds64(a + 256);
        const uint32_t n = hadd2(hsq(x.x, hsq(x.y, hsq(x.z, hsq(x.w, hsq(z.x, 0))))), hsq(y.x, hsq(y.y, hsq(y.z, hsq(y.w, hsq(z.y, 0))))));
        kmax = max(kmax, __float_as_uint(bf_lo(n) + bf_hi(n)) & 0x7fffffffu);
      }
      const uint32_t kbits = __reduce_max_sync(~0u, kmax);
      if (lane == 0) { sts32(bars + 64 + (warp & 1) * 4, kbits); mbar_arrive(bars + 136); }
      return;
    }
    const uint8_t* gk = reinterpret_cast<const uint8_t*>(g_bqkv + (32 + h) * 256 * 96);
    const uint8_t* gv = reinterpret_cast<const uint8_t*>(g_bqkv + (64 + h) * 256 * 96);
    uint32_t todo = 255;
    for (int spin = 0; todo;) {
      const uint32_t up = __ballot_sync(~0u, ld_acquire(p.sync + SY_P + (lane & 15) * 4 + 2) >= bq_items(lane & 15));
      fence_async_global();
#pragma unroll 1
      for (int i = 0; i < 8; i++) {
        if (!(todo >> i & 1) || (up >> 2 * i & 3) != 3) continue;
        todo &= ~(1u << i);
        if (elect()) {
          mbar_expect(bars + 8 * i, 24576);
          bulk_load(sK + i * 12288, gk + i * 12288, 12288, bars + 8 * i);
          bulk_load(sV + i * 12288, gv + i * 12288, 12288, bars + 8 * i);
        }
      }
      spin_guard(spin);
    }
    pdl_launch();
    TRACE(1);
#pragma unroll 1
    for (int i = lane; i < 512 && blockIdx.x < NSLOT; i += 32) reinterpret_cast<uint4*>(pool_at(blockIdx.x * 8192))[i] = make_uint4(0, 0, 0, 0);
    if (!p.next && blockIdx.x < 8) { const int i = blockIdx.x * 32 + lane; g_smpart[i] = 0; if (i < NSLOT) g_orient[i] = 0; }
    if (p.next) {
#pragma unroll 1
      for (int i = 0; i < (PF_NS ? 32 : 0); i++) {
        if (elect()) prefetch_l2(p.pf[i >> 3] + blockIdx.x * 61440 + (i & 7) * 7680, 7680);
        __nanosleep(PF_NS);
      }
      mbar_wait(bars + 128, 0);
      if (quarter == 0 && lane == 0) red_release(p.next + SY_OB, 1);
    }
    return;
  }
  asm volatile("setmaxnreg.inc.sync.aligned.u32 112;");
  constexpr int NT = SEQ / AB_N, PER = 256 / AB_N;
  uint32_t qn[8];
  const int wg = warp >> 2;
  int tile = quarter * 4, left = 4, share = 0;
  auto load_q = [&]() {
    const uint32_t* gq = g_bqkv + (h * 256 + (tile + (wg >> share)) * 8 + (warp & 3) * 2) * 96 + lane;
#pragma unroll
    for (int i = 0; i < 8; i++) qn[i] = __ldcg(gq + (i & 1) * 96 + min(i >> 1, 2) * 32 + (i < 6 ? 0 : 3 - (lane & 3)));
  };
  mbar_wait(bars + 8 * quarter, 0);
  load_q();
#pragma unroll 1
  for (int pass = 0; left; pass++) {
    const int row0 = (tile + (wg >> share)) * 64 + (warp & 3) * 16, part = wg & ((1 << share) - 1), k0 = part * NT >> share, k1 = k0 + (NT >> share), group = share;
    const uint32_t q0 = qn[0], q1 = qn[1], q2 = qn[2], q3 = qn[3], z0 = qn[6], z1 = qn[7];
    uint32_t q4 = qn[4], q5 = qn[5];
    if ((lane & 3) == 2) { q4 = 0x43BCu; q5 = 0x43BCu; }
    float o[12] = {};
    reg_fence<12>(o);
    uint64_t dk = mkdesc(sK, 128, 384, 0), dk2 = mkdesc(sK + 256, 0, 384, 0), dv = mkdesc(sV, 384, 128, 0) + k0 * (AB_N * 3);
    float sa[AB_N / 2], sb2[AB_N / 2];
    uint32_t pa[AB_N / 4], pb[AB_N / 4];
    if (pass == 0) mbar_wait(bars, 0);
    BT(1 + 2 * min(pass, 1));
    wg_fence();
    attn_b_qk(sa, q0, q1, q2, q3, q4, q5, z0, z1, dk + k0 * (AB_N * 3), dk2 + k0 * (AB_N * 3));
    wg_commit();
    attn_b_qk(sb2, q0, q1, q2, q3, q4, q5, z0, z1, dk + (k0 + 1) * (AB_N * 3), dk2 + (k0 + 1) * (AB_N * 3));
    wg_commit();
    int kt = k0;
#pragma unroll 1
    do {
      const int nx = kt + 2 < NT ? kt + 2 : 0;
      if (pass == 0 && (nx & (PER - 1)) == 0) mbar_wait(bars + 8 * (nx / PER), 0);
      const uint64_t nk = dk + nx * (AB_N * 3), nk2 = dk2 + nx * (AB_N * 3);
      wg_wait<1>();
      reg_fence<AB_N / 2>(sa);
#pragma unroll
      for (int i = 0; i < AB_N / 4; i++) pa[i] = pack2(ex2(sa[2 * i]), poly_group(i >> 1) ? ex2_poly(sa[2 * i + 1]) : ex2(sa[2 * i + 1]));
      wg_fence();
#pragma unroll
      for (int kk = 0; kk < AB_N / 16; kk++) wg_rs24_01(o, pa[4 * kk], pa[4 * kk + 1], pa[4 * kk + 2], pa[4 * kk + 3], dv + kk * 48, 1);
      attn_b_qk(sa, q0, q1, q2, q3, q4, q5, z0, z1, nk, nk2);
      wg_commit();
      wg_wait<1>();
      reg_fence<AB_N / 2>(sb2);
#pragma unroll
      for (int i = 0; i < AB_N / 4; i++) pb[i] = pack2(ex2(sb2[2 * i]), poly_group((i >> 1) + AB_N / 8) ? ex2_poly(sb2[2 * i + 1]) : ex2(sb2[2 * i + 1]));
      wg_fence();
#pragma unroll
      for (int kk = 0; kk < AB_N / 16; kk++) wg_rs24_01(o, pb[4 * kk], pb[4 * kk + 1], pb[4 * kk + 2], pb[4 * kk + 3], dv + AB_N * 3 + kk * 48, 1);
      attn_b_qk(sb2, q0, q1, q2, q3, q4, q5, z0, z1, nk + AB_N * 3, nk2 + AB_N * 3);
      wg_commit();
      dv += AB_N * 6;
    } while ((kt += 2) < k1);
    wg_wait<0>();
    reg_fence<12>(o); reg_fence<AB_N / 2>(sa); reg_fence<AB_N / 2>(sb2);
    BT(2 + 2 * min(pass, 1));
    mbar_wait(bars + 136, 0);
    const uint4 kb = lds128(bars + 64);
    const float kmax = __uint_as_float(max(kb.x, kb.y));
    tile += 4 >> share; left -= 4 >> share;
    if (pass == 0) { tile = __shfl_sync(~0u, kb.z, 0); left = __shfl_sync(~0u, kb.w, 0); }
    share = left >= 4 ? 0 : left >= 2 ? 1 : 2;
    if (left) load_q();
    if (group) {
      const uint32_t slot = bars + 256 + (threadIdx.x & 127) * 16 + (group == 1 ? wg >> 1 : 2) * 6144;
      if (part) {
#pragma unroll
        for (int i = 0; i < 3; i++) sts128f(slot + (part - 1) * 6144 + i * 2048, o[4 * i], o[4 * i + 1], o[4 * i + 2], o[4 * i + 3]);
        bar_arrive(4 + group * 2 + (wg >> group), 128 << group);
        continue;
      }
      bar_sync(4 + group * 2 + (wg >> group), 128 << group);
#pragma unroll 1
      for (int u = 0; u < 2 * group - 1; u++) {
#pragma unroll
        for (int i = 0; i < 3; i++) { const float4 x = lds128f(slot + u * 6144 + i * 2048); o[4 * i] += x.x; o[4 * i + 1] += x.y; o[4 * i + 2] += x.z; o[4 * i + 3] += x.w; }
      }
    }
    if ((lane & 3) == 2) q4 = q5 = 0;
    float n0 = sq2(q0) + sq2(q2) + sq2(q4), n1 = sq2(q1) + sq2(q3) + sq2(q5);
    n0 += __shfl_xor_sync(~0u, n0, 1); n1 += __shfl_xor_sync(~0u, n1, 1);
    n0 += __shfl_xor_sync(~0u, n0, 2); n1 += __shfl_xor_sync(~0u, n1, 2);
    uint32_t redo;
    asm volatile("{.reg .pred p, q; setp.ne.u32 p, %1, 0; bar.red.or.pred q, %2, 128, p; selp.u32 %0, 1, 0, q;}"
                 : "=r"(redo) : "r"((uint32_t)!(n0 * kmax <= 9500.f && n1 * kmax <= 9500.f)), "r"(2 + (warp >> 2)) : "memory");
    if (redo) {
#pragma unroll
      for (int i = 0; i < 12; i++) o[i] = 0.f;
      float m0 = -INFINITY, m1 = -INFINITY;
#pragma unroll 1
      for (int kt = 0; kt < 64; kt++) {
        float s[16];
        wg_fence();
        wg_rs32_00(s, q0, q1, q2, q3, dk + kt * 96, 0);
        wg_rs32_00(s, q4, q5, z0, z1, dk2 + kt * 96, 1);
        wg_commit();
        wg_wait<0>();
        reg_fence<16>(s); reg_fence<12>(o);
        float n0 = m0, n1 = m1;
#pragma unroll
        for (int jj = 0; jj < 4; jj++) { n0 = fmaxf(n0, fmaxf(s[4 * jj], s[4 * jj + 1])); n1 = fmaxf(n1, fmaxf(s[4 * jj + 2], s[4 * jj + 3])); }
        n0 = fmaxf(n0, __shfl_xor_sync(~0u, n0, 1)); n0 = fmaxf(n0, __shfl_xor_sync(~0u, n0, 2));
        n1 = fmaxf(n1, __shfl_xor_sync(~0u, n1, 1)); n1 = fmaxf(n1, __shfl_xor_sync(~0u, n1, 2));
        const float r0 = ex2(m0 - n0), r1 = ex2(m1 - n1);
        m0 = n0; m1 = n1;
#pragma unroll
        for (int jj = 0; jj < 3; jj++) { o[4 * jj] *= r0; o[4 * jj + 1] *= r0; o[4 * jj + 2] *= r1; o[4 * jj + 3] *= r1; }
        uint32_t pp[8];
#pragma unroll
        for (int jj = 0; jj < 4; jj++) {
          pp[2 * jj] = pack2(ex2(s[4 * jj] - m0), ex2(s[4 * jj + 1] - m0));
          pp[2 * jj + 1] = pack2(ex2(s[4 * jj + 2] - m1), ex2(s[4 * jj + 3] - m1));
        }
        reg_fence<12>(o);
        wg_fence();
#pragma unroll
        for (int kk = 0; kk < 2; kk++) wg_rs24_01(o, pp[4 * kk], pp[4 * kk + 1], pp[4 * kk + 2], pp[4 * kk + 3], mkdesc(sV, 384, 128, 0) + kt * 96 + kk * 48, 1);
        wg_commit();
      }
      wg_wait<0>();
      reg_fence<12>(o);
    }
    attn_b_store(o, h, row0, lane);
    __syncwarp();
    if (pass == 0) mbar_arrive_one(bars + 128);
  }
  BT(5);
  TRACE(2);
}

typedef CUresult (*EncodeFn)(CUtensorMap*, CUtensorMapDataType, cuuint32_t, void*, const cuuint64_t*, const cuuint64_t*,
                             const cuuint32_t*, const cuuint32_t*, CUtensorMapInterleave, CUtensorMapSwizzle,
                             CUtensorMapL2promotion, CUtensorMapFloatOOBfill);

void make_map(EncodeFn enc, CUtensorMap* m, const void* ptr, int cols, int rows, int box_rows, int box_cols = 64) {
  const cuuint64_t dims[2] = {(cuuint64_t)cols, (cuuint64_t)rows};
  const cuuint64_t strides[1] = {(cuuint64_t)cols * 2};
  const cuuint32_t box[2] = {(cuuint32_t)box_cols, (cuuint32_t)box_rows}, es[2] = {1, 1};
  enc(m, CU_TENSOR_MAP_DATA_TYPE_BFLOAT16, 2, const_cast<void*>(ptr), dims, strides, box, es, CU_TENSOR_MAP_INTERLEAVE_NONE,
      box_cols == 64 ? CU_TENSOR_MAP_SWIZZLE_128B : box_cols == 32 ? CU_TENSOR_MAP_SWIZZLE_64B : CU_TENSOR_MAP_SWIZZLE_NONE, CU_TENSOR_MAP_L2_PROMOTION_L2_256B, CU_TENSOR_MAP_FLOAT_OOB_FILL_NONE);
}
void make_map5(EncodeFn enc, CUtensorMap* m, const void* ptr, bool words, const cuuint64_t (&dims)[5], const cuuint64_t (&strides)[4], const cuuint32_t (&box)[5]) {
  const cuuint32_t es[5] = {1, 1, 1, 1, 1};
  enc(m, words ? CU_TENSOR_MAP_DATA_TYPE_UINT64 : CU_TENSOR_MAP_DATA_TYPE_BFLOAT16, 5, const_cast<void*>(ptr), dims, strides, box, es, CU_TENSOR_MAP_INTERLEAVE_NONE,
      words ? CU_TENSOR_MAP_SWIZZLE_NONE : CU_TENSOR_MAP_SWIZZLE_128B, dims[0] % 64 ? CU_TENSOR_MAP_L2_PROMOTION_L2_128B : CU_TENSOR_MAP_L2_PROMOTION_L2_256B,
      CU_TENSOR_MAP_FLOAT_OOB_FILL_NONE);
}
void make_tiles(EncodeFn enc, CUtensorMap* m, const void* ptr, cuuint64_t cols, cuuint64_t tile) {
  make_map5(enc, m, ptr, false, {tile, 1, 1, cols / tile, DM}, {tile * 2, tile * 2, tile * 2, cols * 2}, {64, 1, 1, 1, 64});
}
template <class... KA, class... A>
void launch(void (*kern)(KA...), int grid, int block, int smem, int cluster, bool pdl, A... args) {
  cudaFuncSetAttribute(kern, cudaFuncAttributeMaxDynamicSharedMemorySize, smem);
  cudaLaunchConfig_t cfg = {};
  cfg.gridDim = dim3(grid); cfg.blockDim = dim3(block); cfg.dynamicSmemBytes = smem; cfg.stream = cudaStreamPerThread;
  cudaLaunchAttribute at[2];
  int n = 0;
  if (cluster > 1) { at[n].id = cudaLaunchAttributeClusterDimension; at[n].val.clusterDim.x = cluster; at[n].val.clusterDim.y = 1; at[n].val.clusterDim.z = 1; n++; }
  if (pdl) { at[n].id = cudaLaunchAttributeProgrammaticStreamSerialization; at[n].val.programmaticStreamSerializationAllowed = 1; n++; }
  cfg.attrs = at; cfg.numAttrs = n;
  cudaLaunchKernelEx(&cfg, kern, args...);
}
template <class T> void* sym(T& s) { void* p = nullptr; cudaGetSymbolAddress(&p, s); return p; }

}

#define MODE(b) 0
extern "C" void kernel_launch(void* const* d_in, const int* in_sizes, int n_in, void* d_out, int out_size) {
  const __nv_bfloat16* x = (const __nv_bfloat16*)d_in[0];
  void* fn = nullptr; cudaDriverEntryPointQueryResult qr;
  cudaGetDriverEntryPoint("cuTensorMapEncodeTiled", &fn, cudaEnableDefault, &qr);
  EncodeFn enc = (EncodeFn)fn;

  WorkParams wk = {};
  ChainParams& ch = wk.ch;
  AttnParams at = {};
  make_map(enc, &ch.wq, d_in[2], HD, DM, 160); make_map(enc, &ch.wk, d_in[3], HD, DM, 160); make_map(enc, &ch.wv, d_in[4], HD, DM, 160);
  make_map(enc, &ch.wo, d_in[5], DM, HD, 192, 32);
  ch.mem0 = (const __nv_bfloat16*)d_in[1];
  ch.wb = (const uint8_t*)d_in[8];
  ch.d1 = 250; ch.d2 = 200; ch.dn = 150; ch.dx = 950;
  make_map5(enc, &wk.wq, d_in[2], false, {64, 1, 1, DM, HD / 64}, {128, 128, HD * 2, 128}, {64, 1, 1, 64, 3});
  for (int i = 0; i < 3; i++) make_tiles(enc, &wk.wb[i], d_in[8], 1920, 80 << i);
  for (int i = 0; i < 2; i++) make_tiles(enc, &wk.wc[i], d_in[9], DM, 80 << 2 * i);
  make_map(enc, &wk.out, d_out, DM, SEQ, 16, 80);
  make_map5(enc, &wk.wo, d_in[5], false, {DM, 2, 4, 4, HD / 32}, {DM * 2, DM * 16, DM * 4, DM * 64}, {64, 2, 4, 4, 2});
  make_map5(enc, &wk.xn, sym(g_xn), true, {1280, 1, 1, 256, 1}, {10240, 10240, 10240, 10240}, {128, 1, 1, 16, 1});
  make_map5(enc, &ch.xc, sym(g_xn), true, {160, 1, 1, 256, 8}, {1280, 1280, 10240, 1280}, {160, 1, 1, 4, 2});
  wk.x = x;
  for (int i = 0; i < 4; i++) at.pf[i] = (const uint8_t*)d_in[i < 2 ? 3 + i : i == 2 ? 2 : 5];
  int qa_end[2] = {12, 12}, pace = 85;
  for (int layer = 0; layer < 2; layer++) {
    ch.sync = wk.sync = at.sync = (uint32_t*)sym(g_sync) + layer * SY_N;
    ch.other = (uint32_t*)sym(g_sync) + (1 - layer) * SY_N;
    ch.layer = layer;
    at.next = layer ? nullptr : ch.other;
    wk.qa_end = qa_end[layer];
    wk.kind = layer ? WK_LEAD : WK_FIRST; wk.pace = pace;
    launch(work_kernel, 132, 384, CH_SMEM, 1, layer != 0, wk);
    wk.kind = WK_CHAIN; wk.pace = 0;
    launch(work_kernel, 96, 384, CH_SMEM, 3, true, wk);
    launch(attn_b_kernel, 128, AB_T + 128, AB_SMEM, 1, true, at);
  }
  wk.kind = WK_LAST;
  launch(work_kernel, 128, 384, CH_SMEM, 1, true, wk);
}
```

```cpp
#include <cuda_runtime.h>
#include <cuda_bf16.h>
#include <cuda.h>
#include <stdint.h>
#include <stdlib.h>

namespace {

constexpr int SEQ = 2048, DM = 640, HD = 6144, NSEG = 64;
constexpr int SPIN_LIMIT = 1 << 20;

__device__ __align__(128) uint2 g_x[256 * 17 * 1280];
__device__ __align__(128) uint32_t g_xn[SEQ * DM / 2];
__device__ __align__(128) uint32_t g_of[SEQ * DM / 2];
__device__ __align__(128) uint4 g_o[SEQ * HD / 8];
__device__ __align__(128) uint4 g_q[SEQ * HD / 8];
constexpr int KV_M = 4096, KV_SEG = 5120, KV_PART = 20480, KV_V = 3 * KV_PART;
__device__ __align__(128) uint8_t g_kv[16 * 32 * 6 * KV_PART];
#define OP_B8 11
#define OP_B16 13
#define OP_N4 14
#define BQ_12 13
#define BQ_24 16
#define FIN_16 12
#define OP_N8 16
#define OP_E16 14
__host__ __device__ constexpr int op_shift(int b) { return b < OP_N4 ? 1 : b < OP_N8 ? 2 : 3; }
__host__ __device__ constexpr int op_tiles(int b) { return 1 << op_shift(b); }
__host__ __device__ constexpr int op_split(int b) { return b < OP_B8 ? 4 : b < OP_B16 || b >= OP_E16 ? 8 : 16; }
__host__ __device__ constexpr int op_steps(int b) { return b < OP_B8 ? 24 : b < OP_B16 || b >= OP_E16 ? 12 : 6; }
__host__ __device__ constexpr int fin_items(int b) { return b < OP_B8 ? 4 : b < FIN_16 ? 8 : 16; }
__host__ __device__ constexpr int bq_items(int b) { return b < BQ_12 ? 6 : b < BQ_24 ? 12 : 24; }
__host__ __device__ constexpr int ln_items(int layer, int b) { return layer == 0 && b < 2 ? 16 : 4; }
constexpr int SY_P = 128, SY_T = 192, SY_UP = 224, SY_OB = 225, SY_PRE = 256, SY_PART = 288, SY_TIME = 384, SY_B = 448, SY_N = 576;
__device__ __align__(128) uint32_t g_sync[2 * SY_N];
constexpr int NSLOT = 92;
__device__ uint32_t g_pool[(NSLOT + 2) * 2048];
__device__ uint32_t g_smpart[256], g_orient[NSLOT];
__device__ __align__(128) uint32_t g_bqkv[3 * 32 * 256 * 96];

#define BT(i)
#define MISS(k, n)
#define PRO(i)
#define TRACE(w)
#define EV(code, w)
#define ITEM(code, w)
#define STAT(k)
#define TMV(i, v)
#define TM(i)
#define TMD(i, dep)

__device__ __forceinline__ uint32_t gtime() { uint32_t c; asm volatile("mov.u32 %0, %%globaltimer_lo;" : "=r"(c) :: "memory"); return c; }
__device__ __forceinline__ uint32_t clk32() { uint32_t c; asm volatile("mov.u32 %0, %%clock;" : "=r"(c) :: "memory"); return c; }
__device__ __forceinline__ uint32_t fresh_tid() { uint32_t t; asm volatile("mov.u32 %0, %%tid.x;" : "=r"(t)); return t; }
__device__ __forceinline__ uint32_t s2u(const void* p) { return (uint32_t)__cvta_generic_to_shared(p); }
__device__ __forceinline__ uint32_t pack2(float a, float b) {
  uint32_t r; asm("cvt.rn.bf16x2.f32 %0, %1, %2;" : "=r"(r) : "f"(b), "f"(a)); return r; }
__device__ __forceinline__ float bf_lo(uint32_t w) { return __uint_as_float(w << 16); }
__device__ __forceinline__ float bf_hi(uint32_t w) { return __uint_as_float(w & 0xffff0000u); }
__device__ __forceinline__ float ex2(float x) { float y; asm("ex2.approx.ftz.f32 %0, %1;" : "=f"(y) : "f"(x)); return y; }

__device__ __forceinline__ void mbar_init(uint32_t bar, uint32_t n) {
  asm volatile("mbarrier.init.shared::cta.b64 [%0], %1;" :: "r"(bar), "r"(n) : "memory"); }
__device__ __forceinline__ void mbar_expect(uint32_t bar, uint32_t bytes) {
  asm volatile("mbarrier.arrive.expect_tx.shared::cta.b64 _, [%0], %1;" :: "r"(bar), "r"(bytes) : "memory"); }
__device__ __forceinline__ void mbar_arrive(uint32_t bar) {
  asm volatile("mbarrier.arrive.shared::cta.b64 _, [%0];" :: "r"(bar) : "memory"); }
#define ONE "{.reg .pred one; elect.sync _|one, 0xffffffff; @one "
__device__ __forceinline__ void mbar_arrive_one(uint32_t bar) { asm volatile(ONE "mbarrier.arrive.shared::cta.b64 _, [%0];}" :: "r"(bar) : "memory"); }
__device__ __forceinline__ void mbar_expect_one(uint32_t bar, uint32_t bytes) {
  asm volatile(ONE "mbarrier.arrive.expect_tx.shared::cta.b64 _, [%0], %1;}" :: "r"(bar), "r"(bytes) : "memory"); }
__device__ __forceinline__ uint32_t atomic_inc_one(uint32_t* p) {
  uint32_t v = 0; asm volatile(ONE "atom.relaxed.gpu.global.add.u32 %0, [%1], 1;}" : "+r"(v) : "l"(p) : "memory"); return v; }
__device__ __forceinline__ void mbar_arrive_remote(uint32_t bar) {
  asm volatile("mbarrier.arrive.shared::cluster.b64 _, [%0];" :: "r"(bar) : "memory"); }
__device__ __forceinline__ void mbar_wait(uint32_t bar, uint32_t ph) {
  asm volatile("{.reg .pred p; .reg .u32 n; mov.u32 n, 0;\n"
               "W: mbarrier.try_wait.parity.shared::cta.b64 p, [%0], %1; @p bra.uni D;\n"
               "add.u32 n, n, 1; setp.gt.u32 p, n, %2; @p trap; bra.uni W;\n"
               "D: }" :: "r"(bar), "r"(ph), "n"(SPIN_LIMIT) : "memory");
}
__device__ __forceinline__ bool elect() {
  uint32_t p; asm volatile("{.reg .pred q; elect.sync _|q, 0xffffffff; selp.u32 %0, 1, 0, q;}" : "=r"(p)); return p; }
__device__ __forceinline__ void spin_guard(int& n) {
  asm volatile("{.reg .pred p; add.s32 %0, %0, 1; setp.gt.s32 p, %0, %1; @p trap;}" : "+r"(n) : "n"(SPIN_LIMIT));
}
__device__ __forceinline__ void pdl_wait() { asm volatile("griddepcontrol.wait;" ::: "memory"); TRACE(1); }
__device__ __forceinline__ void pdl_launch() { asm volatile("griddepcontrol.launch_dependents;" ::: "memory"); }
__device__ __forceinline__ uint32_t ld_acquire(const uint32_t* p) { uint32_t v; asm volatile("ld.acquire.gpu.global.u32 %0, [%1];" : "=r"(v) : "l"(p) : "memory"); return v; }
__device__ __forceinline__ void red_release(uint32_t* p, uint32_t v) { asm volatile("red.release.gpu.global.add.u32 [%0], %1;" :: "l"(p), "r"(v) : "memory"); }
__device__ __forceinline__ void fence_async_global() { asm volatile("fence.proxy.async.global;" ::: "memory"); }
__device__ __forceinline__ void fence_async() { asm volatile("fence.proxy.async.shared::cta;" ::: "memory"); }
__device__ __forceinline__ void bar_sync(int id, int n) { asm volatile("bar.sync %0, %1;" :: "r"(id), "r"(n) : "memory"); }
__device__ __forceinline__ void bar_arrive(int id, int n) { asm volatile("bar.arrive %0, %1;" :: "r"(id), "r"(n) : "memory"); }
__device__ __forceinline__ void tma_load(uint32_t dst, const CUtensorMap* m, int c0, int c1, uint32_t bar) {
  asm volatile("cp.async.bulk.tensor.2d.shared::cluster.global.mbarrier::complete_tx::bytes [%0], [%1, {%3, %4}], [%2];"
               :: "r"(dst), "l"(m), "r"(bar), "r"(c0), "r"(c1) : "memory"); }
__device__ __forceinline__ void tma_load5_one(uint32_t dst, const CUtensorMap* m, int c0, int c3, int c4, uint32_t bar) {
  asm volatile(ONE "cp.async.bulk.tensor.5d.shared::cluster.global.mbarrier::complete_tx::bytes [%0], [%1, {%3, %6, %6, %4, %5}], [%2];}"
               :: "r"(dst), "l"(m), "r"(bar), "r"(c0), "r"(c3), "r"(c4), "r"(0) : "memory"); }
__device__ __forceinline__ void tma_store(const CUtensorMap* m, uint32_t src, int c0, int c1) {
  asm volatile("cp.async.bulk.tensor.2d.global.shared::cta.bulk_group [%0, {%2, %3}], [%1];"
               :: "l"(m), "r"(src), "r"(c0), "r"(c1) : "memory"); }
__device__ __forceinline__ uint64_t evict_first() { uint64_t p; asm("createpolicy.fractional.L2::evict_first.b64 %0, 1.0;" : "=l"(p)); return p; }
__device__ __forceinline__ void bulk_load_last_one(uint32_t dst, const void* src, uint32_t bytes, uint32_t bar) {
  asm volatile(ONE "cp.async.bulk.shared::cluster.global.mbarrier::complete_tx::bytes.L2::cache_hint [%0], [%1], %2, [%3], %4;}"
               :: "r"(dst), "l"(src), "r"(bytes), "r"(bar), "l"(evict_first()) : "memory"); }
__device__ __forceinline__ void bulk_store_stream(void* dst, uint32_t src, uint32_t bytes) {
  asm volatile("cp.async.bulk.global.shared::cta.bulk_group.L2::cache_hint [%0], [%1], %2, %3;" :: "l"(dst), "r"(src), "r"(bytes), "l"(evict_first()) : "memory"); }
__device__ __forceinline__ void bulk_load(uint32_t dst, const void* src, uint32_t bytes, uint32_t bar) {
  asm volatile("cp.async.bulk.shared::cluster.global.mbarrier::complete_tx::bytes [%0], [%1], %2, [%3];"
               :: "r"(dst), "l"(src), "r"(bytes), "r"(bar) : "memory"); }
__device__ __forceinline__ void bulk_push(uint32_t dst, uint32_t src, uint32_t bytes, uint32_t bar) {
  asm volatile("cp.async.bulk.shared::cluster.shared::cta.mbarrier::complete_tx::bytes [%0], [%1], %2, [%3];"
               :: "r"(dst), "r"(src), "r"(bytes), "r"(bar) : "memory"); }
__device__ __forceinline__ void bulk_store(void* dst, uint32_t src, uint32_t bytes) {
  asm volatile("cp.async.bulk.global.shared::cta.bulk_group [%0], [%1], %2;" :: "l"(dst), "r"(src), "r"(bytes) : "memory"); }
__device__ __forceinline__ void bulk_commit() { asm volatile("cp.async.bulk.commit_group;" ::: "memory"); }
template <int N> __device__ __forceinline__ void bulk_wait_read() { asm volatile("cp.async.bulk.wait_group.read %0;" :: "n"(N) : "memory"); }
template <int N> __device__ __forceinline__ void bulk_wait() { asm volatile("cp.async.bulk.wait_group %0;" :: "n"(N) : "memory"); }

__device__ __forceinline__ uint64_t mkdesc(uint32_t addr, uint32_t lbo, uint32_t sbo, uint32_t sw) {
  return (uint64_t)((addr & 0x3FFFF) >> 4) | ((uint64_t)(lbo >> 4) << 16) | ((uint64_t)(sbo >> 4) << 32) | ((uint64_t)sw << 62); }
__device__ __forceinline__ void wg_fence() { asm volatile("wgmma.fence.sync.aligned;" ::: "memory"); }
__device__ __forceinline__ void wg_commit() { asm volatile("wgmma.commit_group.sync.aligned;" ::: "memory"); }
template <int N> __device__ __forceinline__ void wg_wait() { asm volatile("wgmma.wait_group.sync.aligned %0;" :: "n"(N) : "memory"); }
template <int N> __device__ __forceinline__ void reg_fence(float* d) {
#pragma unroll
  for (int i = 0; i < N; i++) asm volatile("" : "+f"(d[i]) :: "memory");
}

__device__ __forceinline__ void mma16(float* d, uint32_t a0, uint32_t a1, uint32_t a2, uint32_t a3, uint32_t b0, uint32_t b1) {
  asm volatile("mma.sync.aligned.m16n8k16.row.col.f32.bf16.bf16.f32 {%0,%1,%2,%3},{%4,%5,%6,%7},{%8,%9},{%0,%1,%2,%3};"
               : "+f"(d[0]), "+f"(d[1]), "+f"(d[2]), "+f"(d[3]) : "r"(a0), "r"(a1), "r"(a2), "r"(a3), "r"(b0), "r"(b1)); }
__device__ __forceinline__ void mma8(float* d, uint32_t a0, uint32_t a1, uint32_t b0) {
  asm volatile("mma.sync.aligned.m16n8k8.row.col.f32.bf16.bf16.f32 {%0,%1,%2,%3},{%4,%5},{%6},{%0,%1,%2,%3};"
               : "+f"(d[0]), "+f"(d[1]), "+f"(d[2]), "+f"(d[3]) : "r"(a0), "r"(a1), "r"(b0)); }
__device__ __forceinline__ void ldsm4(uint32_t* r, uint32_t a) {
  asm volatile("ldmatrix.sync.aligned.m8n8.x4.shared.b16 {%0,%1,%2,%3},[%4];" : "=r"(r[0]), "=r"(r[1]), "=r"(r[2]), "=r"(r[3]) : "r"(a) : "memory"); }
__device__ __forceinline__ uint4 ldsm4v(uint32_t a) { uint32_t r[4]; ldsm4(r, a); return make_uint4(r[0], r[1], r[2], r[3]); }
__device__ __forceinline__ void ldsm4t(uint32_t* r, uint32_t a) {
  asm volatile("ldmatrix.sync.aligned.m8n8.x4.trans.shared.b16 {%0,%1,%2,%3},[%4];" : "=r"(r[0]), "=r"(r[1]), "=r"(r[2]), "=r"(r[3]) : "r"(a) : "memory"); }
__device__ __forceinline__ void ldsm2(uint32_t* r, uint32_t a) {
  asm volatile("ldmatrix.sync.aligned.m8n8.x2.shared.b16 {%0,%1},[%2];" : "=r"(r[0]), "=r"(r[1]) : "r"(a) : "memory"); }
__device__ __forceinline__ void ldsm2t(uint32_t* r, uint32_t a) {
  asm volatile("ldmatrix.sync.aligned.m8n8.x2.trans.shared.b16 {%0,%1},[%2];" : "=r"(r[0]), "=r"(r[1]) : "r"(a) : "memory"); }
__device__ __forceinline__ void stsm4(uint32_t a, uint32_t r0, uint32_t r1, uint32_t r2, uint32_t r3) {
  asm volatile("stmatrix.sync.aligned.m8n8.x4.shared.b16 [%0], {%1,%2,%3,%4};" :: "r"(a), "r"(r0), "r"(r1), "r"(r2), "r"(r3) : "memory"); }
__device__ __forceinline__ void stsm4t(uint32_t a, uint32_t r0, uint32_t r1, uint32_t r2, uint32_t r3) {
  asm volatile("stmatrix.sync.aligned.m8n8.x4.trans.shared.b16 [%0], {%1,%2,%3,%4};" :: "r"(a), "r"(r0), "r"(r1), "r"(r2), "r"(r3) : "memory"); }
__device__ __forceinline__ void stsm2(uint32_t a, uint32_t r0, uint32_t r1) {
  asm volatile("stmatrix.sync.aligned.m8n8.x2.shared.b16 [%0], {%1,%2};" :: "r"(a), "r"(r0), "r"(r1) : "memory"); }
__device__ __forceinline__ void stsm2t(uint32_t a, uint32_t r0, uint32_t r1) {
  asm volatile("stmatrix.sync.aligned.m8n8.x2.trans.shared.b16 [%0], {%1,%2};" :: "r"(a), "r"(r0), "r"(r1) : "memory"); }
__device__ __forceinline__ void sts32(uint32_t a, uint32_t v) { asm volatile("st.shared.b32 [%0], %1;" :: "r"(a), "r"(v) : "memory"); }
__device__ __forceinline__ void sts64f(uint32_t a, float x, float y) { asm volatile("st.shared.v2.f32 [%0], {%1,%2};" :: "r"(a), "f"(x), "f"(y) : "memory"); }
__device__ __forceinline__ void sts128(uint32_t a, uint4 v) {
  asm volatile("st.shared.v4.b32 [%0], {%1,%2,%3,%4};" :: "r"(a), "r"(v.x), "r"(v.y), "r"(v.z), "r"(v.w) : "memory"); }
__device__ __forceinline__ void sts128f(uint32_t a, float x, float y, float z, float w) {
  asm volatile("st.shared.v4.f32 [%0], {%1,%2,%3,%4};" :: "r"(a), "f"(x), "f"(y), "f"(z), "f"(w) : "memory"); }
__device__ __forceinline__ float lds32f(uint32_t a) { float v; asm volatile("ld.shared.f32 %0, [%1];" : "=f"(v) : "r"(a) : "memory"); return v; }
__device__ __forceinline__ float2 lds64f(uint32_t a) { float2 v; asm volatile("ld.shared.v2.f32 {%0,%1}, [%2];" : "=f"(v.x), "=f"(v.y) : "r"(a) : "memory"); return v; }
__device__ __forceinline__ float4 lds128f(uint32_t a) {
  float4 v; asm volatile("ld.shared.v4.f32 {%0,%1,%2,%3}, [%4];" : "=f"(v.x), "=f"(v.y), "=f"(v.z), "=f"(v.w) : "r"(a) : "memory"); return v; }
__device__ __forceinline__ uint4 lds128(uint32_t a) {
  uint4 v; asm volatile("ld.shared.v4.b32 {%0,%1,%2,%3}, [%4];" : "=r"(v.x), "=r"(v.y), "=r"(v.z), "=r"(v.w) : "r"(a) : "memory"); return v; }
__device__ __forceinline__ uint4 ldg_strong128(const void* p) {
  uint4 v; asm volatile("ld.relaxed.gpu.global.v4.u32 {%0,%1,%2,%3}, [%4];" : "=r"(v.x), "=r"(v.y), "=r"(v.z), "=r"(v.w) : "l"(p) : "memory"); return v; }
__device__ __forceinline__ uint2 ldg_strong64(const void* p) {
  uint2 v; asm volatile("ld.relaxed.gpu.global.v2.u32 {%0,%1}, [%2];" : "=r"(v.x), "=r"(v.y) : "l"(p) : "memory"); return v; }
__device__ __forceinline__ void stg_strong32(void* p, uint32_t v) { asm volatile("st.relaxed.gpu.global.u32 [%0], %1;" :: "l"(p), "r"(v) : "memory"); }
__device__ __forceinline__ void stg_strong128(void* p, uint4 v) {
  asm volatile("st.relaxed.gpu.global.v4.u32 [%0], {%1,%2,%3,%4};" :: "l"(p), "r"(v.x), "r"(v.y), "r"(v.z), "r"(v.w) : "memory"); }
__device__ __forceinline__ uint32_t mapa(uint32_t a, uint32_t r) {
  uint32_t o; asm("mapa.shared::cluster.u32 %0, %1, %2;" : "=r"(o) : "r"(a), "r"(r)); return o; }
__device__ __forceinline__ void st_async2f(uint32_t a, float x, float y, uint32_t bar) {
  asm volatile("st.async.shared::cluster.mbarrier::complete_tx::bytes.v2.f32 [%0], {%1,%2}, [%3];" :: "r"(a), "f"(x), "f"(y), "r"(bar) : "memory"); }
__device__ __forceinline__ void st_async32(uint32_t a, uint32_t x, uint32_t bar) {
  asm volatile("st.async.shared::cluster.mbarrier::complete_tx::bytes.b32 [%0], %1, [%2];" :: "r"(a), "r"(x), "r"(bar) : "memory"); }
__device__ __forceinline__ uint32_t lds32(uint32_t a) { uint32_t v; asm volatile("ld.shared.b32 %0, [%1];" : "=r"(v) : "r"(a) : "memory"); return v; }
__device__ __forceinline__ void st_async64(uint32_t a, uint32_t x, uint32_t y, uint32_t bar) {
  asm volatile("st.async.shared::cluster.mbarrier::complete_tx::bytes.v2.b32 [%0], {%1,%2}, [%3];" :: "r"(a), "r"(x), "r"(y), "r"(bar) : "memory"); }
__device__ __forceinline__ void st_async128(uint32_t a, uint4 v, uint32_t bar) {
  asm volatile("st.async.shared::cluster.mbarrier::complete_tx::bytes.v4.b32 [%0], {%1,%2,%3,%4}, [%5];" :: "r"(a), "r"(v.x), "r"(v.y), "r"(v.z), "r"(v.w), "r"(bar) : "memory"); }
__device__ __forceinline__ uint2 lds64(uint32_t a) { uint2 v; asm volatile("ld.shared.v2.b32 {%0,%1}, [%2];" : "=r"(v.x), "=r"(v.y) : "r"(a) : "memory"); return v; }
__device__ __forceinline__ void sts64(uint32_t a, uint32_t x, uint32_t y) { asm volatile("st.shared.v2.b32 [%0], {%1,%2};" :: "r"(a), "r"(x), "r"(y) : "memory"); }
__device__ __forceinline__ uint32_t ldg_strong32(const void* p) { uint32_t v; asm volatile("ld.relaxed.gpu.global.u32 %0, [%1];" : "=r"(v) : "l"(p) : "memory"); return v; }
__device__ __forceinline__ uint32_t transpose8(uint32_t x) { uint32_t r; asm volatile("movmatrix.sync.aligned.m8n8.trans.b16 %0, %1;" : "=r"(r) : "r"(x)); return r; }
__device__ __forceinline__ uint32_t hadd2(uint32_t a, uint32_t b) { uint32_t r; asm("add.rn.bf16x2 %0, %1, %2;" : "=r"(r) : "r"(a), "r"(b)); return r; }
__device__ __forceinline__ uint32_t min4(uint4 v) { return min(__vimin3_u32(v.x, v.y, v.z), v.w); }

__device__ __forceinline__ void wg_ss192_01(float* d, uint64_t da, uint64_t db, int sd) {
  asm volatile("{.reg .pred p; setp.ne.b32 p, %98, 0;\n"
    "wgmma.mma_async.sync.aligned.m64n192k16.f32.bf16.bf16 {%0,%1,%2,%3,%4,%5,%6,%7,%8,%9,%10,%11,%12,%13,%14,%15,%16,%17,%18,%19,%20,%21,%22,%23,%24,%25,%26,%27,%28,%29,%30,%31,%32,%33,%34,%35,%36,%37,%38,%39,%40,%41,%42,%43,%44,%45,%46,%47,%48,%49,%50,%51,%52,%53,%54,%55,%56,%57,%58,%59,%60,%61,%62,%63,%64,%65,%66,%67,%68,%69,%70,%71,%72,%73,%74,%75,%76,%77,%78,%79,%80,%81,%82,%83,%84,%85,%86,%87,%88,%89,%90,%91,%92,%93,%94,%95}, %96, %97, p, 1, 1, 0, 1;}"
    : "+f"(d[0]),"+f"(d[1]),"+f"(d[2]),"+f"(d[3]),"+f"(d[4]),"+f"(d[5]),"+f"(d[6]),"+f"(d[7]),"+f"(d[8]),"+f"(d[9]),"+f"(d[10]),"+f"(d[11]),"+f"(d[12]),"+f"(d[13]),"+f"(d[14]),"+f"(d[15]),"+f"(d[16]),"+f"(d[17]),"+f"(d[18]),"+f"(d[19]),"+f"(d[20]),"+f"(d[21]),"+f"(d[22]),"+f"(d[23]),"+f"(d[24]),"+f"(d[25]),"+f"(d[26]),"+f"(d[27]),"+f"(d[28]),"+f"(d[29]),"+f"(d[30]),"+f"(d[31]),"+f"(d[32]),"+f"(d[33]),"+f"(d[34]),"+f"(d[35]),"+f"(d[36]),"+f"(d[37]),"+f"(d[38]),"+f"(d[39]),"+f"(d[40]),"+f"(d[41]),"+f"(d[42]),"+f"(d[43]),"+f"(d[44]),"+f"(d[45]),"+f"(d[46]),"+f"(d[47]),"+f"(d[48]),"+f"(d[49]),"+f"(d[50]),"+f"(d[51]),"+f"(d[52]),"+f"(d[53]),"+f"(d[54]),"+f"(d[55]),"+f"(d[56]),"+f"(d[57]),"+f"(d[58]),"+f"(d[59]),"+f"(d[60]),"+f"(d[61]),"+f"(d[62]),"+f"(d[63]),"+f"(d[64]),"+f"(d[65]),"+f"(d[66]),"+f"(d[67]),"+f"(d[68]),"+f"(d[69]),"+f"(d[70]),"+f"(d[71]),"+f"(d[72]),"+f"(d[73]),"+f"(d[74]),"+f"(d[75]),"+f"(d[76]),"+f"(d[77]),"+f"(d[78]),"+f"(d[79]),"+f"(d[80]),"+f"(d[81]),"+f"(d[82]),"+f"(d[83]),"+f"(d[84]),"+f"(d[85]),"+f"(d[86]),"+f"(d[87]),"+f"(d[88]),"+f"(d[89]),"+f"(d[90]),"+f"(d[91]),"+f"(d[92]),"+f"(d[93]),"+f"(d[94]),"+f"(d[95])
    : "l"(da), "l"(db), "r"(sd));
}
__device__ __forceinline__ void wg_ss128_01(float* d, uint64_t da, uint64_t db, int sd) {
  asm volatile("{.reg .pred p; setp.ne.b32 p, %66, 0;\n"
    "wgmma.mma_async.sync.aligned.m64n128k16.f32.bf16.bf16 {%0,%1,%2,%3,%4,%5,%6,%7,%8,%9,%10,%11,%12,%13,%14,%15,%16,%17,%18,%19,%20,%21,%22,%23,%24,%25,%26,%27,%28,%29,%30,%31,%32,%33,%34,%35,%36,%37,%38,%39,%40,%41,%42,%43,%44,%45,%46,%47,%48,%49,%50,%51,%52,%53,%54,%55,%56,%57,%58,%59,%60,%61,%62,%63}, %64, %65, p, 1, 1, 0, 1;}"
    : "+f"(d[0]),"+f"(d[1]),"+f"(d[2]),"+f"(d[3]),"+f"(d[4]),"+f"(d[5]),"+f"(d[6]),"+f"(d[7]),"+f"(d[8]),"+f"(d[9]),"+f"(d[10]),"+f"(d[11]),"+f"(d[12]),"+f"(d[13]),"+f"(d[14]),"+f"(d[15]),"+f"(d[16]),"+f"(d[17]),"+f"(d[18]),"+f"(d[19]),"+f"(d[20]),"+f"(d[21]),"+f"(d[22]),"+f"(d[23]),"+f"(d[24]),"+f"(d[25]),"+f"(d[26]),"+f"(d[27]),"+f"(d[28]),"+f"(d[29]),"+f"(d[30]),"+f"(d[31]),"+f"(d[32]),"+f"(d[33]),"+f"(d[34]),"+f"(d[35]),"+f"(d[36]),"+f"(d[37]),"+f"(d[38]),"+f"(d[39]),"+f"(d[40]),"+f"(d[41]),"+f"(d[42]),"+f"(d[43]),"+f"(d[44]),"+f"(d[45]),"+f"(d[46]),"+f"(d[47]),"+f"(d[48]),"+f"(d[49]),"+f"(d[50]),"+f"(d[51]),"+f"(d[52]),"+f"(d[53]),"+f"(d[54]),"+f"(d[55]),"+f"(d[56]),"+f"(d[57]),"+f"(d[58]),"+f"(d[59]),"+f"(d[60]),"+f"(d[61]),"+f"(d[62]),"+f"(d[63])
    : "l"(da), "l"(db), "r"(sd));
}
__device__ __forceinline__ void wg_ss160_01(float* d, uint64_t da, uint64_t db, int sd) {
  asm volatile("{.reg .pred p; setp.ne.b32 p, %82, 0;\n"
    "wgmma.mma_async.sync.aligned.m64n160k16.f32.bf16.bf16 {%0,%1,%2,%3,%4,%5,%6,%7,%8,%9,%10,%11,%12,%13,%14,%15,%16,%17,%18,%19,%20,%21,%22,%23,%24,%25,%26,%27,%28,%29,%30,%31,%32,%33,%34,%35,%36,%37,%38,%39,%40,%41,%42,%43,%44,%45,%46,%47,%48,%49,%50,%51,%52,%53,%54,%55,%56,%57,%58,%59,%60,%61,%62,%63,%64,%65,%66,%67,%68,%69,%70,%71,%72,%73,%74,%75,%76,%77,%78,%79}, %80, %81, p, 1, 1, 0, 1;}"
    : "+f"(d[0]),"+f"(d[1]),"+f"(d[2]),"+f"(d[3]),"+f"(d[4]),"+f"(d[5]),"+f"(d[6]),"+f"(d[7]),"+f"(d[8]),"+f"(d[9]),"+f"(d[10]),"+f"(d[11]),"+f"(d[12]),"+f"(d[13]),"+f"(d[14]),"+f"(d[15]),"+f"(d[16]),"+f"(d[17]),"+f"(d[18]),"+f"(d[19]),"+f"(d[20]),"+f"(d[21]),"+f"(d[22]),"+f"(d[23]),"+f"(d[24]),"+f"(d[25]),"+f"(d[26]),"+f"(d[27]),"+f"(d[28]),"+f"(d[29]),"+f"(d[30]),"+f"(d[31]),"+f"(d[32]),"+f"(d[33]),"+f"(d[34]),"+f"(d[35]),"+f"(d[36]),"+f"(d[37]),"+f"(d[38]),"+f"(d[39]),"+f"(d[40]),"+f"(d[41]),"+f"(d[42]),"+f"(d[43]),"+f"(d[44]),"+f"(d[45]),"+f"(d[46]),"+f"(d[47]),"+f"(d[48]),"+f"(d[49]),"+f"(d[50]),"+f"(d[51]),"+f"(d[52]),"+f"(d[53]),"+f"(d[54]),"+f"(d[55]),"+f"(d[56]),"+f"(d[57]),"+f"(d[58]),"+f"(d[59]),"+f"(d[60]),"+f"(d[61]),"+f"(d[62]),"+f"(d[63]),"+f"(d[64]),"+f"(d[65]),"+f"(d[66]),"+f"(d[67]),"+f"(d[68]),"+f"(d[69]),"+f"(d[70]),"+f"(d[71]),"+f"(d[72]),"+f"(d[73]),"+f"(d[74]),"+f"(d[75]),"+f"(d[76]),"+f"(d[77]),"+f"(d[78]),"+f"(d[79])
    : "l"(da), "l"(db), "r"(sd));
}
__device__ __forceinline__ void wg_ss80_01(float* d, uint64_t da, uint64_t db, int sd) {
  asm volatile("{.reg .pred p; setp.ne.b32 p, %42, 0;\n"
    "wgmma.mma_async.sync.aligned.m64n80k16.f32.bf16.bf16 {%0,%1,%2,%3,%4,%5,%6,%7,%8,%9,%10,%11,%12,%13,%14,%15,%16,%17,%18,%19,%20,%21,%22,%23,%24,%25,%26,%27,%28,%29,%30,%31,%32,%33,%34,%35,%36,%37,%38,%39}, %40, %41, p, 1, 1, 0, 1;}"
    : "+f"(d[0]),"+f"(d[1]),"+f"(d[2]),"+f"(d[3]),"+f"(d[4]),"+f"(d[5]),"+f"(d[6]),"+f"(d[7]),"+f"(d[8]),"+f"(d[9]),"+f"(d[10]),"+f"(d[11]),"+f"(d[12]),"+f"(d[13]),"+f"(d[14]),"+f"(d[15]),"+f"(d[16]),"+f"(d[17]),"+f"(d[18]),"+f"(d[19]),"+f"(d[20]),"+f"(d[21]),"+f"(d[22]),"+f"(d[23]),"+f"(d[24]),"+f"(d[25]),"+f"(d[26]),"+f"(d[27]),"+f"(d[28]),"+f"(d[29]),"+f"(d[30]),"+f"(d[31]),"+f"(d[32]),"+f"(d[33]),"+f"(d[34]),"+f"(d[35]),"+f"(d[36]),"+f"(d[37]),"+f"(d[38]),"+f"(d[39])
    : "l"(da), "l"(db), "r"(sd));
}
__device__ __forceinline__ void wg_rs32_00(float* d, uint32_t a0, uint32_t a1, uint32_t a2, uint32_t a3, uint64_t db, int sd) {
  asm volatile("{.reg .pred p; setp.ne.b32 p, %21, 0;\n"
    "wgmma.mma_async.sync.aligned.m64n32k16.f32.bf16.bf16 {%0,%1,%2,%3,%4,%5,%6,%7,%8,%9,%10,%11,%12,%13,%14,%15}, {%16,%17,%18,%19}, %20, p, 1, 1, 0;}"
    : "+f"(d[0]),"+f"(d[1]),"+f"(d[2]),"+f"(d[3]),"+f"(d[4]),"+f"(d[5]),"+f"(d[6]),"+f"(d[7]),"+f"(d[8]),"+f"(d[9]),"+f"(d[10]),"+f"(d[11]),"+f"(d[12]),"+f"(d[13]),"+f"(d[14]),"+f"(d[15])
    : "r"(a0), "r"(a1), "r"(a2), "r"(a3), "l"(db), "r"(sd));
}
__device__ __forceinline__ void wg_rs64_00(float* d, uint32_t a0, uint32_t a1, uint32_t a2, uint32_t a3, uint64_t db, int sd) {
  asm volatile("{.reg .pred p; setp.ne.b32 p, %37, 0;\n"
    "wgmma.mma_async.sync.aligned.m64n64k16.f32.bf16.bf16 {%0,%1,%2,%3,%4,%5,%6,%7,%8,%9,%10,%11,%12,%13,%14,%15,%16,%17,%18,%19,%20,%21,%22,%23,%24,%25,%26,%27,%28,%29,%30,%31}, {%32,%33,%34,%35}, %36, p, 1, 1, 0;}"
    : "+f"(d[0]),"+f"(d[1]),"+f"(d[2]),"+f"(d[3]),"+f"(d[4]),"+f"(d[5]),"+f"(d[6]),"+f"(d[7]),"+f"(d[8]),"+f"(d[9]),"+f"(d[10]),"+f"(d[11]),"+f"(d[12]),"+f"(d[13]),"+f"(d[14]),"+f"(d[15]),"+f"(d[16]),"+f"(d[17]),"+f"(d[18]),"+f"(d[19]),"+f"(d[20]),"+f"(d[21]),"+f"(d[22]),"+f"(d[23]),"+f"(d[24]),"+f"(d[25]),"+f"(d[26]),"+f"(d[27]),"+f"(d[28]),"+f"(d[29]),"+f"(d[30]),"+f"(d[31])
    : "r"(a0), "r"(a1), "r"(a2), "r"(a3), "l"(db), "r"(sd));
}
__device__ __forceinline__ void wg_rs80_01(float* d, uint32_t a0, uint32_t a1, uint32_t a2, uint32_t a3, uint64_t db, int sd) {
  asm volatile("{.reg .pred p; setp.ne.b32 p, %45, 0;\n"
    "wgmma.mma_async.sync.aligned.m64n80k16.f32.bf16.bf16 {%0,%1,%2,%3,%4,%5,%6,%7,%8,%9,%10,%11,%12,%13,%14,%15,%16,%17,%18,%19,%20,%21,%22,%23,%24,%25,%26,%27,%28,%29,%30,%31,%32,%33,%34,%35,%36,%37,%38,%39}, {%40,%41,%42,%43}, %44, p, 1, 1, 1;}"
    : "+f"(d[0]),"+f"(d[1]),"+f"(d[2]),"+f"(d[3]),"+f"(d[4]),"+f"(d[5]),"+f"(d[6]),"+f"(d[7]),"+f"(d[8]),"+f"(d[9]),"+f"(d[10]),"+f"(d[11]),"+f"(d[12]),"+f"(d[13]),"+f"(d[14]),"+f"(d[15]),"+f"(d[16]),"+f"(d[17]),"+f"(d[18]),"+f"(d[19]),"+f"(d[20]),"+f"(d[21]),"+f"(d[22]),"+f"(d[23]),"+f"(d[24]),"+f"(d[25]),"+f"(d[26]),"+f"(d[27]),"+f"(d[28]),"+f"(d[29]),"+f"(d[30]),"+f"(d[31]),"+f"(d[32]),"+f"(d[33]),"+f"(d[34]),"+f"(d[35]),"+f"(d[36]),"+f"(d[37]),"+f"(d[38]),"+f"(d[39])
    : "r"(a0), "r"(a1), "r"(a2), "r"(a3), "l"(db), "r"(sd));
}
__device__ __forceinline__ void wg_rs24_01(float* d, uint32_t a0, uint32_t a1, uint32_t a2, uint32_t a3, uint64_t db, int sd) {
  asm volatile("{.reg .pred p; setp.ne.b32 p, %17, 0;\n"
    "wgmma.mma_async.sync.aligned.m64n24k16.f32.bf16.bf16 {%0,%1,%2,%3,%4,%5,%6,%7,%8,%9,%10,%11}, {%12,%13,%14,%15}, %16, p, 1, 1, 1;}"
    : "+f"(d[0]),"+f"(d[1]),"+f"(d[2]),"+f"(d[3]),"+f"(d[4]),"+f"(d[5]),"+f"(d[6]),"+f"(d[7]),"+f"(d[8]),"+f"(d[9]),"+f"(d[10]),"+f"(d[11])
    : "r"(a0), "r"(a1), "r"(a2), "r"(a3), "l"(db), "r"(sd));
}

#define AB_POLY 0x77
__device__ __forceinline__ constexpr bool poly_group(int group) { return (AB_POLY >> (group & 7)) & 1; }

template <int V> struct Int { static constexpr int value = V; };

__device__ __forceinline__ int core_word(int row, int col) {
  return ((((row >> 7) * 10 + (col >> 6)) * 16 + ((row >> 3) & 15)) * 8 + ((col >> 3) & 7)) * 32 + (row & 7) * 4 + ((col & 7) >> 1);
}
__device__ __forceinline__ void wait_count(const uint32_t* c, uint32_t n) {
  for (int spin = 0; !__all_sync(~0u, (ld_acquire(c) & 0xffff) >= n);) { __nanosleep(32); spin_guard(spin); }
  fence_async_global();
}
__device__ __forceinline__ void prefetch_l2(const void* p, uint32_t bytes) {
  asm volatile("cp.async.bulk.prefetch.L2.global [%0], %1;" :: "l"(p), "r"(bytes) : "memory"); }

#define PLACE 4
__device__ __forceinline__ bool helper_sm() {
  uint32_t m; asm volatile("mov.u32 %0, %%smid;" : "=r"(m));
  m = __shfl_sync(~0u, m, 0);
  return m < 2 || m >= 120 || (m >= 92 && m < 102) || (m >= 106 && m < 117) || m == 118;
}

__device__ __forceinline__ uint8_t* pool_at(uint32_t off) {
  return reinterpret_cast<uint8_t*>((reinterpret_cast<uintptr_t>(g_pool) + 8191) & ~(uintptr_t)8191) + off; }
__device__ __forceinline__ void probe_slots(uint32_t scratch) {
  const int w = __shfl_sync(~0u, (threadIdx.x >> 6) & 1, 0), slot = w == 0 ? NSLOT : blockIdx.x;
  if (w == 0 || slot < NSLOT) {
    uint32_t* q = reinterpret_cast<uint32_t*>(pool_at(slot * 8192)) + (w == 0 ? (blockIdx.x & 31) * 32 + (blockIdx.x >> 5) : 0);
    uint32_t best[2] = {~0u, ~0u};
    const bool one = elect();
    if (one) { stg_strong32(q, 0u); stg_strong32(q + 1024, 0u); }
#pragma unroll 1
    for (int r = 0; r < 8; r++) {
      uint32_t v = 0;
      const uint32_t t0 = clk32();
      if (one) asm volatile("atom.relaxed.gpu.global.exch.b32 %0, [%1], 0;" : "=r"(v) : "l"(q + (r & 1) * 1024) : "memory");
      if (__any_sync(~0u, v != 0)) break;
      const uint32_t t = min(clk32() - t0, best[0]);
      best[0] = best[1]; best[1] = t;
    }
    if (one) sts32(scratch + w * 4, best[0] < best[1]);
  }
  bar_sync(2, 64);
  if ((threadIdx.x & 31) == 0) {
    const int part = lds32(scratch) ? 1 : 2;
    if (w == 0) { uint32_t smid; asm("mov.u32 %0, %%smid;" : "=r"(smid)); stg_strong32(g_smpart + (smid & 255), part); }
    else if (slot < NSLOT) stg_strong32(g_orient + slot, lds32(scratch + 4) ? part : 3 - part);
  }
  __syncwarp();
}

constexpr int WK_SLOTS = 28, WK_BAR = WK_SLOTS * 8192;
__device__ __forceinline__ void work_init(uint32_t sb, int w) {
  if (elect()) {
#pragma unroll
    for (int i = 0; i < 8; i++) mbar_init(sb + WK_BAR + 64 * w + 8 * i, 0x18318822 >> (8 * w + (i & 4)) & 15);
  }
  asm volatile("fence.mbarrier_init.release.cluster;" ::: "memory");
}

struct ChainParams {
  CUtensorMap wq, wk, wv, wo, xc;
  const __nv_bfloat16* mem0;
  const uint8_t* wb;
  uint32_t *sync, *other;
  int layer;
  int d1, d2, dn, dx, mode, zero;
};
constexpr int CH_WQ = 0, CH_WO = 81920, CH_X = CH_WO + 86016, CH_M = CH_X, CH_Q = CH_X + 34816, CH_KM = CH_Q + 2048, CH_VP = CH_KM + 2048,
              CH_K = CH_X + 40960, CH_O = CH_K, CH_KS = CH_K + 3072, CH_V = CH_K + 4096, CH_VX = CH_V + 12288, CH_R2 = CH_VX,
              CH_SX = CH_VX + 3072, CH_SO = CH_SX + 2048, CH_ID = CH_SO + 1024, CH_L = CH_ID + 256, CH_TAB = CH_L + 64, CH_BAR = CH_TAB + 384;
constexpr int CH_SMEM = CH_BAR + 144;
constexpr int MB_WO = CH_BAR, MB_WQ = CH_BAR + 8, MB_X = CH_BAR + 16, MB_V = CH_BAR + 24, MB_T = CH_BAR + 32, MB_F = CH_BAR + 40, MB_G = CH_BAR + 48, MB_W = CH_BAR + 56;
enum { NB_PROJ = 1, NB_O = 2, NB_W1 = 3, NB_PRE = 4, NB_ST = 5, NB_MEM = 6, NB_XFREE = 7, NB_H1 = 8, NB_PUB = 9, NB_W2 = 10, NB_PROJ2 = 11, NB_PRE2 = 12, NB_H2 = 13, NB_W1V = 14 };
#define CH_NQ 9
#define CH_XPF 1
#define CH_TPF 1
#define CH_FLY 6
#define CH_TW 1
#define H1VOTE 0
#define CH_G0 3
#define CH_G1 4
#define CH_NQP 2
#define CH_NQ0 5
#define CH_PA 6
#define CH_PB 9
#define CH_PC 13
#define CH_PL 4
#define CH_DBL 0x2108
#define CH_PD 1
#define SCHED() asm volatile("griddepcontrol.launch_dependents;" ::: "memory")
__device__ __forceinline__ uint32_t opaque(uint32_t x) { return __shfl_sync(~0u, x, threadIdx.x & 31); }
__device__ __forceinline__ uint32_t uniform(uint32_t x) { return __shfl_sync(~0u, x, 0); }
__device__ __forceinline__ uint32_t nz(uint32_t x) { uint32_t r; asm("max.u32 %0, %1, 1;" : "=r"(r) : "r"(x)); return r; }
__device__ __forceinline__ uint32_t set_tag(uint32_t w, uint32_t tag) { uint32_t r; asm("lop3.b32 %0, %1, %2, 1, 0xD8;" : "=r"(r) : "r"(w), "r"(tag)); return r; }
__device__ __forceinline__ uint32_t pack_tag(float lo, float hi, uint32_t tag) { return set_tag(__byte_perm(__float_as_uint(lo) + tag, pack2(hi, hi), 0x7632), tag); }
__device__ __forceinline__ uint32_t differ(uint32_t a, uint32_t b, uint32_t t) { uint32_t r; asm("lop3.b32 %0, %1, %2, %3, 0x7E;" : "=r"(r) : "r"(a), "r"(b), "r"(t)); return r; }
__device__ __forceinline__ uint32_t clk64() { uint64_t c; asm volatile("mov.u64 %0, %%clock64;" : "=l"(c) :: "memory"); return (uint32_t)c; }
__device__ __forceinline__ void until(uint32_t t) {
  asm volatile("{.reg .pred p; .reg .u64 c; .reg .s32 d;\nW: mov.u64 c, %%clock64; cvt.u32.u64 d, c; sub.s32 d, d, %0; setp.lt.s32 p, d, 0; @p bra.uni W;}" :: "r"(t) : "memory");
}
__device__ __forceinline__ float rcp(float x) { float y; asm("rcp.approx.ftz.f32 %0, %1;" : "=f"(y) : "f"(x)); return y; }

__device__ __forceinline__ void chain_compute(const ChainParams& p, const uint32_t sb) {
  const int tid = threadIdx.x & 127, WG = __shfl_sync(~0u, threadIdx.x >> 7, 0), t4 = __shfl_sync(~0u, tid >> 5, 0), lane = tid & 31;
  const int cta = blockIdx.x, h = cta / 3, j = cta - 3 * h;
  uint32_t a0[80], a1[80], tw[4 * CH_NQ];
  const uint32_t wq = opaque(sb + CH_WQ + (WG * 320 + (lane & 7) + (lane >> 4) * 8) * 128 + (((2 * t4 + ((lane >> 3) & 1)) ^ (lane & 7)) << 4));
#pragma unroll
  for (int k = 0; k < 40; k++) {
    if (k % 10 == 0) mbar_wait(sb + MB_W + WG * 8 + k / 10 * 16, 0);
    if (k < 20) ldsm4t(&a0[4 * k], wq + k * 2048); else ldsm4t(&a1[4 * k - 80], wq + CH_WO + (k - 20) * 2048);
    if (k % 20 == 19) bar_arrive(k < 20 ? NB_PROJ2 : NB_PRE2, 288);
  }
  const int r1 = j == 2 ? 0 : j + 1, r2 = j == 0 ? 2 : j - 1;
  const uint32_t l16 = opaque(sb + lane * 16), l8 = opaque(sb + lane * 8), l4 = opaque(sb + lane * 4);
  const uint32_t t16 = l16 + t4 * 512, t8 = l8 + t4 * 256;
  uint32_t wo = opaque(sb + CH_WO + (WG == 0 ? (t4 >> 1) * 36864 : 73728 + t4 * 1024) + ((lane & 7) + (lane >> 4) * 8) * 64 +
                       (((((lane >> 3) & 1) + (WG == 0 ? (t4 & 1) * 2 : 0)) ^ ((lane >> 1) & 3)) << 4));
  const uint32_t ko0 = uniform(CH_K + (tid >> 5) * 1024 + (tid >> 6) * 512), ko1 = uniform(CH_K + (tid >> 5) * 1024 + 512 - (tid >> 6) * 512),
                 o768 = uniform((tid >> 5) * 768);
  const uint32_t give = uniform(t4 * 512 + (WG == 0 ? CH_K : CH_V + j * 4096)), own = uniform(t4 * 512 + (WG == 0 ? CH_V + j * 4096 : CH_K)), mem = uniform(CH_M + WG * 5120);
  const uint32_t vxo = uniform(t4 * 256 + CH_VX + j * 1024);
  uint32_t tag = 1, xd = uniform((1024 + CH_X + WG * 20480) >> 4 | 8 << 16);
  asm volatile("barrier.cluster.wait.aligned;" ::: "memory");
  mbar_wait(sb + MB_WQ, 0);
  mbar_wait(sb + MB_T, 0);
  bar_sync(NB_ST, 384);
  uint8_t* pdst[6];
#pragma unroll
  for (int i = 0; i < 6; i++) {
    const int line = WG == 0 ? 24 * j + 12 * (t4 >> 1) + 2 * (t4 & 1) + 4 * (i >> 1) + (i & 1) : j == 0 ? 72 + t4 : 74 + 2 * j + (t4 & 1);
    pdst[i] = pool_at(uniform(lds32(sb + CH_TAB + line * 4)) + h * 128);
  }
  auto batch = [&](float* d, const uint32_t (&a)[80], int acc, int n0, int n1) {
    const uint32_t d0 = xd ^ (tag & (2 << acc));
    wg_fence();
#pragma unroll
    for (int k = 0; k < 20; k++) {
      const int gap = acc ? CH_G1 : CH_G0;
      if (k % gap == 0 && n0 + k / gap < n1) {
        __syncwarp();
        ldsm4t(&tw[4 * (n0 + k / gap)], wq + (n0 + k / gap) * 2048);
        __syncwarp();
      }
      uint64_t db;
      asm("mov.b64 %0, {%1, %2};" : "=l"(db) : "r"(d0 + k / 5 * 320 + k % 5 * 16), "r"(80));
      wg_rs32_00(d, a[4 * k], a[4 * k + 1], a[4 * k + 2], a[4 * k + 3], db, acc | k);
    }
    wg_commit();
    wg_wait<0>();
    reg_fence<16>(d);
  };
#pragma unroll
  for (int k = 0; k < CH_NQP; k++) ldsm4t(&tw[4 * k], wq + k * 2048);
  int s = 0;
#pragma unroll 1
  do {
    {
      float d[16];
      if (!CH_TW) mbar_wait(sb + MB_T, s & 1);
      batch(d, a0, 0, CH_NQP, CH_NQ0);
      s--; TM(10); s++;
      mbar_wait(sb + MB_F, ~s & 1);
#pragma unroll
      for (int i = 0; i < 2; i++)
        sts128(l16 + give + i * 2048, make_uint4(pack2(d[8 * i], d[8 * i + 1]), pack2(d[8 * i + 2], d[8 * i + 3]), pack2(d[8 * i + 4], d[8 * i + 5]), pack2(d[8 * i + 6], d[8 * i + 7])));
      bar_sync(NB_PUB, 384);
#pragma unroll
      for (int i = 0; i < 2; i++) {
        const uint4 t = lds128(l16 + own + i * 2048);
        d[8 * i] = bf_lo(t.x); d[8 * i + 1] = bf_hi(t.x); d[8 * i + 2] = bf_lo(t.y); d[8 * i + 3] = bf_hi(t.y);
        d[8 * i + 4] = bf_lo(t.z); d[8 * i + 5] = bf_hi(t.z); d[8 * i + 6] = bf_lo(t.w); d[8 * i + 7] = bf_hi(t.w);
      }
      reg_fence<16>(d);
      batch(d, a1, 1, CH_NQ0, CH_NQ);
      s--; TM(11); s++;
      if (WG == 0) bar_arrive(NB_XFREE, 256);
#pragma unroll
      for (int i = 0; i < 8; i++) sts32(l4 + (own - t4 * 256) + (i >> 1) * 1024 + (i & 1) * 128, pack2(d[2 * i], d[2 * i + 1]));
      s--; TM(9); s++;
    }
    float dq[4] = {}, d0[4] = {}, d1[4] = {};
    uint32_t b[40], wf[80];
    const uint32_t* kf = &wf[52];
#pragma unroll
    for (int i = 0; i < 4 * CH_NQ; i++) wf[i] = tw[i];
    auto step = [&](int k) {
      mma16(dq, wf[4 * k], wf[4 * k + 1], wf[4 * k + 2], wf[4 * k + 3], b[2 * k], b[2 * k + 1]);
      mma16(d0, a0[4 * k], a0[4 * k + 1], a0[4 * k + 2], a0[4 * k + 3], b[2 * k], b[2 * k + 1]);
      mma16(d1, a1[4 * k], a1[4 * k + 1], a1[4 * k + 2], a1[4 * k + 3], b[2 * k], b[2 * k + 1]);
    };
    auto finish = [&](int wg, const float* dk) {
      const float k2 = 0.07216878364870322f * 1.44269504089f;
      sts32(l4 + t4 * 512 + CH_Q + wg * 128, pack2(dq[0] * k2, dq[1] * k2));
      sts32(l4 + t4 * 512 + CH_Q + wg * 128 + 256, pack2(dq[2] * k2, dq[3] * k2));
      sts32(l4 + t4 * 512 + CH_KM + wg * 256, pack2(dk[0], dk[1]));
      sts32(l4 + t4 * 512 + CH_KM + wg * 256 + 128, pack2(dk[2], dk[3]));
    };
    const bool more = s < NSEG - 1;
    bar_sync(NB_MEM, 384);
    ldsm4t(&b[0], l16 + mem);
    ldsm4t(&b[4], l16 + mem + 512);
    TMD(0, b[0]);
    {
      int nw = CH_NQ, nb = 2;
#pragma unroll
      for (int k = 0; k < 20; k++) {
        SCHED();
        step(k);
#pragma unroll
        for (int i = 0; i < (CH_DBL >> k & 1) + 1; i++) {
          if (nb < 10 && 2 * nb <= nw) { ldsm4t(&b[4 * nb], l16 + mem + nb * 512); nb++; }
          else if (nw < 20) { ldsm4t(&wf[4 * nw], wq + nw * 2048); nw++; }
          else if (nw < 22) {
            const uint32_t x = l16 ^ ((o768 ^ tag) & 256);
            uint32_t* r = &wf[4 * nw - 28];
            asm volatile("{.reg .pred p; setp.ne.u32 p, %5, 0; @p ldmatrix.sync.aligned.m8n8.x4.trans.shared.b16 {%0,%1,%2,%3},[%4];}"
                         : "+r"(r[0]), "+r"(r[1]), "+r"(r[2]), "+r"(r[3]) : "r"(x + (nw == 20 ? ko0 : ko1)), "r"(WG) : "memory");
            nw++;
          }
        }
      }
      SCHED();
    }
    if (WG == 0) {
      finish(0, d0);
      TM(1);
      bar_sync(NB_PROJ, 256);
      if (!more) {
        const float4 pv = lds128f(t16 + CH_VP);
        sts32(l4 + vxo, pack2(d1[0] + pv.x, d1[1] + pv.y));
        sts32(l4 + vxo + 128, pack2(d1[2] + pv.z, d1[3] + pv.w));
        continue;
      }
      const float4 pv = lds128f(t16 + CH_VP);
      const uint32_t xo = l4 + (vxo ^ (tag & 2)), x1 = mapa(xo, r1), x2 = mapa(xo, r2);
      SCHED();
      const uint32_t v0 = pack2(d1[0] + pv.x, d1[1] + pv.y), v1 = pack2(d1[2] + pv.z, d1[3] + pv.w);
      st_async32(x1, v0, mapa(sb + MB_X, r1));
      st_async32(x2, v0, mapa(sb + MB_X, r2));
      st_async32(x1 + 128, v1, mapa(sb + MB_X, r1));
      st_async32(x2 + 128, v1, mapa(sb + MB_X, r2));
      sts32(xo, v0);
      sts32(xo + 128, v1);
      __syncwarp();
      mbar_arrive_one(sb + MB_X);
      bar_arrive(NB_PROJ2, 256);
      TM(3);
      uint32_t w[144];
      auto tile_of = [](int n) { return n < 27 ? n % 3 : (0x26484 >> 2 * (n - 27)) & 3; };
      auto step_of = [](int n) { return n < 27 ? n / 3 : 9 + ((0x29610 >> 2 * (n - 27)) & 3); };
      auto wload = [&](int n) { ldsm4t(&w[4 * n], wo + tile_of(n) * 12288 + (step_of(n) % 3) * 4096 + (step_of(n) / 3) * 1024); };
#pragma unroll
      for (int n = 0; n < CH_PA; n++) wload(n);
      bar_sync(NB_PRE, 256);
#pragma unroll
      for (int n = CH_PA; n < CH_PB; n++) wload(n);
      bar_arrive(NB_PRE2, 256);
      if (CH_PC > CH_PB) {
        mbar_wait(sb + MB_X, s & 1);
        for (int i = 0; i < CH_PD; i++) wo = __shfl_xor_sync(~0u, wo, p.zero);
#pragma unroll
        for (int n = CH_PB; n < CH_PC; n++) wload(n);
      }
      TM(4);
      bar_sync(NB_O, 256);
      {
        float x[3][4] = {};
        uint32_t ob[24];
        float4 l;
        ldsm4t(&ob[0], l16 + CH_O);
        ldsm4t(&ob[4], l16 + CH_O + 512);
        TMD(7, ob[0]);
        int nw = CH_PC, no = 2;
        float i0, i1;
        uint8_t* dst[6];
        uint32_t lo[6], hi[6];
        auto pre = [&](int i) { lo[i] = __float_as_uint(x[i >> 1][2 * (i & 1)] * i0) + tag; hi[i] = pack2(0.f, x[i >> 1][2 * (i & 1) + 1] * i1); };
        auto emit = [&](int i) { stg_strong32(dst[i], set_tag(__byte_perm(lo[i], hi[i], 0x7632), tag)); };
#pragma unroll
        for (int n = 0; n < 36; n++) {
          SCHED();
          mma16(x[tile_of(n)], w[4 * n], w[4 * n + 1], w[4 * n + 2], w[4 * n + 3], ob[step_of(n) * 2], ob[step_of(n) * 2 + 1]);
          if (n >= CH_PL) {
            if (no < 6 && no * 2 <= step_of(min(nw, 35))) { ldsm4t(&ob[4 * no], l16 + CH_O + no * 512); no++; }
            else if (nw < 36) { wload(nw); nw++; if (CH_NQP && nw == 36) bar_arrive(NB_H1, 256); }
            else if (nw < 36 + CH_NQP) { ldsm4t(&tw[4 * (nw - 36)], wq + (nw - 36) * 2048); nw++; }
          }
          if (n == 18) l = lds128f(sb + CH_L + ((l16 ^ tag) & 0x30));
          if (n == 26) { i0 = rcp(l.x + l.y); i1 = rcp(l.z + l.w); asm volatile("" : "+f"(i0), "+f"(i1)); }
          if (n >= 28 && n < 34) { dst[n - 28] = pdst[n - 28] + ((l4 ^ tag) & 0x7c); asm volatile("" : "+l"(dst[n - 28])); }
          if (n == 32) { for (int i = 0; i < 2; i++) { pre(i); asm volatile("" : "+r"(lo[i]), "+r"(hi[i])); } }
          if (n == 33) { emit(0); emit(1); }
        }
        for (int i = 2; i < 6; i++) pre(i);
        for (int i = 2; i < 6; i++) emit(i);
      }
      TM(8);
    } else {
      finish(1, d1);
      sts128f(t16 + CH_VP, d0[0], d0[1], d0[2], d0[3]);
      TM(1);
      bar_sync(NB_PROJ, 256);
      uint32_t pair;
      {
        float d0[4] = {}, d1[4] = {}, dm[4] = {};
        uint32_t q[16], km[4];
#pragma unroll
        for (int e = 0; e < 4; e++) {
          ldsm4t(&q[4 * e], l16 + (e ^ t4) * 512 + CH_Q);
          SCHED();
          if (e == 1) { ldsm4t(km, t16 + CH_KM); SCHED(); }
        }
        const uint32_t xo = l4 + ((t4 * 128) ^ (tag & 2));
        pair = l16 + ((l16 ^ tag) & 256) * 3;
        asm volatile("" : "+r"(pair));
        uint64_t x[4];
#pragma unroll
        for (int i = 0; i < 4; i++) {
          const int r = i & 1 ? r2 : r1;
          asm volatile("mov.b64 %0, {%1, %2};" : "=l"(x[i]) : "r"(mapa(xo, r) + CH_SX + (i & 1) * 1024 + (i & 2) * 256), "r"(mapa(sb + MB_X, r)));
        }
        SCHED();
        mma16(d0, q[0], q[1], q[2], q[3], kf[0], kf[1]);
        SCHED();
        mma16(d1, q[4], q[5], q[6], q[7], kf[2], kf[3]);
        SCHED();
        mma16(dm, q[0], q[1], q[2], q[3], hadd2(km[0], km[2]), hadd2(km[1], km[3]));
        mma16(d0, q[8], q[9], q[10], q[11], kf[4], kf[5]);
        SCHED();
        mma16(d1, q[12], q[13], q[14], q[15], kf[6], kf[7]);
        if (!more) continue;
        const uint32_t w1 = pack2(dm[0] + dm[2], dm[1] + dm[3]);
        st_async32((uint32_t)x[2], w1, x[2] >> 32);
        st_async32((uint32_t)x[3], w1, x[3] >> 32);
        SCHED();
        const uint32_t w0 = pack2((d0[0] + d0[2]) + (d1[0] + d1[2]), (d0[1] + d0[3]) + (d1[1] + d1[3]));
        st_async32((uint32_t)x[0], w0, x[0] >> 32);
        st_async32((uint32_t)x[1], w0, x[1] >> 32);
        sts32(xo + CH_SO, w0);
        sts32(xo + CH_SO + 512, w1);
      }
      TM(3);
      float sc[3][4] = {};
      uint32_t wd[12];
      uint32_t redo;
      auto attend = [&](auto first) {
        uint4 vb[6];
        uint32_t vm[6];
        float e[10];
        uint32_t ow[6];
        if (first.value) {
          const uint2 id = lds64(l8 + CH_ID);
          bar_sync(NB_W1V, 160);
          uint32_t r[8];
          ldsm4(r, l16 + CH_SO); ldsm4(r + 4, l16 + CH_SO + 512);
#pragma unroll
          for (int u = 0; u < 6; u++) vb[u] = ldsm4v(pair + t4 * 256 + CH_V + u * 2048);
          bar_arrive(NB_PRE, 256);
          const uint32_t sxa = pair + CH_SX;
          SCHED();
          mma8(sc[0], r[0], r[1], id.x);
          mma8(sc[1], r[2], r[3], id.x);
          mma16(sc[2], r[4], r[5], r[6], r[7], id.x, id.y);
          TM(7);
          mbar_wait(sb + MB_X, s & 1);
          TM(4);
          uint32_t t[16];
          ldsm4(t, sxa); ldsm4(t + 4, sxa + 256); ldsm4(t + 8, sxa + 512);
          SCHED();
          mma16(sc[0], t[0], t[1], t[2], t[3], id.x, id.y);
          ldsm4(t + 12, sxa + 768);
          SCHED();
          mma16(sc[1], t[4], t[5], t[6], t[7], id.x, id.y);
          ldsm4(vm, pair + t4 * 256 + CH_VX);
          SCHED();
          e[0] = ex2(sc[0][0]);
          mma16(sc[2], t[8], t[9], t[10], t[11], id.x, id.y);
          ldsm2(vm + 4, l16 + t4 * 256 + CH_VX + 2048);
          SCHED();
          e[1] = ex2(sc[0][1]);
          ldsm4t(&wd[0], wo);
          SCHED();
          e[2] = ex2(sc[0][2]);
          SCHED();
          e[3] = ex2(sc[0][3]);
          mma16(sc[2], t[12], t[13], t[14], t[15], id.x, id.y);
          SCHED();
          e[4] = ex2(sc[1][0]);
          ldsm4t(&wd[4], wo + 4096);
          SCHED();
          e[5] = ex2(sc[1][1]);
        } else {
#pragma unroll
          for (int u = 0; u < 6; u++) vb[u] = ldsm4v(pair + t4 * 256 + CH_V + u * 2048);
          ldsm4(vm, pair + t4 * 256 + CH_VX);
          ldsm2(vm + 4, l16 + t4 * 256 + CH_VX + 2048);
        }
        float o[3][4] = {};
        if (!first.value) {
#pragma unroll
          for (int i = 0; i < 6; i++) e[i] = ex2(sc[i >> 2][i & 3]);
        }
        const uint32_t p1 = pack2(e[0], e[1]), p2 = pack2(e[2], e[3]);
        float l = (e[0] + e[1]) + (e[2] + e[3]);
        asm volatile("" : "+f"(l));
        SCHED();
        e[6] = ex2(sc[1][2]);
        mma16(o[0], vb[0].x, vb[0].y, vb[0].z, vb[0].w, p1, p2);
        if (first.value) { sc[2][0] += sc[2][2]; sc[2][1] += sc[2][3]; }
        SCHED();
        e[7] = ex2(sc[1][3]);
        mma16(o[1], vb[2].x, vb[2].y, vb[2].z, vb[2].w, p1, p2);
        SCHED();
        e[8] = ex2(sc[2][0]);
        mma16(o[2], vb[4].x, vb[4].y, vb[4].z, vb[4].w, p1, p2);
        SCHED();
        e[9] = ex2(sc[2][1]);
        SCHED();
        const uint32_t p3 = pack2(e[4], e[5]), p4 = pack2(e[6], e[7]);
        l += (e[4] + e[5]) + (e[6] + e[7]);
#pragma unroll
        for (int u = 0; u < 3; u++) mma16(o[u], vb[2 * u + 1].x, vb[2 * u + 1].y, vb[2 * u + 1].z, vb[2 * u + 1].w, p3, p4);
        SCHED();
        const uint32_t p0 = pack2(e[8], e[9]);
        l += e[8] + e[9];
        const float l2 = __shfl_xor_sync(~0u, l, 1);
        if (first.value) ldsm4t(&wd[8], wo + 8192);
#pragma unroll
        for (int u = 0; u < 3; u++) mma8(o[u], vm[2 * u], vm[2 * u + 1], p0);
        redo = __any_sync(~0u, !(l > 1e-9f && l < 1e9f));
        uint32_t la = sb + CH_L + (((l4 ^ tag) >> 1) & 0x3c);
        asm volatile("" : "+r"(la));
        SCHED();
#pragma unroll
        for (int u = 0; u < 3; u++) { ow[2 * u] = pack2(o[u][0], o[u][1]); ow[2 * u + 1] = pack2(o[u][2], o[u][3]); }
#pragma unroll
        for (int u = 0; u < 6; u++) sts32(l4 + o768 + CH_O + u * 128, ow[u]);
        if (t4 == 0) sts32(la, __float_as_uint(l + l2));
      };
      attend(Int<1>());
      TM(6);
      asm volatile("{.reg .pred p; setp.eq.u32 p, %0, 0; @p bar.sync 2, 256;}" :: "r"(redo) : "memory");
      if (redo) {
        float mx = fmaxf(sc[2][0], sc[2][1]);
#pragma unroll
        for (int i = 0; i < 4; i++) mx = fmaxf(mx, fmaxf(sc[0][i], sc[1][i]));
        mx = fmaxf(mx, __shfl_xor_sync(~0u, mx, 1));
        mx = fmaxf(mx, __shfl_xor_sync(~0u, mx, 2));
#pragma unroll
        for (int i = 0; i < 4; i++) { sc[0][i] -= mx; sc[1][i] -= mx; }
        sc[2][0] -= mx; sc[2][1] -= mx;
        attend(Int<0>());
        bar_arrive(NB_O, 256);
      }
      {
        float z[4] = {};
        const uint32_t scr = l8 + ((CH_V + r1 * 4096) ^ (tag & 2));
        uint32_t ow[6], we[12];
        __syncwarp();
        ldsm4t(ow, l16 + o768 + CH_O);
        ldsm2t(ow + 4, l16 + o768 + CH_O + 512);
        if (j == 0) {
          float y[4] = {};
#pragma unroll
          for (int u = 0; u < 3; u++) ldsm4t(&we[4 * u], (wo ^ 32) + u * 4096);
          SCHED();
#pragma unroll
          for (int u = 0; u < 3; u++) {
            mma16(z, wd[4 * u], wd[4 * u + 1], wd[4 * u + 2], wd[4 * u + 3], ow[2 * u], ow[2 * u + 1]);
            mma16(y, we[4 * u], we[4 * u + 1], we[4 * u + 2], we[4 * u + 3], ow[2 * u], ow[2 * u + 1]);
          }
          sts64f(scr + t4 * 256 + 2048, y[0], y[1]); sts64f(scr + t4 * 256 + 3072, y[2], y[3]);
        } else {
#pragma unroll
          for (int u = 0; u < 3; u++) mma16(z, wd[4 * u], wd[4 * u + 1], wd[4 * u + 2], wd[4 * u + 3], ow[2 * u], ow[2 * u + 1]);
        }
        sts64f(scr + t4 * 256, z[0], z[1]); sts64f(scr + t4 * 256 + 1024, z[2], z[3]);
        bar_sync(NB_W1, 128);
        if (j == 0 || t4 < 2) {
          float2 q[4];
          const float4 l = lds128f(sb + CH_L + ((l16 ^ tag) & 0x30));
#pragma unroll
          for (int i = 0; i < 4; i++) q[i] = lds64f(scr + t4 * 1024 + i * 256);
          SCHED();
          stg_strong32(pdst[0] + ((l4 ^ tag) & 0x7c), pack_tag(((q[0].x + q[1].x) + (q[2].x + q[3].x)) * rcp(l.x + l.y), ((q[0].y + q[1].y) + (q[2].y + q[3].y)) * rcp(l.z + l.w), tag));
        }
      }
      TM(2);
      if (CH_NQP) bar_sync(NB_H1, 256);
#pragma unroll
      for (int k = 0; k < CH_NQP; k++) ldsm4t(&tw[4 * k], wq + k * 2048);
    }
    bar_sync(NB_ST, 384);
    tag ^= 0x10001;
  } while (++s < NSEG);
  if (WG == 1) {
    const uint2 a = lds64(t8 + t4 * 256 + CH_KM), b = lds64(t8 + t4 * 256 + CH_KM + 256);
    sts64(t8 + CH_M, hadd2(a.x, b.x), hadd2(a.y, b.y));
  }
  bar_arrive(NB_PRE2, 288);
}

__device__ __forceinline__ void chain_comm(const ChainParams& p, const uint32_t sb, const CUtensorMap* maps) {
  [[maybe_unused]] constexpr int WG = 2;
  const int tid = threadIdx.x & 127, t4 = __shfl_sync(~0u, tid >> 5, 0), lane = tid & 31;
  const int cta = blockIdx.x, h = cta / 3, j = cta - 3 * h, colbase = cta * 64;
  const uint8_t* const xs = reinterpret_cast<const uint8_t*>(g_xn);
  auto xload = [&](int seg, int i) { tma_load5_one(sb + CH_X + i * 10240, &p.xc, 0, seg * 4, 2 * i, sb + MB_T); };
  uint32_t smid; asm("mov.u32 %0, %%smid;" : "=r"(smid));
  if (t4 == 3) {
    const bool one = elect();
#pragma unroll 1
    for (int i = 0; i < 19 + CH_FLY; i++) {
      if (i >= CH_FLY) mbar_wait(sb + MB_W + 8 * ((i - CH_FLY) & 7), (i - CH_FLY) >> 3 & 1);
      if (i == 11 + CH_FLY && one) mbar_arrive(sb + MB_WQ);
      if (i == 8) { bar_sync(NB_PROJ2, 288); PRO(1); }
      if (i == 12) { bar_sync(NB_PRE2, 288); PRO(2); }
      if (i == 0) { bar_arrive(NB_ST, 384); bar_arrive(NB_PUB, 384); bar_arrive(NB_XFREE, 256); }
      if (i < 19 && one) {
        const int n = (i & 1) * 2 + (i >> 1 & 1), k = i - 12;
        const uint32_t bar = sb + MB_W + 8 * (i & 7);
        mbar_expect(bar, k < 0 ? 20480 : 12288);
        if (k < 0) tma_load(sb + ((i & 4) + n) * 20480, i >= 8 ? &p.wq : (i ^ i >> 2) & 1 ? &p.wv : &p.wk, colbase, n * 160, bar);
        else tma_load(sb + CH_WO + k * 12288, &p.wo, k < 6 ? j * 192 + k * 32 : j == 0 ? 576 : 592 + j * 16, h * 192, bar);
      }
    }
  } else {
    const uint32_t part = max(ldg_strong32(g_smpart + (smid & 255)), 1u);
    if (tid == 0) prefetch_l2(p.mem0, 10240);
    if (tid == 64) stg_strong32(p.sync + SY_PART + cta, part);
    if (t4 == 1) {
      wait_count(p.sync + SY_P + 1, ln_items(p.layer, 0));
      mbar_expect_one(sb + MB_T, 40960);
#pragma unroll 1
      for (int i = 0; i < 4; i++) xload(0, i);
      PRO(0);
    }
    uint32_t reader, orient;
    for (int n = 0;; spin_guard(n)) {
      reader = ldg_strong32(p.sync + SY_PART + (tid >= 80 ? cta : tid));
      orient = ldg_strong32(g_orient + min(tid, NSLOT - 1));
      if (__all_sync(~0u, reader && orient)) break;
    }
    const uint32_t near = __ballot_sync(~0u, reader == part) >> (cta & 7) & 0xffff;
    if (tid < NSLOT) sts32(sb + CH_TAB + tid * 4, tid * 8192 + (orient == reader ? 0 : 4096));
    if (tid == 0) sts32(sb + CH_TAB + NSLOT * 4, cta < 80 ? cta : (cta & 7) + max(__ffs(near) - 1, 0));
    if (t4 == 1) PRO(3);
    bar_sync(NB_ST, 384);
    bar_arrive(NB_PUB, 384);
    if (t4 == 1) PRO(4);
    const uint32_t id = (lane >> 3) == (lane & 3) ? ((lane & 4) ? 0x3f800000u : 0x00003f80u) : 0u;
    if (t4 == 0) sts64(sb + CH_ID + lane * 8, id, id);
#pragma unroll 1
    for (int q = t4; q < 4; q += 3) {
      uint32_t m0[20];
#pragma unroll
      for (int i = 0; i < 20; i++) m0[i] = (reinterpret_cast<const uint32_t*>(p.mem0) + (lane >> 2) * (DM / 2) + q * 80 + (lane & 3))[i * 4];
      if (q < 3) bar_sync(NB_XFREE, 256);
#pragma unroll
      for (int i = 0; i < 20; i += 4) stsm4t(sb + CH_M + (q * 20 + i) * 128 + lane * 16, m0[i], m0[i + 1], m0[i + 2], m0[i + 3]);
    }
    if (t4 == 1) PRO(5);
  }
  if (cta * 128 + tid < SY_N) p.other[cta * 128 + tid] = 0;
  asm volatile("barrier.cluster.wait.aligned;" ::: "memory");
  const uint32_t l8 = opaque(sb + t4 * 256 + lane * 8);
  bar_sync(NB_MEM, 384);
  uint8_t* const pool = pool_at(0);
  const uint8_t* const psrc = pool + opaque(lds32(sb + CH_TAB + lds32(sb + CH_TAB + NSLOT * 4) * 4) + t4 * 1024 + lane * 4);
  const uint32_t mdst = opaque((80 + cta / 20) * 8192 + (t4 & 1) * 4096 + (cta % 20) * 128 + lane * 4);
  int st = 0;
  uint32_t tag = 1, span = ~0u;
  auto send_tokens = [&](int s) {
    uint8_t* dst = g_kv + ((s >> 2) * 192 + cta + 3 * h) * KV_PART + (s & 3) * KV_SEG;
    bulk_store(dst, sb + CH_K, 4096);
    bulk_store(dst + KV_V, sb + CH_V + j * 4096, 4096);
    bulk_commit();
  };
  auto send_memory = [&](int s, uint32_t km) {
    fence_async();
    uint8_t* dst = g_kv + ((s >> 2) * 192 + cta + 3 * h) * KV_PART + KV_M + (s & 3) * KV_SEG;
    bulk_store(dst, km, 1024);
    bulk_store(dst + KV_V, sb + CH_VX + j * 1024, 1024);
    bulk_commit();
    bulk_wait<0>();
    if ((s & 3) == 3) { fence_async_global(); atomicAdd(p.sync + (s >> 2) * 8 + 4, 1); }
  };
#pragma unroll 1
  for (int s = 0; s < NSEG - 1; s++) {
    TM(0);
    STAT(0);
    if (t4 == 0) {
      mbar_expect_one(sb + MB_T, 40960);
      xload(s + 1, 1);
      xload(s + 1, 2);
      if (elect()) {
        fence_async();
#pragma unroll 1
        for (int r = j + 1; r < j + 3; r++) bulk_push(mapa(sb + CH_V + j * 4096, r % 3), sb + CH_V + j * 4096, 4096, mapa(sb + MB_V, r % 3));
        send_tokens(s);
        bulk_wait_read<0>();
      }
      __syncwarp();
    }
    uint32_t c0, g0;
    if (t4 == 1) {
      __syncwarp();
      c0 = clk32(); g0 = gtime();
      if (elect()) atomicMax(p.sync + SY_TIME + s, g0);
    }
    if (t4 == 3 && s >= NSEG - 6 && elect()) asm volatile("prefetch.tensormap [%0];" :: "l"(maps + (NSEG - 2 - s)) : "memory");
    if (t4 == 3 && (s & 3) == 2 && s < NSEG - 2) wait_count(p.sync + SY_P + 5 + (s & ~3), ln_items(p.layer, (s >> 2) + 1));
    if (t4 == 2) { mbar_wait(sb + MB_V, s & 1); bar_arrive(NB_W1V, 160); }
    bar_sync(NB_PROJ2, 256);
    if (t4 == 0) {
      mbar_expect_one(sb + MB_X, 4096);
      xload(s + 1, 0);
    }
    __syncwarp();
    STAT(1);
    TM(1);
    {
      const uint2 a = lds64(l8 + t4 * 256 + CH_KM), b = lds64(l8 + t4 * 256 + CH_KM + 256);
      sts64(l8 + CH_KS, hadd2(a.x, b.x), hadd2(a.y, b.y));
    }
    TM(4);
    bar_sync(NB_PRE2, 256);
    if (t4 == 0) xload(s + 1, 3);
    if (t4 == 0 && elect()) {
      if (CH_XPF && s < NSEG - 2) prefetch_l2(xs + (s + 2) * 40960 + cta % 20 * 2048, 2048);
      if (CH_TPF && s >= NSEG - 7) {
        const int i = s - (NSEG - 7);
        if (i < 2) prefetch_l2(p.wb + (cta * 2 + i) * 12800, 12800);
        else if (i < 4) prefetch_l2(xs + (cta * 2 + i - 2) * 8192, 8192);
        else prefetch_l2(g_q + 15 * 32 * 3072 + (cta * 2 + i - 4) * 512, 8192);
      }
      send_memory(s, sb + CH_KS);
    }
    __syncwarp();
    if (t4 == 1) {
      const uint32_t late = min(ldg_strong32(p.sync + SY_TIME + s) - g0, 640u);
      if (elect()) sts32(sb + CH_TAB + 380, c0 + span + (late * 115 >> 6) + (j ? 60 : 0) + p.d1);
    }
    bar_sync(NB_W2, 128);
    uint32_t due = lds32(sb + CH_TAB + 380);
    due = __shfl_sync(~0u, due, 0);
    const uint8_t* ms = pool + (lds32(sb + CH_TAB + (80 + st * 4 + t4) * 4) + (l8 & 255));
    uint8_t* md = pool + (mdst + (cta >= 80 ? 2 : t4 < 2 ? st : st == 2 ? 0 : st + 1) * 32768);
    asm volatile("" : "+l"(ms), "+l"(md));
    if (CH_TW) mbar_wait(sb + MB_T, ~s & 1);
    TM(2);
    bar_sync(NB_ST, 384);
    __syncwarp();
    uint32_t tg = clk32();
    if (t4 == 3 && elect()) {
      if (s < NSEG - 2) mbar_expect(sb + MB_V, 8192);
      mbar_arrive_remote(mapa(sb + MB_F, j == 2 ? 0 : j + 1));
      mbar_arrive_remote(mapa(sb + MB_F, j == 0 ? 2 : j - 1));
    }
    if (s == NSEG - 2) work_init(sb, t4);
    __syncwarp();
    STAT(2);
    {
      float2 q[4];
      TM(3);
      if (t4 == 1 && s) span = min(span, tg - c0);
      until(s < 2 ? tg + 400 : (int)(due - tg) > p.dn ? due : tg + p.dn);
      for (int n = 0;;) {
        uint32_t v[8];
#pragma unroll
        for (int i = 0; i < 8; i++) v[i] = ldg_strong32(psrc + i * 128);
        sts64f(l8 + CH_R2, ((bf_lo(v[0]) + bf_lo(v[1])) + (bf_lo(v[2]) + bf_lo(v[3]))) + ((bf_lo(v[4]) + bf_lo(v[5])) + (bf_lo(v[6]) + bf_lo(v[7]))),
               ((bf_hi(v[0]) + bf_hi(v[1])) + (bf_hi(v[2]) + bf_hi(v[3]))) + ((bf_hi(v[4]) + bf_hi(v[5])) + (bf_hi(v[6]) + bf_hi(v[7]))));
        uint32_t bad;
        asm volatile("{.reg .pred p, q; .reg .b32 a; lop3.b32 a, %1, %2, %3, 0xFE; lop3.b32 a, a, %4, %6, 0xA8; setp.ne.u32 p, a, 0;\n"
                     "bar.red.or.pred q, %5, 128, p; selp.u32 %0, 1, 0, q;}"
                     : "=r"(bad) : "r"(differ(v[0], v[1], tag)), "r"(differ(v[2], v[3], tag)), "r"(differ(v[4], v[5], tag)), "r"(differ(v[6], v[7], tag)), "n"((int)NB_W2),
                       "r"((uint32_t)(cta < 80 || n < 3)) : "memory");
#pragma unroll
        for (int k = 0; k < 4; k++) asm volatile("ld.volatile.shared.v2.f32 {%0,%1}, [%2];" : "=f"(q[k].x), "=f"(q[k].y) : "r"(l8 - t4 * 256 + CH_R2 + k * 256) : "memory");
        TMV(12, n);
        if (!(H1VOTE ? __any_sync(~0u, bad) : bad)) break;
        spin_guard(n);
      }
      bar_arrive(NB_PUB, 384);
      SCHED();
      TM(9);
      stg_strong32(md, min(nz(pack2((q[0].x + q[1].x) + (q[2].x + q[3].x), (q[0].y + q[1].y) + (q[2].y + q[3].y))), t4 < 2 ? ~0u : 0u));
      tg = clk64() + p.d2;
      if (s >= 2 && (int)(due + p.dx - tg) > 0) tg = due + p.dx;
      TM(8);
    }
    STAT(3);
    until(tg);
    TM(10);
    for (int n = 0;;) {
      uint2 g[10];
#pragma unroll
      for (int i = 0; i < 10; i++) g[i] = ldg_strong64(ms + i * 256);
      if (n == 0) bar_sync(NB_XFREE, 256);
      uint32_t m = ~0u, bad;
#pragma unroll
      for (int i = 0; i < 10; i++) { sts64(l8 + CH_M + t4 * 2304 + i * 256, g[i].x, g[i].y); m = __vimin3_u32(m, g[i].x, g[i].y); }
      TMV(13, n);
      TM(11);
      asm volatile("{.reg .pred p; setp.eq.u32 p, %1, 0; vote.sync.any.pred p, p, 0xffffffff; @!p bar.sync %2, 384; selp.u32 %0, 1, 0, p;}" : "=r"(bad) : "r"(m), "n"((int)NB_MEM) : "memory");
      if (!bad) break;
      spin_guard(n);
    }
    if (++st == 3) st = 0;
    tag ^= 0x10001;
  }
  if (t4 == 0) {
    if (elect()) { fence_async(); send_tokens(NSEG - 1); }
    __syncwarp();
    bar_sync(NB_PRE2, 288);
    if (elect()) {
      send_memory(NSEG - 1, sb + CH_M);
      asm volatile("mbarrier.arrive.shared::cta.b64 _, [%0], 8;" :: "r"(sb + WK_BAR + 64) : "memory");
    }
    __syncwarp();
  }
}

__device__ __forceinline__ void chain_start(const ChainParams& p, const uint32_t sb, const int warp) {
  if (warp == 1 && elect()) {
#pragma unroll
    for (int i = 0; i < 6; i++) mbar_init(sb + CH_BAR + 8 * i, i == 2 ? 5 : i == 5 ? 2 : 1);
    asm volatile("fence.mbarrier_init.release.cluster;" ::: "memory");
    mbar_expect(sb + MB_V, 8192);
    atomicAdd(p.sync + SY_UP, 1);
    asm volatile("{.reg .pred p; setp.ne.u32 p, %0, 1024; @p trap;}" :: "r"(sb & 0xffffff));
  }
  if (warp == 0 && elect()) {
#pragma unroll
    for (int i = 0; i < 8; i++) mbar_init(sb + MB_W + 8 * i, 1);
    asm volatile("fence.mbarrier_init.release.cluster;" ::: "memory");
  }
  __syncthreads();
  asm volatile("barrier.cluster.arrive.relaxed.aligned;" ::: "memory");
}

struct WorkParams {
  ChainParams ch;
  CUtensorMap wo, xn, wb[3], wq, wc[2], out;
  const __nv_bfloat16* x;
  uint32_t* sync;
  int kind, qa_end, pace, idle;
};
#define GO_320 4
#define GO_TAIL 1
#define PF_NS 400
enum { WK_FIRST = 0, WK_LEAD = 1, WK_CHAIN = 2, WK_LAST = 3 };
enum { IT_ATT = 0, IT_OP = 1, IT_FIN = 2, IT_BQ = 3, IT_BO = 4, IT_LN = 5, IT_Q = 6, IT_LN0 = 7, IT_OUT = 8 };
constexpr int C_EARLY = 1 << 20, C_LATE = 1 << 21, C_TAIL = 1 << 22, C_PROJ = 1 << 23;

__device__ __forceinline__ uint32_t item_count(int type, int b) { return type == IT_ATT ? 32 : type == IT_OP ? op_tiles(b) * op_split(b) : type == IT_FIN ? fin_items(b) : bq_items(b); }
__device__ __forceinline__ uint32_t item_need(int type, int b) { return type == IT_ATT ? 96 : item_count(type - 1, b); }
__device__ __forceinline__ int item_cols(int type, int b) {
  return type == IT_ATT || type == IT_Q ? 192 : type == IT_OUT ? 80 : type == IT_BQ ? (b < BQ_12 ? 320 : b < BQ_24 ? 160 : 80) : type == IT_OP ? 640 >> op_shift(b) : 320; }
__device__ __forceinline__ int item_groups(int type, int b) { const int n = type == IT_FIN ? fin_items(b) : ln_items(type == IT_LN, b); return n == 4 ? 4 : n == 8 ? 2 : 1; }
#define RES_OP 0
#define RES_B 6
#define HOLD_B 10
constexpr int RES_N = RES_OP ? op_tiles(14) * op_split(14) : 0, RES_BQ = RES_B;
__device__ __forceinline__ bool reserved(int type, int b) { return type == IT_ATT ? b == 15 : type == IT_OP ? RES_OP && b == 14 : type == IT_BQ && b < RES_BQ; }
__device__ __forceinline__ int reserved_item(int cta) {
  const int h = cta / 3, j = cta - 3 * h, i = h + (j - 1) * 32;
  if (j == 0) return C_EARLY | IT_ATT << 16 | 15 << 8 | h;
  return i < RES_N ? C_TAIL | IT_OP << 16 | 14 << 8 | i : i - RES_N < RES_BQ * 6 ? C_TAIL | IT_BQ << 16 | ((i - RES_N) / 6) << 8 | (i - RES_N) % 6 : -1;
}
constexpr int LEAD1 = 12;
__device__ __forceinline__ int lead_item(int layer, int qa_end, int i) {
  if (layer == 2) return i < 128 ? C_EARLY | C_LATE | IT_OUT << 16 | (i >> 3) << 8 | (i & 7) : -1;
  if (layer == 0) {
    if (i < 32) return IT_LN0 << 16 | (i >> 4) << 8 | (i & 15);
    if (i < 88) return IT_LN0 << 16 | ((i - 24) >> 2) << 8 | (i & 3);
    i -= 88;
  } else {
    if (i < 4) return C_EARLY | IT_BO << 16 | (i >> 1) << 8 | (i & 1);
    if (i < 12) return C_EARLY | IT_LN << 16 | ((i - 4) >> 2) << 8 | (i & 3);
    if (i < 40) return C_EARLY | IT_BO << 16 | ((i - 8) >> 1) << 8 | (i & 1);
    if (i < 96) return C_EARLY | IT_LN << 16 | ((i - 32) >> 2) << 8 | (i & 3);
    i -= 96;
  }
  return i < (16 - qa_end) * 32 ? C_PROJ | IT_Q << 16 | (qa_end + (i >> 5)) << 8 | (i & 31) : -1;
}

struct Ring {
  uint32_t sb;
  int pos, seq;
  __device__ __forceinline__ uint32_t full() const { return sb + WK_BAR + 8 * (seq & 7); }
  __device__ __forceinline__ uint32_t take(int len) { if (pos + len > WK_SLOTS) pos = 0; pos += len; seq++; return sb + (pos - len) * 8192; }
  __device__ __forceinline__ uint32_t wait(int len) { mbar_wait(full(), (seq >> 3) & 1); return take(len); }
  __device__ __forceinline__ void release(int sq) const { mbar_arrive_one(sb + WK_BAR + 64 + 8 * (sq & 7)); }
};

struct Pending {
  uint32_t w[48], done;
  uint4* dst;
  __device__ __forceinline__ void store(int i) const { dst[(i >> 2) * 1024 + (i & 3) * 32] = make_uint4(w[4 * i], w[4 * i + 1], w[4 * i + 2], w[4 * i + 3]); }
  __device__ __forceinline__ void finish() { __syncwarp(); mbar_arrive_one(done); done = 0; }
};

template <int N>
__device__ __forceinline__ void gemm_step(float* d, Ring& r, int warp, int acc) {
  const uint32_t base = r.wait(2 + (N + 63) / 64);
  const uint64_t da = mkdesc(base + (warp >> 2) * 8192, 128, 1024, 0), db = mkdesc(base + 16384, 8192, 1024, 1);
  wg_fence();
#pragma unroll
  for (int kk = 0; kk < 4; kk++) {
    if (N == 80) wg_ss80_01(d, da + kk * 16, db + kk * 128, acc | kk);
    else if (N == 160) wg_ss160_01(d, da + kk * 16, db + kk * 128, acc | kk);
    else wg_ss192_01(d, da + kk * 16, db + kk * 128, acc | kk);
    if (N == 320) wg_ss128_01(d + 96, da + kk * 16, db + kk * 128 + 3 * 512, acc | kk);
  }
  wg_commit();
}
template <int N>
__device__ __forceinline__ void gemm_item(float* d, Ring& r, int warp, int nkb, uint32_t go, int ask) {
#pragma unroll 1
  for (int kb = 0; kb < nkb; kb++) {
    gemm_step<N>(d, r, warp, kb);
    if (kb == ask && go && warp == 0) mbar_arrive_one(go);
    if (kb > 0) { wg_wait<1>(); r.release(r.seq - 2); }
  }
  wg_wait<0>();
  r.release(r.seq - 1);
}

template <class Peek>
__device__ __forceinline__ void attn_a(Ring& r, Pending& pend, Peek peek, const int warp, const int lane) {
  uint32_t (&q)[48] = pend.w;
  const int t = (warp & 1) * 16 + (lane >> 2) - 2 * (lane & 3);
  const bool second = warp & 2;
  const uint32_t rows = (warp >> 2) * 2 * KV_SEG;
  uint32_t pa[20], b2;
  float inv[2];
  bool now;
  const uint32_t b0 = r.wait(5) + rows, b1 = r.wait(5) + rows;
  {
    float s[40];
    wg_fence();
#pragma unroll
    for (int k = 0; k < 12; k++)
      wg_rs80_01(s, q[4 * k], q[4 * k + 1], q[4 * k + 2], q[4 * k + 3], mkdesc(k < 8 ? b0 : b1, 128, 1024, 0) + (k >> 2 & 1) * (KV_PART / 16) + (k & 3) * 16, k);
    wg_commit();
    now = peek();
    b2 = r.wait(5) + rows;
    wg_wait<0>();
    reg_fence<40>(s);
    r.release(r.seq - 3);
    const float k2 = 0.07216878364870322f * 1.44269504089f, NEG = -INFINITY;
#pragma unroll
    for (int i = 0; i < 20; i++) {
      s[i] = second ? s[20 + i] : s[i];
      if (i < 16 && 8 * ((i >> 2) - (i >> 1 & 1)) + (i & 1) > t) s[i] = NEG;
    }
#pragma unroll
    for (int hh = 0; hh < 2; hh++) {
      float m = NEG, l = 0.f;
#pragma unroll
      for (int n = 0; n < 5; n++) m = fmaxf(m, fmaxf(s[4 * n + 2 * hh], s[4 * n + 2 * hh + 1]));
      m = fmaxf(m, __shfl_xor_sync(~0u, m, 1)); m = fmaxf(m, __shfl_xor_sync(~0u, m, 2));
      m *= -k2;
#pragma unroll
      for (int n = 0; n < 5; n++) {
        const float x = ex2(fmaf(s[4 * n + 2 * hh], k2, m)), y = ex2(fmaf(s[4 * n + 2 * hh + 1], k2, m));
        const uint32_t w = pack2(x, y);
        l += x + y;
        pa[2 * n + hh] = second ? 0 : w; pa[10 + 2 * n + hh] = second ? w : 0;
      }
      inv[hh] = l;
    }
  }
  float o[96];
  wg_fence();
#pragma unroll
  for (int u = 0; u < 3; u++) {
#pragma unroll
    for (int k = 0; k < 5; k++)
      wg_rs64_00(o + 32 * u, pa[4 * k], pa[4 * k + 1], pa[4 * k + 2], pa[4 * k + 3], mkdesc(u ? b2 : b1, 1024, 128, 0) + (~u & 1) * (KV_PART / 16) + k * 128, k);
    wg_commit();
  }
#pragma unroll
  for (int hh = 0; hh < 2; hh++) { float l = inv[hh]; l += __shfl_xor_sync(~0u, l, 1); l += __shfl_xor_sync(~0u, l, 2); inv[hh] = rcp(l); }
#pragma unroll
  for (int u = 0; u < 3; u++) {
    if (u == 0) wg_wait<2>(); else if (u == 1) wg_wait<1>(); else wg_wait<0>();
    reg_fence<32>(o + 32 * u);
    if (u != 1) r.release(r.seq - 2 + u / 2);
#pragma unroll
    for (int i = 0; i < 16; i++) { const float* x = &o[32 * u + 4 * (i & 7) + (i >> 2 & 2)]; q[16 * u + i] = pack2(x[0] * inv[i >> 3], x[1] * inv[i >> 3]); }
    if (now) {
#pragma unroll
      for (int i = 0; i < 4; i++) pend.store(4 * u + i);
    }
  }
}

__device__ __forceinline__ void ln_groups(Ring& ring, uint32_t scratch, int planes, int rg, bool two) {
  constexpr int G = 2;
  const int warp = fresh_tid() >> 5, lane = fresh_tid() & 31;
  const uint32_t id = (lane >> 3) == (lane & 3) ? ((lane & 4) ? 0x3f800000u : 0x00003f80u) : 0u;
  const uint32_t at = (warp * 160 + lane) * 8, at1 = planes > 1 ? at : (lane >> 2) * 1280 + warp * 160 + (lane & 3) * 4;
  const uint32_t step = planes > 1 ? 256 : 32, half = planes > 1 ? 4 : 16;
  float v[G][5][4] = {};
#pragma unroll
  for (int r = 0; r < G; r++) {
#pragma unroll 1
    for (int k = r && !two ? 0 : planes; k > 0; k -= 4) {
      const uint32_t a = ring.wait(min(k, 4) + 1);
      if (k == 1) {
#pragma unroll
        for (int i = 0; i < 5; i++) mma8(v[r][i], lds32(a + at1 + i * step), lds32(a + at1 + i * step + half), id);
      } else {
#pragma unroll
        for (int i = 0; i < 10; i++) {
          if (i == 5 && k < 4) break;
          const uint2 x = lds64(a + at + i / 5 * 20480 + i % 5 * 256), y = lds64(a + at + i / 5 * 20480 + 10240 + i % 5 * 256);
          mma16(v[r][i % 5], x.x, x.y, y.x, y.y, id, id);
        }
      }
      ring.release(ring.seq - 1);
    }
  }
  uint2 xr[G][5];
  float mw[G];
  scratch += (lane >> 2) * 64;
#pragma unroll
  for (int r = 0; r < G; r++) {
    float m = 0.f, q2[4] = {};
#pragma unroll
    for (int i = 0; i < 5; i++) {
      float* t = v[r][i];
      xr[r][i] = make_uint2(pack2(t[0], t[1]), pack2(t[2], t[3]));
      t[0] = bf_lo(xr[r][i].x); t[1] = bf_hi(xr[r][i].x); t[2] = bf_lo(xr[r][i].y); t[3] = bf_hi(xr[r][i].y);
      m += (t[0] + t[1]) + (t[2] + t[3]);
    }
    m += __shfl_xor_sync(~0u, m, 1); m += __shfl_xor_sync(~0u, m, 2);
    m *= 1.f / 80;
#pragma unroll
    for (int i = 0; i < 20; i++) { float& t = v[r][i >> 2][i & 3]; t -= m; q2[i & 3] = fmaf(t, t, q2[i & 3]); }
    float q = (q2[0] + q2[1]) + (q2[2] + q2[3]);
    mw[r] = m;
    q += __shfl_xor_sync(~0u, q, 1); q += __shfl_xor_sync(~0u, q, 2);
    if ((lane & 3) == 0) sts64f(scratch + r * 512 + warp * 8, m, q);
  }
  bar_sync(1, 256);
#pragma unroll
  for (int r = 0; r < G; r++) {
    const float4 t = lds128f(scratch + r * 512 + (lane & 3) * 16);
    float mean = t.x + t.z;
    mean += __shfl_xor_sync(~0u, mean, 1); mean += __shfl_xor_sync(~0u, mean, 2);
    mean *= 0.125f;
    float var = (t.y + t.w) + 80.f * ((t.x - mean) * (t.x - mean) + (t.z - mean) * (t.z - mean));
    var += __shfl_xor_sync(~0u, var, 1); var += __shfl_xor_sync(~0u, var, 2);
    float rs;
    asm("rsqrt.approx.ftz.f32 %0, %1;" : "=f"(rs) : "f"(var * (1.f / DM) + 1e-5f));
#pragma unroll
    for (int i = 0; i < 20; i++) v[r][i >> 2][i & 3] = fmaf(v[r][i >> 2][i & 3], rs, (mw[r] - mean) * rs);
  }
#pragma unroll
  for (int r = 0; r < G; r++) {
    if (r && !two) break;
    uint32_t* xn = g_xn + (rg + r) * 2560 + warp * 320 + lane;
#pragma unroll
    for (int i = 0; i < 10; i++) xn[i * 32] = pack2(v[r][i >> 1][2 * (i & 1)], v[r][i >> 1][2 * (i & 1) + 1]);
#pragma unroll
    for (int i = 0; i < 5; i++) g_x[(rg + r) * 17 * 1280 + warp * 160 + i * 32 + lane] = xr[r][i];
  }
}

__device__ __forceinline__ void store_partial(const float* d, int b, int split, int unit, int nu) {
  uint2* dst = g_x + (((b * 16 + (fresh_tid() >> 5) * 2) * 17 + 1 + split) * 40 + unit) * 32 + (fresh_tid() & 31);
#pragma unroll
  for (int u = 0; u < 20; u++) {
    if ((u == 5 || u == 10) && nu == u) break;
    dst[u * 32] = make_uint2(pack2(d[8 * u], d[8 * u + 1]), pack2(d[8 * u + 4], d[8 * u + 5]));
    dst[(680 + u) * 32] = make_uint2(pack2(d[8 * u + 2], d[8 * u + 3]), pack2(d[8 * u + 6], d[8 * u + 7]));
  }
}

__device__ __forceinline__ void store_bqkv(const float* d, int b, int idx, int nh) {
  const int lane = fresh_tid() & 31, c = lane & 3, rg = b * 16 + (fresh_tid() >> 5) * 2, h0 = idx * nh;
  const float sc = h0 < 32 ? 0.22360679775f * 1.44269504089f : 1.f;
  const bool lo = c < 2;
  uint32_t* da = g_bqkv + (h0 * 256 + rg) * 96 + lane;
  uint32_t* db = da + 256 * 96 + (lo ? 2 : -2);
  uint32_t pad[2];
#pragma unroll
  for (int r = 0; r < 2; r++) pad[r] = !(c & 1) && (h0 >= 64 || (h0 >= 32 && (lane & 4) && poly_group(rg + r))) ? 0x00003f80u : 0u;
#pragma unroll
  for (int q = 0; q < 8; q++) {
    if ((q == 2 || q == 4) && nh == 2 * q) break;
#pragma unroll
    for (int r = 0; r < 2; r++) {
      uint32_t w[5];
#pragma unroll
      for (int i = 0; i < 5; i++) w[i] = pack2(d[20 * q + 4 * i + 2 * r] * sc, d[20 * q + 4 * i + 2 * r + 1] * sc);
      const int o = q * 2 * 256 * 96 + r * 96;
      da[o] = w[0]; da[o + 32] = w[1]; da[o + 64] = lo ? w[2] : pad[r];
      db[o] = lo ? w[3] : w[2]; db[o + 32] = lo ? w[4] : w[3]; db[o + 64] = lo ? pad[r] : w[4];
    }
  }
}

__device__ __forceinline__ void work_loader(const WorkParams& p, const uint32_t sb, const bool weights) {
  const uint32_t bars = sb + WK_BAR, bIF = bars + 128, bIE = bars + 160, bGo = bars + 224, slots = bars + 272;
  int pos = 0, seq = 0, tail = 0, used = 0;
  uint32_t lens = 0, tn = clk64();
  if (p.kind == WK_CHAIN) {
    seq = 1; used = lens = 8;
    mbar_arrive_one(bars);
  }
#pragma unroll 1
  for (int n = 0, part = 0;;) {
    if (part == 0) mbar_wait(bIF + 8 * (n & 3), (n >> 2) & 1);
    const int code = __shfl_sync(~0u, (int)lds32(slots + 4 * (n & 3)), 0);
    if (code < 0) break;
    const int type = (code >> 16) & 15, b = (code >> 8) & 255, idx = code & 255;
    const bool qa = code & C_PROJ, ln = type == IT_FIN || type == IT_LN || type == IT_LN0;
    const int parts = ln ? item_groups(type, b) : type == IT_ATT ? 2 : 1;
    {
      int bytes = 163840, chunk = 40960, nb = 0, flag = b * 8 + 4 + type, need = item_need(type & 3, b), c0 = 0, c3 = idx, c4 = 0, s3 = 0, s4 = 64;
      const uint8_t* src = g_kv + (b * 32 + idx) * 6 * KV_PART;
      const CUtensorMap* m = nullptr;
      if (ln) {
        const int rg = b * 16 + idx * parts + part;
        bytes = (type == IT_FIN ? op_split(b) + 1 : type == IT_LN ? 2 : 1) * 10240;
        src = type == IT_LN0 ? reinterpret_cast<const uint8_t*>(p.x) + rg * 10240 : reinterpret_cast<const uint8_t*>(g_x) + rg * 174080;
        if (type == IT_LN) { flag = SY_P + b * 4; need = 2; }
        if (type == IT_LN0 || part) need = 0;
      } else if (part) {
        bytes = 6 * KV_PART;
      } else if (type == IT_ATT && !qa) {
        bytes = chunk = 49152;
        src = reinterpret_cast<const uint8_t*>(g_q) + (b * 32 + idx) * 49152;
        flag = SY_P + b * 4 + 3; need = 32;
      } else {
        const int cols = item_cols(type, b);
        chunk = 16384; nb = (cols + 63) >> 6;
        src = reinterpret_cast<const uint8_t*>(g_of) + b * 163840;
        if (type == IT_OP) {
          const int nkb = op_steps(b), kb0 = (idx >> op_shift(b)) * nkb;
          bytes = nkb * 16384;
          src = reinterpret_cast<const uint8_t*>(g_o) + (b * 96 + kb0) * 16384;
          if (weights) m = &p.wo;
          c0 = (idx & (op_tiles(b) - 1)) * cols; c3 = 0; c4 = kb0 * 2; s4 = 2;
        } else if (type == IT_BQ) {
          m = weights ? &p.wb[cols >> 7] : &p.xn;
        } else if (type == IT_BO || type == IT_OUT) {
          if (weights) m = &p.wc[cols >> 8];
          flag = SY_OB; need = type == IT_BO && b < 2 ? 32 : -1;
        } else {
          m = weights ? &p.wq : &p.xn;
          c3 = 0; c4 = idx * 3; s3 = 64; s4 = 0;
          flag = SY_P + b * 4 + 1; need = ln_items(p.ch.layer, b);
        }
      }
      if (!weights) {
        c3 = b * 16; c4 = s3 = s4 = 0;
        if (need < 0) pdl_wait(); else if (need) { wait_count(p.sync + flag, need); EV(code, 2); }
        if ((ln ? !part : part && (!qa || (code & C_EARLY)))) mbar_arrive_one(bGo);
      }
      if (++part == parts) { mbar_arrive_one(bIE + 8 * (n & 3)); part = 0; n++; }
      const int pace = code & C_TAIL ? 0 : p.pace;
      const int boxes = weights && !s3 ? nb : m != nullptr;
#pragma unroll 1
      for (; bytes > 0; bytes -= chunk) {
        const int now = min(bytes, chunk), len = ((now + 8191) >> 13) + nb, skip = pos + len > WK_SLOTS ? WK_SLOTS - pos : 0, sh = 4 * (seq & 7);
        used += len + skip;
        while (used > WK_SLOTS || seq - tail >= 8) {
          mbar_wait(bars + 64 + 8 * (tail & 7), (tail >> 3) & 1);
          used -= (lens >> 4 * (tail & 7)) & 15;
          tail++;
        }
        lens = (lens & ~(15u << sh)) | (len + skip) << sh;
        if (pos + len > WK_SLOTS) pos = 0;
        const uint32_t bar = bars + 2 * sh, dst = sb + pos * 8192 + weights * 16384;
        if (pace) { until(tn); tn = clk64() + len * pace; }
        mbar_expect_one(bar, weights ? nb * 8192 : now);
#pragma unroll 1
        for (int i = 0; i < boxes; i++)
          tma_load5_one(dst + i * 8192, m, c0 + i * 64, c3, c4, bar);
        if (!weights && !m) bulk_load_last_one(dst, src, now, bar);
        c3 += s3; c4 += s4;
        if (!weights) c0 += 128;
        src += chunk; pos += len; seq++;
      }
    }
  }
}

__global__ void __launch_bounds__(384, 1) work_kernel(const __grid_constant__ WorkParams p) {
  extern __shared__ __align__(1024) uint8_t smem_raw[];
  const uint32_t sb = s2u(smem_raw), bars = sb + WK_BAR;
  const uint32_t bIF = bars + 128, bIE = bars + 160, done = bars + 192, bGo = bars + 224, slots = bars + 272, scratch = bars + 384;
  const int warp = __shfl_sync(~0u, threadIdx.x >> 5, 0);
  uint32_t* const sync = p.sync;
  TRACE(0);
  pdl_launch();
  if (p.kind == WK_LEAD && !helper_sm() && __any_sync(~0u, __syncthreads_or(threadIdx.x == 0 && ldg_strong32(sync + SY_PRE + 1) >= LEAD1))) { pdl_wait(); return; }
  if (p.kind == WK_CHAIN) {
    chain_start(p.ch, sb, warp);
  } else {
    if (warp < 4) work_init(sb, warp);
    __syncthreads();
    if (p.kind == WK_FIRST) {
      if (!(warp & 13)) probe_slots(bars + 320);
      if (!helper_sm()) return;
    }
  }
  if (warp >= 8) {
    asm volatile("setmaxnreg.dec.sync.aligned.u32 40;");
    if (p.kind == WK_CHAIN) chain_comm(p.ch, sb, &p.wo);
    const int warp = __shfl_sync(~0u, fresh_tid() >> 5, 0), lane = fresh_tid() & 31;
    if (warp == 9) {
      const bool keep = p.kind > WK_LEAD || helper_sm();
      int n = 0, code = p.kind == WK_CHAIN ? reserved_item(blockIdx.x) : -1;
      if (code >= 0) {
        sts32(slots, code);
        mbar_arrive_one(bIF);
        n = 1;
      }
      const int b = lane & 15, layer = p.kind == WK_LAST ? 2 : sync != g_sync;
      bool first = layer == 1, lead = p.kind != WK_CHAIN;
      for (;; n++) {
        if (n > 0) mbar_wait(bGo, (n - 1) & 1);
        mbar_wait(bIE + 8 * (n & 3), ((n >> 2) & 1) ^ 1);
        code = -1;
        if (lead) {
          int i = blockIdx.x + n * 256;
          if (first) { i = __reduce_add_sync(~0u, atomic_inc_one(sync + SY_PRE + 1)); first = i < LEAD1; }
          if (layer < 2 && !first) {
            i = 1 << 20;
            if (keep) i = __reduce_add_sync(~0u, atomic_inc_one(sync + SY_PRE)) + layer * LEAD1; else pdl_wait();
          }
          code = lead_item(layer, p.qa_end, i);
          lead = code >= 0 || layer == 2 || !keep;
          if (!lead && p.kind <= WK_LEAD) {
            const uint32_t t0 = gtime();
            while (!lead && __all_sync(~0u, ldg_strong32(sync + SY_UP) < 96)) lead = __any_sync(~0u, gtime() - t0 > 20000);
          }
        }
        if (!lead) {
          int spin = 0;
          const int ticket = atomic_inc_one(sync + SY_T);
          for (;;) {
            const uint4 hd = ldg_strong128(sync + b * 8), pr = ldg_strong128(sync + b * 8 + 4);
            const uint32_t hv[4] = {hd.x, hd.y, hd.z, hd.w}, pv[4] = {pr.x, pr.y, pr.z, pr.w};
            const uint32_t chain_done = __ballot_sync(~0u, (pr.x & 0xffff) >= 96) | (p.kind == WK_CHAIN) << 15;
            int left[4], avail[4], rdy = 0, claimed = 0, upstream = 0;
#pragma unroll
            for (int t = 0; t < 4; t++) {
              const int cnt = lane < 16 && !reserved(t, b) ? item_count(t, b) : 0;
              left[t] = max(cnt - (int)hv[t], 0);
              claimed += cnt - left[t];
              const bool ready = (pv[t] & 0xffff) >= item_need(t, b);
              rdy |= ready << t;
              bool ok = ready || (t != IT_ATT && (chain_done >> 15 & 1) && !left[t - 1] && (t < 2 || !left[t - 2]));
              if (t == IT_BQ && (chain_done >> HOLD_B & 1) && !(chain_done >> 15 & 1)) ok = false;
              avail[t] = ok ? left[t] : 0;
              upstream |= __any_sync(~0u, left[t] > 0);
            }
            if (!upstream) { code = -1; break; }
            int rank = max(__reduce_add_sync(~0u, ticket - claimed), 0), type = -1, mine = 0;
#pragma unroll
            for (int c = 0; c < 7; c++) {
              const int t = c == 0 || c == 6 ? IT_ATT : c == 1 || c == 4 ? IT_FIN : c == 2 ? IT_OP : IT_BQ;
              int a = c == 2 || (rdy >> t & 1) == (c < 4) ? avail[t] : 0;
              if (c == 6) a = b < p.qa_end && !(rdy & 1) && ((chain_done << 1 | 1) >> b & 1) ? left[t] : 0;
              const int tot = __reduce_add_sync(~0u, a);
              if (type < 0) { if (rank < tot) { type = t; mine = a; } else rank -= tot; }
            }
            if (type >= 0) {
#pragma unroll
              for (int o = 1; o < 16; o <<= 1) { const int y = __shfl_up_sync(~0u, mine, o); if (lane >= o) mine += y; }
              const int blk = __ffs(__ballot_sync(~0u, mine > rank)) - 1;
              const int early = !(__shfl_sync(~0u, rdy, blk) >> type & 1);
              const uint32_t idx = __reduce_add_sync(~0u, atomic_inc_one(sync + blk * 8 + type));
              if (idx < item_count(type, blk)) { code = (type == IT_ATT && blk < p.qa_end) << 23 | (chain_done >> 14 & 1) << 22 | early << 20 | type << 16 | blk << 8 | idx; break; }
            } else {
              __nanosleep(50);
            }
            spin_guard(spin);
          }
        }
        sts32(slots + 4 * (n & 3), code);
        mbar_arrive_one(bIF + 8 * (n & 3));
        if (code < 0) break;
      }
    } else if (warp >= 10) {
      work_loader(p, sb, warp == 10);
    } else {
      for (int n = 0;; n++) {
        mbar_wait(bIF + 8 * (n & 3), (n >> 2) & 1);
        const int code = __shfl_sync(~0u, (int)lds32(slots + 4 * (n & 3)), 0);
        if (code < 0) break;
        const int type = (code >> 16) & 15, b = (code >> 8) & 255;
        mbar_wait(done + 8 * (n & 3), (n >> 2) & 1);
        const uint32_t t_done = gtime();
        if (elect()) {
          if (type != IT_OUT) red_release(sync + (type < IT_BQ ? b * 8 + 5 + type : SY_P + b * 4 + ((0x13102 >> 4 * (type - IT_BQ)) & 3)), 1);
          mbar_arrive(bIE + 8 * (n & 3));
          EV(code, 1);
        }
        __syncwarp();
      }
    }
  } else {
    asm volatile("setmaxnreg.inc.sync.aligned.u32 232;");
    if (p.kind == WK_CHAIN) chain_compute(p.ch, sb);
    const int warp = __shfl_sync(~0u, fresh_tid() >> 5, 0), lane = fresh_tid() & 31;
    Ring r{sb, 0, p.kind == WK_CHAIN};
    int nln = 0;
#pragma unroll 1
    for (int n = 0;; n++) {
      mbar_wait(bIF + 8 * (n & 3), (n >> 2) & 1);
      int code = __shfl_sync(~0u, (int)lds32(slots + 4 * (n & 3)), 0);
      if (code < 0) { TRACE(2); break; }
      if (((code >> 16) & 15) == IT_ATT || (code & C_PROJ)) {
        Pending pend = {};
#pragma unroll 1
        for (;; n++) {
          const int tile = (((code >> 8) & 255) * 32 + (code & 255)) * 3072 + warp * 128;
          int next = 0;
          auto peek = [&]() {
            uint32_t here;
            asm volatile("{.reg .pred p; mbarrier.test_wait.parity.shared::cta.b64 p, [%1], %2; selp.u32 %0, -1, 0, p;}" : "=r"(here) : "r"(bIF + 8 * ((n + 1) & 3)), "r"(((n + 1) >> 2) & 1) : "memory");
            next = __shfl_sync(~0u, (int)(lds32(slots + 4 * ((n + 1) & 3) + (here & p.ch.zero)) & here), 0);
            return next < C_PROJ;
          };
          ITEM(code & 0xfffff, 0);
          if (code & C_PROJ) {
            float d[96];
            ITEM(9 << 16 | (code & 0xffff), 0);
            gemm_step<192>(d, r, warp, 0);
#pragma unroll 1
            for (int kb = 1; kb < 10; kb++) {
              gemm_step<192>(d, r, warp, 1);
              if (kb == 4 && (code & (C_EARLY | 15 << 16)) != C_EARLY && warp == 0) mbar_arrive_one(bGo);
              if (pend.done) {
#pragma unroll
                for (int i = 0; i < 12; i++) if (kb == 1 + i / 2) pend.store(i);
                if (kb == 6) pend.finish();
              }
              wg_wait<1>();
              r.release(r.seq - 2);
            }
            wg_wait<0>();
            reg_fence<96>(d);
            r.release(r.seq - 1);
            ITEM(9 << 16 | (code & 0xffff), 1);
#pragma unroll
            for (int i = 0; i < 48; i++) pend.w[i] = pack2(d[2 * i], d[2 * i + 1]);
          } else {
            const uint32_t base = r.wait(6) + warp * 2048 + lane * 16;
#pragma unroll
            for (int i = 0; i < 12; i++) {
              const uint4 t = lds128(base + (i >> 2) * 16384 + (i & 3) * 512);
              pend.w[4 * i] = t.x; pend.w[4 * i + 1] = t.y; pend.w[4 * i + 2] = t.z; pend.w[4 * i + 3] = t.w;
            }
            __syncwarp();
            r.release(r.seq - 1);
          }
          if (code & 15 << 16) {
            pend.dst = g_q + tile + lane;
            if (peek()) {
#pragma unroll
              for (int i = 0; i < 12; i++) pend.store(i);
            }
          } else {
            pend.dst = g_o + tile + (lane & 3) * 8 + (lane >> 2);
            attn_a(r, pend, peek, warp, lane);
          }
          pend.done = done + 8 * (n & 3);
          ITEM(code & 0xfffff, 1);
          if (next < C_PROJ) break;
          code = next;
        }
        pend.finish();
      } else {
        const int type = (code >> 16) & 15, b = (code >> 8) & 255, idx = code & 255;
        const uint32_t go = code & C_LATE ? 0 : bGo;
        ITEM(code & 0xfffff, 0);
        if (type == IT_FIN || type == IT_LN || type == IT_LN0) {
          const int ng = item_groups(type, b);
          const int planes = type == IT_FIN ? op_split(b) + 1 : type == IT_LN ? 2 : 1;
#pragma unroll 1
          for (int i = 0; i < ng; i += 2) ln_groups(r, scratch + (nln++ & 1) * 1024, planes, b * 16 + idx * ng + i, ng > 1);
        } else {
          const int cols = item_cols(type, b), nkb = type == IT_OP ? op_steps(b) : 10;
          float d[160] = {};
          if (type == IT_OUT) {
            const uint2* x = g_x + ((b * 16 + warp * 2) * 680 + idx * 5) * 32 + lane;
#pragma unroll
            for (int i = 0; i < 10; i++) { const uint2 y = __ldcg(x + (i / 5 * 680 + i % 5) * 32); d[40 + 2 * i] = __uint_as_float(y.x); d[41 + 2 * i] = __uint_as_float(y.y); }
          }
          reg_fence<160>(d);
          if (type != IT_OUT) ITEM((type == IT_BQ ? 10 : 11) << 16 | (code & 0xffff), 0);
          const int ask = max(nkb - ((code & C_TAIL ? GO_TAIL : GO_320) << (2 - (cols >> 7))), 0);
          if (cols == 320) gemm_item<320>(d, r, warp, nkb, go, ask);
          else if (cols == 160) gemm_item<160>(d, r, warp, nkb, go, ask);
          else gemm_item<80>(d, r, warp, nkb, go, ask);
          if (type != IT_OUT) ITEM((type == IT_BQ ? 10 : 11) << 16 | (code & 0xffff), 1);
          reg_fence<160>(d);
          if (type == IT_OUT) {
            bar_sync(1, 256);
            const uint32_t dst = sb + (warp * 16 + (lane & 15)) * 160 + (lane >> 4) * 16;
#pragma unroll
            for (int u = 0; u < 5; u++) {
              uint32_t w[4];
#pragma unroll
              for (int i = 0; i < 4; i++) { const uint32_t y = __float_as_uint(d[40 + (i & 1) * 10 + 2 * u + (i >> 1)]); w[i] = pack2(bf_lo(y) + d[8 * u + 2 * i], bf_hi(y) + d[8 * u + 2 * i + 1]); }
              stsm4(dst + u * 32, w[0], w[1], w[2], w[3]);
            }
            fence_async();
            __syncwarp();
            if (elect()) { tma_store(&p.out, sb + warp * 2560, idx * 80, b * 128 + warp * 16); bulk_commit(); bulk_wait<0>(); }
          } else {
            if (warp >= 4) bar_sync(7, 256);
            if (type == IT_BQ) store_bqkv(d, b, idx, 4 << (cols >> 7));
            else { const int sh = 3 - (cols >> 7); store_partial(d, b, idx >> sh, (idx & ((1 << sh) - 1)) * (cols >> 4), cols >> 4); }
            if (warp < 4) bar_arrive(7, 256);
          }
        }
        __syncwarp();
        mbar_arrive_one(done + 8 * (n & 3));
        if ((code & C_LATE) && warp == 4) mbar_arrive_one(bGo);
        ITEM(code & 0xfffff, 1);
      }
    }
  }
}

constexpr int AB_SMEM = 1024 + 2 * 98304 + 256 + 5 * 6144;
#define AB_N 32
constexpr int AB_T = 512;
#define AB_NS 4300
__device__ __forceinline__ float ex2_poly(float t) {
  const uint32_t r = __float_as_uint(t) & 0xffff8000u;
  const float f = t - __uint_as_float(r);
  const float p = fmaf(fmaf(fmaf(-5.869912678e-38f, f, -1.700740250e-37f), f, -5.234869734e-37f), f, -7.522601252e-37f);
  uint32_t y;
  asm("mad.lo.u32 %0, %1, 256, %2;" : "=r"(y) : "r"(r), "r"(__float_as_uint(p)));
  return __uint_as_float(y);
}
__device__ __forceinline__ uint32_t hsq(uint32_t w, uint32_t c) { uint32_t r; asm("fma.rn.bf16x2 %0, %1, %1, %2;" : "=r"(r) : "r"(w), "r"(c)); return r; }
__device__ __forceinline__ float sq2(uint32_t w) { const float a = bf_lo(w), b = bf_hi(w); return fmaf(a, a, b * b); }

__device__ __forceinline__ void attn_b_store(const float* o, int h, int row0, int lane) {
  const int g = lane >> 2, c = lane & 3;
  const float i0 = rcp(__shfl_sync(~0u, o[8], (lane & ~3) | 2)), i1 = rcp(__shfl_sync(~0u, o[10], (lane & ~3) | 2));
#pragma unroll
  for (int jj = 0; jj < 3; jj++) {
    if (jj < 2 || c < 2) {
      const int col = h * 20 + 8 * jj + 2 * c;
      g_of[core_word(row0 + g, col)] = pack2(o[4 * jj] * i0, o[4 * jj + 1] * i0);
      g_of[core_word(row0 + g + 8, col)] = pack2(o[4 * jj + 2] * i1, o[4 * jj + 3] * i1);
    }
  }
}

__device__ __forceinline__ void attn_b_qk(float* s, uint32_t q0, uint32_t q1, uint32_t q2, uint32_t q3, uint32_t q4, uint32_t q5, uint32_t z0, uint32_t z1,
                                          uint64_t dk, uint64_t dk2) {
  wg_rs32_00(s, q0, q1, q2, q3, dk, 0);
  wg_rs32_00(s, q4, q5, z0, z1, dk2, 1);
}

struct AttnParams { const uint8_t* pf[4]; uint32_t *sync, *next; };
__global__ void __launch_bounds__(AB_T + 128, 1) attn_b_kernel(const __grid_constant__ AttnParams p) {
  extern __shared__ uint8_t smem_raw[];
  const uint32_t sb = (s2u(smem_raw) + 1023) & ~1023u, sK = sb, sV = sb + 98304, bars = sb + 2 * 98304;
  const int warp = __shfl_sync(~0u, threadIdx.x >> 5, 0), lane = threadIdx.x & 31;
  const int h = blockIdx.x & 31, quarter = blockIdx.x >> 5;
  BT(0);
  TRACE(0);
  if (warp < 10 && elect()) {
    mbar_init(bars + 8 * warp + (warp & 8) * 8, warp < 8 ? 1 : warp == 8 ? AB_T / 32 : 3);
    asm volatile("fence.mbarrier_init.release.cluster;" ::: "memory");
  }
  __syncthreads();
  if (warp >= AB_T / 32) {
    asm volatile("setmaxnreg.dec.sync.aligned.u32 32;");
    if (warp == AB_T / 32 + 1) {
      mbar_wait(bars + 8 * quarter, 0);
      uint32_t t = gtime();
#pragma unroll 1
      for (int i = 0; i < 8; i++) {
        mbar_wait(bars + 8 * i, 0);
        const uint32_t now = gtime();
        t = ((int)(now - t) > 0 ? now : t) + AB_NS / 2;
      }
      uint32_t* ends = p.sync + SY_B + h * 4;
      if (lane == 0) stg_strong32(ends + quarter, t | 1);
      for (int spin = 0; t = ldg_strong32(ends + (lane & 3)), !__all_sync(~0u, t);) spin_guard(spin);
      int e = (int)(t - __shfl_sync(~0u, t, 0)) * 4 + (lane & 3), n = 0;
#pragma unroll 1
      for (int i = 0; i < 16; i++)
        if (e == __reduce_min_sync(~0u, e)) { e += 4 * AB_NS; n++; }
      const int first = 16 + __reduce_add_sync(~0u, lane < quarter ? n : 0);
      if (lane == quarter) { sts64(bars + 72, first, n); mbar_arrive(bars + 136); }
      return;
    }
    if (warp > AB_T / 32) {
      uint32_t kmax = 0;
#pragma unroll 1
      for (int i = 0; i < 32; i++) {
        if (!(i & 3)) mbar_wait(bars + 2 * i, 0);
        const uint32_t a = sK + i * 3072 + ((threadIdx.x >> 3) & 7) * 384 + (lane & 7) * 16;
        const uint4 x = lds128(a), y = lds128(a + 128);
        const uint2 z = lds64(a + 256);
        const uint32_t n = hadd2(hsq(x.x, hsq(x.y, hsq(x.z, hsq(x.w, hsq(z.x, 0))))), hsq(y.x, hsq(y.y, hsq(y.z, hsq(y.w, hsq(z.y, 0))))));
        kmax = max(kmax, __float_as_uint(bf_lo(n) + bf_hi(n)) & 0x7fffffffu);
      }
      const uint32_t kbits = __reduce_max_sync(~0u, kmax);
      if (lane == 0) { sts32(bars + 64 + (warp & 1) * 4, kbits); mbar_arrive(bars + 136); }
      return;
    }
    const uint8_t* gk = reinterpret_cast<const uint8_t*>(g_bqkv + (32 + h) * 256 * 96);
    const uint8_t* gv = reinterpret_cast<const uint8_t*>(g_bqkv + (64 + h) * 256 * 96);
    uint32_t todo = 255;
    for (int spin = 0; todo;) {
      const uint32_t up = __ballot_sync(~0u, ld_acquire(p.sync + SY_P + (lane & 15) * 4 + 2) >= bq_items(lane & 15));
      fence_async_global();
#pragma unroll 1
      for (int i = 0; i < 8; i++) {
        if (!(todo >> i & 1) || (up >> 2 * i & 3) != 3) continue;
        todo &= ~(1u << i);
        if (elect()) {
          mbar_expect(bars + 8 * i, 24576);
          bulk_load(sK + i * 12288, gk + i * 12288, 12288, bars + 8 * i);
          bulk_load(sV + i * 12288, gv + i * 12288, 12288, bars + 8 * i);
        }
      }
      spin_guard(spin);
    }
    pdl_launch();
    TRACE(1);
#pragma unroll 1
    for (int i = lane; i < 512 && blockIdx.x < NSLOT; i += 32) reinterpret_cast<uint4*>(pool_at(blockIdx.x * 8192))[i] = make_uint4(0, 0, 0, 0);
    if (!p.next && blockIdx.x < 8) { const int i = blockIdx.x * 32 + lane; g_smpart[i] = 0; if (i < NSLOT) g_orient[i] = 0; }
    if (p.next) {
#pragma unroll 1
      for (int i = 0; i < (PF_NS ? 32 : 0); i++) {
        if (elect()) prefetch_l2(p.pf[i >> 3] + blockIdx.x * 61440 + (i & 7) * 7680, 7680);
        __nanosleep(PF_NS);
      }
      mbar_wait(bars + 128, 0);
      if (quarter == 0 && lane == 0) red_release(p.next + SY_OB, 1);
    }
    return;
  }
  asm volatile("setmaxnreg.inc.sync.aligned.u32 112;");
  constexpr int NT = SEQ / AB_N, PER = 256 / AB_N;
  uint32_t qn[8];
  const int wg = warp >> 2;
  int tile = quarter * 4, left = 4, share = 0;
  auto load_q = [&]() {
    const uint32_t* gq = g_bqkv + (h * 256 + (tile + (wg >> share)) * 8 + (warp & 3) * 2) * 96 + lane;
#pragma unroll
    for (int i = 0; i < 8; i++) qn[i] = __ldcg(gq + (i & 1) * 96 + min(i >> 1, 2) * 32 + (i < 6 ? 0 : 3 - (lane & 3)));
  };
  mbar_wait(bars + 8 * quarter, 0);
  load_q();
#pragma unroll 1
  for (int pass = 0; left; pass++) {
    const int row0 = (tile + (wg >> share)) * 64 + (warp & 3) * 16, part = wg & ((1 << share) - 1), k0 = part * NT >> share, k1 = k0 + (NT >> share), group = share;
    const uint32_t q0 = qn[0], q1 = qn[1], q2 = qn[2], q3 = qn[3], z0 = qn[6], z1 = qn[7];
    uint32_t q4 = qn[4], q5 = qn[5];
    if ((lane & 3) == 2) { q4 = 0x43BCu; q5 = 0x43BCu; }
    float o[12] = {};
    reg_fence<12>(o);
    uint64_t dk = mkdesc(sK, 128, 384, 0), dk2 = mkdesc(sK + 256, 0, 384, 0), dv = mkdesc(sV, 384, 128, 0) + k0 * (AB_N * 3);
    float sa[AB_N / 2], sb2[AB_N / 2];
    uint32_t pa[AB_N / 4], pb[AB_N / 4];
    if (pass == 0) mbar_wait(bars, 0);
    BT(1 + 2 * min(pass, 1));
    wg_fence();
    attn_b_qk(sa, q0, q1, q2, q3, q4, q5, z0, z1, dk + k0 * (AB_N * 3), dk2 + k0 * (AB_N * 3));
    wg_commit();
    attn_b_qk(sb2, q0, q1, q2, q3, q4, q5, z0, z1, dk + (k0 + 1) * (AB_N * 3), dk2 + (k0 + 1) * (AB_N * 3));
    wg_commit();
    int kt = k0;
#pragma unroll 1
    do {
      const int nx = kt + 2 < NT ? kt + 2 : 0;
      if (pass == 0 && (nx & (PER - 1)) == 0) mbar_wait(bars + 8 * (nx / PER), 0);
      const uint64_t nk = dk + nx * (AB_N * 3), nk2 = dk2 + nx * (AB_N * 3);
      wg_wait<1>();
      reg_fence<AB_N / 2>(sa);
#pragma unroll
      for (int i = 0; i < AB_N / 4; i++) pa[i] = pack2(ex2(sa[2 * i]), poly_group(i >> 1) ? ex2_poly(sa[2 * i + 1]) : ex2(sa[2 * i + 1]));
      wg_fence();
#pragma unroll
      for (int kk = 0; kk < AB_N / 16; kk++) wg_rs24_01(o, pa[4 * kk], pa[4 * kk + 1], pa[4 * kk + 2], pa[4 * kk + 3], dv + kk * 48, 1);
      attn_b_qk(sa, q0, q1, q2, q3, q4, q5, z0, z1, nk, nk2);
      wg_commit();
      wg_wait<1>();
      reg_fence<AB_N / 2>(sb2);
#pragma unroll
      for (int i = 0; i < AB_N / 4; i++) pb[i] = pack2(ex2(sb2[2 * i]), poly_group((i >> 1) + AB_N / 8) ? ex2_poly(sb2[2 * i + 1]) : ex2(sb2[2 * i + 1]));
      wg_fence();
#pragma unroll
      for (int kk = 0; kk < AB_N / 16; kk++) wg_rs24_01(o, pb[4 * kk], pb[4 * kk + 1], pb[4 * kk + 2], pb[4 * kk + 3], dv + AB_N * 3 + kk * 48, 1);
      attn_b_qk(sb2, q0, q1, q2, q3, q4, q5, z0, z1, nk + AB_N * 3, nk2 + AB_N * 3);
      wg_commit();
      dv += AB_N * 6;
    } while ((kt += 2) < k1);
    wg_wait<0>();
    reg_fence<12>(o); reg_fence<AB_N / 2>(sa); reg_fence<AB_N / 2>(sb2);
    BT(2 + 2 * min(pass, 1));
    mbar_wait(bars + 136, 0);
    const uint4 kb = lds128(bars + 64);
    const float kmax = __uint_as_float(max(kb.x, kb.y));
    tile += 4 >> share; left -= 4 >> share;
    if (pass == 0) { tile = __shfl_sync(~0u, kb.z, 0); left = __shfl_sync(~0u, kb.w, 0); }
    share = left >= 4 ? 0 : left >= 2 ? 1 : 2;
    if (left) load_q();
    if (group) {
      const uint32_t slot = bars + 256 + (threadIdx.x & 127) * 16 + (group == 1 ? wg >> 1 : 2) * 6144;
      if (part) {
#pragma unroll
        for (int i = 0; i < 3; i++) sts128f(slot + (part - 1) * 6144 + i * 2048, o[4 * i], o[4 * i + 1], o[4 * i + 2], o[4 * i + 3]);
        bar_arrive(4 + group * 2 + (wg >> group), 128 << group);
        continue;
      }
      bar_sync(4 + group * 2 + (wg >> group), 128 << group);
#pragma unroll 1
      for (int u = 0; u < 2 * group - 1; u++) {
#pragma unroll
        for (int i = 0; i < 3; i++) { const float4 x = lds128f(slot + u * 6144 + i * 2048); o[4 * i] += x.x; o[4 * i + 1] += x.y; o[4 * i + 2] += x.z; o[4 * i + 3] += x.w; }
      }
    }
    if ((lane & 3) == 2) q4 = q5 = 0;
    float n0 = sq2(q0) + sq2(q2) + sq2(q4), n1 = sq2(q1) + sq2(q3) + sq2(q5);
    n0 += __shfl_xor_sync(~0u, n0, 1); n1 += __shfl_xor_sync(~0u, n1, 1);
    n0 += __shfl_xor_sync(~0u, n0, 2); n1 += __shfl_xor_sync(~0u, n1, 2);
    uint32_t redo;
    asm volatile("{.reg .pred p, q; setp.ne.u32 p, %1, 0; bar.red.or.pred q, %2, 128, p; selp.u32 %0, 1, 0, q;}"
                 : "=r"(redo) : "r"((uint32_t)!(n0 * kmax <= 9500.f && n1 * kmax <= 9500.f)), "r"(2 + (warp >> 2)) : "memory");
    if (redo) {
#pragma unroll
      for (int i = 0; i < 12; i++) o[i] = 0.f;
      float m0 = -INFINITY, m1 = -INFINITY;
#pragma unroll 1
      for (int kt = 0; kt < 64; kt++) {
        float s[16];
        wg_fence();
        wg_rs32_00(s, q0, q1, q2, q3, dk + kt * 96, 0);
        wg_rs32_00(s, q4, q5, z0, z1, dk2 + kt * 96, 1);
        wg_commit();
        wg_wait<0>();
        reg_fence<16>(s); reg_fence<12>(o);
        float n0 = m0, n1 = m1;
#pragma unroll
        for (int jj = 0; jj < 4; jj++) { n0 = fmaxf(n0, fmaxf(s[4 * jj], s[4 * jj + 1])); n1 = fmaxf(n1, fmaxf(s[4 * jj + 2], s[4 * jj + 3])); }
        n0 = fmaxf(n0, __shfl_xor_sync(~0u, n0, 1)); n0 = fmaxf(n0, __shfl_xor_sync(~0u, n0, 2));
        n1 = fmaxf(n1, __shfl_xor_sync(~0u, n1, 1)); n1 = fmaxf(n1, __shfl_xor_sync(~0u, n1, 2));
        const float r0 = ex2(m0 - n0), r1 = ex2(m1 - n1);
        m0 = n0; m1 = n1;
#pragma unroll
        for (int jj = 0; jj < 3; jj++) { o[4 * jj] *= r0; o[4 * jj + 1] *= r0; o[4 * jj + 2] *= r1; o[4 * jj + 3] *= r1; }
        uint32_t pp[8];
#pragma unroll
        for (int jj = 0; jj < 4; jj++) {
          pp[2 * jj] = pack2(ex2(s[4 * jj] - m0), ex2(s[4 * jj + 1] - m0));
          pp[2 * jj + 1] = pack2(ex2(s[4 * jj + 2] - m1), ex2(s[4 * jj + 3] - m1));
        }
        reg_fence<12>(o);
        wg_fence();
#pragma unroll
        for (int kk = 0; kk < 2; kk++) wg_rs24_01(o, pp[4 * kk], pp[4 * kk + 1], pp[4 * kk + 2], pp[4 * kk + 3], mkdesc(sV, 384, 128, 0) + kt * 96 + kk * 48, 1);
        wg_commit();
      }
      wg_wait<0>();
      reg_fence<12>(o);
    }
    attn_b_store(o, h, row0, lane);
    __syncwarp();
    if (pass == 0) mbar_arrive_one(bars + 128);
  }
  BT(5);
  TRACE(2);
}

typedef CUresult (*EncodeFn)(CUtensorMap*, CUtensorMapDataType, cuuint32_t, void*, const cuuint64_t*, const cuuint64_t*,
                             const cuuint32_t*, const cuuint32_t*, CUtensorMapInterleave, CUtensorMapSwizzle,
                             CUtensorMapL2promotion, CUtensorMapFloatOOBfill);

void make_map(EncodeFn enc, CUtensorMap* m, const void* ptr, int cols, int rows, int box_rows, int box_cols = 64) {
  const cuuint64_t dims[2] = {(cuuint64_t)cols, (cuuint64_t)rows};
  const cuuint64_t strides[1] = {(cuuint64_t)cols * 2};
  const cuuint32_t box[2] = {(cuuint32_t)box_cols, (cuuint32_t)box_rows}, es[2] = {1, 1};
  enc(m, CU_TENSOR_MAP_DATA_TYPE_BFLOAT16, 2, const_cast<void*>(ptr), dims, strides, box, es, CU_TENSOR_MAP_INTERLEAVE_NONE,
      box_cols == 64 ? CU_TENSOR_MAP_SWIZZLE_128B : box_cols == 32 ? CU_TENSOR_MAP_SWIZZLE_64B : CU_TENSOR_MAP_SWIZZLE_NONE, CU_TENSOR_MAP_L2_PROMOTION_L2_256B, CU_TENSOR_MAP_FLOAT_OOB_FILL_NONE);
}
void make_map5(EncodeFn enc, CUtensorMap* m, const void* ptr, bool words, const cuuint64_t (&dims)[5], const cuuint64_t (&strides)[4], const cuuint32_t (&box)[5]) {
  const cuuint32_t es[5] = {1, 1, 1, 1, 1};
  enc(m, words ? CU_TENSOR_MAP_DATA_TYPE_UINT64 : CU_TENSOR_MAP_DATA_TYPE_BFLOAT16, 5, const_cast<void*>(ptr), dims, strides, box, es, CU_TENSOR_MAP_INTERLEAVE_NONE,
      words ? CU_TENSOR_MAP_SWIZZLE_NONE : CU_TENSOR_MAP_SWIZZLE_128B, dims[0] % 64 ? CU_TENSOR_MAP_L2_PROMOTION_L2_128B : CU_TENSOR_MAP_L2_PROMOTION_L2_256B,
      CU_TENSOR_MAP_FLOAT_OOB_FILL_NONE);
}
void make_tiles(EncodeFn enc, CUtensorMap* m, const void* ptr, cuuint64_t cols, cuuint64_t tile) {
  make_map5(enc, m, ptr, false, {tile, 1, 1, cols / tile, DM}, {tile * 2, tile * 2, tile * 2, cols * 2}, {64, 1, 1, 1, 64});
}
template <class... KA, class... A>
void launch(void (*kern)(KA...), int grid, int block, int smem, int cluster, bool pdl, A... args) {
  cudaFuncSetAttribute(kern, cudaFuncAttributeMaxDynamicSharedMemorySize, smem);
  cudaLaunchConfig_t cfg = {};
  cfg.gridDim = dim3(grid); cfg.blockDim = dim3(block); cfg.dynamicSmemBytes = smem; cfg.stream = cudaStreamPerThread;
  cudaLaunchAttribute at[2];
  int n = 0;
  if (cluster > 1) { at[n].id = cudaLaunchAttributeClusterDimension; at[n].val.clusterDim.x = cluster; at[n].val.clusterDim.y = 1; at[n].val.clusterDim.z = 1; n++; }
  if (pdl) { at[n].id = cudaLaunchAttributeProgrammaticStreamSerialization; at[n].val.programmaticStreamSerializationAllowed = 1; n++; }
  cfg.attrs = at; cfg.numAttrs = n;
  cudaLaunchKernelEx(&cfg, kern, args...);
}
template <class T> void* sym(T& s) { void* p = nullptr; cudaGetSymbolAddress(&p, s); return p; }

}

#define MODE(b) 0
extern "C" void kernel_launch(void* const* d_in, const int* in_sizes, int n_in, void* d_out, int out_size) {
  const __nv_bfloat16* x = (const __nv_bfloat16*)d_in[0];
  void* fn = nullptr; cudaDriverEntryPointQueryResult qr;
  cudaGetDriverEntryPoint("cuTensorMapEncodeTiled", &fn, cudaEnableDefault, &qr);
  EncodeFn enc = (EncodeFn)fn;

  WorkParams wk = {};
  ChainParams& ch = wk.ch;
  AttnParams at = {};
  make_map(enc, &ch.wq, d_in[2], HD, DM, 160); make_map(enc, &ch.wk, d_in[3], HD, DM, 160); make_map(enc, &ch.wv, d_in[4], HD, DM, 160);
  make_map(enc, &ch.wo, d_in[5], DM, HD, 192, 32);
  ch.mem0 = (const __nv_bfloat16*)d_in[1];
  ch.wb = (const uint8_t*)d_in[8];
  ch.d1 = 250; ch.d2 = 200; ch.dn = 150; ch.dx = 1000;
  make_map5(enc, &wk.wq, d_in[2], false, {64, 1, 1, DM, HD / 64}, {128, 128, HD * 2, 128}, {64, 1, 1, 64, 3});
  for (int i = 0; i < 3; i++) make_tiles(enc, &wk.wb[i], d_in[8], 1920, 80 << i);
  for (int i = 0; i < 2; i++) make_tiles(enc, &wk.wc[i], d_in[9], DM, 80 << 2 * i);
  make_map(enc, &wk.out, d_out, DM, SEQ, 16, 80);
  make_map5(enc, &wk.wo, d_in[5], false, {DM, 2, 4, 4, HD / 32}, {DM * 2, DM * 16, DM * 4, DM * 64}, {64, 2, 4, 4, 2});
  make_map5(enc, &wk.xn, sym(g_xn), true, {1280, 1, 1, 256, 1}, {10240, 10240, 10240, 10240}, {128, 1, 1, 16, 1});
  make_map5(enc, &ch.xc, sym(g_xn), true, {160, 1, 1, 256, 8}, {1280, 1280, 10240, 1280}, {160, 1, 1, 4, 2});
  wk.x = x;
  for (int i = 0; i < 4; i++) at.pf[i] = (const uint8_t*)d_in[i < 2 ? 3 + i : i == 2 ? 2 : 5];
  int qa_end[2] = {12, 12}, pace = 85;
  for (int layer = 0; layer < 2; layer++) {
    ch.sync = wk.sync = at.sync = (uint32_t*)sym(g_sync) + layer * SY_N;
    ch.other = (uint32_t*)sym(g_sync) + (1 - layer) * SY_N;
    ch.layer = layer;
    at.next = layer ? nullptr : ch.other;
    wk.qa_end = qa_end[layer];
    wk.kind = layer ? WK_LEAD : WK_FIRST; wk.pace = pace;
    launch(work_kernel, 132, 384, CH_SMEM, 1, layer != 0, wk);
    wk.kind = WK_CHAIN; wk.pace = 0;
    launch(work_kernel, 96, 384, CH_SMEM, 3, true, wk);
    launch(attn_b_kernel, 128, AB_T + 128, AB_SMEM, 1, true, at);
  }
  wk.kind = WK_LAST;
  launch(work_kernel, 128, 384, CH_SMEM, 1, true, wk);
}
```

```cpp
#include <cuda_runtime.h>
#include <cuda_bf16.h>
#include <cuda.h>
#include <stdint.h>
#include <stdlib.h>

namespace {

constexpr int SEQ = 2048, DM = 640, HD = 6144, NSEG = 64;
constexpr int SPIN_LIMIT = 1 << 20;

__device__ __align__(128) uint2 g_x[256 * 17 * 1280];
__device__ __align__(128) uint32_t g_xn[SEQ * DM / 2];
__device__ __align__(128) uint32_t g_of[SEQ * DM / 2];
__device__ __align__(128) uint4 g_o[SEQ * HD / 8];
__device__ __align__(128) uint4 g_q[SEQ * HD / 8];
constexpr int KV_M = 4096, KV_SEG = 5120, KV_PART = 20480, KV_V = 3 * KV_PART;
__device__ __align__(128) uint8_t g_kv[16 * 32 * 6 * KV_PART];
#define OP_B8 11
#define OP_B16 13
#define OP_N4 14
#define BQ_12 13
#define BQ_24 16
#define FIN_16 12
#define OP_N8 16
#define OP_E16 14
__host__ __device__ constexpr int op_shift(int b) { return b < OP_N4 ? 1 : b < OP_N8 ? 2 : 3; }
__host__ __device__ constexpr int op_tiles(int b) { return 1 << op_shift(b); }
__host__ __device__ constexpr int op_split(int b) { return b < OP_B8 ? 4 : b < OP_B16 || b >= OP_E16 ? 8 : 16; }
__host__ __device__ constexpr int op_steps(int b) { return b < OP_B8 ? 24 : b < OP_B16 || b >= OP_E16 ? 12 : 6; }
__host__ __device__ constexpr int fin_items(int b) { return b < OP_B8 ? 4 : b < FIN_16 ? 8 : 16; }
__host__ __device__ constexpr int bq_items(int b) { return b < BQ_12 ? 6 : b < BQ_24 ? 12 : 24; }
__host__ __device__ constexpr int ln_items(int layer, int b) { return layer == 0 && b < 2 ? 16 : 4; }
constexpr int SY_P = 128, SY_T = 192, SY_UP = 224, SY_OB = 225, SY_PRE = 256, SY_PART = 288, SY_TIME = 384, SY_B = 448, SY_N = 576;
__device__ __align__(128) uint32_t g_sync[2 * SY_N];
constexpr int NSLOT = 92;
__device__ uint32_t g_pool[(NSLOT + 2) * 2048];
__device__ uint32_t g_smpart[256], g_orient[NSLOT];
__device__ __align__(128) uint32_t g_bqkv[3 * 32 * 256 * 96];

#define BT(i)
#define MISS(k, n)
#define PRO(i)
#define TRACE(w)
#define EV(code, w)
#define ITEM(code, w)
#define STAT(k)
#define TMV(i, v)
#define TM(i)
#define TMD(i, dep)

__device__ __forceinline__ uint32_t gtime() { uint32_t c; asm volatile("mov.u32 %0, %%globaltimer_lo;" : "=r"(c) :: "memory"); return c; }
__device__ __forceinline__ uint32_t clk32() { uint32_t c; asm volatile("mov.u32 %0, %%clock;" : "=r"(c) :: "memory"); return c; }
__device__ __forceinline__ uint32_t fresh_tid() { uint32_t t; asm volatile("mov.u32 %0, %%tid.x;" : "=r"(t)); return t; }
__device__ __forceinline__ uint32_t s2u(const void* p) { return (uint32_t)__cvta_generic_to_shared(p); }
__device__ __forceinline__ uint32_t pack2(float a, float b) {
  uint32_t r; asm("cvt.rn.bf16x2.f32 %0, %1, %2;" : "=r"(r) : "f"(b), "f"(a)); return r; }
__device__ __forceinline__ float bf_lo(uint32_t w) { return __uint_as_float(w << 16); }
__device__ __forceinline__ float bf_hi(uint32_t w) { return __uint_as_float(w & 0xffff0000u); }
__device__ __forceinline__ float ex2(float x) { float y; asm("ex2.approx.ftz.f32 %0, %1;" : "=f"(y) : "f"(x)); return y; }

__device__ __forceinline__ void mbar_init(uint32_t bar, uint32_t n) {
  asm volatile("mbarrier.init.shared::cta.b64 [%0], %1;" :: "r"(bar), "r"(n) : "memory"); }
__device__ __forceinline__ void mbar_expect(uint32_t bar, uint32_t bytes) {
  asm volatile("mbarrier.arrive.expect_tx.shared::cta.b64 _, [%0], %1;" :: "r"(bar), "r"(bytes) : "memory"); }
__device__ __forceinline__ void mbar_arrive(uint32_t bar) {
  asm volatile("mbarrier.arrive.shared::cta.b64 _, [%0];" :: "r"(bar) : "memory"); }
#define ONE "{.reg .pred one; elect.sync _|one, 0xffffffff; @one "
__device__ __forceinline__ void mbar_arrive_one(uint32_t bar) { asm volatile(ONE "mbarrier.arrive.shared::cta.b64 _, [%0];}" :: "r"(bar) : "memory"); }
__device__ __forceinline__ void mbar_expect_one(uint32_t bar, uint32_t bytes) {
  asm volatile(ONE "mbarrier.arrive.expect_tx.shared::cta.b64 _, [%0], %1;}" :: "r"(bar), "r"(bytes) : "memory"); }
__device__ __forceinline__ uint32_t atomic_inc_one(uint32_t* p) {
  uint32_t v = 0; asm volatile(ONE "atom.relaxed.gpu.global.add.u32 %0, [%1], 1;}" : "+r"(v) : "l"(p) : "memory"); return v; }
__device__ __forceinline__ void mbar_arrive_remote(uint32_t bar) {
  asm volatile("mbarrier.arrive.shared::cluster.b64 _, [%0];" :: "r"(bar) : "memory"); }
__device__ __forceinline__ void mbar_wait(uint32_t bar, uint32_t ph) {
  asm volatile("{.reg .pred p; .reg .u32 n; mov.u32 n, 0;\n"
               "W: mbarrier.try_wait.parity.shared::cta.b64 p, [%0], %1; @p bra.uni D;\n"
               "add.u32 n, n, 1; setp.gt.u32 p, n, %2; @p trap; bra.uni W;\n"
               "D: }" :: "r"(bar), "r"(ph), "n"(SPIN_LIMIT) : "memory");
}
__device__ __forceinline__ bool elect() {
  uint32_t p; asm volatile("{.reg .pred q; elect.sync _|q, 0xffffffff; selp.u32 %0, 1, 0, q;}" : "=r"(p)); return p; }
__device__ __forceinline__ void spin_guard(int& n) {
  asm volatile("{.reg .pred p; add.s32 %0, %0, 1; setp.gt.s32 p, %0, %1; @p trap;}" : "+r"(n) : "n"(SPIN_LIMIT));
}
__device__ __forceinline__ void pdl_wait() { asm volatile("griddepcontrol.wait;" ::: "memory"); TRACE(1); }
__device__ __forceinline__ void pdl_launch() { asm volatile("griddepcontrol.launch_dependents;" ::: "memory"); }
__device__ __forceinline__ uint32_t ld_acquire(const uint32_t* p) { uint32_t v; asm volatile("ld.acquire.gpu.global.u32 %0, [%1];" : "=r"(v) : "l"(p) : "memory"); return v; }
__device__ __forceinline__ void red_release(uint32_t* p, uint32_t v) { asm volatile("red.release.gpu.global.add.u32 [%0], %1;" :: "l"(p), "r"(v) : "memory"); }
__device__ __forceinline__ void fence_async_global() { asm volatile("fence.proxy.async.global;" ::: "memory"); }
__device__ __forceinline__ void fence_async() { asm volatile("fence.proxy.async.shared::cta;" ::: "memory"); }
__device__ __forceinline__ void bar_sync(int id, int n) { asm volatile("bar.sync %0, %1;" :: "r"(id), "r"(n) : "memory"); }
__device__ __forceinline__ void bar_arrive(int id, int n) { asm volatile("bar.arrive %0, %1;" :: "r"(id), "r"(n) : "memory"); }
__device__ __forceinline__ void tma_load(uint32_t dst, const CUtensorMap* m, int c0, int c1, uint32_t bar) {
  asm volatile("cp.async.bulk.tensor.2d.shared::cluster.global.mbarrier::complete_tx::bytes [%0], [%1, {%3, %4}], [%2];"
               :: "r"(dst), "l"(m), "r"(bar), "r"(c0), "r"(c1) : "memory"); }
__device__ __forceinline__ void tma_load5_one(uint32_t dst, const CUtensorMap* m, int c0, int c3, int c4, uint32_t bar) {
  asm volatile(ONE "cp.async.bulk.tensor.5d.shared::cluster.global.mbarrier::complete_tx::bytes [%0], [%1, {%3, %6, %6, %4, %5}], [%2];}"
               :: "r"(dst), "l"(m), "r"(bar), "r"(c0), "r"(c3), "r"(c4), "r"(0) : "memory"); }
__device__ __forceinline__ void tma_store(const CUtensorMap* m, uint32_t src, int c0, int c1) {
  asm volatile("cp.async.bulk.tensor.2d.global.shared::cta.bulk_group [%0, {%2, %3}], [%1];"
               :: "l"(m), "r"(src), "r"(c0), "r"(c1) : "memory"); }
__device__ __forceinline__ uint64_t evict_first() { uint64_t p; asm("createpolicy.fractional.L2::evict_first.b64 %0, 1.0;" : "=l"(p)); return p; }
__device__ __forceinline__ void bulk_load_last_one(uint32_t dst, const void* src, uint32_t bytes, uint32_t bar) {
  asm volatile(ONE "cp.async.bulk.shared::cluster.global.mbarrier::complete_tx::bytes.L2::cache_hint [%0], [%1], %2, [%3], %4;}"
               :: "r"(dst), "l"(src), "r"(bytes), "r"(bar), "l"(evict_first()) : "memory"); }
__device__ __forceinline__ void bulk_store_stream(void* dst, uint32_t src, uint32_t bytes) {
  asm volatile("cp.async.bulk.global.shared::cta.bulk_group.L2::cache_hint [%0], [%1], %2, %3;" :: "l"(dst), "r"(src), "r"(bytes), "l"(evict_first()) : "memory"); }
__device__ __forceinline__ void bulk_load(uint32_t dst, const void* src, uint32_t bytes, uint32_t bar) {
  asm volatile("cp.async.bulk.shared::cluster.global.mbarrier::complete_tx::bytes [%0], [%1], %2, [%3];"
               :: "r"(dst), "l"(src), "r"(bytes), "r"(bar) : "memory"); }
__device__ __forceinline__ void bulk_push(uint32_t dst, uint32_t src, uint32_t bytes, uint32_t bar) {
  asm volatile("cp.async.bulk.shared::cluster.shared::cta.mbarrier::complete_tx::bytes [%0], [%1], %2, [%3];"
               :: "r"(dst), "r"(src), "r"(bytes), "r"(bar) : "memory"); }
__device__ __forceinline__ void bulk_store(void* dst, uint32_t src, uint32_t bytes) {
  asm volatile("cp.async.bulk.global.shared::cta.bulk_group [%0], [%1], %2;" :: "l"(dst), "r"(src), "r"(bytes) : "memory"); }
__device__ __forceinline__ void bulk_commit() { asm volatile("cp.async.bulk.commit_group;" ::: "memory"); }
template <int N> __device__ __forceinline__ void bulk_wait_read() { asm volatile("cp.async.bulk.wait_group.read %0;" :: "n"(N) : "memory"); }
template <int N> __device__ __forceinline__ void bulk_wait() { asm volatile("cp.async.bulk.wait_group %0;" :: "n"(N) : "memory"); }

__device__ __forceinline__ uint64_t mkdesc(uint32_t addr, uint32_t lbo, uint32_t sbo, uint32_t sw) {
  return (uint64_t)((addr & 0x3FFFF) >> 4) | ((uint64_t)(lbo >> 4) << 16) | ((uint64_t)(sbo >> 4) << 32) | ((uint64_t)sw << 62); }
__device__ __forceinline__ void wg_fence() { asm volatile("wgmma.fence.sync.aligned;" ::: "memory"); }
__device__ __forceinline__ void wg_commit() { asm volatile("wgmma.commit_group.sync.aligned;" ::: "memory"); }
template <int N> __device__ __forceinline__ void wg_wait() { asm volatile("wgmma.wait_group.sync.aligned %0;" :: "n"(N) : "memory"); }
template <int N> __device__ __forceinline__ void reg_fence(float* d) {
#pragma unroll
  for (int i = 0; i < N; i++) asm volatile("" : "+f"(d[i]) :: "memory");
}

__device__ __forceinline__ void mma16(float* d, uint32_t a0, uint32_t a1, uint32_t a2, uint32_t a3, uint32_t b0, uint32_t b1) {
  asm volatile("mma.sync.aligned.m16n8k16.row.col.f32.bf16.bf16.f32 {%0,%1,%2,%3},{%4,%5,%6,%7},{%8,%9},{%0,%1,%2,%3};"
               : "+f"(d[0]), "+f"(d[1]), "+f"(d[2]), "+f"(d[3]) : "r"(a0), "r"(a1), "r"(a2), "r"(a3), "r"(b0), "r"(b1)); }
__device__ __forceinline__ void mma8(float* d, uint32_t a0, uint32_t a1, uint32_t b0) {
  asm volatile("mma.sync.aligned.m16n8k8.row.col.f32.bf16.bf16.f32 {%0,%1,%2,%3},{%4,%5},{%6},{%0,%1,%2,%3};"
               : "+f"(d[0]), "+f"(d[1]), "+f"(d[2]), "+f"(d[3]) : "r"(a0), "r"(a1), "r"(b0)); }
__device__ __forceinline__ void ldsm4(uint32_t* r, uint32_t a) {
  asm volatile("ldmatrix.sync.aligned.m8n8.x4.shared.b16 {%0,%1,%2,%3},[%4];" : "=r"(r[0]), "=r"(r[1]), "=r"(r[2]), "=r"(r[3]) : "r"(a) : "memory"); }
__device__ __forceinline__ uint4 ldsm4v(uint32_t a) { uint32_t r[4]; ldsm4(r, a); return make_uint4(r[0], r[1], r[2], r[3]); }
__device__ __forceinline__ void ldsm4t(uint32_t* r, uint32_t a) {
  asm volatile("ldmatrix.sync.aligned.m8n8.x4.trans.shared.b16 {%0,%1,%2,%3},[%4];" : "=r"(r[0]), "=r"(r[1]), "=r"(r[2]), "=r"(r[3]) : "r"(a) : "memory"); }
__device__ __forceinline__ void ldsm2(uint32_t* r, uint32_t a) {
  asm volatile("ldmatrix.sync.aligned.m8n8.x2.shared.b16 {%0,%1},[%2];" : "=r"(r[0]), "=r"(r[1]) : "r"(a) : "memory"); }
__device__ __forceinline__ void ldsm2t(uint32_t* r, uint32_t a) {
  asm volatile("ldmatrix.sync.aligned.m8n8.x2.trans.shared.b16 {%0,%1},[%2];" : "=r"(r[0]), "=r"(r[1]) : "r"(a) : "memory"); }
__device__ __forceinline__ void stsm4(uint32_t a, uint32_t r0, uint32_t r1, uint32_t r2, uint32_t r3) {
  asm volatile("stmatrix.sync.aligned.m8n8.x4.shared.b16 [%0], {%1,%2,%3,%4};" :: "r"(a), "r"(r0), "r"(r1), "r"(r2), "r"(r3) : "memory"); }
__device__ __forceinline__ void stsm4t(uint32_t a, uint32_t r0, uint32_t r1, uint32_t r2, uint32_t r3) {
  asm volatile("stmatrix.sync.aligned.m8n8.x4.trans.shared.b16 [%0], {%1,%2,%3,%4};" :: "r"(a), "r"(r0), "r"(r1), "r"(r2), "r"(r3) : "memory"); }
__device__ __forceinline__ void stsm2(uint32_t a, uint32_t r0, uint32_t r1) {
  asm volatile("stmatrix.sync.aligned.m8n8.x2.shared.b16 [%0], {%1,%2};" :: "r"(a), "r"(r0), "r"(r1) : "memory"); }
__device__ __forceinline__ void stsm2t(uint32_t a, uint32_t r0, uint32_t r1) {
  asm volatile("stmatrix.sync.aligned.m8n8.x2.trans.shared.b16 [%0], {%1,%2};" :: "r"(a), "r"(r0), "r"(r1) : "memory"); }
__device__ __forceinline__ void sts32(uint32_t a, uint32_t v) { asm volatile("st.shared.b32 [%0], %1;" :: "r"(a), "r"(v) : "memory"); }
__device__ __forceinline__ void sts64f(uint32_t a, float x, float y) { asm volatile("st.shared.v2.f32 [%0], {%1,%2};" :: "r"(a), "f"(x), "f"(y) : "memory"); }
__device__ __forceinline__ void sts128(uint32_t a, uint4 v) {
  asm volatile("st.shared.v4.b32 [%0], {%1,%2,%3,%4};" :: "r"(a), "r"(v.x), "r"(v.y), "r"(v.z), "r"(v.w) : "memory"); }
__device__ __forceinline__ void sts128f(uint32_t a, float x, float y, float z, float w) {
  asm volatile("st.shared.v4.f32 [%0], {%1,%2,%3,%4};" :: "r"(a), "f"(x), "f"(y), "f"(z), "f"(w) : "memory"); }
__device__ __forceinline__ float lds32f(uint32_t a) { float v; asm volatile("ld.shared.f32 %0, [%1];" : "=f"(v) : "r"(a) : "memory"); return v; }
__device__ __forceinline__ float2 lds64f(uint32_t a) { float2 v; asm volatile("ld.shared.v2.f32 {%0,%1}, [%2];" : "=f"(v.x), "=f"(v.y) : "r"(a) : "memory"); return v; }
__device__ __forceinline__ float4 lds128f(uint32_t a) {
  float4 v; asm volatile("ld.shared.v4.f32 {%0,%1,%2,%3}, [%4];" : "=f"(v.x), "=f"(v.y), "=f"(v.z), "=f"(v.w) : "r"(a) : "memory"); return v; }
__device__ __forceinline__ uint4 lds128(uint32_t a) {
  uint4 v; asm volatile("ld.shared.v4.b32 {%0,%1,%2,%3}, [%4];" : "=r"(v.x), "=r"(v.y), "=r"(v.z), "=r"(v.w) : "r"(a) : "memory"); return v; }
__device__ __forceinline__ uint4 ldg_strong128(const void* p) {
  uint4 v; asm volatile("ld.relaxed.gpu.global.v4.u32 {%0,%1,%2,%3}, [%4];" : "=r"(v.x), "=r"(v.y), "=r"(v.z), "=r"(v.w) : "l"(p) : "memory"); return v; }
__device__ __forceinline__ uint2 ldg_strong64(const void* p) {
  uint2 v; asm volatile("ld.relaxed.gpu.global.v2.u32 {%0,%1}, [%2];" : "=r"(v.x), "=r"(v.y) : "l"(p) : "memory"); return v; }
__device__ __forceinline__ void stg_strong32(void* p, uint32_t v) { asm volatile("st.relaxed.gpu.global.u32 [%0], %1;" :: "l"(p), "r"(v) : "memory"); }
__device__ __forceinline__ void stg_strong128(void* p, uint4 v) {
  asm volatile("st.relaxed.gpu.global.v4.u32 [%0], {%1,%2,%3,%4};" :: "l"(p), "r"(v.x), "r"(v.y), "r"(v.z), "r"(v.w) : "memory"); }
__device__ __forceinline__ uint32_t mapa(uint32_t a, uint32_t r) {
  uint32_t o; asm("mapa.shared::cluster.u32 %0, %1, %2;" : "=r"(o) : "r"(a), "r"(r)); return o; }
__device__ __forceinline__ void st_async2f(uint32_t a, float x, float y, uint32_t bar) {
  asm volatile("st.async.shared::cluster.mbarrier::complete_tx::bytes.v2.f32 [%0], {%1,%2}, [%3];" :: "r"(a), "f"(x), "f"(y), "r"(bar) : "memory"); }
__device__ __forceinline__ void st_async32(uint32_t a, uint32_t x, uint32_t bar) {
  asm volatile("st.async.shared::cluster.mbarrier::complete_tx::bytes.b32 [%0], %1, [%2];" :: "r"(a), "r"(x), "r"(bar) : "memory"); }
__device__ __forceinline__ uint32_t lds32(uint32_t a) { uint32_t v; asm volatile("ld.shared.b32 %0, [%1];" : "=r"(v) : "r"(a) : "memory"); return v; }
__device__ __forceinline__ void st_async64(uint32_t a, uint32_t x, uint32_t y, uint32_t bar) {
  asm volatile("st.async.shared::cluster.mbarrier::complete_tx::bytes.v2.b32 [%0], {%1,%2}, [%3];" :: "r"(a), "r"(x), "r"(y), "r"(bar) : "memory"); }
__device__ __forceinline__ void st_async128(uint32_t a, uint4 v, uint32_t bar) {
  asm volatile("st.async.shared::cluster.mbarrier::complete_tx::bytes.v4.b32 [%0], {%1,%2,%3,%4}, [%5];" :: "r"(a), "r"(v.x), "r"(v.y), "r"(v.z), "r"(v.w), "r"(bar) : "memory"); }
__device__ __forceinline__ uint2 lds64(uint32_t a) { uint2 v; asm volatile("ld.shared.v2.b32 {%0,%1}, [%2];" : "=r"(v.x), "=r"(v.y) : "r"(a) : "memory"); return v; }
__device__ __forceinline__ void sts64(uint32_t a, uint32_t x, uint32_t y) { asm volatile("st.shared.v2.b32 [%0], {%1,%2};" :: "r"(a), "r"(x), "r"(y) : "memory"); }
__device__ __forceinline__ uint32_t ldg_strong32(const void* p) { uint32_t v; asm volatile("ld.relaxed.gpu.global.u32 %0, [%1];" : "=r"(v) : "l"(p) : "memory"); return v; }
__device__ __forceinline__ uint32_t transpose8(uint32_t x) { uint32_t r; asm volatile("movmatrix.sync.aligned.m8n8.trans.b16 %0, %1;" : "=r"(r) : "r"(x)); return r; }
__device__ __forceinline__ uint32_t hadd2(uint32_t a, uint32_t b) { uint32_t r; asm("add.rn.bf16x2 %0, %1, %2;" : "=r"(r) : "r"(a), "r"(b)); return r; }
__device__ __forceinline__ uint32_t min4(uint4 v) { return min(__vimin3_u32(v.x, v.y, v.z), v.w); }

__device__ __forceinline__ void wg_ss192_01(float* d, uint64_t da, uint64_t db, int sd) {
  asm volatile("{.reg .pred p; setp.ne.b32 p, %98, 0;\n"
    "wgmma.mma_async.sync.aligned.m64n192k16.f32.bf16.bf16 {%0,%1,%2,%3,%4,%5,%6,%7,%8,%9,%10,%11,%12,%13,%14,%15,%16,%17,%18,%19,%20,%21,%22,%23,%24,%25,%26,%27,%28,%29,%30,%31,%32,%33,%34,%35,%36,%37,%38,%39,%40,%41,%42,%43,%44,%45,%46,%47,%48,%49,%50,%51,%52,%53,%54,%55,%56,%57,%58,%59,%60,%61,%62,%63,%64,%65,%66,%67,%68,%69,%70,%71,%72,%73,%74,%75,%76,%77,%78,%79,%80,%81,%82,%83,%84,%85,%86,%87,%88,%89,%90,%91,%92,%93,%94,%95}, %96, %97, p, 1, 1, 0, 1;}"
    : "+f"(d[0]),"+f"(d[1]),"+f"(d[2]),"+f"(d[3]),"+f"(d[4]),"+f"(d[5]),"+f"(d[6]),"+f"(d[7]),"+f"(d[8]),"+f"(d[9]),"+f"(d[10]),"+f"(d[11]),"+f"(d[12]),"+f"(d[13]),"+f"(d[14]),"+f"(d[15]),"+f"(d[16]),"+f"(d[17]),"+f"(d[18]),"+f"(d[19]),"+f"(d[20]),"+f"(d[21]),"+f"(d[22]),"+f"(d[23]),"+f"(d[24]),"+f"(d[25]),"+f"(d[26]),"+f"(d[27]),"+f"(d[28]),"+f"(d[29]),"+f"(d[30]),"+f"(d[31]),"+f"(d[32]),"+f"(d[33]),"+f"(d[34]),"+f"(d[35]),"+f"(d[36]),"+f"(d[37]),"+f"(d[38]),"+f"(d[39]),"+f"(d[40]),"+f"(d[41]),"+f"(d[42]),"+f"(d[43]),"+f"(d[44]),"+f"(d[45]),"+f"(d[46]),"+f"(d[47]),"+f"(d[48]),"+f"(d[49]),"+f"(d[50]),"+f"(d[51]),"+f"(d[52]),"+f"(d[53]),"+f"(d[54]),"+f"(d[55]),"+f"(d[56]),"+f"(d[57]),"+f"(d[58]),"+f"(d[59]),"+f"(d[60]),"+f"(d[61]),"+f"(d[62]),"+f"(d[63]),"+f"(d[64]),"+f"(d[65]),"+f"(d[66]),"+f"(d[67]),"+f"(d[68]),"+f"(d[69]),"+f"(d[70]),"+f"(d[71]),"+f"(d[72]),"+f"(d[73]),"+f"(d[74]),"+f"(d[75]),"+f"(d[76]),"+f"(d[77]),"+f"(d[78]),"+f"(d[79]),"+f"(d[80]),"+f"(d[81]),"+f"(d[82]),"+f"(d[83]),"+f"(d[84]),"+f"(d[85]),"+f"(d[86]),"+f"(d[87]),"+f"(d[88]),"+f"(d[89]),"+f"(d[90]),"+f"(d[91]),"+f"(d[92]),"+f"(d[93]),"+f"(d[94]),"+f"(d[95])
    : "l"(da), "l"(db), "r"(sd));
}
__device__ __forceinline__ void wg_ss128_01(float* d, uint64_t da, uint64_t db, int sd) {
  asm volatile("{.reg .pred p; setp.ne.b32 p, %66, 0;\n"
    "wgmma.mma_async.sync.aligned.m64n128k16.f32.bf16.bf16 {%0,%1,%2,%3,%4,%5,%6,%7,%8,%9,%10,%11,%12,%13,%14,%15,%16,%17,%18,%19,%20,%21,%22,%23,%24,%25,%26,%27,%28,%29,%30,%31,%32,%33,%34,%35,%36,%37,%38,%39,%40,%41,%42,%43,%44,%45,%46,%47,%48,%49,%50,%51,%52,%53,%54,%55,%56,%57,%58,%59,%60,%61,%62,%63}, %64, %65, p, 1, 1, 0, 1;}"
    : "+f"(d[0]),"+f"(d[1]),"+f"(d[2]),"+f"(d[3]),"+f"(d[4]),"+f"(d[5]),"+f"(d[6]),"+f"(d[7]),"+f"(d[8]),"+f"(d[9]),"+f"(d[10]),"+f"(d[11]),"+f"(d[12]),"+f"(d[13]),"+f"(d[14]),"+f"(d[15]),"+f"(d[16]),"+f"(d[17]),"+f"(d[18]),"+f"(d[19]),"+f"(d[20]),"+f"(d[21]),"+f"(d[22]),"+f"(d[23]),"+f"(d[24]),"+f"(d[25]),"+f"(d[26]),"+f"(d[27]),"+f"(d[28]),"+f"(d[29]),"+f"(d[30]),"+f"(d[31]),"+f"(d[32]),"+f"(d[33]),"+f"(d[34]),"+f"(d[35]),"+f"(d[36]),"+f"(d[37]),"+f"(d[38]),"+f"(d[39]),"+f"(d[40]),"+f"(d[41]),"+f"(d[42]),"+f"(d[43]),"+f"(d[44]),"+f"(d[45]),"+f"(d[46]),"+f"(d[47]),"+f"(d[48]),"+f"(d[49]),"+f"(d[50]),"+f"(d[51]),"+f"(d[52]),"+f"(d[53]),"+f"(d[54]),"+f"(d[55]),"+f"(d[56]),"+f"(d[57]),"+f"(d[58]),"+f"(d[59]),"+f"(d[60]),"+f"(d[61]),"+f"(d[62]),"+f"(d[63])
    : "l"(da), "l"(db), "r"(sd));
}
__device__ __forceinline__ void wg_ss160_01(float* d, uint64_t da, uint64_t db, int sd) {
  asm volatile("{.reg .pred p; setp.ne.b32 p, %82, 0;\n"
    "wgmma.mma_async.sync.aligned.m64n160k16.f32.bf16.bf16 {%0,%1,%2,%3,%4,%5,%6,%7,%8,%9,%10,%11,%12,%13,%14,%15,%16,%17,%18,%19,%20,%21,%22,%23,%24,%25,%26,%27,%28,%29,%30,%31,%32,%33,%34,%35,%36,%37,%38,%39,%40,%41,%42,%43,%44,%45,%46,%47,%48,%49,%50,%51,%52,%53,%54,%55,%56,%57,%58,%59,%60,%61,%62,%63,%64,%65,%66,%67,%68,%69,%70,%71,%72,%73,%74,%75,%76,%77,%78,%79}, %80, %81, p, 1, 1, 0, 1;}"
    : "+f"(d[0]),"+f"(d[1]),"+f"(d[2]),"+f"(d[3]),"+f"(d[4]),"+f"(d[5]),"+f"(d[6]),"+f"(d[7]),"+f"(d[8]),"+f"(d[9]),"+f"(d[10]),"+f"(d[11]),"+f"(d[12]),"+f"(d[13]),"+f"(d[14]),"+f"(d[15]),"+f"(d[16]),"+f"(d[17]),"+f"(d[18]),"+f"(d[19]),"+f"(d[20]),"+f"(d[21]),"+f"(d[22]),"+f"(d[23]),"+f"(d[24]),"+f"(d[25]),"+f"(d[26]),"+f"(d[27]),"+f"(d[28]),"+f"(d[29]),"+f"(d[30]),"+f"(d[31]),"+f"(d[32]),"+f"(d[33]),"+f"(d[34]),"+f"(d[35]),"+f"(d[36]),"+f"(d[37]),"+f"(d[38]),"+f"(d[39]),"+f"(d[40]),"+f"(d[41]),"+f"(d[42]),"+f"(d[43]),"+f"(d[44]),"+f"(d[45]),"+f"(d[46]),"+f"(d[47]),"+f"(d[48]),"+f"(d[49]),"+f"(d[50]),"+f"(d[51]),"+f"(d[52]),"+f"(d[53]),"+f"(d[54]),"+f"(d[55]),"+f"(d[56]),"+f"(d[57]),"+f"(d[58]),"+f"(d[59]),"+f"(d[60]),"+f"(d[61]),"+f"(d[62]),"+f"(d[63]),"+f"(d[64]),"+f"(d[65]),"+f"(d[66]),"+f"(d[67]),"+f"(d[68]),"+f"(d[69]),"+f"(d[70]),"+f"(d[71]),"+f"(d[72]),"+f"(d[73]),"+f"(d[74]),"+f"(d[75]),"+f"(d[76]),"+f"(d[77]),"+f"(d[78]),"+f"(d[79])
    : "l"(da), "l"(db), "r"(sd));
}
__device__ __forceinline__ void wg_ss80_01(float* d, uint64_t da, uint64_t db, int sd) {
  asm volatile("{.reg .pred p; setp.ne.b32 p, %42, 0;\n"
    "wgmma.mma_async.sync.aligned.m64n80k16.f32.bf16.bf16 {%0,%1,%2,%3,%4,%5,%6,%7,%8,%9,%10,%11,%12,%13,%14,%15,%16,%17,%18,%19,%20,%21,%22,%23,%24,%25,%26,%27,%28,%29,%30,%31,%32,%33,%34,%35,%36,%37,%38,%39}, %40, %41, p, 1, 1, 0, 1;}"
    : "+f"(d[0]),"+f"(d[1]),"+f"(d[2]),"+f"(d[3]),"+f"(d[4]),"+f"(d[5]),"+f"(d[6]),"+f"(d[7]),"+f"(d[8]),"+f"(d[9]),"+f"(d[10]),"+f"(d[11]),"+f"(d[12]),"+f"(d[13]),"+f"(d[14]),"+f"(d[15]),"+f"(d[16]),"+f"(d[17]),"+f"(d[18]),"+f"(d[19]),"+f"(d[20]),"+f"(d[21]),"+f"(d[22]),"+f"(d[23]),"+f"(d[24]),"+f"(d[25]),"+f"(d[26]),"+f"(d[27]),"+f"(d[28]),"+f"(d[29]),"+f"(d[30]),"+f"(d[31]),"+f"(d[32]),"+f"(d[33]),"+f"(d[34]),"+f"(d[35]),"+f"(d[36]),"+f"(d[37]),"+f"(d[38]),"+f"(d[39])
    : "l"(da), "l"(db), "r"(sd));
}
__device__ __forceinline__ void wg_rs32_00(float* d, uint32_t a0, uint32_t a1, uint32_t a2, uint32_t a3, uint64_t db, int sd) {
  asm volatile("{.reg .pred p; setp.ne.b32 p, %21, 0;\n"
    "wgmma.mma_async.sync.aligned.m64n32k16.f32.bf16.bf16 {%0,%1,%2,%3,%4,%5,%6,%7,%8,%9,%10,%11,%12,%13,%14,%15}, {%16,%17,%18,%19}, %20, p, 1, 1, 0;}"
    : "+f"(d[0]),"+f"(d[1]),"+f"(d[2]),"+f"(d[3]),"+f"(d[4]),"+f"(d[5]),"+f"(d[6]),"+f"(d[7]),"+f"(d[8]),"+f"(d[9]),"+f"(d[10]),"+f"(d[11]),"+f"(d[12]),"+f"(d[13]),"+f"(d[14]),"+f"(d[15])
    : "r"(a0), "r"(a1), "r"(a2), "r"(a3), "l"(db), "r"(sd));
}
__device__ __forceinline__ void wg_rs64_00(float* d, uint32_t a0, uint32_t a1, uint32_t a2, uint32_t a3, uint64_t db, int sd) {
  asm volatile("{.reg .pred p; setp.ne.b32 p, %37, 0;\n"
    "wgmma.mma_async.sync.aligned.m64n64k16.f32.bf16.bf16 {%0,%1,%2,%3,%4,%5,%6,%7,%8,%9,%10,%11,%12,%13,%14,%15,%16,%17,%18,%19,%20,%21,%22,%23,%24,%25,%26,%27,%28,%29,%30,%31}, {%32,%33,%34,%35}, %36, p, 1, 1, 0;}"
    : "+f"(d[0]),"+f"(d[1]),"+f"(d[2]),"+f"(d[3]),"+f"(d[4]),"+f"(d[5]),"+f"(d[6]),"+f"(d[7]),"+f"(d[8]),"+f"(d[9]),"+f"(d[10]),"+f"(d[11]),"+f"(d[12]),"+f"(d[13]),"+f"(d[14]),"+f"(d[15]),"+f"(d[16]),"+f"(d[17]),"+f"(d[18]),"+f"(d[19]),"+f"(d[20]),"+f"(d[21]),"+f"(d[22]),"+f"(d[23]),"+f"(d[24]),"+f"(d[25]),"+f"(d[26]),"+f"(d[27]),"+f"(d[28]),"+f"(d[29]),"+f"(d[30]),"+f"(d[31])
    : "r"(a0), "r"(a1), "r"(a2), "r"(a3), "l"(db), "r"(sd));
}
__device__ __forceinline__ void wg_rs80_01(float* d, uint32_t a0, uint32_t a1, uint32_t a2, uint32_t a3, uint64_t db, int sd) {
  asm volatile("{.reg .pred p; setp.ne.b32 p, %45, 0;\n"
    "wgmma.mma_async.sync.aligned.m64n80k16.f32.bf16.bf16 {%0,%1,%2,%3,%4,%5,%6,%7,%8,%9,%10,%11,%12,%13,%14,%15,%16,%17,%18,%19,%20,%21,%22,%23,%24,%25,%26,%27,%28,%29,%30,%31,%32,%33,%34,%35,%36,%37,%38,%39}, {%40,%41,%42,%43}, %44, p, 1, 1, 1;}"
    : "+f"(d[0]),"+f"(d[1]),"+f"(d[2]),"+f"(d[3]),"+f"(d[4]),"+f"(d[5]),"+f"(d[6]),"+f"(d[7]),"+f"(d[8]),"+f"(d[9]),"+f"(d[10]),"+f"(d[11]),"+f"(d[12]),"+f"(d[13]),"+f"(d[14]),"+f"(d[15]),"+f"(d[16]),"+f"(d[17]),"+f"(d[18]),"+f"(d[19]),"+f"(d[20]),"+f"(d[21]),"+f"(d[22]),"+f"(d[23]),"+f"(d[24]),"+f"(d[25]),"+f"(d[26]),"+f"(d[27]),"+f"(d[28]),"+f"(d[29]),"+f"(d[30]),"+f"(d[31]),"+f"(d[32]),"+f"(d[33]),"+f"(d[34]),"+f"(d[35]),"+f"(d[36]),"+f"(d[37]),"+f"(d[38]),"+f"(d[39])
    : "r"(a0), "r"(a1), "r"(a2), "r"(a3), "l"(db), "r"(sd));
}
__device__ __forceinline__ void wg_rs24_01(float* d, uint32_t a0, uint32_t a1, uint32_t a2, uint32_t a3, uint64_t db, int sd) {
  asm volatile("{.reg .pred p; setp.ne.b32 p, %17, 0;\n"
    "wgmma.mma_async.sync.aligned.m64n24k16.f32.bf16.bf16 {%0,%1,%2,%3,%4,%5,%6,%7,%8,%9,%10,%11}, {%12,%13,%14,%15}, %16, p, 1, 1, 1;}"
    : "+f"(d[0]),"+f"(d[1]),"+f"(d[2]),"+f"(d[3]),"+f"(d[4]),"+f"(d[5]),"+f"(d[6]),"+f"(d[7]),"+f"(d[8]),"+f"(d[9]),"+f"(d[10]),"+f"(d[11])
    : "r"(a0), "r"(a1), "r"(a2), "r"(a3), "l"(db), "r"(sd));
}

#define AB_POLY 0x77
__device__ __forceinline__ constexpr bool poly_group(int group) { return (AB_POLY >> (group & 7)) & 1; }

template <int V> struct Int { static constexpr int value = V; };

__device__ __forceinline__ int core_word(int row, int col) {
  return ((((row >> 7) * 10 + (col >> 6)) * 16 + ((row >> 3) & 15)) * 8 + ((col >> 3) & 7)) * 32 + (row & 7) * 4 + ((col & 7) >> 1);
}
__device__ __forceinline__ void wait_count(const uint32_t* c, uint32_t n) {
  for (int spin = 0; !__all_sync(~0u, (ld_acquire(c) & 0xffff) >= n);) { __nanosleep(32); spin_guard(spin); }
  fence_async_global();
}
__device__ __forceinline__ void prefetch_l2(const void* p, uint32_t bytes) {
  asm volatile("cp.async.bulk.prefetch.L2.global [%0], %1;" :: "l"(p), "r"(bytes) : "memory"); }

#define PLACE 4
__device__ __forceinline__ bool helper_sm() {
  uint32_t m; asm volatile("mov.u32 %0, %%smid;" : "=r"(m));
  m = __shfl_sync(~0u, m, 0);
  return m < 2 || m >= 120 || (m >= 92 && m < 102) || (m >= 106 && m < 117) || m == 118;
}

__device__ __forceinline__ uint8_t* pool_at(uint32_t off) {
  return reinterpret_cast<uint8_t*>((reinterpret_cast<uintptr_t>(g_pool) + 8191) & ~(uintptr_t)8191) + off; }
__device__ __forceinline__ void probe_slots(uint32_t scratch) {
  const int w = __shfl_sync(~0u, (threadIdx.x >> 6) & 1, 0), slot = w == 0 ? NSLOT : blockIdx.x;
  if (w == 0 || slot < NSLOT) {
    uint32_t* q = reinterpret_cast<uint32_t*>(pool_at(slot * 8192)) + (w == 0 ? (blockIdx.x & 31) * 32 + (blockIdx.x >> 5) : 0);
    uint32_t best[2] = {~0u, ~0u};
    const bool one = elect();
    if (one) { stg_strong32(q, 0u); stg_strong32(q + 1024, 0u); }
#pragma unroll 1
    for (int r = 0; r < 8; r++) {
      uint32_t v = 0;
      const uint32_t t0 = clk32();
      if (one) asm volatile("atom.relaxed.gpu.global.exch.b32 %0, [%1], 0;" : "=r"(v) : "l"(q + (r & 1) * 1024) : "memory");
      if (__any_sync(~0u, v != 0)) break;
      const uint32_t t = min(clk32() - t0, best[0]);
      best[0] = best[1]; best[1] = t;
    }
    if (one) sts32(scratch + w * 4, best[0] < best[1]);
  }
  bar_sync(2, 64);
  if ((threadIdx.x & 31) == 0) {
    const int part = lds32(scratch) ? 1 : 2;
    if (w == 0) { uint32_t smid; asm("mov.u32 %0, %%smid;" : "=r"(smid)); stg_strong32(g_smpart + (smid & 255), part); }
    else if (slot < NSLOT) stg_strong32(g_orient + slot, lds32(scratch + 4) ? part : 3 - part);
  }
  __syncwarp();
}

constexpr int WK_SLOTS = 28, WK_BAR = WK_SLOTS * 8192;
__device__ __forceinline__ void work_init(uint32_t sb, int w) {
  if (elect()) {
#pragma unroll
    for (int i = 0; i < 8; i++) mbar_init(sb + WK_BAR + 64 * w + 8 * i, 0x18318822 >> (8 * w + (i & 4)) & 15);
  }
  asm volatile("fence.mbarrier_init.release.cluster;" ::: "memory");
}

struct ChainParams {
  CUtensorMap wq, wk, wv, wo, xc;
  const __nv_bfloat16* mem0;
  const uint8_t* wb;
  uint32_t *sync, *other;
  int layer;
  int d1, d2, dn, dx, mode, zero;
};
constexpr int CH_WQ = 0, CH_WO = 81920, CH_X = CH_WO + 86016, CH_M = CH_X, CH_Q = CH_X + 34816, CH_KM = CH_Q + 2048, CH_VP = CH_KM + 2048,
              CH_K = CH_X + 40960, CH_O = CH_K, CH_KS = CH_K + 3072, CH_V = CH_K + 4096, CH_VX = CH_V + 12288, CH_R2 = CH_VX,
              CH_SX = CH_VX + 3072, CH_SO = CH_SX + 2048, CH_ID = CH_SO + 1024, CH_L = CH_ID + 256, CH_TAB = CH_L + 64, CH_BAR = CH_TAB + 384;
constexpr int CH_SMEM = CH_BAR + 144;
constexpr int MB_WO = CH_BAR, MB_WQ = CH_BAR + 8, MB_X = CH_BAR + 16, MB_V = CH_BAR + 24, MB_T = CH_BAR + 32, MB_F = CH_BAR + 40, MB_G = CH_BAR + 48, MB_W = CH_BAR + 56;
enum { NB_PROJ = 1, NB_O = 2, NB_W1 = 3, NB_PRE = 4, NB_ST = 5, NB_MEM = 6, NB_XFREE = 7, NB_H1 = 8, NB_PUB = 9, NB_W2 = 10, NB_PROJ2 = 11, NB_PRE2 = 12, NB_H2 = 13, NB_W1V = 14 };
#define CH_NQ 9
#define CH_XPF 1
#define CH_TPF 1
#define CH_FLY 6
#define CH_TW 1
#define H1VOTE 0
#define CH_G0 3
#define CH_G1 4
#define CH_NQP 2
#define CH_NQ0 5
#define CH_PA 6
#define CH_PB 9
#define CH_PC 13
#define CH_PL 4
#define CH_DBL 0x2108
#define CH_PD 1
#define SCHED() asm volatile("griddepcontrol.launch_dependents;" ::: "memory")
__device__ __forceinline__ uint32_t opaque(uint32_t x) { return __shfl_sync(~0u, x, threadIdx.x & 31); }
__device__ __forceinline__ uint32_t uniform(uint32_t x) { return __shfl_sync(~0u, x, 0); }
__device__ __forceinline__ uint32_t nz(uint32_t x) { uint32_t r; asm("max.u32 %0, %1, 1;" : "=r"(r) : "r"(x)); return r; }
__device__ __forceinline__ uint32_t set_tag(uint32_t w, uint32_t tag) { uint32_t r; asm("lop3.b32 %0, %1, %2, 1, 0xD8;" : "=r"(r) : "r"(w), "r"(tag)); return r; }
__device__ __forceinline__ uint32_t pack_tag(float lo, float hi, uint32_t tag) { return set_tag(__byte_perm(__float_as_uint(lo) + tag, pack2(hi, hi), 0x7632), tag); }
__device__ __forceinline__ uint32_t differ(uint32_t a, uint32_t b, uint32_t t) { uint32_t r; asm("lop3.b32 %0, %1, %2, %3, 0x7E;" : "=r"(r) : "r"(a), "r"(b), "r"(t)); return r; }
__device__ __forceinline__ uint32_t clk64() { uint64_t c; asm volatile("mov.u64 %0, %%clock64;" : "=l"(c) :: "memory"); return (uint32_t)c; }
__device__ __forceinline__ void until(uint32_t t) {
  asm volatile("{.reg .pred p; .reg .u64 c; .reg .s32 d;\nW: mov.u64 c, %%clock64; cvt.u32.u64 d, c; sub.s32 d, d, %0; setp.lt.s32 p, d, 0; @p bra.uni W;}" :: "r"(t) : "memory");
}
__device__ __forceinline__ float rcp(float x) { float y; asm("rcp.approx.ftz.f32 %0, %1;" : "=f"(y) : "f"(x)); return y; }

__device__ __forceinline__ void chain_compute(const ChainParams& p, const uint32_t sb) {
  const int tid = threadIdx.x & 127, WG = __shfl_sync(~0u, threadIdx.x >> 7, 0), t4 = __shfl_sync(~0u, tid >> 5, 0), lane = tid & 31;
  const int cta = blockIdx.x, h = cta / 3, j = cta - 3 * h;
  uint32_t a0[80], a1[80], tw[4 * CH_NQ];
  const uint32_t wq = opaque(sb + CH_WQ + (WG * 320 + (lane & 7) + (lane >> 4) * 8) * 128 + (((2 * t4 + ((lane >> 3) & 1)) ^ (lane & 7)) << 4));
#pragma unroll
  for (int k = 0; k < 40; k++) {
    if (k % 10 == 0) mbar_wait(sb + MB_W + WG * 8 + k / 10 * 16, 0);
    if (k < 20) ldsm4t(&a0[4 * k], wq + k * 2048); else ldsm4t(&a1[4 * k - 80], wq + CH_WO + (k - 20) * 2048);
    if (k % 20 == 19) bar_arrive(k < 20 ? NB_PROJ2 : NB_PRE2, 288);
  }
  const int r1 = j == 2 ? 0 : j + 1, r2 = j == 0 ? 2 : j - 1;
  const uint32_t l16 = opaque(sb + lane * 16), l8 = opaque(sb + lane * 8), l4 = opaque(sb + lane * 4);
  const uint32_t t16 = l16 + t4 * 512, t8 = l8 + t4 * 256;
  uint32_t wo = opaque(sb + CH_WO + (WG == 0 ? (t4 >> 1) * 36864 : 73728 + t4 * 1024) + ((lane & 7) + (lane >> 4) * 8) * 64 +
                       (((((lane >> 3) & 1) + (WG == 0 ? (t4 & 1) * 2 : 0)) ^ ((lane >> 1) & 3)) << 4));
  const uint32_t ko0 = uniform(CH_K + (tid >> 5) * 1024 + (tid >> 6) * 512), ko1 = uniform(CH_K + (tid >> 5) * 1024 + 512 - (tid >> 6) * 512),
                 o768 = uniform((tid >> 5) * 768);
  const uint32_t give = uniform(t4 * 512 + (WG == 0 ? CH_K : CH_V + j * 4096)), own = uniform(t4 * 512 + (WG == 0 ? CH_V + j * 4096 : CH_K)), mem = uniform(CH_M + WG * 5120);
  const uint32_t vxo = uniform(t4 * 256 + CH_VX + j * 1024);
  uint32_t tag = 1, xd = uniform((1024 + CH_X + WG * 20480) >> 4 | 8 << 16);
  asm volatile("barrier.cluster.wait.aligned;" ::: "memory");
  mbar_wait(sb + MB_WQ, 0);
  mbar_wait(sb + MB_T, 0);
  bar_sync(NB_ST, 384);
  uint8_t* pdst[6];
#pragma unroll
  for (int i = 0; i < 6; i++) {
    const int line = WG == 0 ? 24 * j + 12 * (t4 >> 1) + 2 * (t4 & 1) + 4 * (i >> 1) + (i & 1) : 72 + 3 * j + t4;
    pdst[i] = pool_at(uniform(lds32(sb + CH_TAB + line * 4)) + h * 128);
  }
  auto batch = [&](float* d, const uint32_t (&a)[80], int acc, int n0, int n1) {
    const uint32_t d0 = xd ^ (tag & (2 << acc));
    wg_fence();
#pragma unroll
    for (int k = 0; k < 20; k++) {
      const int gap = acc ? CH_G1 : CH_G0;
      if (k % gap == 0 && n0 + k / gap < n1) {
        __syncwarp();
        ldsm4t(&tw[4 * (n0 + k / gap)], wq + (n0 + k / gap) * 2048);
        __syncwarp();
      }
      uint64_t db;
      asm("mov.b64 %0, {%1, %2};" : "=l"(db) : "r"(d0 + k / 5 * 320 + k % 5 * 16), "r"(80));
      wg_rs32_00(d, a[4 * k], a[4 * k + 1], a[4 * k + 2], a[4 * k + 3], db, acc | k);
    }
    wg_commit();
    wg_wait<0>();
    reg_fence<16>(d);
  };
#pragma unroll
  for (int k = 0; k < CH_NQP; k++) ldsm4t(&tw[4 * k], wq + k * 2048);
  int s = 0;
#pragma unroll 1
  do {
    {
      float d[16];
      if (!CH_TW) mbar_wait(sb + MB_T, s & 1);
      batch(d, a0, 0, CH_NQP, CH_NQ0);
      s--; TM(10); s++;
      mbar_wait(sb + MB_F, ~s & 1);
#pragma unroll
      for (int i = 0; i < 2; i++)
        sts128(l16 + give + i * 2048, make_uint4(pack2(d[8 * i], d[8 * i + 1]), pack2(d[8 * i + 2], d[8 * i + 3]), pack2(d[8 * i + 4], d[8 * i + 5]), pack2(d[8 * i + 6], d[8 * i + 7])));
      bar_sync(NB_PUB, 384);
#pragma unroll
      for (int i = 0; i < 2; i++) {
        const uint4 t = lds128(l16 + own + i * 2048);
        d[8 * i] = bf_lo(t.x); d[8 * i + 1] = bf_hi(t.x); d[8 * i + 2] = bf_lo(t.y); d[8 * i + 3] = bf_hi(t.y);
        d[8 * i + 4] = bf_lo(t.z); d[8 * i + 5] = bf_hi(t.z); d[8 * i + 6] = bf_lo(t.w); d[8 * i + 7] = bf_hi(t.w);
      }
      reg_fence<16>(d);
      batch(d, a1, 1, CH_NQ0, CH_NQ);
      s--; TM(11); s++;
      if (WG == 0) bar_arrive(NB_XFREE, 256);
#pragma unroll
      for (int i = 0; i < 8; i++) sts32(l4 + (own - t4 * 256) + (i >> 1) * 1024 + (i & 1) * 128, pack2(d[2 * i], d[2 * i + 1]));
      s--; TM(9); s++;
    }
    float dq[4] = {}, d0[4] = {}, d1[4] = {};
    uint32_t b[40], wf[80];
    const uint32_t* kf = &wf[52];
#pragma unroll
    for (int i = 0; i < 4 * CH_NQ; i++) wf[i] = tw[i];
    auto step = [&](int k) {
      mma16(dq, wf[4 * k], wf[4 * k + 1], wf[4 * k + 2], wf[4 * k + 3], b[2 * k], b[2 * k + 1]);
      mma16(d0, a0[4 * k], a0[4 * k + 1], a0[4 * k + 2], a0[4 * k + 3], b[2 * k], b[2 * k + 1]);
      mma16(d1, a1[4 * k], a1[4 * k + 1], a1[4 * k + 2], a1[4 * k + 3], b[2 * k], b[2 * k + 1]);
    };
    auto finish = [&](int wg, const float* dk) {
      const float k2 = 0.07216878364870322f * 1.44269504089f;
      sts32(l4 + t4 * 512 + CH_Q + wg * 128, pack2(dq[0] * k2, dq[1] * k2));
      sts32(l4 + t4 * 512 + CH_Q + wg * 128 + 256, pack2(dq[2] * k2, dq[3] * k2));
      sts32(l4 + t4 * 512 + CH_KM + wg * 256, pack2(dk[0], dk[1]));
      sts32(l4 + t4 * 512 + CH_KM + wg * 256 + 128, pack2(dk[2], dk[3]));
    };
    const bool more = s < NSEG - 1;
    bar_sync(NB_MEM, 384);
    ldsm4t(&b[0], l16 + mem);
    ldsm4t(&b[4], l16 + mem + 512);
    TMD(0, b[0]);
    {
      int nw = CH_NQ, nb = 2;
#pragma unroll
      for (int k = 0; k < 20; k++) {
        SCHED();
        step(k);
#pragma unroll
        for (int i = 0; i < (CH_DBL >> k & 1) + 1; i++) {
          if (nb < 10 && 2 * nb <= nw) { ldsm4t(&b[4 * nb], l16 + mem + nb * 512); nb++; }
          else if (nw < 20) { ldsm4t(&wf[4 * nw], wq + nw * 2048); nw++; }
          else if (nw < 22) {
            const uint32_t x = l16 ^ ((o768 ^ tag) & 256);
            uint32_t* r = &wf[4 * nw - 28];
            asm volatile("{.reg .pred p; setp.ne.u32 p, %5, 0; @p ldmatrix.sync.aligned.m8n8.x4.trans.shared.b16 {%0,%1,%2,%3},[%4];}"
                         : "+r"(r[0]), "+r"(r[1]), "+r"(r[2]), "+r"(r[3]) : "r"(x + (nw == 20 ? ko0 : ko1)), "r"(WG) : "memory");
            nw++;
          }
        }
      }
      SCHED();
    }
    if (WG == 0) {
      finish(0, d0);
      TM(1);
      bar_sync(NB_PROJ, 256);
      if (!more) {
        const float4 pv = lds128f(t16 + CH_VP);
        sts32(l4 + vxo, pack2(d1[0] + pv.x, d1[1] + pv.y));
        sts32(l4 + vxo + 128, pack2(d1[2] + pv.z, d1[3] + pv.w));
        continue;
      }
      const float4 pv = lds128f(t16 + CH_VP);
      const uint32_t xo = l4 + (vxo ^ (tag & 2)), x1 = mapa(xo, r1), x2 = mapa(xo, r2);
      SCHED();
      const uint32_t v0 = pack2(d1[0] + pv.x, d1[1] + pv.y), v1 = pack2(d1[2] + pv.z, d1[3] + pv.w);
      st_async32(x1, v0, mapa(sb + MB_X, r1));
      st_async32(x2, v0, mapa(sb + MB_X, r2));
      st_async32(x1 + 128, v1, mapa(sb + MB_X, r1));
      st_async32(x2 + 128, v1, mapa(sb + MB_X, r2));
      sts32(xo, v0);
      sts32(xo + 128, v1);
      __syncwarp();
      mbar_arrive_one(sb + MB_X);
      bar_arrive(NB_PROJ2, 256);
      TM(3);
      uint32_t w[144];
      auto tile_of = [](int n) { return n < 27 ? n % 3 : (0x26484 >> 2 * (n - 27)) & 3; };
      auto step_of = [](int n) { return n < 27 ? n / 3 : 9 + ((0x29610 >> 2 * (n - 27)) & 3); };
      auto wload = [&](int n) { ldsm4t(&w[4 * n], wo + tile_of(n) * 12288 + (step_of(n) % 3) * 4096 + (step_of(n) / 3) * 1024); };
#pragma unroll
      for (int n = 0; n < CH_PA; n++) wload(n);
      bar_sync(NB_PRE, 256);
#pragma unroll
      for (int n = CH_PA; n < CH_PB; n++) wload(n);
      bar_arrive(NB_PRE2, 256);
      if (CH_PC > CH_PB) {
        mbar_wait(sb + MB_X, s & 1);
        for (int i = 0; i < CH_PD; i++) wo = __shfl_xor_sync(~0u, wo, p.zero);
#pragma unroll
        for (int n = CH_PB; n < CH_PC; n++) wload(n);
      }
      TM(4);
      bar_sync(NB_O, 256);
      {
        float x[3][4] = {};
        uint32_t ob[24];
        float4 l;
        ldsm4t(&ob[0], l16 + CH_O);
        ldsm4t(&ob[4], l16 + CH_O + 512);
        TMD(7, ob[0]);
        int nw = CH_PC, no = 2;
        float i0, i1;
        uint8_t* dst[6];
        uint32_t lo[6], hi[6];
        auto pre = [&](int i) { lo[i] = __float_as_uint(x[i >> 1][2 * (i & 1)] * i0) + tag; hi[i] = pack2(0.f, x[i >> 1][2 * (i & 1) + 1] * i1); };
        auto emit = [&](int i) { stg_strong32(dst[i], set_tag(__byte_perm(lo[i], hi[i], 0x7632), tag)); };
#pragma unroll
        for (int n = 0; n < 36; n++) {
          SCHED();
          mma16(x[tile_of(n)], w[4 * n], w[4 * n + 1], w[4 * n + 2], w[4 * n + 3], ob[step_of(n) * 2], ob[step_of(n) * 2 + 1]);
          if (n >= CH_PL) {
            if (no < 6 && no * 2 <= step_of(min(nw, 35))) { ldsm4t(&ob[4 * no], l16 + CH_O + no * 512); no++; }
            else if (nw < 36) { wload(nw); nw++; if (CH_NQP && nw == 36) bar_arrive(NB_H1, 256); }
            else if (nw < 36 + CH_NQP) { ldsm4t(&tw[4 * (nw - 36)], wq + (nw - 36) * 2048); nw++; }
          }
          if (n == 18) l = lds128f(sb + CH_L + ((l16 ^ tag) & 0x30));
          if (n == 26) { i0 = rcp(l.x + l.y); i1 = rcp(l.z + l.w); asm volatile("" : "+f"(i0), "+f"(i1)); }
          if (n >= 28 && n < 34) { dst[n - 28] = pdst[n - 28] + ((l4 ^ tag) & 0x7c); asm volatile("" : "+l"(dst[n - 28])); }
          if (n == 32) { for (int i = 0; i < 2; i++) { pre(i); asm volatile("" : "+r"(lo[i]), "+r"(hi[i])); } }
          if (n == 33) { emit(0); emit(1); }
        }
        for (int i = 2; i < 6; i++) pre(i);
        for (int i = 2; i < 6; i++) emit(i);
      }
      TM(8);
    } else {
      finish(1, d1);
      sts128f(t16 + CH_VP, d0[0], d0[1], d0[2], d0[3]);
      TM(1);
      bar_sync(NB_PROJ, 256);
      uint32_t pair;
      {
        float d0[4] = {}, d1[4] = {}, dm[4] = {};
        uint32_t q[16], km[4];
#pragma unroll
        for (int e = 0; e < 4; e++) {
          ldsm4t(&q[4 * e], l16 + (e ^ t4) * 512 + CH_Q);
          SCHED();
          if (e == 1) { ldsm4t(km, t16 + CH_KM); SCHED(); }
        }
        const uint32_t xo = l4 + ((t4 * 128) ^ (tag & 2));
        pair = l16 + ((l16 ^ tag) & 256) * 3;
        asm volatile("" : "+r"(pair));
        uint64_t x[4];
#pragma unroll
        for (int i = 0; i < 4; i++) {
          const int r = i & 1 ? r2 : r1;
          asm volatile("mov.b64 %0, {%1, %2};" : "=l"(x[i]) : "r"(mapa(xo, r) + CH_SX + (i & 1) * 1024 + (i & 2) * 256), "r"(mapa(sb + MB_X, r)));
        }
        SCHED();
        mma16(d0, q[0], q[1], q[2], q[3], kf[0], kf[1]);
        SCHED();
        mma16(d1, q[4], q[5], q[6], q[7], kf[2], kf[3]);
        SCHED();
        mma16(dm, q[0], q[1], q[2], q[3], hadd2(km[0], km[2]), hadd2(km[1], km[3]));
        mma16(d0, q[8], q[9], q[10], q[11], kf[4], kf[5]);
        SCHED();
        mma16(d1, q[12], q[13], q[14], q[15], kf[6], kf[7]);
        if (!more) continue;
        const uint32_t w1 = pack2(dm[0] + dm[2], dm[1] + dm[3]);
        st_async32((uint32_t)x[2], w1, x[2] >> 32);
        st_async32((uint32_t)x[3], w1, x[3] >> 32);
        SCHED();
        const uint32_t w0 = pack2((d0[0] + d0[2]) + (d1[0] + d1[2]), (d0[1] + d0[3]) + (d1[1] + d1[3]));
        st_async32((uint32_t)x[0], w0, x[0] >> 32);
        st_async32((uint32_t)x[1], w0, x[1] >> 32);
        sts32(xo + CH_SO, w0);
        sts32(xo + CH_SO + 512, w1);
      }
      TM(3);
      float sc[3][4] = {};
      uint32_t wd[12], we[6];
      uint32_t redo;
      auto attend = [&](auto first) {
        uint4 vb[6];
        uint32_t vm[6];
        float e[10];
        uint32_t ow[6];
        if (first.value) {
          const uint2 id = lds64(l8 + CH_ID);
          bar_sync(NB_W1V, 160);
          uint32_t r[8];
          ldsm4(r, l16 + CH_SO); ldsm4(r + 4, l16 + CH_SO + 512);
#pragma unroll
          for (int u = 0; u < 6; u++) vb[u] = ldsm4v(pair + t4 * 256 + CH_V + u * 2048);
          bar_arrive(NB_PRE, 256);
          const uint32_t sxa = pair + CH_SX;
          SCHED();
          mma8(sc[0], r[0], r[1], id.x);
          mma8(sc[1], r[2], r[3], id.x);
          mma16(sc[2], r[4], r[5], r[6], r[7], id.x, id.y);
          TM(7);
          mbar_wait(sb + MB_X, s & 1);
          TM(4);
          uint32_t t[16];
          ldsm4(t, sxa); ldsm4(t + 4, sxa + 256); ldsm4(t + 8, sxa + 512);
          SCHED();
          mma16(sc[0], t[0], t[1], t[2], t[3], id.x, id.y);
          ldsm4(t + 12, sxa + 768);
          SCHED();
          mma16(sc[1], t[4], t[5], t[6], t[7], id.x, id.y);
          ldsm4(vm, pair + t4 * 256 + CH_VX);
          SCHED();
          e[0] = ex2(sc[0][0]);
          mma16(sc[2], t[8], t[9], t[10], t[11], id.x, id.y);
          ldsm2(vm + 4, l16 + t4 * 256 + CH_VX + 2048);
          SCHED();
          e[1] = ex2(sc[0][1]);
          ldsm4t(&wd[0], wo);
          SCHED();
          e[2] = ex2(sc[0][2]);
          SCHED();
          e[3] = ex2(sc[0][3]);
          mma16(sc[2], t[12], t[13], t[14], t[15], id.x, id.y);
          SCHED();
          e[4] = ex2(sc[1][0]);
          ldsm4t(&wd[4], wo + 4096);
          SCHED();
          e[5] = ex2(sc[1][1]);
        } else {
#pragma unroll
          for (int u = 0; u < 6; u++) vb[u] = ldsm4v(pair + t4 * 256 + CH_V + u * 2048);
          ldsm4(vm, pair + t4 * 256 + CH_VX);
          ldsm2(vm + 4, l16 + t4 * 256 + CH_VX + 2048);
        }
        float o[3][4] = {};
        if (!first.value) {
#pragma unroll
          for (int i = 0; i < 6; i++) e[i] = ex2(sc[i >> 2][i & 3]);
        }
        const uint32_t p1 = pack2(e[0], e[1]), p2 = pack2(e[2], e[3]);
        float l = (e[0] + e[1]) + (e[2] + e[3]);
        asm volatile("" : "+f"(l));
        SCHED();
        e[6] = ex2(sc[1][2]);
        mma16(o[0], vb[0].x, vb[0].y, vb[0].z, vb[0].w, p1, p2);
        if (first.value) { sc[2][0] += sc[2][2]; sc[2][1] += sc[2][3]; }
        SCHED();
        e[7] = ex2(sc[1][3]);
        mma16(o[1], vb[2].x, vb[2].y, vb[2].z, vb[2].w, p1, p2);
        SCHED();
        e[8] = ex2(sc[2][0]);
        mma16(o[2], vb[4].x, vb[4].y, vb[4].z, vb[4].w, p1, p2);
        SCHED();
        e[9] = ex2(sc[2][1]);
        SCHED();
        const uint32_t p3 = pack2(e[4], e[5]), p4 = pack2(e[6], e[7]);
        l += (e[4] + e[5]) + (e[6] + e[7]);
#pragma unroll
        for (int u = 0; u < 3; u++) mma16(o[u], vb[2 * u + 1].x, vb[2 * u + 1].y, vb[2 * u + 1].z, vb[2 * u + 1].w, p3, p4);
        SCHED();
        const uint32_t p0 = pack2(e[8], e[9]);
        l += e[8] + e[9];
        const float l2 = __shfl_xor_sync(~0u, l, 1);
        if (first.value) {
          const uint32_t t = (l16 ^ tag) & 128, wx = (wo ^ 32 ^ t >> 3) + t * 4 + ((l16 ^ tag) & 256) * 14;
          ldsm4t(&wd[8], wo + 8192);
          ldsm4t(we, wx);
          ldsm2t(we + 4, wx + 8192);
        }
#pragma unroll
        for (int u = 0; u < 3; u++) mma8(o[u], vm[2 * u], vm[2 * u + 1], p0);
        redo = __any_sync(~0u, !(l > 1e-9f && l < 1e9f));
        uint32_t la = sb + CH_L + (((l4 ^ tag) >> 1) & 0x3c);
        asm volatile("" : "+r"(la));
        SCHED();
#pragma unroll
        for (int u = 0; u < 3; u++) { ow[2 * u] = pack2(o[u][0], o[u][1]); ow[2 * u + 1] = pack2(o[u][2], o[u][3]); }
#pragma unroll
        for (int u = 0; u < 6; u++) sts32(l4 + o768 + CH_O + u * 128, ow[u]);
        if (t4 == 0) sts32(la, __float_as_uint(l + l2));
      };
      attend(Int<1>());
      TM(6);
      asm volatile("{.reg .pred p; setp.eq.u32 p, %0, 0; @p bar.sync 2, 256;}" :: "r"(redo) : "memory");
      if (redo) {
        float mx = fmaxf(sc[2][0], sc[2][1]);
#pragma unroll
        for (int i = 0; i < 4; i++) mx = fmaxf(mx, fmaxf(sc[0][i], sc[1][i]));
        mx = fmaxf(mx, __shfl_xor_sync(~0u, mx, 1));
        mx = fmaxf(mx, __shfl_xor_sync(~0u, mx, 2));
#pragma unroll
        for (int i = 0; i < 4; i++) { sc[0][i] -= mx; sc[1][i] -= mx; }
        sc[2][0] -= mx; sc[2][1] -= mx;
        attend(Int<0>());
        bar_arrive(NB_O, 256);
      }
      {
        float z[4] = {};
        const uint32_t scr = l8 + ((CH_V + r1 * 4096) ^ (tag & 2));
        float y[2][4] = {};
        uint32_t ow[6];
        __syncwarp();
        ldsm4t(ow, l16 + o768 + CH_O);
        ldsm2t(ow + 4, l16 + o768 + CH_O + 512);
#pragma unroll
        for (int u = 0; u < 3; u++) {
          mma16(z, wd[4 * u], wd[4 * u + 1], wd[4 * u + 2], wd[4 * u + 3], ow[2 * u], ow[2 * u + 1]);
          mma8(y[0], we[2 * u], we[2 * u + 1], ow[2 * u]);
          mma8(y[1], we[2 * u], we[2 * u + 1], ow[2 * u + 1]);
        }
        sts64f(scr + t4 * 256, z[0], z[1]); sts64f(scr + t4 * 256 + 1024, z[2], z[3]);
        sts64f(scr + t4 * 256 + 2048, y[0][0] + y[1][2], y[0][1] + y[1][3]);
        bar_sync(NB_W1, 128);
        if (t4 + j / 2 < 3) {
          float2 q[4];
          const float4 l = lds128f(sb + CH_L + ((l16 ^ tag) & 0x30));
#pragma unroll
          for (int i = 0; i < 4; i++) q[i] = lds64f(scr + t4 * 1024 + i * 256);
          SCHED();
          stg_strong32(pdst[0] + ((l4 ^ tag) & 0x7c), pack_tag(((q[0].x + q[1].x) + (q[2].x + q[3].x)) * rcp(l.x + l.y), ((q[0].y + q[1].y) + (q[2].y + q[3].y)) * rcp(l.z + l.w), tag));
        }
      }
      TM(2);
      if (CH_NQP) bar_sync(NB_H1, 256);
#pragma unroll
      for (int k = 0; k < CH_NQP; k++) ldsm4t(&tw[4 * k], wq + k * 2048);
    }
    bar_sync(NB_ST, 384);
    tag ^= 0x10001;
  } while (++s < NSEG);
  if (WG == 1) {
    const uint2 a = lds64(t8 + t4 * 256 + CH_KM), b = lds64(t8 + t4 * 256 + CH_KM + 256);
    sts64(t8 + CH_M, hadd2(a.x, b.x), hadd2(a.y, b.y));
  }
  bar_arrive(NB_PRE2, 288);
}

__device__ __forceinline__ void chain_comm(const ChainParams& p, const uint32_t sb, const CUtensorMap* maps) {
  [[maybe_unused]] constexpr int WG = 2;
  const int tid = threadIdx.x & 127, t4 = __shfl_sync(~0u, tid >> 5, 0), lane = tid & 31;
  const int cta = blockIdx.x, h = cta / 3, j = cta - 3 * h, colbase = cta * 64;
  const uint8_t* const xs = reinterpret_cast<const uint8_t*>(g_xn);
  auto xload = [&](int seg, int i) { tma_load5_one(sb + CH_X + i * 10240, &p.xc, 0, seg * 4, 2 * i, sb + MB_T); };
  uint32_t smid; asm("mov.u32 %0, %%smid;" : "=r"(smid));
  if (t4 == 3) {
    const bool one = elect();
#pragma unroll 1
    for (int i = 0; i < 19 + CH_FLY; i++) {
      if (i >= CH_FLY) mbar_wait(sb + MB_W + 8 * ((i - CH_FLY) & 7), (i - CH_FLY) >> 3 & 1);
      if (i == 11 + CH_FLY && one) mbar_arrive(sb + MB_WQ);
      if (i == 8) { bar_sync(NB_PROJ2, 288); PRO(1); }
      if (i == 12) { bar_sync(NB_PRE2, 288); PRO(2); }
      if (i == 0) { bar_arrive(NB_ST, 384); bar_arrive(NB_PUB, 384); bar_arrive(NB_XFREE, 256); }
      if (i < 19 && one) {
        const int n = (i & 1) * 2 + (i >> 1 & 1), k = i - 12;
        const uint32_t bar = sb + MB_W + 8 * (i & 7);
        mbar_expect(bar, k < 0 ? 20480 : 12288);
        if (k < 0) tma_load(sb + ((i & 4) + n) * 20480, i >= 8 ? &p.wq : (i ^ i >> 2) & 1 ? &p.wv : &p.wk, colbase, n * 160, bar);
        else tma_load(sb + CH_WO + k * 12288, &p.wo, k < 6 ? j * 192 + k * 32 : 576 + j * 24, h * 192, bar);
      }
    }
  } else {
    const uint32_t part = max(ldg_strong32(g_smpart + (smid & 255)), 1u);
    if (tid == 0) prefetch_l2(p.mem0, 10240);
    if (tid == 64) stg_strong32(p.sync + SY_PART + cta, part);
    if (t4 == 1) {
      wait_count(p.sync + SY_P + 1, ln_items(p.layer, 0));
      mbar_expect_one(sb + MB_T, 40960);
#pragma unroll 1
      for (int i = 0; i < 4; i++) xload(0, i);
      PRO(0);
    }
    uint32_t reader, orient;
    for (int n = 0;; spin_guard(n)) {
      reader = ldg_strong32(p.sync + SY_PART + (tid >= 80 ? cta : tid));
      orient = ldg_strong32(g_orient + min(tid, NSLOT - 1));
      if (__all_sync(~0u, reader && orient)) break;
    }
    const uint32_t near = __ballot_sync(~0u, reader == part) >> (cta & 7) & 0xffff;
    if (tid < NSLOT) sts32(sb + CH_TAB + tid * 4, tid * 8192 + (orient == reader ? 0 : 4096));
    if (tid == 0) sts32(sb + CH_TAB + NSLOT * 4, cta < 80 ? cta : (cta & 7) + max(__ffs(near) - 1, 0));
    if (t4 == 1) PRO(3);
    bar_sync(NB_ST, 384);
    bar_arrive(NB_PUB, 384);
    if (t4 == 1) PRO(4);
    const uint32_t id = (lane >> 3) == (lane & 3) ? ((lane & 4) ? 0x3f800000u : 0x00003f80u) : 0u;
    if (t4 == 0) sts64(sb + CH_ID + lane * 8, id, id);
#pragma unroll 1
    for (int q = t4; q < 4; q += 3) {
      uint32_t m0[20];
#pragma unroll
      for (int i = 0; i < 20; i++) m0[i] = (reinterpret_cast<const uint32_t*>(p.mem0) + (lane >> 2) * (DM / 2) + q * 80 + (lane & 3))[i * 4];
      if (q < 3) bar_sync(NB_XFREE, 256);
#pragma unroll
      for (int i = 0; i < 20; i += 4) stsm4t(sb + CH_M + (q * 20 + i) * 128 + lane * 16, m0[i], m0[i + 1], m0[i + 2], m0[i + 3]);
    }
    if (t4 == 1) PRO(5);
  }
  if (cta * 128 + tid < SY_N) p.other[cta * 128 + tid] = 0;
  asm volatile("barrier.cluster.wait.aligned;" ::: "memory");
  const uint32_t l8 = opaque(sb + t4 * 256 + lane * 8);
  bar_sync(NB_MEM, 384);
  uint8_t* const pool = pool_at(0);
  const uint8_t* const psrc = pool + opaque(lds32(sb + CH_TAB + lds32(sb + CH_TAB + NSLOT * 4) * 4) + t4 * 1024 + lane * 4);
  const uint32_t mdst = opaque((80 + cta / 20) * 8192 + (t4 & 1) * 4096 + (cta % 20) * 128 + lane * 4);
  int st = 0;
  uint32_t tag = 1, span = ~0u;
  auto send_tokens = [&](int s) {
    uint8_t* dst = g_kv + ((s >> 2) * 192 + cta + 3 * h) * KV_PART + (s & 3) * KV_SEG;
    bulk_store(dst, sb + CH_K, 4096);
    bulk_store(dst + KV_V, sb + CH_V + j * 4096, 4096);
    bulk_commit();
  };
  auto send_memory = [&](int s, uint32_t km) {
    fence_async();
    uint8_t* dst = g_kv + ((s >> 2) * 192 + cta + 3 * h) * KV_PART + KV_M + (s & 3) * KV_SEG;
    bulk_store(dst, km, 1024);
    bulk_store(dst + KV_V, sb + CH_VX + j * 1024, 1024);
    bulk_commit();
    bulk_wait<0>();
    if ((s & 3) == 3) { fence_async_global(); atomicAdd(p.sync + (s >> 2) * 8 + 4, 1); }
  };
#pragma unroll 1
  for (int s = 0; s < NSEG - 1; s++) {
    TM(0);
    STAT(0);
    if (t4 == 0) {
      mbar_expect_one(sb + MB_T, 40960);
      xload(s + 1, 1);
      xload(s + 1, 2);
      if (elect()) {
        fence_async();
#pragma unroll 1
        for (int r = j + 1; r < j + 3; r++) bulk_push(mapa(sb + CH_V + j * 4096, r % 3), sb + CH_V + j * 4096, 4096, mapa(sb + MB_V, r % 3));
        send_tokens(s);
        bulk_wait_read<0>();
      }
      __syncwarp();
    }
    uint32_t c0, g0;
    if (t4 == 1) {
      __syncwarp();
      c0 = clk32(); g0 = gtime();
      if (elect()) atomicMax(p.sync + SY_TIME + s, g0);
    }
    if (t4 == 3 && s >= NSEG - 6 && elect()) asm volatile("prefetch.tensormap [%0];" :: "l"(maps + (NSEG - 2 - s)) : "memory");
    if (t4 == 3 && (s & 3) == 2 && s < NSEG - 2) wait_count(p.sync + SY_P + 5 + (s & ~3), ln_items(p.layer, (s >> 2) + 1));
    if (t4 == 2) { mbar_wait(sb + MB_V, s & 1); bar_arrive(NB_W1V, 160); }
    bar_sync(NB_PROJ2, 256);
    if (t4 == 0) {
      mbar_expect_one(sb + MB_X, 4096);
      xload(s + 1, 0);
    }
    __syncwarp();
    STAT(1);
    TM(1);
    {
      const uint2 a = lds64(l8 + t4 * 256 + CH_KM), b = lds64(l8 + t4 * 256 + CH_KM + 256);
      sts64(l8 + CH_KS, hadd2(a.x, b.x), hadd2(a.y, b.y));
    }
    TM(4);
    bar_sync(NB_PRE2, 256);
    if (t4 == 0) xload(s + 1, 3);
    if (t4 == 0 && elect()) {
      if (CH_XPF && s < NSEG - 2) prefetch_l2(xs + (s + 2) * 40960 + cta % 20 * 2048, 2048);
      if (CH_TPF && s >= NSEG - 7) {
        const int i = s - (NSEG - 7);
        if (i < 2) prefetch_l2(p.wb + (cta * 2 + i) * 12800, 12800);
        else if (i < 4) prefetch_l2(xs + (cta * 2 + i - 2) * 8192, 8192);
        else prefetch_l2(g_q + 15 * 32 * 3072 + (cta * 2 + i - 4) * 512, 8192);
      }
      send_memory(s, sb + CH_KS);
    }
    __syncwarp();
    if (t4 == 1) {
      const uint32_t late = min(ldg_strong32(p.sync + SY_TIME + s) - g0, 640u);
      if (elect()) sts32(sb + CH_TAB + 380, c0 + span + (late * 115 >> 6) + p.d1);
    }
    bar_sync(NB_W2, 128);
    uint32_t due = lds32(sb + CH_TAB + 380);
    due = __shfl_sync(~0u, due, 0);
    const uint8_t* ms = pool + (lds32(sb + CH_TAB + (80 + st * 4 + t4) * 4) + (l8 & 255));
    uint8_t* md = pool + (mdst + (cta >= 80 ? 2 : t4 < 2 ? st : st == 2 ? 0 : st + 1) * 32768);
    asm volatile("" : "+l"(ms), "+l"(md));
    if (CH_TW) mbar_wait(sb + MB_T, ~s & 1);
    TM(2);
    bar_sync(NB_ST, 384);
    __syncwarp();
    uint32_t tg = clk32();
    if (t4 == 3 && elect()) {
      if (s < NSEG - 2) mbar_expect(sb + MB_V, 8192);
      mbar_arrive_remote(mapa(sb + MB_F, j == 2 ? 0 : j + 1));
      mbar_arrive_remote(mapa(sb + MB_F, j == 0 ? 2 : j - 1));
    }
    if (s == NSEG - 2) work_init(sb, t4);
    __syncwarp();
    STAT(2);
    {
      float2 q[4];
      TM(3);
      if (t4 == 1 && s) span = min(span, tg - c0);
      until(s < 2 ? tg + 400 : (int)(due - tg) > p.dn ? due : tg + p.dn);
      for (int n = 0;;) {
        uint32_t v[8];
#pragma unroll
        for (int i = 0; i < 8; i++) v[i] = ldg_strong32(psrc + i * 128);
        sts64f(l8 + CH_R2, ((bf_lo(v[0]) + bf_lo(v[1])) + (bf_lo(v[2]) + bf_lo(v[3]))) + ((bf_lo(v[4]) + bf_lo(v[5])) + (bf_lo(v[6]) + bf_lo(v[7]))),
               ((bf_hi(v[0]) + bf_hi(v[1])) + (bf_hi(v[2]) + bf_hi(v[3]))) + ((bf_hi(v[4]) + bf_hi(v[5])) + (bf_hi(v[6]) + bf_hi(v[7]))));
        uint32_t bad;
        asm volatile("{.reg .pred p, q; .reg .b32 a; lop3.b32 a, %1, %2, %3, 0xFE; lop3.b32 a, a, %4, %6, 0xA8; setp.ne.u32 p, a, 0;\n"
                     "bar.red.or.pred q, %5, 128, p; selp.u32 %0, 1, 0, q;}"
                     : "=r"(bad) : "r"(differ(v[0], v[1], tag)), "r"(differ(v[2], v[3], tag)), "r"(differ(v[4], v[5], tag)), "r"(differ(v[6], v[7], tag)), "n"((int)NB_W2),
                       "r"((uint32_t)(cta < 80 || n < 3)) : "memory");
#pragma unroll
        for (int k = 0; k < 4; k++) asm volatile("ld.volatile.shared.v2.f32 {%0,%1}, [%2];" : "=f"(q[k].x), "=f"(q[k].y) : "r"(l8 - t4 * 256 + CH_R2 + k * 256) : "memory");
        TMV(12, n);
        if (!(H1VOTE ? __any_sync(~0u, bad) : bad)) break;
        spin_guard(n);
      }
      bar_arrive(NB_PUB, 384);
      SCHED();
      TM(9);
      stg_strong32(md, min(nz(pack2((q[0].x + q[1].x) + (q[2].x + q[3].x), (q[0].y + q[1].y) + (q[2].y + q[3].y))), t4 < 2 ? ~0u : 0u));
      tg = clk64() + p.d2;
      if (s >= 2 && (int)(due + p.dx - tg) > 0) tg = due + p.dx;
      TM(8);
    }
    STAT(3);
    until(tg);
    TM(10);
    for (int n = 0;;) {
      uint2 g[10];
#pragma unroll
      for (int i = 0; i < 10; i++) g[i] = ldg_strong64(ms + i * 256);
      if (n == 0) bar_sync(NB_XFREE, 256);
      uint32_t m = ~0u, bad;
#pragma unroll
      for (int i = 0; i < 10; i++) { sts64(l8 + CH_M + t4 * 2304 + i * 256, g[i].x, g[i].y); m = __vimin3_u32(m, g[i].x, g[i].y); }
      TMV(13, n);
      TM(11);
      asm volatile("{.reg .pred p; setp.eq.u32 p, %1, 0; vote.sync.any.pred p, p, 0xffffffff; @!p bar.sync %2, 384; selp.u32 %0, 1, 0, p;}" : "=r"(bad) : "r"(m), "n"((int)NB_MEM) : "memory");
      if (!bad) break;
      spin_guard(n);
    }
    if (++st == 3) st = 0;
    tag ^= 0x10001;
  }
  if (t4 == 0) {
    if (elect()) { fence_async(); send_tokens(NSEG - 1); }
    __syncwarp();
    bar_sync(NB_PRE2, 288);
    if (elect()) {
      send_memory(NSEG - 1, sb + CH_M);
      asm volatile("mbarrier.arrive.shared::cta.b64 _, [%0], 8;" :: "r"(sb + WK_BAR + 64) : "memory");
    }
    __syncwarp();
  }
}

__device__ __forceinline__ void chain_start(const ChainParams& p, const uint32_t sb, const int warp) {
  if (warp == 1 && elect()) {
#pragma unroll
    for (int i = 0; i < 6; i++) mbar_init(sb + CH_BAR + 8 * i, i == 2 ? 5 : i == 5 ? 2 : 1);
    asm volatile("fence.mbarrier_init.release.cluster;" ::: "memory");
    mbar_expect(sb + MB_V, 8192);
    atomicAdd(p.sync + SY_UP, 1);
    asm volatile("{.reg .pred p; setp.ne.u32 p, %0, 1024; @p trap;}" :: "r"(sb & 0xffffff));
  }
  if (warp == 0 && elect()) {
#pragma unroll
    for (int i = 0; i < 8; i++) mbar_init(sb + MB_W + 8 * i, 1);
    asm volatile("fence.mbarrier_init.release.cluster;" ::: "memory");
  }
  __syncthreads();
  asm volatile("barrier.cluster.arrive.relaxed.aligned;" ::: "memory");
}

struct WorkParams {
  ChainParams ch;
  CUtensorMap wo, xn, wb[3], wq, wc[2], out;
  const __nv_bfloat16* x;
  uint32_t* sync;
  int kind, qa_end, pace, idle;
};
#define GO_320 4
#define GO_TAIL 1
#define PF_NS 400
enum { WK_FIRST = 0, WK_LEAD = 1, WK_CHAIN = 2, WK_LAST = 3 };
enum { IT_ATT = 0, IT_OP = 1, IT_FIN = 2, IT_BQ = 3, IT_BO = 4, IT_LN = 5, IT_Q = 6, IT_LN0 = 7, IT_OUT = 8 };
constexpr int C_EARLY = 1 << 20, C_LATE = 1 << 21, C_TAIL = 1 << 22, C_PROJ = 1 << 23;

__device__ __forceinline__ uint32_t item_count(int type, int b) { return type == IT_ATT ? 32 : type == IT_OP ? op_tiles(b) * op_split(b) : type == IT_FIN ? fin_items(b) : bq_items(b); }
__device__ __forceinline__ uint32_t item_need(int type, int b) { return type == IT_ATT ? 96 : item_count(type - 1, b); }
__device__ __forceinline__ int item_cols(int type, int b) {
  return type == IT_ATT || type == IT_Q ? 192 : type == IT_OUT ? 80 : type == IT_BQ ? (b < BQ_12 ? 320 : b < BQ_24 ? 160 : 80) : type == IT_OP ? 640 >> op_shift(b) : 320; }
__device__ __forceinline__ int item_groups(int type, int b) { const int n = type == IT_FIN ? fin_items(b) : ln_items(type == IT_LN, b); return n == 4 ? 4 : n == 8 ? 2 : 1; }
#define RES_OP 0
#define RES_B 6
#define HOLD_B 10
constexpr int RES_N = RES_OP ? op_tiles(14) * op_split(14) : 0, RES_BQ = RES_B;
__device__ __forceinline__ bool reserved(int type, int b) { return type == IT_ATT ? b == 15 : type == IT_OP ? RES_OP && b == 14 : type == IT_BQ && b < RES_BQ; }
__device__ __forceinline__ int reserved_item(int cta) {
  const int h = cta / 3, j = cta - 3 * h, i = h + (j - 1) * 32;
  if (j == 0) return C_EARLY | IT_ATT << 16 | 15 << 8 | h;
  return i < RES_N ? C_TAIL | IT_OP << 16 | 14 << 8 | i : i - RES_N < RES_BQ * 6 ? C_TAIL | IT_BQ << 16 | ((i - RES_N) / 6) << 8 | (i - RES_N) % 6 : -1;
}
constexpr int LEAD1 = 12;
__device__ __forceinline__ int lead_item(int layer, int qa_end, int i) {
  if (layer == 2) return i < 128 ? C_EARLY | C_LATE | IT_OUT << 16 | (i >> 3) << 8 | (i & 7) : -1;
  if (layer == 0) {
    if (i < 32) return IT_LN0 << 16 | (i >> 4) << 8 | (i & 15);
    if (i < 88) return IT_LN0 << 16 | ((i - 24) >> 2) << 8 | (i & 3);
    i -= 88;
  } else {
    if (i < 4) return C_EARLY | IT_BO << 16 | (i >> 1) << 8 | (i & 1);
    if (i < 12) return C_EARLY | IT_LN << 16 | ((i - 4) >> 2) << 8 | (i & 3);
    if (i < 40) return C_EARLY | IT_BO << 16 | ((i - 8) >> 1) << 8 | (i & 1);
    if (i < 96) return C_EARLY | IT_LN << 16 | ((i - 32) >> 2) << 8 | (i & 3);
    i -= 96;
  }
  return i < (16 - qa_end) * 32 ? C_PROJ | IT_Q << 16 | (qa_end + (i >> 5)) << 8 | (i & 31) : -1;
}

struct Ring {
  uint32_t sb;
  int pos, seq;
  __device__ __forceinline__ uint32_t full() const { return sb + WK_BAR + 8 * (seq & 7); }
  __device__ __forceinline__ uint32_t take(int len) { if (pos + len > WK_SLOTS) pos = 0; pos += len; seq++; return sb + (pos - len) * 8192; }
  __device__ __forceinline__ uint32_t wait(int len) { mbar_wait(full(), (seq >> 3) & 1); return take(len); }
  __device__ __forceinline__ void release(int sq) const { mbar_arrive_one(sb + WK_BAR + 64 + 8 * (sq & 7)); }
};

struct Pending {
  uint32_t w[48], done;
  uint4* dst;
  __device__ __forceinline__ void store(int i) const { dst[(i >> 2) * 1024 + (i & 3) * 32] = make_uint4(w[4 * i], w[4 * i + 1], w[4 * i + 2], w[4 * i + 3]); }
  __device__ __forceinline__ void finish() { __syncwarp(); mbar_arrive_one(done); done = 0; }
};

template <int N>
__device__ __forceinline__ void gemm_step(float* d, Ring& r, int warp, int acc) {
  const uint32_t base = r.wait(2 + (N + 63) / 64);
  const uint64_t da = mkdesc(base + (warp >> 2) * 8192, 128, 1024, 0), db = mkdesc(base + 16384, 8192, 1024, 1);
  wg_fence();
#pragma unroll
  for (int kk = 0; kk < 4; kk++) {
    if (N == 80) wg_ss80_01(d, da + kk * 16, db + kk * 128, acc | kk);
    else if (N == 160) wg_ss160_01(d, da + kk * 16, db + kk * 128, acc | kk);
    else wg_ss192_01(d, da + kk * 16, db + kk * 128, acc | kk);
    if (N == 320) wg_ss128_01(d + 96, da + kk * 16, db + kk * 128 + 3 * 512, acc | kk);
  }
  wg_commit();
}
template <int N>
__device__ __forceinline__ void gemm_item(float* d, Ring& r, int warp, int nkb, uint32_t go, int ask) {
#pragma unroll 1
  for (int kb = 0; kb < nkb; kb++) {
    gemm_step<N>(d, r, warp, kb);
    if (kb == ask && go && warp == 0) mbar_arrive_one(go);
    if (kb > 0) { wg_wait<1>(); r.release(r.seq - 2); }
  }
  wg_wait<0>();
  r.release(r.seq - 1);
}

template <class Peek>
__device__ __forceinline__ void attn_a(Ring& r, Pending& pend, Peek peek, const int warp, const int lane) {
  uint32_t (&q)[48] = pend.w;
  const int t = (warp & 1) * 16 + (lane >> 2) - 2 * (lane & 3);
  const bool second = warp & 2;
  const uint32_t rows = (warp >> 2) * 2 * KV_SEG;
  uint32_t pa[20], b2;
  float inv[2];
  bool now;
  const uint32_t b0 = r.wait(5) + rows, b1 = r.wait(5) + rows;
  {
    float s[40];
    wg_fence();
#pragma unroll
    for (int k = 0; k < 12; k++)
      wg_rs80_01(s, q[4 * k], q[4 * k + 1], q[4 * k + 2], q[4 * k + 3], mkdesc(k < 8 ? b0 : b1, 128, 1024, 0) + (k >> 2 & 1) * (KV_PART / 16) + (k & 3) * 16, k);
    wg_commit();
    now = peek();
    b2 = r.wait(5) + rows;
    wg_wait<0>();
    reg_fence<40>(s);
    r.release(r.seq - 3);
    const float k2 = 0.07216878364870322f * 1.44269504089f, NEG = -INFINITY;
#pragma unroll
    for (int i = 0; i < 20; i++) {
      s[i] = second ? s[20 + i] : s[i];
      if (i < 16 && 8 * ((i >> 2) - (i >> 1 & 1)) + (i & 1) > t) s[i] = NEG;
    }
#pragma unroll
    for (int hh = 0; hh < 2; hh++) {
      float m = NEG, l = 0.f;
#pragma unroll
      for (int n = 0; n < 5; n++) m = fmaxf(m, fmaxf(s[4 * n + 2 * hh], s[4 * n + 2 * hh + 1]));
      m = fmaxf(m, __shfl_xor_sync(~0u, m, 1)); m = fmaxf(m, __shfl_xor_sync(~0u, m, 2));
      m *= -k2;
#pragma unroll
      for (int n = 0; n < 5; n++) {
        const float x = ex2(fmaf(s[4 * n + 2 * hh], k2, m)), y = ex2(fmaf(s[4 * n + 2 * hh + 1], k2, m));
        const uint32_t w = pack2(x, y);
        l += x + y;
        pa[2 * n + hh] = second ? 0 : w; pa[10 + 2 * n + hh] = second ? w : 0;
      }
      inv[hh] = l;
    }
  }
  float o[96];
  wg_fence();
#pragma unroll
  for (int u = 0; u < 3; u++) {
#pragma unroll
    for (int k = 0; k < 5; k++)
      wg_rs64_00(o + 32 * u, pa[4 * k], pa[4 * k + 1], pa[4 * k + 2], pa[4 * k + 3], mkdesc(u ? b2 : b1, 1024, 128, 0) + (~u & 1) * (KV_PART / 16) + k * 128, k);
    wg_commit();
  }
#pragma unroll
  for (int hh = 0; hh < 2; hh++) { float l = inv[hh]; l += __shfl_xor_sync(~0u, l, 1); l += __shfl_xor_sync(~0u, l, 2); inv[hh] = rcp(l); }
#pragma unroll
  for (int u = 0; u < 3; u++) {
    if (u == 0) wg_wait<2>(); else if (u == 1) wg_wait<1>(); else wg_wait<0>();
    reg_fence<32>(o + 32 * u);
    if (u != 1) r.release(r.seq - 2 + u / 2);
#pragma unroll
    for (int i = 0; i < 16; i++) { const float* x = &o[32 * u + 4 * (i & 7) + (i >> 2 & 2)]; q[16 * u + i] = pack2(x[0] * inv[i >> 3], x[1] * inv[i >> 3]); }
    if (now) {
#pragma unroll
      for (int i = 0; i < 4; i++) pend.store(4 * u + i);
    }
  }
}

__device__ __forceinline__ void ln_groups(Ring& ring, uint32_t scratch, int planes, int rg, bool two) {
  constexpr int G = 2;
  const int warp = fresh_tid() >> 5, lane = fresh_tid() & 31;
  const uint32_t id = (lane >> 3) == (lane & 3) ? ((lane & 4) ? 0x3f800000u : 0x00003f80u) : 0u;
  const uint32_t at = (warp * 160 + lane) * 8, at1 = planes > 1 ? at : (lane >> 2) * 1280 + warp * 160 + (lane & 3) * 4;
  const uint32_t step = planes > 1 ? 256 : 32, half = planes > 1 ? 4 : 16;
  float v[G][5][4] = {};
#pragma unroll
  for (int r = 0; r < G; r++) {
#pragma unroll 1
    for (int k = r && !two ? 0 : planes; k > 0; k -= 4) {
      const uint32_t a = ring.wait(min(k, 4) + 1);
      if (k == 1) {
#pragma unroll
        for (int i = 0; i < 5; i++) mma8(v[r][i], lds32(a + at1 + i * step), lds32(a + at1 + i * step + half), id);
      } else {
#pragma unroll
        for (int i = 0; i < 10; i++) {
          if (i == 5 && k < 4) break;
          const uint2 x = lds64(a + at + i / 5 * 20480 + i % 5 * 256), y = lds64(a + at + i / 5 * 20480 + 10240 + i % 5 * 256);
          mma16(v[r][i % 5], x.x, x.y, y.x, y.y, id, id);
        }
      }
      ring.release(ring.seq - 1);
    }
  }
  uint2 xr[G][5];
  float mw[G];
  scratch += (lane >> 2) * 64;
#pragma unroll
  for (int r = 0; r < G; r++) {
    float m = 0.f, q2[4] = {};
#pragma unroll
    for (int i = 0; i < 5; i++) {
      float* t = v[r][i];
      xr[r][i] = make_uint2(pack2(t[0], t[1]), pack2(t[2], t[3]));
      t[0] = bf_lo(xr[r][i].x); t[1] = bf_hi(xr[r][i].x); t[2] = bf_lo(xr[r][i].y); t[3] = bf_hi(xr[r][i].y);
      m += (t[0] + t[1]) + (t[2] + t[3]);
    }
    m += __shfl_xor_sync(~0u, m, 1); m += __shfl_xor_sync(~0u, m, 2);
    m *= 1.f / 80;
#pragma unroll
    for (int i = 0; i < 20; i++) { float& t = v[r][i >> 2][i & 3]; t -= m; q2[i & 3] = fmaf(t, t, q2[i & 3]); }
    float q = (q2[0] + q2[1]) + (q2[2] + q2[3]);
    mw[r] = m;
    q += __shfl_xor_sync(~0u, q, 1); q += __shfl_xor_sync(~0u, q, 2);
    if ((lane & 3) == 0) sts64f(scratch + r * 512 + warp * 8, m, q);
  }
  bar_sync(1, 256);
#pragma unroll
  for (int r = 0; r < G; r++) {
    const float4 t = lds128f(scratch + r * 512 + (lane & 3) * 16);
    float mean = t.x + t.z;
    mean += __shfl_xor_sync(~0u, mean, 1); mean += __shfl_xor_sync(~0u, mean, 2);
    mean *= 0.125f;
    float var = (t.y + t.w) + 80.f * ((t.x - mean) * (t.x - mean) + (t.z - mean) * (t.z - mean));
    var += __shfl_xor_sync(~0u, var, 1); var += __shfl_xor_sync(~0u, var, 2);
    float rs;
    asm("rsqrt.approx.ftz.f32 %0, %1;" : "=f"(rs) : "f"(var * (1.f / DM) + 1e-5f));
#pragma unroll
    for (int i = 0; i < 20; i++) v[r][i >> 2][i & 3] = fmaf(v[r][i >> 2][i & 3], rs, (mw[r] - mean) * rs);
  }
#pragma unroll
  for (int r = 0; r < G; r++) {
    if (r && !two) break;
    uint32_t* xn = g_xn + (rg + r) * 2560 + warp * 320 + lane;
#pragma unroll
    for (int i = 0; i < 10; i++) xn[i * 32] = pack2(v[r][i >> 1][2 * (i & 1)], v[r][i >> 1][2 * (i & 1) + 1]);
#pragma unroll
    for (int i = 0; i < 5; i++) g_x[(rg + r) * 17 * 1280 + warp * 160 + i * 32 + lane] = xr[r][i];
  }
}

__device__ __forceinline__ void store_partial(const float* d, int b, int split, int unit, int nu) {
  uint2* dst = g_x + (((b * 16 + (fresh_tid() >> 5) * 2) * 17 + 1 + split) * 40 + unit) * 32 + (fresh_tid() & 31);
#pragma unroll
  for (int u = 0; u < 20; u++) {
    if ((u == 5 || u == 10) && nu == u) break;
    dst[u * 32] = make_uint2(pack2(d[8 * u], d[8 * u + 1]), pack2(d[8 * u + 4], d[8 * u + 5]));
    dst[(680 + u) * 32] = make_uint2(pack2(d[8 * u + 2], d[8 * u + 3]), pack2(d[8 * u + 6], d[8 * u + 7]));
  }
}

__device__ __forceinline__ void store_bqkv(const float* d, int b, int idx, int nh) {
  const int lane = fresh_tid() & 31, c = lane & 3, rg = b * 16 + (fresh_tid() >> 5) * 2, h0 = idx * nh;
  const float sc = h0 < 32 ? 0.22360679775f * 1.44269504089f : 1.f;
  const bool lo = c < 2;
  uint32_t* da = g_bqkv + (h0 * 256 + rg) * 96 + lane;
  uint32_t* db = da + 256 * 96 + (lo ? 2 : -2);
  uint32_t pad[2];
#pragma unroll
  for (int r = 0; r < 2; r++) pad[r] = !(c & 1) && (h0 >= 64 || (h0 >= 32 && (lane & 4) && poly_group(rg + r))) ? 0x00003f80u : 0u;
#pragma unroll
  for (int q = 0; q < 8; q++) {
    if ((q == 2 || q == 4) && nh == 2 * q) break;
#pragma unroll
    for (int r = 0; r < 2; r++) {
      uint32_t w[5];
#pragma unroll
      for (int i = 0; i < 5; i++) w[i] = pack2(d[20 * q + 4 * i + 2 * r] * sc, d[20 * q + 4 * i + 2 * r + 1] * sc);
      const int o = q * 2 * 256 * 96 + r * 96;
      da[o] = w[0]; da[o + 32] = w[1]; da[o + 64] = lo ? w[2] : pad[r];
      db[o] = lo ? w[3] : w[2]; db[o + 32] = lo ? w[4] : w[3]; db[o + 64] = lo ? pad[r] : w[4];
    }
  }
}

__device__ __forceinline__ void work_loader(const WorkParams& p, const uint32_t sb, const bool weights) {
  const uint32_t bars = sb + WK_BAR, bIF = bars + 128, bIE = bars + 160, bGo = bars + 224, slots = bars + 272;
  int pos = 0, seq = 0, tail = 0, used = 0;
  uint32_t lens = 0, tn = clk64();
  if (p.kind == WK_CHAIN) {
    seq = 1; used = lens = 8;
    mbar_arrive_one(bars);
  }
#pragma unroll 1
  for (int n = 0, part = 0;;) {
    if (part == 0) mbar_wait(bIF + 8 * (n & 3), (n >> 2) & 1);
    const int code = __shfl_sync(~0u, (int)lds32(slots + 4 * (n & 3)), 0);
    if (code < 0) break;
    const int type = (code >> 16) & 15, b = (code >> 8) & 255, idx = code & 255;
    const bool qa = code & C_PROJ, ln = type == IT_FIN || type == IT_LN || type == IT_LN0;
    const int parts = ln ? item_groups(type, b) : type == IT_ATT ? 2 : 1;
    {
      int bytes = 163840, chunk = 40960, nb = 0, flag = b * 8 + 4 + type, need = item_need(type & 3, b), c0 = 0, c3 = idx, c4 = 0, s3 = 0, s4 = 64;
      const uint8_t* src = g_kv + (b * 32 + idx) * 6 * KV_PART;
      const CUtensorMap* m = nullptr;
      if (ln) {
        const int rg = b * 16 + idx * parts + part;
        bytes = (type == IT_FIN ? op_split(b) + 1 : type == IT_LN ? 2 : 1) * 10240;
        src = type == IT_LN0 ? reinterpret_cast<const uint8_t*>(p.x) + rg * 10240 : reinterpret_cast<const uint8_t*>(g_x) + rg * 174080;
        if (type == IT_LN) { flag = SY_P + b * 4; need = 2; }
        if (type == IT_LN0 || part) need = 0;
      } else if (part) {
        bytes = 6 * KV_PART;
      } else if (type == IT_ATT && !qa) {
        bytes = chunk = 49152;
        src = reinterpret_cast<const uint8_t*>(g_q) + (b * 32 + idx) * 49152;
        flag = SY_P + b * 4 + 3; need = 32;
      } else {
        const int cols = item_cols(type, b);
        chunk = 16384; nb = (cols + 63) >> 6;
        src = reinterpret_cast<const uint8_t*>(g_of) + b * 163840;
        if (type == IT_OP) {
          const int nkb = op_steps(b), kb0 = (idx >> op_shift(b)) * nkb;
          bytes = nkb * 16384;
          src = reinterpret_cast<const uint8_t*>(g_o) + (b * 96 + kb0) * 16384;
          if (weights) m = &p.wo;
          c0 = (idx & (op_tiles(b) - 1)) * cols; c3 = 0; c4 = kb0 * 2; s4 = 2;
        } else if (type == IT_BQ) {
          m = weights ? &p.wb[cols >> 7] : &p.xn;
        } else if (type == IT_BO || type == IT_OUT) {
          if (weights) m = &p.wc[cols >> 8];
          flag = SY_OB; need = type == IT_BO && b < 2 ? 32 : -1;
        } else {
          m = weights ? &p.wq : &p.xn;
          c3 = 0; c4 = idx * 3; s3 = 64; s4 = 0;
          flag = SY_P + b * 4 + 1; need = ln_items(p.ch.layer, b);
        }
      }
      if (!weights) {
        c3 = b * 16; c4 = s3 = s4 = 0;
        if (need < 0) pdl_wait(); else if (need) { wait_count(p.sync + flag, need); EV(code, 2); }
        if ((ln ? !part : part && (!qa || (code & C_EARLY)))) mbar_arrive_one(bGo);
      }
      if (++part == parts) { mbar_arrive_one(bIE + 8 * (n & 3)); part = 0; n++; }
      const int pace = code & C_TAIL ? 0 : p.pace;
      const int boxes = weights && !s3 ? nb : m != nullptr;
#pragma unroll 1
      for (; bytes > 0; bytes -= chunk) {
        const int now = min(bytes, chunk), len = ((now + 8191) >> 13) + nb, skip = pos + len > WK_SLOTS ? WK_SLOTS - pos : 0, sh = 4 * (seq & 7);
        used += len + skip;
        while (used > WK_SLOTS || seq - tail >= 8) {
          mbar_wait(bars + 64 + 8 * (tail & 7), (tail >> 3) & 1);
          used -= (lens >> 4 * (tail & 7)) & 15;
          tail++;
        }
        lens = (lens & ~(15u << sh)) | (len + skip) << sh;
        if (pos + len > WK_SLOTS) pos = 0;
        const uint32_t bar = bars + 2 * sh, dst = sb + pos * 8192 + weights * 16384;
        if (pace) { until(tn); tn = clk64() + len * pace; }
        mbar_expect_one(bar, weights ? nb * 8192 : now);
#pragma unroll 1
        for (int i = 0; i < boxes; i++)
          tma_load5_one(dst + i * 8192, m, c0 + i * 64, c3, c4, bar);
        if (!weights && !m) bulk_load_last_one(dst, src, now, bar);
        c3 += s3; c4 += s4;
        if (!weights) c0 += 128;
        src += chunk; pos += len; seq++;
      }
    }
  }
}

__global__ void __launch_bounds__(384, 1) work_kernel(const __grid_constant__ WorkParams p) {
  extern __shared__ __align__(1024) uint8_t smem_raw[];
  const uint32_t sb = s2u(smem_raw), bars = sb + WK_BAR;
  const uint32_t bIF = bars + 128, bIE = bars + 160, done = bars + 192, bGo = bars + 224, slots = bars + 272, scratch = bars + 384;
  const int warp = __shfl_sync(~0u, threadIdx.x >> 5, 0);
  uint32_t* const sync = p.sync;
  TRACE(0);
  pdl_launch();
  if (p.kind == WK_LEAD && !helper_sm() && __any_sync(~0u, __syncthreads_or(threadIdx.x == 0 && ldg_strong32(sync + SY_PRE + 1) >= LEAD1))) { pdl_wait(); return; }
  if (p.kind == WK_CHAIN) {
    chain_start(p.ch, sb, warp);
  } else {
    if (warp < 4) work_init(sb, warp);
    __syncthreads();
    if (p.kind == WK_FIRST) {
      if (!(warp & 13)) probe_slots(bars + 320);
      if (!helper_sm()) return;
    }
  }
  if (warp >= 8) {
    asm volatile("setmaxnreg.dec.sync.aligned.u32 40;");
    if (p.kind == WK_CHAIN) chain_comm(p.ch, sb, &p.wo);
    const int warp = __shfl_sync(~0u, fresh_tid() >> 5, 0), lane = fresh_tid() & 31;
    if (warp == 9) {
      const bool keep = p.kind > WK_LEAD || helper_sm();
      int n = 0, code = p.kind == WK_CHAIN ? reserved_item(blockIdx.x) : -1;
      if (code >= 0) {
        sts32(slots, code);
        mbar_arrive_one(bIF);
        n = 1;
      }
      const int b = lane & 15, layer = p.kind == WK_LAST ? 2 : sync != g_sync;
      bool first = layer == 1, lead = p.kind != WK_CHAIN;
      for (;; n++) {
        if (n > 0) mbar_wait(bGo, (n - 1) & 1);
        mbar_wait(bIE + 8 * (n & 3), ((n >> 2) & 1) ^ 1);
        code = -1;
        if (lead) {
          int i = blockIdx.x + n * 256;
          if (first) { i = __reduce_add_sync(~0u, atomic_inc_one(sync + SY_PRE + 1)); first = i < LEAD1; }
          if (layer < 2 && !first) {
            i = 1 << 20;
            if (keep) i = __reduce_add_sync(~0u, atomic_inc_one(sync + SY_PRE)) + layer * LEAD1; else pdl_wait();
          }
          code = lead_item(layer, p.qa_end, i);
          lead = code >= 0 || layer == 2 || !keep;
          if (!lead && p.kind <= WK_LEAD) {
            const uint32_t t0 = gtime();
            while (!lead && __all_sync(~0u, ldg_strong32(sync + SY_UP) < 96)) lead = __any_sync(~0u, gtime() - t0 > 20000);
          }
        }
        if (!lead) {
          int spin = 0;
          const int ticket = atomic_inc_one(sync + SY_T);
          for (;;) {
            const uint4 hd = ldg_strong128(sync + b * 8), pr = ldg_strong128(sync + b * 8 + 4);
            const uint32_t hv[4] = {hd.x, hd.y, hd.z, hd.w}, pv[4] = {pr.x, pr.y, pr.z, pr.w};
            const uint32_t chain_done = __ballot_sync(~0u, (pr.x & 0xffff) >= 96) | (p.kind == WK_CHAIN) << 15;
            int left[4], avail[4], rdy = 0, claimed = 0, upstream = 0;
#pragma unroll
            for (int t = 0; t < 4; t++) {
              const int cnt = lane < 16 && !reserved(t, b) ? item_count(t, b) : 0;
              left[t] = max(cnt - (int)hv[t], 0);
              claimed += cnt - left[t];
              const bool ready = (pv[t] & 0xffff) >= item_need(t, b);
              rdy |= ready << t;
              bool ok = ready || (t != IT_ATT && (chain_done >> 15 & 1) && !left[t - 1] && (t < 2 || !left[t - 2]));
              if (t == IT_BQ && (chain_done >> HOLD_B & 1) && !(chain_done >> 15 & 1)) ok = false;
              avail[t] = ok ? left[t] : 0;
              upstream |= __any_sync(~0u, left[t] > 0);
            }
            if (!upstream) { code = -1; break; }
            int rank = max(__reduce_add_sync(~0u, ticket - claimed), 0), type = -1, mine = 0;
#pragma unroll
            for (int c = 0; c < 7; c++) {
              const int t = c == 0 || c == 6 ? IT_ATT : c == 1 || c == 4 ? IT_FIN : c == 2 ? IT_OP : IT_BQ;
              int a = c == 2 || (rdy >> t & 1) == (c < 4) ? avail[t] : 0;
              if (c == 6) a = b < p.qa_end && !(rdy & 1) && ((chain_done << 1 | 1) >> b & 1) ? left[t] : 0;
              const int tot = __reduce_add_sync(~0u, a);
              if (type < 0) { if (rank < tot) { type = t; mine = a; } else rank -= tot; }
            }
            if (type >= 0) {
#pragma unroll
              for (int o = 1; o < 16; o <<= 1) { const int y = __shfl_up_sync(~0u, mine, o); if (lane >= o) mine += y; }
              const int blk = __ffs(__ballot_sync(~0u, mine > rank)) - 1;
              const int early = !(__shfl_sync(~0u, rdy, blk) >> type & 1);
              const uint32_t idx = __reduce_add_sync(~0u, atomic_inc_one(sync + blk * 8 + type));
              if (idx < item_count(type, blk)) { code = (type == IT_ATT && blk < p.qa_end) << 23 | (chain_done >> 14 & 1) << 22 | early << 20 | type << 16 | blk << 8 | idx; break; }
            } else {
              __nanosleep(50);
            }
            spin_guard(spin);
          }
        }
        sts32(slots + 4 * (n & 3), code);
        mbar_arrive_one(bIF + 8 * (n & 3));
        if (code < 0) break;
      }
    } else if (warp >= 10) {
      work_loader(p, sb, warp == 10);
    } else {
      for (int n = 0;; n++) {
        mbar_wait(bIF + 8 * (n & 3), (n >> 2) & 1);
        const int code = __shfl_sync(~0u, (int)lds32(slots + 4 * (n & 3)), 0);
        if (code < 0) break;
        const int type = (code >> 16) & 15, b = (code >> 8) & 255;
        mbar_wait(done + 8 * (n & 3), (n >> 2) & 1);
        const uint32_t t_done = gtime();
        if (elect()) {
          if (type != IT_OUT) red_release(sync + (type < IT_BQ ? b * 8 + 5 + type : SY_P + b * 4 + ((0x13102 >> 4 * (type - IT_BQ)) & 3)), 1);
          mbar_arrive(bIE + 8 * (n & 3));
          EV(code, 1);
        }
        __syncwarp();
      }
    }
  } else {
    asm volatile("setmaxnreg.inc.sync.aligned.u32 232;");
    if (p.kind == WK_CHAIN) chain_compute(p.ch, sb);
    const int warp = __shfl_sync(~0u, fresh_tid() >> 5, 0), lane = fresh_tid() & 31;
    Ring r{sb, 0, p.kind == WK_CHAIN};
    int nln = 0;
#pragma unroll 1
    for (int n = 0;; n++) {
      mbar_wait(bIF + 8 * (n & 3), (n >> 2) & 1);
      int code = __shfl_sync(~0u, (int)lds32(slots + 4 * (n & 3)), 0);
      if (code < 0) { TRACE(2); break; }
      if (((code >> 16) & 15) == IT_ATT || (code & C_PROJ)) {
        Pending pend = {};
#pragma unroll 1
        for (;; n++) {
          const int tile = (((code >> 8) & 255) * 32 + (code & 255)) * 3072 + warp * 128;
          int next = 0;
          auto peek = [&]() {
            uint32_t here;
            asm volatile("{.reg .pred p; mbarrier.test_wait.parity.shared::cta.b64 p, [%1], %2; selp.u32 %0, -1, 0, p;}" : "=r"(here) : "r"(bIF + 8 * ((n + 1) & 3)), "r"(((n + 1) >> 2) & 1) : "memory");
            next = __shfl_sync(~0u, (int)(lds32(slots + 4 * ((n + 1) & 3) + (here & p.ch.zero)) & here), 0);
            return next < C_PROJ;
          };
          ITEM(code & 0xfffff, 0);
          if (code & C_PROJ) {
            float d[96];
            ITEM(9 << 16 | (code & 0xffff), 0);
            gemm_step<192>(d, r, warp, 0);
#pragma unroll 1
            for (int kb = 1; kb < 10; kb++) {
              gemm_step<192>(d, r, warp, 1);
              if (kb == 4 && (code & (C_EARLY | 15 << 16)) != C_EARLY && warp == 0) mbar_arrive_one(bGo);
              if (pend.done) {
#pragma unroll
                for (int i = 0; i < 12; i++) if (kb == 1 + i / 2) pend.store(i);
                if (kb == 6) pend.finish();
              }
              wg_wait<1>();
              r.release(r.seq - 2);
            }
            wg_wait<0>();
            reg_fence<96>(d);
            r.release(r.seq - 1);
            ITEM(9 << 16 | (code & 0xffff), 1);
#pragma unroll
            for (int i = 0; i < 48; i++) pend.w[i] = pack2(d[2 * i], d[2 * i + 1]);
          } else {
            const uint32_t base = r.wait(6) + warp * 2048 + lane * 16;
#pragma unroll
            for (int i = 0; i < 12; i++) {
              const uint4 t = lds128(base + (i >> 2) * 16384 + (i & 3) * 512);
              pend.w[4 * i] = t.x; pend.w[4 * i + 1] = t.y; pend.w[4 * i + 2] = t.z; pend.w[4 * i + 3] = t.w;
            }
            __syncwarp();
            r.release(r.seq - 1);
          }
          if (code & 15 << 16) {
            pend.dst = g_q + tile + lane;
            if (peek()) {
#pragma unroll
              for (int i = 0; i < 12; i++) pend.store(i);
            }
          } else {
            pend.dst = g_o + tile + (lane & 3) * 8 + (lane >> 2);
            attn_a(r, pend, peek, warp, lane);
          }
          pend.done = done + 8 * (n & 3);
          ITEM(code & 0xfffff, 1);
          if (next < C_PROJ) break;
          code = next;
        }
        pend.finish();
      } else {
        const int type = (code >> 16) & 15, b = (code >> 8) & 255, idx = code & 255;
        const uint32_t go = code & C_LATE ? 0 : bGo;
        ITEM(code & 0xfffff, 0);
        if (type == IT_FIN || type == IT_LN || type == IT_LN0) {
          const int ng = item_groups(type, b);
          const int planes = type == IT_FIN ? op_split(b) + 1 : type == IT_LN ? 2 : 1;
#pragma unroll 1
          for (int i = 0; i < ng; i += 2) ln_groups(r, scratch + (nln++ & 1) * 1024, planes, b * 16 + idx * ng + i, ng > 1);
        } else {
          const int cols = item_cols(type, b), nkb = type == IT_OP ? op_steps(b) : 10;
          float d[160] = {};
          if (type == IT_OUT) {
            const uint2* x = g_x + ((b * 16 + warp * 2) * 680 + idx * 5) * 32 + lane;
#pragma unroll
            for (int i = 0; i < 10; i++) { const uint2 y = __ldcg(x + (i / 5 * 680 + i % 5) * 32); d[40 + 2 * i] = __uint_as_float(y.x); d[41 + 2 * i] = __uint_as_float(y.y); }
          }
          reg_fence<160>(d);
          if (type != IT_OUT) ITEM((type == IT_BQ ? 10 : 11) << 16 | (code & 0xffff), 0);
          const int ask = max(nkb - ((code & C_TAIL ? GO_TAIL : GO_320) << (2 - (cols >> 7))), 0);
          if (cols == 320) gemm_item<320>(d, r, warp, nkb, go, ask);
          else if (cols == 160) gemm_item<160>(d, r, warp, nkb, go, ask);
          else gemm_item<80>(d, r, warp, nkb, go, ask);
          if (type != IT_OUT) ITEM((type == IT_BQ ? 10 : 11) << 16 | (code & 0xffff), 1);
          reg_fence<160>(d);
          if (type == IT_OUT) {
            bar_sync(1, 256);
            const uint32_t dst = sb + (warp * 16 + (lane & 15)) * 160 + (lane >> 4) * 16;
#pragma unroll
            for (int u = 0; u < 5; u++) {
              uint32_t w[4];
#pragma unroll
              for (int i = 0; i < 4; i++) { const uint32_t y = __float_as_uint(d[40 + (i & 1) * 10 + 2 * u + (i >> 1)]); w[i] = pack2(bf_lo(y) + d[8 * u + 2 * i], bf_hi(y) + d[8 * u + 2 * i + 1]); }
              stsm4(dst + u * 32, w[0], w[1], w[2], w[3]);
            }
            fence_async();
            __syncwarp();
            if (elect()) { tma_store(&p.out, sb + warp * 2560, idx * 80, b * 128 + warp * 16); bulk_commit(); bulk_wait<0>(); }
          } else {
            if (warp >= 4) bar_sync(7, 256);
            if (type == IT_BQ) store_bqkv(d, b, idx, 4 << (cols >> 7));
            else { const int sh = 3 - (cols >> 7); store_partial(d, b, idx >> sh, (idx & ((1 << sh) - 1)) * (cols >> 4), cols >> 4); }
            if (warp < 4) bar_arrive(7, 256);
          }
        }
        __syncwarp();
        mbar_arrive_one(done + 8 * (n & 3));
        if ((code & C_LATE) && warp == 4) mbar_arrive_one(bGo);
        ITEM(code & 0xfffff, 1);
      }
    }
  }
}

constexpr int AB_SMEM = 1024 + 2 * 98304 + 256 + 5 * 6144;
#define AB_N 32
constexpr int AB_T = 512;
#define AB_NS 4300
__device__ __forceinline__ float ex2_poly(float t) {
  const uint32_t r = __float_as_uint(t) & 0xffff8000u;
  const float f = t - __uint_as_float(r);
  const float p = fmaf(fmaf(fmaf(-5.869912678e-38f, f, -1.700740250e-37f), f, -5.234869734e-37f), f, -7.522601252e-37f);
  uint32_t y;
  asm("mad.lo.u32 %0, %1, 256, %2;" : "=r"(y) : "r"(r), "r"(__float_as_uint(p)));
  return __uint_as_float(y);
}
__device__ __forceinline__ uint32_t hsq(uint32_t w, uint32_t c) { uint32_t r; asm("fma.rn.bf16x2 %0, %1, %1, %2;" : "=r"(r) : "r"(w), "r"(c)); return r; }
__device__ __forceinline__ float sq2(uint32_t w) { const float a = bf_lo(w), b = bf_hi(w); return fmaf(a, a, b * b); }

__device__ __forceinline__ void attn_b_store(const float* o, int h, int row0, int lane) {
  const int g = lane >> 2, c = lane & 3;
  const float i0 = rcp(__shfl_sync(~0u, o[8], (lane & ~3) | 2)), i1 = rcp(__shfl_sync(~0u, o[10], (lane & ~3) | 2));
#pragma unroll
  for (int jj = 0; jj < 3; jj++) {
    if (jj < 2 || c < 2) {
      const int col = h * 20 + 8 * jj + 2 * c;
      g_of[core_word(row0 + g, col)] = pack2(o[4 * jj] * i0, o[4 * jj + 1] * i0);
      g_of[core_word(row0 + g + 8, col)] = pack2(o[4 * jj + 2] * i1, o[4 * jj + 3] * i1);
    }
  }
}

__device__ __forceinline__ void attn_b_qk(float* s, uint32_t q0, uint32_t q1, uint32_t q2, uint32_t q3, uint32_t q4, uint32_t q5, uint32_t z0, uint32_t z1,
                                          uint64_t dk, uint64_t dk2) {
  wg_rs32_00(s, q0, q1, q2, q3, dk, 0);
  wg_rs32_00(s, q4, q5, z0, z1, dk2, 1);
}

struct AttnParams { const uint8_t* pf[4]; uint32_t *sync, *next; };
__global__ void __launch_bounds__(AB_T + 128, 1) attn_b_kernel(const __grid_constant__ AttnParams p) {
  extern __shared__ uint8_t smem_raw[];
  const uint32_t sb = (s2u(smem_raw) + 1023) & ~1023u, sK = sb, sV = sb + 98304, bars = sb + 2 * 98304;
  const int warp = __shfl_sync(~0u, threadIdx.x >> 5, 0), lane = threadIdx.x & 31;
  const int h = blockIdx.x & 31, quarter = blockIdx.x >> 5;
  BT(0);
  TRACE(0);
  if (warp < 10 && elect()) {
    mbar_init(bars + 8 * warp + (warp & 8) * 8, warp < 8 ? 1 : warp == 8 ? AB_T / 32 : 3);
    asm volatile("fence.mbarrier_init.release.cluster;" ::: "memory");
  }
  __syncthreads();
  if (warp >= AB_T / 32) {
    asm volatile("setmaxnreg.dec.sync.aligned.u32 32;");
    if (warp == AB_T / 32 + 1) {
      mbar_wait(bars + 8 * quarter, 0);
      uint32_t t = gtime();
#pragma unroll 1
      for (int i = 0; i < 8; i++) {
        mbar_wait(bars + 8 * i, 0);
        const uint32_t now = gtime();
        t = ((int)(now - t) > 0 ? now : t) + AB_NS / 2;
      }
      uint32_t* ends = p.sync + SY_B + h * 4;
      if (lane == 0) stg_strong32(ends + quarter, t | 1);
      for (int spin = 0; t = ldg_strong32(ends + (lane & 3)), !__all_sync(~0u, t);) spin_guard(spin);
      int e = (int)(t - __shfl_sync(~0u, t, 0)) * 4 + (lane & 3), n = 0;
#pragma unroll 1
      for (int i = 0; i < 16; i++)
        if (e == __reduce_min_sync(~0u, e)) { e += 4 * AB_NS; n++; }
      const int first = 16 + __reduce_add_sync(~0u, lane < quarter ? n : 0);
      if (lane == quarter) { sts64(bars + 72, first, n); mbar_arrive(bars + 136); }
      return;
    }
    if (warp > AB_T / 32) {
      uint32_t kmax = 0;
#pragma unroll 1
      for (int i = 0; i < 32; i++) {
        if (!(i & 3)) mbar_wait(bars + 2 * i, 0);
        const uint32_t a = sK + i * 3072 + ((threadIdx.x >> 3) & 7) * 384 + (lane & 7) * 16;
        const uint4 x = lds128(a), y = lds128(a + 128);
        const uint2 z = lds64(a + 256);
        const uint32_t n = hadd2(hsq(x.x, hsq(x.y, hsq(x.z, hsq(x.w, hsq(z.x, 0))))), hsq(y.x, hsq(y.y, hsq(y.z, hsq(y.w, hsq(z.y, 0))))));
        kmax = max(kmax, __float_as_uint(bf_lo(n) + bf_hi(n)) & 0x7fffffffu);
      }
      const uint32_t kbits = __reduce_max_sync(~0u, kmax);
      if (lane == 0) { sts32(bars + 64 + (warp & 1) * 4, kbits); mbar_arrive(bars + 136); }
      return;
    }
    const uint8_t* gk = reinterpret_cast<const uint8_t*>(g_bqkv + (32 + h) * 256 * 96);
    const uint8_t* gv = reinterpret_cast<const uint8_t*>(g_bqkv + (64 + h) * 256 * 96);
    uint32_t todo = 255;
    for (int spin = 0; todo;) {
      const uint32_t up = __ballot_sync(~0u, ld_acquire(p.sync + SY_P + (lane & 15) * 4 + 2) >= bq_items(lane & 15));
      fence_async_global();
#pragma unroll 1
      for (int i = 0; i < 8; i++) {
        if (!(todo >> i & 1) || (up >> 2 * i & 3) != 3) continue;
        todo &= ~(1u << i);
        if (elect()) {
          mbar_expect(bars + 8 * i, 24576);
          bulk_load(sK + i * 12288, gk + i * 12288, 12288, bars + 8 * i);
          bulk_load(sV + i * 12288, gv + i * 12288, 12288, bars + 8 * i);
        }
      }
      spin_guard(spin);
    }
    pdl_launch();
    TRACE(1);
#pragma unroll 1
    for (int i = lane; i < 512 && blockIdx.x < NSLOT; i += 32) reinterpret_cast<uint4*>(pool_at(blockIdx.x * 8192))[i] = make_uint4(0, 0, 0, 0);
    if (!p.next && blockIdx.x < 8) { const int i = blockIdx.x * 32 + lane; g_smpart[i] = 0; if (i < NSLOT) g_orient[i] = 0; }
    if (p.next) {
#pragma unroll 1
      for (int i = 0; i < (PF_NS ? 32 : 0); i++) {
        if (elect()) prefetch_l2(p.pf[i >> 3] + blockIdx.x * 61440 + (i & 7) * 7680, 7680);
        __nanosleep(PF_NS);
      }
      mbar_wait(bars + 128, 0);
      if (quarter == 0 && lane == 0) red_release(p.next + SY_OB, 1);
    }
    return;
  }
  asm volatile("setmaxnreg.inc.sync.aligned.u32 112;");
  constexpr int NT = SEQ / AB_N, PER = 256 / AB_N;
  uint32_t qn[8];
  const int wg = warp >> 2;
  int tile = quarter * 4, left = 4, share = 0;
  auto load_q = [&]() {
    const uint32_t* gq = g_bqkv + (h * 256 + (tile + (wg >> share)) * 8 + (warp & 3) * 2) * 96 + lane;
#pragma unroll
    for (int i = 0; i < 8; i++) qn[i] = __ldcg(gq + (i & 1) * 96 + min(i >> 1, 2) * 32 + (i < 6 ? 0 : 3 - (lane & 3)));
  };
  mbar_wait(bars + 8 * quarter, 0);
  load_q();
#pragma unroll 1
  for (int pass = 0; left; pass++) {
    const int row0 = (tile + (wg >> share)) * 64 + (warp & 3) * 16, part = wg & ((1 << share) - 1), k0 = part * NT >> share, k1 = k0 + (NT >> share), group = share;
    const uint32_t q0 = qn[0], q1 = qn[1], q2 = qn[2], q3 = qn[3], z0 = qn[6], z1 = qn[7];
    uint32_t q4 = qn[4], q5 = qn[5];
    if ((lane & 3) == 2) { q4 = 0x43BCu; q5 = 0x43BCu; }
    float o[12] = {};
    reg_fence<12>(o);
    uint64_t dk = mkdesc(sK, 128, 384, 0), dk2 = mkdesc(sK + 256, 0, 384, 0), dv = mkdesc(sV, 384, 128, 0) + k0 * (AB_N * 3);
    float sa[AB_N / 2], sb2[AB_N / 2];
    uint32_t pa[AB_N / 4], pb[AB_N / 4];
    if (pass == 0) mbar_wait(bars, 0);
    BT(1 + 2 * min(pass, 1));
    wg_fence();
    attn_b_qk(sa, q0, q1, q2, q3, q4, q5, z0, z1, dk + k0 * (AB_N * 3), dk2 + k0 * (AB_N * 3));
    wg_commit();
    attn_b_qk(sb2, q0, q1, q2, q3, q4, q5, z0, z1, dk + (k0 + 1) * (AB_N * 3), dk2 + (k0 + 1) * (AB_N * 3));
    wg_commit();
    int kt = k0;
#pragma unroll 1
    do {
      const int nx = kt + 2 < NT ? kt + 2 : 0;
      if (pass == 0 && (nx & (PER - 1)) == 0) mbar_wait(bars + 8 * (nx / PER), 0);
      const uint64_t nk = dk + nx * (AB_N * 3), nk2 = dk2 + nx * (AB_N * 3);
      wg_wait<1>();
      reg_fence<AB_N / 2>(sa);
#pragma unroll
      for (int i = 0; i < AB_N / 4; i++) pa[i] = pack2(ex2(sa[2 * i]), poly_group(i >> 1) ? ex2_poly(sa[2 * i + 1]) : ex2(sa[2 * i + 1]));
      wg_fence();
#pragma unroll
      for (int kk = 0; kk < AB_N / 16; kk++) wg_rs24_01(o, pa[4 * kk], pa[4 * kk + 1], pa[4 * kk + 2], pa[4 * kk + 3], dv + kk * 48, 1);
      attn_b_qk(sa, q0, q1, q2, q3, q4, q5, z0, z1, nk, nk2);
      wg_commit();
      wg_wait<1>();
      reg_fence<AB_N / 2>(sb2);
#pragma unroll
      for (int i = 0; i < AB_N / 4; i++) pb[i] = pack2(ex2(sb2[2 * i]), poly_group((i >> 1) + AB_N / 8) ? ex2_poly(sb2[2 * i + 1]) : ex2(sb2[2 * i + 1]));
      wg_fence();
#pragma unroll
      for (int kk = 0; kk < AB_N / 16; kk++) wg_rs24_01(o, pb[4 * kk], pb[4 * kk + 1], pb[4 * kk + 2], pb[4 * kk + 3], dv + AB_N * 3 + kk * 48, 1);
      attn_b_qk(sb2, q0, q1, q2, q3, q4, q5, z0, z1, nk + AB_N * 3, nk2 + AB_N * 3);
      wg_commit();
      dv += AB_N * 6;
    } while ((kt += 2) < k1);
    wg_wait<0>();
    reg_fence<12>(o); reg_fence<AB_N / 2>(sa); reg_fence<AB_N / 2>(sb2);
    BT(2 + 2 * min(pass, 1));
    mbar_wait(bars + 136, 0);
    const uint4 kb = lds128(bars + 64);
    const float kmax = __uint_as_float(max(kb.x, kb.y));
    tile += 4 >> share; left -= 4 >> share;
    if (pass == 0) { tile = __shfl_sync(~0u, kb.z, 0); left = __shfl_sync(~0u, kb.w, 0); }
    share = left >= 4 ? 0 : left >= 2 ? 1 : 2;
    if (left) load_q();
    if (group) {
      const uint32_t slot = bars + 256 + (threadIdx.x & 127) * 16 + (group == 1 ? wg >> 1 : 2) * 6144;
      if (part) {
#pragma unroll
        for (int i = 0; i < 3; i++) sts128f(slot + (part - 1) * 6144 + i * 2048, o[4 * i], o[4 * i + 1], o[4 * i + 2], o[4 * i + 3]);
        bar_arrive(4 + group * 2 + (wg >> group), 128 << group);
        continue;
      }
      bar_sync(4 + group * 2 + (wg >> group), 128 << group);
#pragma unroll 1
      for (int u = 0; u < 2 * group - 1; u++) {
#pragma unroll
        for (int i = 0; i < 3; i++) { const float4 x = lds128f(slot + u * 6144 + i * 2048); o[4 * i] += x.x; o[4 * i + 1] += x.y; o[4 * i + 2] += x.z; o[4 * i + 3] += x.w; }
      }
    }
    if ((lane & 3) == 2) q4 = q5 = 0;
    float n0 = sq2(q0) + sq2(q2) + sq2(q4), n1 = sq2(q1) + sq2(q3) + sq2(q5);
    n0 += __shfl_xor_sync(~0u, n0, 1); n1 += __shfl_xor_sync(~0u, n1, 1);
    n0 += __shfl_xor_sync(~0u, n0, 2); n1 += __shfl_xor_sync(~0u, n1, 2);
    uint32_t redo;
    asm volatile("{.reg .pred p, q; setp.ne.u32 p, %1, 0; bar.red.or.pred q, %2, 128, p; selp.u32 %0, 1, 0, q;}"
                 : "=r"(redo) : "r"((uint32_t)!(n0 * kmax <= 9500.f && n1 * kmax <= 9500.f)), "r"(2 + (warp >> 2)) : "memory");
    if (redo) {
#pragma unroll
      for (int i = 0; i < 12; i++) o[i] = 0.f;
      float m0 = -INFINITY, m1 = -INFINITY;
#pragma unroll 1
      for (int kt = 0; kt < 64; kt++) {
        float s[16];
        wg_fence();
        wg_rs32_00(s, q0, q1, q2, q3, dk + kt * 96, 0);
        wg_rs32_00(s, q4, q5, z0, z1, dk2 + kt * 96, 1);
        wg_commit();
        wg_wait<0>();
        reg_fence<16>(s); reg_fence<12>(o);
        float n0 = m0, n1 = m1;
#pragma unroll
        for (int jj = 0; jj < 4; jj++) { n0 = fmaxf(n0, fmaxf(s[4 * jj], s[4 * jj + 1])); n1 = fmaxf(n1, fmaxf(s[4 * jj + 2], s[4 * jj + 3])); }
        n0 = fmaxf(n0, __shfl_xor_sync(~0u, n0, 1)); n0 = fmaxf(n0, __shfl_xor_sync(~0u, n0, 2));
        n1 = fmaxf(n1, __shfl_xor_sync(~0u, n1, 1)); n1 = fmaxf(n1, __shfl_xor_sync(~0u, n1, 2));
        const float r0 = ex2(m0 - n0), r1 = ex2(m1 - n1);
        m0 = n0; m1 = n1;
#pragma unroll
        for (int jj = 0; jj < 3; jj++) { o[4 * jj] *= r0; o[4 * jj + 1] *= r0; o[4 * jj + 2] *= r1; o[4 * jj + 3] *= r1; }
        uint32_t pp[8];
#pragma unroll
        for (int jj = 0; jj < 4; jj++) {
          pp[2 * jj] = pack2(ex2(s[4 * jj] - m0), ex2(s[4 * jj + 1] - m0));
          pp[2 * jj + 1] = pack2(ex2(s[4 * jj + 2] - m1), ex2(s[4 * jj + 3] - m1));
        }
        reg_fence<12>(o);
        wg_fence();
#pragma unroll
        for (int kk = 0; kk < 2; kk++) wg_rs24_01(o, pp[4 * kk], pp[4 * kk + 1], pp[4 * kk + 2], pp[4 * kk + 3], mkdesc(sV, 384, 128, 0) + kt * 96 + kk * 48, 1);
        wg_commit();
      }
      wg_wait<0>();
      reg_fence<12>(o);
    }
    attn_b_store(o, h, row0, lane);
    __syncwarp();
    if (pass == 0) mbar_arrive_one(bars + 128);
  }
  BT(5);
  TRACE(2);
}

typedef CUresult (*EncodeFn)(CUtensorMap*, CUtensorMapDataType, cuuint32_t, void*, const cuuint64_t*, const cuuint64_t*,
                             const cuuint32_t*, const cuuint32_t*, CUtensorMapInterleave, CUtensorMapSwizzle,
                             CUtensorMapL2promotion, CUtensorMapFloatOOBfill);

void make_map(EncodeFn enc, CUtensorMap* m, const void* ptr, int cols, int rows, int box_rows, int box_cols = 64) {
  const cuuint64_t dims[2] = {(cuuint64_t)cols, (cuuint64_t)rows};
  const cuuint64_t strides[1] = {(cuuint64_t)cols * 2};
  const cuuint32_t box[2] = {(cuuint32_t)box_cols, (cuuint32_t)box_rows}, es[2] = {1, 1};
  enc(m, CU_TENSOR_MAP_DATA_TYPE_BFLOAT16, 2, const_cast<void*>(ptr), dims, strides, box, es, CU_TENSOR_MAP_INTERLEAVE_NONE,
      box_cols == 64 ? CU_TENSOR_MAP_SWIZZLE_128B : box_cols == 32 ? CU_TENSOR_MAP_SWIZZLE_64B : CU_TENSOR_MAP_SWIZZLE_NONE, CU_TENSOR_MAP_L2_PROMOTION_L2_256B, CU_TENSOR_MAP_FLOAT_OOB_FILL_NONE);
}
void make_map5(EncodeFn enc, CUtensorMap* m, const void* ptr, bool words, const cuuint64_t (&dims)[5], const cuuint64_t (&strides)[4], const cuuint32_t (&box)[5]) {
  const cuuint32_t es[5] = {1, 1, 1, 1, 1};
  enc(m, words ? CU_TENSOR_MAP_DATA_TYPE_UINT64 : CU_TENSOR_MAP_DATA_TYPE_BFLOAT16, 5, const_cast<void*>(ptr), dims, strides, box, es, CU_TENSOR_MAP_INTERLEAVE_NONE,
      words ? CU_TENSOR_MAP_SWIZZLE_NONE : CU_TENSOR_MAP_SWIZZLE_128B, dims[0] % 64 ? CU_TENSOR_MAP_L2_PROMOTION_L2_128B : CU_TENSOR_MAP_L2_PROMOTION_L2_256B,
      CU_TENSOR_MAP_FLOAT_OOB_FILL_NONE);
}
void make_tiles(EncodeFn enc, CUtensorMap* m, const void* ptr, cuuint64_t cols, cuuint64_t tile) {
  make_map5(enc, m, ptr, false, {tile, 1, 1, cols / tile, DM}, {tile * 2, tile * 2, tile * 2, cols * 2}, {64, 1, 1, 1, 64});
}
template <class... KA, class... A>
void launch(void (*kern)(KA...), int grid, int block, int smem, int cluster, bool pdl, A... args) {
  cudaFuncSetAttribute(kern, cudaFuncAttributeMaxDynamicSharedMemorySize, smem);
  cudaLaunchConfig_t cfg = {};
  cfg.gridDim = dim3(grid); cfg.blockDim = dim3(block); cfg.dynamicSmemBytes = smem; cfg.stream = cudaStreamPerThread;
  cudaLaunchAttribute at[2];
  int n = 0;
  if (cluster > 1) { at[n].id = cudaLaunchAttributeClusterDimension; at[n].val.clusterDim.x = cluster; at[n].val.clusterDim.y = 1; at[n].val.clusterDim.z = 1; n++; }
  if (pdl) { at[n].id = cudaLaunchAttributeProgrammaticStreamSerialization; at[n].val.programmaticStreamSerializationAllowed = 1; n++; }
  cfg.attrs = at; cfg.numAttrs = n;
  cudaLaunchKernelEx(&cfg, kern, args...);
}
template <class T> void* sym(T& s) { void* p = nullptr; cudaGetSymbolAddress(&p, s); return p; }

}

#define MODE(b) 0
extern "C" void kernel_launch(void* const* d_in, const int* in_sizes, int n_in, void* d_out, int out_size) {
  const __nv_bfloat16* x = (const __nv_bfloat16*)d_in[0];
  void* fn = nullptr; cudaDriverEntryPointQueryResult qr;
  cudaGetDriverEntryPoint("cuTensorMapEncodeTiled", &fn, cudaEnableDefault, &qr);
  EncodeFn enc = (EncodeFn)fn;

  WorkParams wk = {};
  ChainParams& ch = wk.ch;
  AttnParams at = {};
  make_map(enc, &ch.wq, d_in[2], HD, DM, 160); make_map(enc, &ch.wk, d_in[3], HD, DM, 160); make_map(enc, &ch.wv, d_in[4], HD, DM, 160);
  make_map(enc, &ch.wo, d_in[5], DM, HD, 192, 32);
  ch.mem0 = (const __nv_bfloat16*)d_in[1];
  ch.wb = (const uint8_t*)d_in[8];
  ch.d1 = 250; ch.d2 = 200; ch.dn = 150; ch.dx = 1000;
  make_map5(enc, &wk.wq, d_in[2], false, {64, 1, 1, DM, HD / 64}, {128, 128, HD * 2, 128}, {64, 1, 1, 64, 3});
  for (int i = 0; i < 3; i++) make_tiles(enc, &wk.wb[i], d_in[8], 1920, 80 << i);
  for (int i = 0; i < 2; i++) make_tiles(enc, &wk.wc[i], d_in[9], DM, 80 << 2 * i);
  make_map(enc, &wk.out, d_out, DM, SEQ, 16, 80);
  make_map5(enc, &wk.wo, d_in[5], false, {DM, 2, 4, 4, HD / 32}, {DM * 2, DM * 16, DM * 4, DM * 64}, {64, 2, 4, 4, 2});
  make_map5(enc, &wk.xn, sym(g_xn), true, {1280, 1, 1, 256, 1}, {10240, 10240, 10240, 10240}, {128, 1, 1, 16, 1});
  make_map5(enc, &ch.xc, sym(g_xn), true, {160, 1, 1, 256, 8}, {1280, 1280, 10240, 1280}, {160, 1, 1, 4, 2});
  wk.x = x;
  for (int i = 0; i < 4; i++) at.pf[i] = (const uint8_t*)d_in[i < 2 ? 3 + i : i == 2 ? 2 : 5];
  int qa_end[2] = {12, 12}, pace = 85;
  for (int layer = 0; layer < 2; layer++) {
    ch.sync = wk.sync = at.sync = (uint32_t*)sym(g_sync) + layer * SY_N;
    ch.other = (uint32_t*)sym(g_sync) + (1 - layer) * SY_N;
    ch.layer = layer;
    at.next = layer ? nullptr : ch.other;
    wk.qa_end = qa_end[layer];
    wk.kind = layer ? WK_LEAD : WK_FIRST; wk.pace = pace;
    launch(work_kernel, 132, 384, CH_SMEM, 1, layer != 0, wk);
    wk.kind = WK_CHAIN; wk.pace = 0;
    launch(work_kernel, 96, 384, CH_SMEM, 3, true, wk);
    launch(attn_b_kernel, 128, AB_T + 128, AB_SMEM, 1, true, at);
  }
  wk.kind = WK_LAST;
  launch(work_kernel, 128, 384, CH_SMEM, 1, true, wk);
}
```
